```python
import torch

def _softmax(x, axis=-1):
    return torch.softmax(x, dim=axis)
def _gelu(x):
    return torch.nn.functional.gelu(x, approximate="tanh")
def _silu(x):
    return torch.nn.functional.silu(x)
def _sigmoid(x):
    return torch.sigmoid(x)
def _layernorm(x, axis=-1, eps=1e-5):
    m = x.mean(dim=axis, keepdim=True)
    v = x.var(dim=axis, keepdim=True, unbiased=False)
    return (x - m) / torch.sqrt(v + eps)
def _scatter_add(tgt, idx, src, axis=0):
    return tgt.clone().index_add_(axis, idx, src)
def _segment_sum(src, seg, n):
    out = torch.zeros((n,) + src.shape[1:], dtype=src.dtype)
    return out.index_add_(0, seg, src)
def _pad(x, pw):
    flat = tuple(v for pair in reversed(pw) for v in pair)
    return torch.nn.functional.pad(x, flat)

kernel_name = 'gated_mix__sliding_block__dense_activation_mish__prompt'

def setup_inputs():

    _w = (lambda a: (lambda t: t.to(torch.bfloat16) if t.is_floating_point() else t)(torch.as_tensor(a)))
    def _A_setup():
        B, S, D = 1, 2048, 512
        return {
            "x": _w((lambda *s: torch.randn(*s, dtype=torch.bfloat16) * 0.05)(B, S, D)),
            "wqkv": _w((lambda *s: torch.randn(*s, dtype=torch.bfloat16) * 0.8)(D, 3 * D)),
            "wo": _w((lambda *s: torch.randn(*s, dtype=torch.bfloat16) * 0.05)(D, D)),
        }
    _A_in = _A_setup()

    def _B_setup():
        B, S, D, F = 1, 2048, 512, 1376
        return {
            "x": _w((lambda *s: torch.randn(*s, dtype=torch.bfloat16) * 0.05)(B, S, D)),
            "w1": _w((lambda *s: torch.randn(*s, dtype=torch.bfloat16) * 12.8)(D, F) * (D ** -0.5)),
            "b1": _w((lambda *s: torch.randn(*s, dtype=torch.bfloat16) * 0.8)(F)),
            "w2": _w((lambda *s: torch.randn(*s, dtype=torch.bfloat16) * 0.8)(F, D) * (F ** -0.5)),
        }
    _B_in = _B_setup()

    return {
        "A_x": _A_in["x"],
        "A_wqkv": _A_in["wqkv"],
        "A_wo": _A_in["wo"],
        "B_x": _B_in["x"],
        "B_w1": _B_in["w1"],
        "B_b1": _B_in["b1"],
        "B_w2": _B_in["w2"],
        "gate_w": _w((lambda *s: torch.randn(*s, dtype=torch.bfloat16) * 0.05)(512) * 16.0),
    }

def reference(A_x, A_wqkv, A_wo, B_x, B_w1, B_b1, B_w2, gate_w):
    def _A_ref(x, wqkv, wo):
        B, S, D = x.shape
        H = 32; Dh = D // H; W = 256
        qkv = (lambda x, *d: x.permute(*d))((x @ wqkv).reshape(B, S, 3, H, Dh), 2, 0, 3, 1, 4)
        q, k, v = qkv[0], qkv[1], qkv[2]
        scores = torch.einsum("bhqd,bhkd->bhqk", q, k) * (Dh ** -0.5)
        idx = torch.arange(S)
        mask = (idx[:, None] - idx[None, :] >= 0) & (idx[:, None] - idx[None, :] < W)
        scores = torch.where(mask[None, None], scores, -1e9)
        p = _softmax(scores, axis=-1)
        o = torch.einsum("bhqk,bhkd->bhqd", p, v)
        return (lambda x, *d: x.permute(*d))(o, 0, 2, 1, 3).reshape(B, S, D) @ wo

    def _B_ref(x, w1, b1, w2):
        h = torch.einsum("bsd,df->bsf", x, w1) + b1
        sp = torch.log1p(torch.exp(-torch.abs(h))) + torch.where(h > 0, h, torch.zeros_like(h))
        act = h * torch.tanh(sp)
        return torch.einsum("bsf,fd->bsd", act, w2)

    x = A_x
    g = _sigmoid((x * gate_w).sum(-1, keepdims=True))
    a = _A_ref(x, A_wqkv, A_wo)
    b = _B_ref(x, B_w1, B_b1, B_w2)
    return g * a + (1 - g) * b
```

```cpp
#include <cuda_runtime.h>
#include <cuda_bf16.h>
#include <cuda.h>
#include <stdint.h>

typedef __nv_bfloat16 bf16;

constexpr int S_ = 2048, D_ = 512, F_ = 1376;
constexpr int KA2 = D_ + F_;
constexpr int FCH = 176;

__device__ bf16  g_qkv[8 * S_ * 192];
__device__ bf16  g_a2[S_ * KA2];
__device__ float g_gate[S_];

__device__ __forceinline__ uint32_t smem_u32(const void* p) { return (uint32_t)__cvta_generic_to_shared(p); }
__device__ __forceinline__ void mbar_init(uint32_t bar, uint32_t count) {
    asm volatile("mbarrier.init.shared::cta.b64 [%0], %1;" :: "r"(bar), "r"(count) : "memory");
}
__device__ __forceinline__ void mbar_expect_tx(uint32_t bar, uint32_t bytes) {
    asm volatile("mbarrier.arrive.expect_tx.shared::cta.b64 _, [%0], %1;" :: "r"(bar), "r"(bytes) : "memory");
}
__device__ __forceinline__ void mbar_arrive(uint32_t bar) {
    asm volatile("mbarrier.arrive.shared::cta.b64 _, [%0];" :: "r"(bar) : "memory");
}
__device__ __forceinline__ bool mbar_try_wait(uint32_t bar, uint32_t parity) {
    uint32_t ok;
    asm volatile("{\n.reg .pred p;\nmbarrier.try_wait.parity.shared::cta.b64 p, [%1], %2;\nselp.u32 %0, 1, 0, p;\n}"
                 : "=r"(ok) : "r"(bar), "r"(parity) : "memory");
    return ok != 0;
}
__device__ __forceinline__ void mbar_wait(uint32_t bar, uint32_t parity) {
    for (uint32_t it = 0; it < (1u << 22); ++it) { if (mbar_try_wait(bar, parity)) break; }
}
__device__ __forceinline__ void tma_load_2d(uint32_t dst, const CUtensorMap* map, int c0, int c1, uint32_t bar) {
    asm volatile("cp.async.bulk.tensor.2d.shared::cluster.global.mbarrier::complete_tx::bytes [%0], [%1, {%3, %4}], [%2];"
                 :: "r"(dst), "l"(map), "r"(bar), "r"(c0), "r"(c1) : "memory");
}
__device__ __forceinline__ void fence_barrier_init() { asm volatile("fence.mbarrier_init.release.cluster;" ::: "memory"); }
__device__ __forceinline__ void wgmma_fence()  { asm volatile("wgmma.fence.sync.aligned;" ::: "memory"); }
__device__ __forceinline__ void wgmma_commit() { asm volatile("wgmma.commit_group.sync.aligned;" ::: "memory"); }
template <int N> __device__ __forceinline__ void wgmma_wait() { asm volatile("wgmma.wait_group.sync.aligned %0;" :: "n"(N) : "memory"); }
template <int R> __device__ __forceinline__ void reg_alloc()   { asm volatile("setmaxnreg.inc.sync.aligned.u32 %0;" :: "n"(R)); }
template <int R> __device__ __forceinline__ void reg_dealloc() { asm volatile("setmaxnreg.dec.sync.aligned.u32 %0;" :: "n"(R)); }
__device__ __forceinline__ void bar_sync(int id, int n)   { asm volatile("bar.sync %0, %1;" :: "r"(id), "r"(n) : "memory"); }
__device__ __forceinline__ void bar_arrive(int id, int n) { asm volatile("bar.arrive %0, %1;" :: "r"(id), "r"(n) : "memory"); }

__device__ __forceinline__ uint64_t make_desc(uint32_t addr, uint32_t lbo, uint32_t sbo) {
    uint64_t d = (uint64_t)((addr & 0x3FFFF) >> 4);
    d |= (uint64_t)((lbo & 0x3FFFF) >> 4) << 16;
    d |= (uint64_t)((sbo & 0x3FFFF) >> 4) << 32;
    d |= (uint64_t)1 << 62;
    return d;
}

template <int TB>
__device__ __forceinline__ void wgmma_n64(float (&d)[32], uint64_t da, uint64_t db, int scale_d) {
    asm volatile("{\n.reg .pred p;\nsetp.ne.b32 p, %34, 0;\n"
        "wgmma.mma_async.sync.aligned.m64n64k16.f32.bf16.bf16 {%0, %1, %2, %3, %4, %5, %6, %7, %8, %9, %10, %11, %12, %13, %14, %15, %16, %17, %18, %19, %20, %21, %22, %23, %24, %25, %26, %27, %28, %29, %30, %31}, %32, %33, p, 1, 1, 0, %35;\n}\n"
        : "+f"(d[0]), "+f"(d[1]), "+f"(d[2]), "+f"(d[3]), "+f"(d[4]), "+f"(d[5]), "+f"(d[6]), "+f"(d[7]), "+f"(d[8]), "+f"(d[9]), "+f"(d[10]), "+f"(d[11]), "+f"(d[12]), "+f"(d[13]), "+f"(d[14]), "+f"(d[15]), "+f"(d[16]), "+f"(d[17]), "+f"(d[18]), "+f"(d[19]), "+f"(d[20]), "+f"(d[21]), "+f"(d[22]), "+f"(d[23]), "+f"(d[24]), "+f"(d[25]), "+f"(d[26]), "+f"(d[27]), "+f"(d[28]), "+f"(d[29]), "+f"(d[30]), "+f"(d[31])
        : "l"(da), "l"(db), "r"(scale_d), "n"(TB));
}

template <int TB>
__device__ __forceinline__ void wgmma_n128(float (&d)[64], uint64_t da, uint64_t db, int scale_d) {
    asm volatile("{\n.reg .pred p;\nsetp.ne.b32 p, %66, 0;\n"
        "wgmma.mma_async.sync.aligned.m64n128k16.f32.bf16.bf16 {%0, %1, %2, %3, %4, %5, %6, %7, %8, %9, %10, %11, %12, %13, %14, %15, %16, %17, %18, %19, %20, %21, %22, %23, %24, %25, %26, %27, %28, %29, %30, %31, %32, %33, %34, %35, %36, %37, %38, %39, %40, %41, %42, %43, %44, %45, %46, %47, %48, %49, %50, %51, %52, %53, %54, %55, %56, %57, %58, %59, %60, %61, %62, %63}, %64, %65, p, 1, 1, 0, %67;\n}\n"
        : "+f"(d[0]), "+f"(d[1]), "+f"(d[2]), "+f"(d[3]), "+f"(d[4]), "+f"(d[5]), "+f"(d[6]), "+f"(d[7]), "+f"(d[8]), "+f"(d[9]), "+f"(d[10]), "+f"(d[11]), "+f"(d[12]), "+f"(d[13]), "+f"(d[14]), "+f"(d[15]), "+f"(d[16]), "+f"(d[17]), "+f"(d[18]), "+f"(d[19]), "+f"(d[20]), "+f"(d[21]), "+f"(d[22]), "+f"(d[23]), "+f"(d[24]), "+f"(d[25]), "+f"(d[26]), "+f"(d[27]), "+f"(d[28]), "+f"(d[29]), "+f"(d[30]), "+f"(d[31]), "+f"(d[32]), "+f"(d[33]), "+f"(d[34]), "+f"(d[35]), "+f"(d[36]), "+f"(d[37]), "+f"(d[38]), "+f"(d[39]), "+f"(d[40]), "+f"(d[41]), "+f"(d[42]), "+f"(d[43]), "+f"(d[44]), "+f"(d[45]), "+f"(d[46]), "+f"(d[47]), "+f"(d[48]), "+f"(d[49]), "+f"(d[50]), "+f"(d[51]), "+f"(d[52]), "+f"(d[53]), "+f"(d[54]), "+f"(d[55]), "+f"(d[56]), "+f"(d[57]), "+f"(d[58]), "+f"(d[59]), "+f"(d[60]), "+f"(d[61]), "+f"(d[62]), "+f"(d[63])
        : "l"(da), "l"(db), "r"(scale_d), "n"(TB));
}

template <int TB>
__device__ __forceinline__ void wgmma_n176(float (&d)[88], uint64_t da, uint64_t db, int scale_d) {
    asm volatile("{\n.reg .pred p;\nsetp.ne.b32 p, %90, 0;\n"
        "wgmma.mma_async.sync.aligned.m64n176k16.f32.bf16.bf16 {%0, %1, %2, %3, %4, %5, %6, %7, %8, %9, %10, %11, %12, %13, %14, %15, %16, %17, %18, %19, %20, %21, %22, %23, %24, %25, %26, %27, %28, %29, %30, %31, %32, %33, %34, %35, %36, %37, %38, %39, %40, %41, %42, %43, %44, %45, %46, %47, %48, %49, %50, %51, %52, %53, %54, %55, %56, %57, %58, %59, %60, %61, %62, %63, %64, %65, %66, %67, %68, %69, %70, %71, %72, %73, %74, %75, %76, %77, %78, %79, %80, %81, %82, %83, %84, %85, %86, %87}, %88, %89, p, 1, 1, 0, %91;\n}\n"
        : "+f"(d[0]), "+f"(d[1]), "+f"(d[2]), "+f"(d[3]), "+f"(d[4]), "+f"(d[5]), "+f"(d[6]), "+f"(d[7]), "+f"(d[8]), "+f"(d[9]), "+f"(d[10]), "+f"(d[11]), "+f"(d[12]), "+f"(d[13]), "+f"(d[14]), "+f"(d[15]), "+f"(d[16]), "+f"(d[17]), "+f"(d[18]), "+f"(d[19]), "+f"(d[20]), "+f"(d[21]), "+f"(d[22]), "+f"(d[23]), "+f"(d[24]), "+f"(d[25]), "+f"(d[26]), "+f"(d[27]), "+f"(d[28]), "+f"(d[29]), "+f"(d[30]), "+f"(d[31]), "+f"(d[32]), "+f"(d[33]), "+f"(d[34]), "+f"(d[35]), "+f"(d[36]), "+f"(d[37]), "+f"(d[38]), "+f"(d[39]), "+f"(d[40]), "+f"(d[41]), "+f"(d[42]), "+f"(d[43]), "+f"(d[44]), "+f"(d[45]), "+f"(d[46]), "+f"(d[47]), "+f"(d[48]), "+f"(d[49]), "+f"(d[50]), "+f"(d[51]), "+f"(d[52]), "+f"(d[53]), "+f"(d[54]), "+f"(d[55]), "+f"(d[56]), "+f"(d[57]), "+f"(d[58]), "+f"(d[59]), "+f"(d[60]), "+f"(d[61]), "+f"(d[62]), "+f"(d[63]), "+f"(d[64]), "+f"(d[65]), "+f"(d[66]), "+f"(d[67]), "+f"(d[68]), "+f"(d[69]), "+f"(d[70]), "+f"(d[71]), "+f"(d[72]), "+f"(d[73]), "+f"(d[74]), "+f"(d[75]), "+f"(d[76]), "+f"(d[77]), "+f"(d[78]), "+f"(d[79]), "+f"(d[80]), "+f"(d[81]), "+f"(d[82]), "+f"(d[83]), "+f"(d[84]), "+f"(d[85]), "+f"(d[86]), "+f"(d[87])
        : "l"(da), "l"(db), "r"(scale_d), "n"(TB));
}

template <int TB>
__device__ __forceinline__ void wgmma_n192(float (&d)[96], uint64_t da, uint64_t db, int scale_d) {
    asm volatile("{\n.reg .pred p;\nsetp.ne.b32 p, %98, 0;\n"
        "wgmma.mma_async.sync.aligned.m64n192k16.f32.bf16.bf16 {%0, %1, %2, %3, %4, %5, %6, %7, %8, %9, %10, %11, %12, %13, %14, %15, %16, %17, %18, %19, %20, %21, %22, %23, %24, %25, %26, %27, %28, %29, %30, %31, %32, %33, %34, %35, %36, %37, %38, %39, %40, %41, %42, %43, %44, %45, %46, %47, %48, %49, %50, %51, %52, %53, %54, %55, %56, %57, %58, %59, %60, %61, %62, %63, %64, %65, %66, %67, %68, %69, %70, %71, %72, %73, %74, %75, %76, %77, %78, %79, %80, %81, %82, %83, %84, %85, %86, %87, %88, %89, %90, %91, %92, %93, %94, %95}, %96, %97, p, 1, 1, 0, %99;\n}\n"
        : "+f"(d[0]), "+f"(d[1]), "+f"(d[2]), "+f"(d[3]), "+f"(d[4]), "+f"(d[5]), "+f"(d[6]), "+f"(d[7]), "+f"(d[8]), "+f"(d[9]), "+f"(d[10]), "+f"(d[11]), "+f"(d[12]), "+f"(d[13]), "+f"(d[14]), "+f"(d[15]), "+f"(d[16]), "+f"(d[17]), "+f"(d[18]), "+f"(d[19]), "+f"(d[20]), "+f"(d[21]), "+f"(d[22]), "+f"(d[23]), "+f"(d[24]), "+f"(d[25]), "+f"(d[26]), "+f"(d[27]), "+f"(d[28]), "+f"(d[29]), "+f"(d[30]), "+f"(d[31]), "+f"(d[32]), "+f"(d[33]), "+f"(d[34]), "+f"(d[35]), "+f"(d[36]), "+f"(d[37]), "+f"(d[38]), "+f"(d[39]), "+f"(d[40]), "+f"(d[41]), "+f"(d[42]), "+f"(d[43]), "+f"(d[44]), "+f"(d[45]), "+f"(d[46]), "+f"(d[47]), "+f"(d[48]), "+f"(d[49]), "+f"(d[50]), "+f"(d[51]), "+f"(d[52]), "+f"(d[53]), "+f"(d[54]), "+f"(d[55]), "+f"(d[56]), "+f"(d[57]), "+f"(d[58]), "+f"(d[59]), "+f"(d[60]), "+f"(d[61]), "+f"(d[62]), "+f"(d[63]), "+f"(d[64]), "+f"(d[65]), "+f"(d[66]), "+f"(d[67]), "+f"(d[68]), "+f"(d[69]), "+f"(d[70]), "+f"(d[71]), "+f"(d[72]), "+f"(d[73]), "+f"(d[74]), "+f"(d[75]), "+f"(d[76]), "+f"(d[77]), "+f"(d[78]), "+f"(d[79]), "+f"(d[80]), "+f"(d[81]), "+f"(d[82]), "+f"(d[83]), "+f"(d[84]), "+f"(d[85]), "+f"(d[86]), "+f"(d[87]), "+f"(d[88]), "+f"(d[89]), "+f"(d[90]), "+f"(d[91]), "+f"(d[92]), "+f"(d[93]), "+f"(d[94]), "+f"(d[95])
        : "l"(da), "l"(db), "r"(scale_d), "n"(TB));
}


__device__ __forceinline__ uint32_t pack_bf16(float lo, float hi) {
    uint32_t r;
    asm("cvt.rn.bf16x2.f32 %0, %1, %2;" : "=r"(r) : "f"(hi), "f"(lo));
    return r;
}
__device__ __forceinline__ float bf_lo(uint32_t v) { return __uint_as_float(v << 16); }
__device__ __forceinline__ float bf_hi(uint32_t v) { return __uint_as_float(v & 0xffff0000u); }

__device__ __forceinline__ void quad_transpose(uint32_t (&w)[4], int q) {
    const bool o1 = q & 1, o2 = q & 2;
    {
        uint32_t s0 = o1 ? w[0] : w[1], s1 = o1 ? w[2] : w[3];
        s0 = __shfl_xor_sync(0xffffffffu, s0, 1); s1 = __shfl_xor_sync(0xffffffffu, s1, 1);
        if (o1) { w[0] = s0; w[2] = s1; } else { w[1] = s0; w[3] = s1; }
    }
    {
        uint32_t s0 = o2 ? w[0] : w[2], s1 = o2 ? w[1] : w[3];
        s0 = __shfl_xor_sync(0xffffffffu, s0, 2); s1 = __shfl_xor_sync(0xffffffffu, s1, 2);
        if (o2) { w[0] = s0; w[1] = s1; } else { w[2] = s0; w[3] = s1; }
    }
}

__device__ __forceinline__ float mish_f(float h) {
    const float w = __expf(-fabsf(h));
    const float t = w * w;
    float num, den;
    if (h > 0.f) { num = fmaf(2.f, w, 1.f); den = fmaf(2.f, t, num); }
    else         { num = fmaf(2.f, w, t);   den = num + 2.f; }
    return h * __fdividef(num, den);
}

constexpr int K1_STAGES = 4;
constexpr int K1_XBYTES = 128 * 512 * 2;
constexpr int K1_BSTAGE = 3 * 8192;
constexpr int K1_SMEM   = K1_XBYTES + K1_STAGES * K1_BSTAGE + 1024   + 1024  ;

__global__ void __launch_bounds__(384, 1)
k1_kernel(const __grid_constant__ CUtensorMap tmX, const __grid_constant__ CUtensorMap tmWqkv,
          const __grid_constant__ CUtensorMap tmW1, const bf16* __restrict__ b1,
          const bf16* __restrict__ gate_w)
{
    extern __shared__ uint8_t smem_raw[];
    const uint32_t sbase = (smem_u32(smem_raw) + 1023u) & ~1023u;
    uint8_t* sgen = smem_raw + (sbase - smem_u32(smem_raw));
    const uint32_t sX = sbase;
    const uint32_t sB = sbase + K1_XBYTES;
    const uint32_t sBar = sB + K1_STAGES * K1_BSTAGE;
    const uint32_t x_full = sBar;
    const uint32_t b_full = sBar + 64;
    const uint32_t b_empty = sBar + 96;
    float* sGate = (float*)(sgen + K1_XBYTES + K1_STAGES * K1_BSTAGE + 256);

    const int rb = blockIdx.x >> 3, j = blockIdx.x & 7;
    const int tid = threadIdx.x, wg = tid >> 7, warp = tid >> 5, lane = tid & 31;

    if (tid == 0) {
        for (int i = 0; i < 8; i++) mbar_init(x_full + 8 * i, 1);
        for (int i = 0; i < K1_STAGES; i++) { mbar_init(b_full + 8 * i, 1); mbar_init(b_empty + 8 * i, 4); }
        fence_barrier_init();
    }
    __syncthreads();

    if (wg == 2) {
        reg_dealloc<40>();
        if (tid == 256) {
            for (int it = 0; it < 16; it++) {
                if (it < 8) {
                    mbar_expect_tx(x_full + 8 * it, 16384);
                    tma_load_2d(sX + it * 16384, &tmX, it * 64, rb * 128, x_full + 8 * it);
                }
                const int st = it & 3;
                if (it >= K1_STAGES) mbar_wait(b_empty + 8 * st, ((it >> 2) - 1) & 1);
                mbar_expect_tx(b_full + 8 * st, K1_BSTAGE);
                const uint32_t dst = sB + st * K1_BSTAGE;
                if (it < 8) {
                    for (int b = 0; b < 3; b++) tma_load_2d(dst + b * 8192, &tmW1, j * FCH + b * 64, it * 64, b_full + 8 * st);
                } else {
                    for (int b = 0; b < 3; b++) tma_load_2d(dst + b * 8192, &tmWqkv, b * 512 + j * 64, (it - 8) * 64, b_full + 8 * st);
                }
            }
        }
    } else if (wg == 0) {
        reg_alloc<232>();
        float acc[2][88];
#pragma unroll
        for (int kc = 0; kc < 8; kc++) {
            const int st = kc & 3;
            mbar_wait(x_full + 8 * kc, 0);
            mbar_wait(b_full + 8 * st, (kc >> 2) & 1);
            wgmma_fence();
#pragma unroll
            for (int k16 = 0; k16 < 4; k16++) {
                const uint64_t db = make_desc(sB + st * K1_BSTAGE + k16 * 2048, 8192, 1024);
#pragma unroll
                for (int h = 0; h < 2; h++) {
                    const uint64_t da = make_desc(sX + kc * 16384 + h * 8192 + k16 * 32, 16, 1024);
                    wgmma_n176<1>(acc[h], da, db, (kc | k16) != 0);
                }
            }
            wgmma_commit();
            if (kc > 0) { wgmma_wait<1>(); if (lane == 0) mbar_arrive(b_empty + 8 * ((kc - 1) & 3)); }
        }
        wgmma_wait<0>();
        if (lane == 0) mbar_arrive(b_empty + 8 * 3);
        bar_sync(1, 256);
        const int q = lane & 3;
        const int n0 = j * FCH;
#pragma unroll
        for (int h = 0; h < 2; h++) {
            const int rl = h * 64 + warp * 16 + (lane >> 2);
            const float om0 = 1.f - sGate[rl], om1 = 1.f - sGate[rl + 8];
            bf16* orow0 = g_a2 + (size_t)(rb * 128 + rl) * KA2 + D_ + n0;
            bf16* orow1 = orow0 + 8 * KA2;
#pragma unroll
            for (int u = 0; u < 6; u++) {
                uint32_t w0[4], w1[4];
#pragma unroll
                for (int i = 0; i < 4; i++) {
                    const int t = u * 4 + i;
                    if (t < 22) {
                        const int c = t * 8 + q * 2;
                        float bb0 = 0.f, bb1 = 0.f;
                        if (n0 + c < F_) { uint32_t bv = *(const uint32_t*)(b1 + n0 + c); bb0 = bf_lo(bv); bb1 = bf_hi(bv); }
                        w0[i] = pack_bf16(mish_f(acc[h][t * 4 + 0] + bb0) * om0, mish_f(acc[h][t * 4 + 1] + bb1) * om0);
                        w1[i] = pack_bf16(mish_f(acc[h][t * 4 + 2] + bb0) * om1, mish_f(acc[h][t * 4 + 3] + bb1) * om1);
                    } else { w0[i] = 0; w1[i] = 0; }
                }
                quad_transpose(w0, q);
                quad_transpose(w1, q);
                const int c = (u * 4 + q) * 8;
                if (c < FCH && n0 + c < F_) {
                    *(uint4*)(orow0 + c) = make_uint4(w0[0], w0[1], w0[2], w0[3]);
                    *(uint4*)(orow1 + c) = make_uint4(w1[0], w1[1], w1[2], w1[3]);
                }
            }
        }
    } else {
        reg_alloc<232>();
        {
            const int r = tid - 128;
            float s = 0.f;
            for (int kc = 0; kc < 8; kc++) {
                mbar_wait(x_full + 8 * kc, 0);
#pragma unroll
                for (int c = 0; c < 8; c++) {
                    const uint4 xv = *(const uint4*)(sgen + kc * 16384 + r * 128 + ((c ^ (r & 7)) << 4));
                    const uint4 gv = __ldg((const uint4*)(gate_w + kc * 64 + c * 8));
                    s = fmaf(bf_lo(xv.x), bf_lo(gv.x), s); s = fmaf(bf_hi(xv.x), bf_hi(gv.x), s);
                    s = fmaf(bf_lo(xv.y), bf_lo(gv.y), s); s = fmaf(bf_hi(xv.y), bf_hi(gv.y), s);
                    s = fmaf(bf_lo(xv.z), bf_lo(gv.z), s); s = fmaf(bf_hi(xv.z), bf_hi(gv.z), s);
                    s = fmaf(bf_lo(xv.w), bf_lo(gv.w), s); s = fmaf(bf_hi(xv.w), bf_hi(gv.w), s);
                }
            }
            const float g = 1.f / (1.f + __expf(-s));
            sGate[r] = g;
            if (j == 0) g_gate[rb * 128 + r] = g;
            __threadfence_block();
            bar_arrive(1, 256);
        }
        float acc[2][96];
        const int w4 = warp - 4;
#pragma unroll
        for (int kc = 0; kc < 8; kc++) {
            const int st = kc & 3;
            mbar_wait(b_full + 8 * st, ((kc + 8) >> 2) & 1);
            wgmma_fence();
#pragma unroll
            for (int k16 = 0; k16 < 4; k16++) {
                const uint64_t db = make_desc(sB + st * K1_BSTAGE + k16 * 2048, 8192, 1024);
#pragma unroll
                for (int h = 0; h < 2; h++) {
                    const uint64_t da = make_desc(sX + kc * 16384 + h * 8192 + k16 * 32, 16, 1024);
                    wgmma_n192<1>(acc[h], da, db, (kc | k16) != 0);
                }
            }
            wgmma_commit();
            if (kc > 0) { wgmma_wait<1>(); if (lane == 0) mbar_arrive(b_empty + 8 * ((kc - 1) & 3)); }
        }
        wgmma_wait<0>();
        const int q = lane & 3;
#pragma unroll
        for (int h = 0; h < 2; h++) {
            const int rl = h * 64 + w4 * 16 + (lane >> 2);
            bf16* orow0 = g_qkv + ((size_t)j * S_ + rb * 128 + rl) * 192;
            bf16* orow1 = orow0 + 8 * 192;
#pragma unroll
            for (int u = 0; u < 6; u++) {
                uint32_t w0[4], w1[4];
#pragma unroll
                for (int i = 0; i < 4; i++) {
                    const int t = u * 4 + i;
                    w0[i] = pack_bf16(acc[h][t * 4 + 0], acc[h][t * 4 + 1]);
                    w1[i] = pack_bf16(acc[h][t * 4 + 2], acc[h][t * 4 + 3]);
                }
                quad_transpose(w0, q);
                quad_transpose(w1, q);
                const int c = (u * 4 + q) * 8;
                *(uint4*)(orow0 + c) = make_uint4(w0[0], w0[1], w0[2], w0[3]);
                *(uint4*)(orow1 + c) = make_uint4(w1[0], w1[1], w1[2], w1[3]);
            }
        }
    }
}

constexpr int K2_PITCH = 144;
constexpr int K2_SMEM = (384 * 2 + 128) * K2_PITCH;

__device__ __forceinline__ void ldsm_x4(uint32_t (&r)[4], uint32_t addr) {
    asm volatile("ldmatrix.sync.aligned.m8n8.x4.shared.b16 {%0,%1,%2,%3}, [%4];"
                 : "=r"(r[0]), "=r"(r[1]), "=r"(r[2]), "=r"(r[3]) : "r"(addr));
}
__device__ __forceinline__ void ldsm_x4_t(uint32_t (&r)[4], uint32_t addr) {
    asm volatile("ldmatrix.sync.aligned.m8n8.x4.trans.shared.b16 {%0,%1,%2,%3}, [%4];"
                 : "=r"(r[0]), "=r"(r[1]), "=r"(r[2]), "=r"(r[3]) : "r"(addr));
}
__device__ __forceinline__ void mma16816(float (&d)[4], const uint32_t (&a)[4], uint32_t b0, uint32_t b1) {
    asm volatile("mma.sync.aligned.m16n8k16.row.col.f32.bf16.bf16.f32 {%0,%1,%2,%3}, {%4,%5,%6,%7}, {%8,%9}, {%0,%1,%2,%3};"
                 : "+f"(d[0]), "+f"(d[1]), "+f"(d[2]), "+f"(d[3])
                 : "r"(a[0]), "r"(a[1]), "r"(a[2]), "r"(a[3]), "r"(b0), "r"(b1));
}
__device__ __forceinline__ float ex2(float x) { float y; asm("ex2.approx.ftz.f32 %0, %1;" : "=f"(y) : "f"(x)); return y; }

template <bool HEAD_MASK>
__device__ __forceinline__ void attn_task(uint32_t sQ, uint32_t sK, uint32_t sV, int q0g, int lane,
                                          bf16* __restrict__ out  , const float* __restrict__ gate)
{
    const float C = 0.25f * 1.4426950408889634f;
    uint32_t qa[4];
    ldsm_x4(qa, sQ + (lane & 15) * K2_PITCH + (lane >> 4) * 16);
    float s[34][4];
    {
        const uint32_t ka = sK + ((lane & 7) + ((lane >> 4) << 3)) * K2_PITCH + ((lane >> 3) & 1) * 16;
#pragma unroll
        for (int kb = 0; kb < 17; kb++) {
            uint32_t kf[4];
            ldsm_x4(kf, ka + kb * 16 * K2_PITCH);
#pragma unroll
            for (int e = 0; e < 4; e++) { s[2 * kb][e] = 0.f; s[2 * kb + 1][e] = 0.f; }
            mma16816(s[2 * kb], qa, kf[0], kf[1]);
            mma16816(s[2 * kb + 1], qa, kf[2], kf[3]);
        }
    }
    const int r0 = lane >> 2, c0 = (lane & 3) * 2;
    const float NEG = -1e30f;
#pragma unroll
    for (int t = 0; t < 2; t++) {
#pragma unroll
        for (int e = 0; e < 4; e++) {
            const int r = r0 + (e >> 1) * 8, c = t * 8 + c0 + (e & 1);
            if (c <= r) s[t][e] = NEG;
            if (c > r) s[32 + t][e] = NEG;
        }
    }
    if (HEAD_MASK) {
#pragma unroll
        for (int t = 0; t < 32; t++) {
            const int kg = q0g - 256 + t * 8 + c0;
            if (kg < 0) { s[t][0] = NEG; s[t][1] = NEG; s[t][2] = NEG; s[t][3] = NEG; }
        }
    }
    float m0 = NEG, m1 = NEG;
#pragma unroll
    for (int t = 0; t < 34; t++) {
        m0 = fmaxf(m0, fmaxf(s[t][0], s[t][1]));
        m1 = fmaxf(m1, fmaxf(s[t][2], s[t][3]));
    }
    m0 = fmaxf(m0, __shfl_xor_sync(0xffffffffu, m0, 1)); m0 = fmaxf(m0, __shfl_xor_sync(0xffffffffu, m0, 2));
    m1 = fmaxf(m1, __shfl_xor_sync(0xffffffffu, m1, 1)); m1 = fmaxf(m1, __shfl_xor_sync(0xffffffffu, m1, 2));
    const float mc0 = m0 * C, mc1 = m1 * C;
    float l0 = 0.f, l1 = 0.f;
    float o[2][4] = {{0.f, 0.f, 0.f, 0.f}, {0.f, 0.f, 0.f, 0.f}};
    const uint32_t va = sV + (lane & 15) * K2_PITCH + (lane >> 4) * 16;
#pragma unroll
    for (int kb = 0; kb < 17; kb++) {
        uint32_t pa[4];
#pragma unroll
        for (int t = 0; t < 2; t++) {
            const float p0 = ex2(fmaf(s[2 * kb + t][0], C, -mc0)), p1 = ex2(fmaf(s[2 * kb + t][1], C, -mc0));
            const float p2 = ex2(fmaf(s[2 * kb + t][2], C, -mc1)), p3 = ex2(fmaf(s[2 * kb + t][3], C, -mc1));
            l0 += p0 + p1; l1 += p2 + p3;
            pa[2 * t] = pack_bf16(p0, p1); pa[2 * t + 1] = pack_bf16(p2, p3);
        }
        uint32_t vf[4];
        ldsm_x4_t(vf, va + kb * 16 * K2_PITCH);
        mma16816(o[0], pa, vf[0], vf[1]);
        mma16816(o[1], pa, vf[2], vf[3]);
    }
    l0 += __shfl_xor_sync(0xffffffffu, l0, 1); l0 += __shfl_xor_sync(0xffffffffu, l0, 2);
    l1 += __shfl_xor_sync(0xffffffffu, l1, 1); l1 += __shfl_xor_sync(0xffffffffu, l1, 2);
    const float f0 = gate[r0] / l0, f1 = gate[r0 + 8] / l1;
#pragma unroll
    for (int t = 0; t < 2; t++) {
        *(uint32_t*)(out + (size_t)r0 * KA2 + t * 8 + c0) = pack_bf16(o[t][0] * f0, o[t][1] * f0);
        *(uint32_t*)(out + (size_t)(r0 + 8) * KA2 + t * 8 + c0) = pack_bf16(o[t][2] * f1, o[t][3] * f1);
    }
}

__global__ void __launch_bounds__(512, 1) k2_kernel()
{
    extern __shared__ uint8_t smem_raw[];
    const uint32_t sK = smem_u32(smem_raw), sV = sK + 384 * K2_PITCH, sQ = sV + 384 * K2_PITCH;
    const int rb = blockIdx.x >> 3, j = blockIdx.x & 7;
    const int tid = threadIdx.x, warp = tid >> 5, lane = tid & 31;
    const bf16* src = g_qkv + (size_t)j * S_ * 192;
    for (int i = tid; i < 384 * 16; i += 512) {
        const int r = i >> 4, c = i & 15;
        const int gr = rb * 128 - 256 + r;
        const uint32_t dst = (c < 8 ? sK : sV) + r * K2_PITCH + (c & 7) * 16;
        if (gr >= 0) {
            asm volatile("cp.async.cg.shared.global [%0], [%1], 16;" :: "r"(dst), "l"(src + (size_t)gr * 192 + 64 + c * 8) : "memory");
        } else {
            asm volatile("st.shared.v4.u32 [%0], {%1,%1,%1,%1};" :: "r"(dst), "r"(0) : "memory");
        }
    }
    for (int i = tid; i < 128 * 8; i += 512) {
        const int r = i >> 3, c = i & 7;
        asm volatile("cp.async.cg.shared.global [%0], [%1], 16;" :: "r"(sQ + r * K2_PITCH + c * 16), "l"(src + (size_t)(rb * 128 + r) * 192 + c * 8) : "memory");
    }
    asm volatile("cp.async.commit_group;\ncp.async.wait_group 0;" ::: "memory");
    __syncthreads();
    const int qt = warp & 7;
    const int q0g = rb * 128 + qt * 16;
#pragma unroll 1
    for (int hh = 0; hh < 2; hh++) {
        const int hl = (warp >> 3) * 2 + hh;
        const uint32_t q_addr = sQ + qt * 16 * K2_PITCH + hl * 32;
        const uint32_t k_addr = sK + qt * 16 * K2_PITCH + hl * 32;
        const uint32_t v_addr = sV + qt * 16 * K2_PITCH + hl * 32;
        bf16* out = g_a2 + (size_t)q0g * KA2 + (j * 4 + hl) * 16;
        if (q0g < 256) attn_task<true>(q_addr, k_addr, v_addr, q0g, lane, out, g_gate + q0g);
        else           attn_task<false>(q_addr, k_addr, v_addr, q0g, lane, out, g_gate + q0g);
    }
}

constexpr int K3_STAGES = 8;
constexpr int K3_STAGE = 16384 + 8192;
constexpr int K3_SMEM = K3_STAGES * K3_STAGE + 1024 + 1024;
constexpr int K3_KSTEPS = 30;

__global__ void __launch_bounds__(384, 1)
k3_kernel(const __grid_constant__ CUtensorMap tmA2, const __grid_constant__ CUtensorMap tmWo,
          const __grid_constant__ CUtensorMap tmW2, bf16* __restrict__ out)
{
    extern __shared__ uint8_t smem_raw[];
    const uint32_t sbase = (smem_u32(smem_raw) + 1023u) & ~1023u;
    const uint32_t sBar = sbase + K3_STAGES * K3_STAGE;
    const uint32_t full = sBar, empty = sBar + 64;
    const int rb = blockIdx.x >> 3, nb = blockIdx.x & 7;
    const int tid = threadIdx.x, wg = tid >> 7, warp = tid >> 5, lane = tid & 31;
    if (tid == 0) {
        for (int i = 0; i < K3_STAGES; i++) { mbar_init(full + 8 * i, 1); mbar_init(empty + 8 * i, 8); }
        fence_barrier_init();
    }
    __syncthreads();
    if (wg == 2) {
        reg_dealloc<40>();
        if (tid == 256) {
            for (int ks = 0; ks < K3_KSTEPS; ks++) {
                const int st = ks % K3_STAGES;
                if (ks >= K3_STAGES) mbar_wait(empty + 8 * st, ((ks / K3_STAGES) - 1) & 1);
                mbar_expect_tx(full + 8 * st, K3_STAGE);
                const uint32_t dst = sbase + st * K3_STAGE;
                tma_load_2d(dst, &tmA2, ks * 64, rb * 128, full + 8 * st);
                if (ks < 8) tma_load_2d(dst + 16384, &tmWo, nb * 64, ks * 64, full + 8 * st);
                else        tma_load_2d(dst + 16384, &tmW2, nb * 64, (ks - 8) * 64, full + 8 * st);
            }
        }
    } else {
        reg_alloc<232>();
        float acc[32];
        for (int ks = 0; ks < K3_KSTEPS; ks++) {
            const int st = ks % K3_STAGES;
            mbar_wait(full + 8 * st, (ks / K3_STAGES) & 1);
            wgmma_fence();
#pragma unroll
            for (int k16 = 0; k16 < 4; k16++) {
                const uint64_t da = make_desc(sbase + st * K3_STAGE + wg * 8192 + k16 * 32, 16, 1024);
                const uint64_t db = make_desc(sbase + st * K3_STAGE + 16384 + k16 * 2048, 8192, 1024);
                wgmma_n64<1>(acc, da, db, (ks | k16) != 0);
            }
            wgmma_commit();
            if (ks > 0) { wgmma_wait<1>(); if (lane == 0) mbar_arrive(empty + 8 * ((ks - 1) % K3_STAGES)); }
        }
        wgmma_wait<0>();
        const int q = lane & 3;
        const int r = rb * 128 + wg * 64 + (warp & 3) * 16 + (lane >> 2);
        bf16* orow0 = out + (size_t)r * D_ + nb * 64;
        bf16* orow1 = orow0 + 8 * D_;
#pragma unroll
        for (int u = 0; u < 2; u++) {
            uint32_t w0[4], w1[4];
#pragma unroll
            for (int i = 0; i < 4; i++) {
                const int t = u * 4 + i;
                w0[i] = pack_bf16(acc[t * 4 + 0], acc[t * 4 + 1]);
                w1[i] = pack_bf16(acc[t * 4 + 2], acc[t * 4 + 3]);
            }
            quad_transpose(w0, q);
            quad_transpose(w1, q);
            const int c = (u * 4 + q) * 8;
            *(uint4*)(orow0 + c) = make_uint4(w0[0], w0[1], w0[2], w0[3]);
            *(uint4*)(orow1 + c) = make_uint4(w1[0], w1[1], w1[2], w1[3]);
        }
    }
}

typedef CUresult (*PFN_encodeTiled)(CUtensorMap*, CUtensorMapDataType, cuuint32_t, void*, const cuuint64_t*,
                                    const cuuint64_t*, const cuuint32_t*, const cuuint32_t*, CUtensorMapInterleave,
                                    CUtensorMapSwizzle, CUtensorMapL2promotion, CUtensorMapFloatOOBfill);

static void make_map(PFN_encodeTiled enc, CUtensorMap* m, const void* ptr, uint64_t cols, uint64_t rows,
                     uint32_t box_cols, uint32_t box_rows)
{
    cuuint64_t dims[2] = {cols, rows};
    cuuint64_t strides[1] = {cols * 2};
    cuuint32_t box[2] = {box_cols, box_rows};
    cuuint32_t es[2] = {1, 1};
    enc(m, CU_TENSOR_MAP_DATA_TYPE_BFLOAT16, 2, const_cast<void*>(ptr), dims, strides, box, es,
        CU_TENSOR_MAP_INTERLEAVE_NONE, CU_TENSOR_MAP_SWIZZLE_128B, CU_TENSOR_MAP_L2_PROMOTION_L2_128B,
        CU_TENSOR_MAP_FLOAT_OOB_FILL_NONE);
}

extern "C" void kernel_launch(void* const* d_in, const int* in_sizes, int n_in, void* d_out, int out_size)
{
    const bf16* x    = (const bf16*)d_in[0];
    const bf16* wqkv = (const bf16*)d_in[1];
    const bf16* wo   = (const bf16*)d_in[2];
    const bf16* w1   = (const bf16*)d_in[4];
    const bf16* b1   = (const bf16*)d_in[5];
    const bf16* w2   = (const bf16*)d_in[6];
    const bf16* gw   = (const bf16*)d_in[7];

    static PFN_encodeTiled enc = nullptr;
    if (!enc) {
        void* fn = nullptr;
        cudaDriverEntryPointQueryResult qr;
        cudaGetDriverEntryPoint("cuTensorMapEncodeTiled", &fn, cudaEnableDefault, &qr);
        enc = (PFN_encodeTiled)fn;
        cudaFuncSetAttribute(k1_kernel, cudaFuncAttributeMaxDynamicSharedMemorySize, K1_SMEM);
        cudaFuncSetAttribute(k2_kernel, cudaFuncAttributeMaxDynamicSharedMemorySize, K2_SMEM);
        cudaFuncSetAttribute(k3_kernel, cudaFuncAttributeMaxDynamicSharedMemorySize, K3_SMEM);
    }
    void* a2p = nullptr;
    cudaGetSymbolAddress(&a2p, g_a2);
    CUtensorMap tmX, tmWqkv, tmW1, tmA2, tmWo, tmW2;
    make_map(enc, &tmX, x, D_, S_, 64, 128);
    make_map(enc, &tmWqkv, wqkv, 3 * D_, D_, 64, 64);
    make_map(enc, &tmW1, w1, F_, D_, 64, 64);
    make_map(enc, &tmA2, a2p, KA2, S_, 64, 128);
    make_map(enc, &tmWo, wo, D_, D_, 64, 64);
    make_map(enc, &tmW2, w2, D_, F_, 64, 64);

    cudaStream_t st = cudaStreamPerThread;
    k1_kernel<<<128, 384, K1_SMEM, st>>>(tmX, tmWqkv, tmW1, b1, gw);
    k2_kernel<<<128, 512, K2_SMEM, st>>>();
    k3_kernel<<<128, 384, K3_SMEM, st>>>(tmA2, tmWo, tmW2, (bf16*)d_out);
}
```

```cpp
#include <cuda_runtime.h>
#include <cuda_bf16.h>
#include <cuda.h>
#include <stdint.h>

typedef __nv_bfloat16 bf16;

constexpr int S_ = 2048, D_ = 512, F_ = 1376;
constexpr int KA2 = D_ + F_;
constexpr int FCH = 176;

__device__ bf16  g_qkv[8 * S_ * 192];
__device__ bf16  g_a2[S_ * KA2];
__device__ float g_gate[S_];

#define TS(k, cond) do { } while (0)

__device__ __forceinline__ uint32_t smem_u32(const void* p) { return (uint32_t)__cvta_generic_to_shared(p); }
__device__ __forceinline__ void mbar_init(uint32_t bar, uint32_t count) {
    asm volatile("mbarrier.init.shared::cta.b64 [%0], %1;" :: "r"(bar), "r"(count) : "memory");
}
__device__ __forceinline__ void mbar_expect_tx(uint32_t bar, uint32_t bytes) {
    asm volatile("mbarrier.arrive.expect_tx.shared::cta.b64 _, [%0], %1;" :: "r"(bar), "r"(bytes) : "memory");
}
__device__ __forceinline__ void mbar_arrive(uint32_t bar) {
    asm volatile("mbarrier.arrive.shared::cta.b64 _, [%0];" :: "r"(bar) : "memory");
}
__device__ __forceinline__ bool mbar_try_wait(uint32_t bar, uint32_t parity) {
    uint32_t ok;
    asm volatile("{\n.reg .pred p;\nmbarrier.try_wait.parity.shared::cta.b64 p, [%1], %2;\nselp.u32 %0, 1, 0, p;\n}"
                 : "=r"(ok) : "r"(bar), "r"(parity) : "memory");
    return ok != 0;
}
__device__ __forceinline__ void mbar_wait(uint32_t bar, uint32_t parity) {
    for (uint32_t it = 0; it < (1u << 22); ++it) { if (mbar_try_wait(bar, parity)) break; }
}
__device__ __forceinline__ void tma_load_2d(uint32_t dst, const CUtensorMap* map, int c0, int c1, uint32_t bar) {
    asm volatile("cp.async.bulk.tensor.2d.shared::cluster.global.mbarrier::complete_tx::bytes [%0], [%1, {%3, %4}], [%2];"
                 :: "r"(dst), "l"(map), "r"(bar), "r"(c0), "r"(c1) : "memory");
}
__device__ __forceinline__ void l2_prefetch(const void* p, uint32_t bytes) {
    asm volatile("cp.async.bulk.prefetch.L2.global [%0], %1;" :: "l"(p), "r"(bytes) : "memory");
}
__device__ __forceinline__ void fence_barrier_init() { asm volatile("fence.mbarrier_init.release.cluster;" ::: "memory"); }
__device__ __forceinline__ void wgmma_fence()  { asm volatile("wgmma.fence.sync.aligned;" ::: "memory"); }
__device__ __forceinline__ void wgmma_commit() { asm volatile("wgmma.commit_group.sync.aligned;" ::: "memory"); }
template <int N> __device__ __forceinline__ void wgmma_wait() { asm volatile("wgmma.wait_group.sync.aligned %0;" :: "n"(N) : "memory"); }
template <int R> __device__ __forceinline__ void reg_alloc()   { asm volatile("setmaxnreg.inc.sync.aligned.u32 %0;" :: "n"(R)); }
template <int R> __device__ __forceinline__ void reg_dealloc() { asm volatile("setmaxnreg.dec.sync.aligned.u32 %0;" :: "n"(R)); }
__device__ __forceinline__ void bar_sync(int id, int n)   { asm volatile("bar.sync %0, %1;" :: "r"(id), "r"(n) : "memory"); }
__device__ __forceinline__ void bar_arrive(int id, int n) { asm volatile("bar.arrive %0, %1;" :: "r"(id), "r"(n) : "memory"); }

__device__ __forceinline__ uint64_t make_desc(uint32_t addr, uint32_t lbo, uint32_t sbo) {
    uint64_t d = (uint64_t)((addr & 0x3FFFF) >> 4);
    d |= (uint64_t)((lbo & 0x3FFFF) >> 4) << 16;
    d |= (uint64_t)((sbo & 0x3FFFF) >> 4) << 32;
    d |= (uint64_t)1 << 62;
    return d;
}

template <int TB>
__device__ __forceinline__ void wgmma_n64(float (&d)[32], uint64_t da, uint64_t db, int scale_d) {
    asm volatile("{\n.reg .pred p;\nsetp.ne.b32 p, %34, 0;\n"
        "wgmma.mma_async.sync.aligned.m64n64k16.f32.bf16.bf16 {%0, %1, %2, %3, %4, %5, %6, %7, %8, %9, %10, %11, %12, %13, %14, %15, %16, %17, %18, %19, %20, %21, %22, %23, %24, %25, %26, %27, %28, %29, %30, %31}, %32, %33, p, 1, 1, 0, %35;\n}\n"
        : "+f"(d[0]), "+f"(d[1]), "+f"(d[2]), "+f"(d[3]), "+f"(d[4]), "+f"(d[5]), "+f"(d[6]), "+f"(d[7]), "+f"(d[8]), "+f"(d[9]), "+f"(d[10]), "+f"(d[11]), "+f"(d[12]), "+f"(d[13]), "+f"(d[14]), "+f"(d[15]), "+f"(d[16]), "+f"(d[17]), "+f"(d[18]), "+f"(d[19]), "+f"(d[20]), "+f"(d[21]), "+f"(d[22]), "+f"(d[23]), "+f"(d[24]), "+f"(d[25]), "+f"(d[26]), "+f"(d[27]), "+f"(d[28]), "+f"(d[29]), "+f"(d[30]), "+f"(d[31])
        : "l"(da), "l"(db), "r"(scale_d), "n"(TB));
}

template <int TB>
__device__ __forceinline__ void wgmma_n128(float (&d)[64], uint64_t da, uint64_t db, int scale_d) {
    asm volatile("{\n.reg .pred p;\nsetp.ne.b32 p, %66, 0;\n"
        "wgmma.mma_async.sync.aligned.m64n128k16.f32.bf16.bf16 {%0, %1, %2, %3, %4, %5, %6, %7, %8, %9, %10, %11, %12, %13, %14, %15, %16, %17, %18, %19, %20, %21, %22, %23, %24, %25, %26, %27, %28, %29, %30, %31, %32, %33, %34, %35, %36, %37, %38, %39, %40, %41, %42, %43, %44, %45, %46, %47, %48, %49, %50, %51, %52, %53, %54, %55, %56, %57, %58, %59, %60, %61, %62, %63}, %64, %65, p, 1, 1, 0, %67;\n}\n"
        : "+f"(d[0]), "+f"(d[1]), "+f"(d[2]), "+f"(d[3]), "+f"(d[4]), "+f"(d[5]), "+f"(d[6]), "+f"(d[7]), "+f"(d[8]), "+f"(d[9]), "+f"(d[10]), "+f"(d[11]), "+f"(d[12]), "+f"(d[13]), "+f"(d[14]), "+f"(d[15]), "+f"(d[16]), "+f"(d[17]), "+f"(d[18]), "+f"(d[19]), "+f"(d[20]), "+f"(d[21]), "+f"(d[22]), "+f"(d[23]), "+f"(d[24]), "+f"(d[25]), "+f"(d[26]), "+f"(d[27]), "+f"(d[28]), "+f"(d[29]), "+f"(d[30]), "+f"(d[31]), "+f"(d[32]), "+f"(d[33]), "+f"(d[34]), "+f"(d[35]), "+f"(d[36]), "+f"(d[37]), "+f"(d[38]), "+f"(d[39]), "+f"(d[40]), "+f"(d[41]), "+f"(d[42]), "+f"(d[43]), "+f"(d[44]), "+f"(d[45]), "+f"(d[46]), "+f"(d[47]), "+f"(d[48]), "+f"(d[49]), "+f"(d[50]), "+f"(d[51]), "+f"(d[52]), "+f"(d[53]), "+f"(d[54]), "+f"(d[55]), "+f"(d[56]), "+f"(d[57]), "+f"(d[58]), "+f"(d[59]), "+f"(d[60]), "+f"(d[61]), "+f"(d[62]), "+f"(d[63])
        : "l"(da), "l"(db), "r"(scale_d), "n"(TB));
}

template <int TB>
__device__ __forceinline__ void wgmma_n176(float (&d)[88], uint64_t da, uint64_t db, int scale_d) {
    asm volatile("{\n.reg .pred p;\nsetp.ne.b32 p, %90, 0;\n"
        "wgmma.mma_async.sync.aligned.m64n176k16.f32.bf16.bf16 {%0, %1, %2, %3, %4, %5, %6, %7, %8, %9, %10, %11, %12, %13, %14, %15, %16, %17, %18, %19, %20, %21, %22, %23, %24, %25, %26, %27, %28, %29, %30, %31, %32, %33, %34, %35, %36, %37, %38, %39, %40, %41, %42, %43, %44, %45, %46, %47, %48, %49, %50, %51, %52, %53, %54, %55, %56, %57, %58, %59, %60, %61, %62, %63, %64, %65, %66, %67, %68, %69, %70, %71, %72, %73, %74, %75, %76, %77, %78, %79, %80, %81, %82, %83, %84, %85, %86, %87}, %88, %89, p, 1, 1, 0, %91;\n}\n"
        : "+f"(d[0]), "+f"(d[1]), "+f"(d[2]), "+f"(d[3]), "+f"(d[4]), "+f"(d[5]), "+f"(d[6]), "+f"(d[7]), "+f"(d[8]), "+f"(d[9]), "+f"(d[10]), "+f"(d[11]), "+f"(d[12]), "+f"(d[13]), "+f"(d[14]), "+f"(d[15]), "+f"(d[16]), "+f"(d[17]), "+f"(d[18]), "+f"(d[19]), "+f"(d[20]), "+f"(d[21]), "+f"(d[22]), "+f"(d[23]), "+f"(d[24]), "+f"(d[25]), "+f"(d[26]), "+f"(d[27]), "+f"(d[28]), "+f"(d[29]), "+f"(d[30]), "+f"(d[31]), "+f"(d[32]), "+f"(d[33]), "+f"(d[34]), "+f"(d[35]), "+f"(d[36]), "+f"(d[37]), "+f"(d[38]), "+f"(d[39]), "+f"(d[40]), "+f"(d[41]), "+f"(d[42]), "+f"(d[43]), "+f"(d[44]), "+f"(d[45]), "+f"(d[46]), "+f"(d[47]), "+f"(d[48]), "+f"(d[49]), "+f"(d[50]), "+f"(d[51]), "+f"(d[52]), "+f"(d[53]), "+f"(d[54]), "+f"(d[55]), "+f"(d[56]), "+f"(d[57]), "+f"(d[58]), "+f"(d[59]), "+f"(d[60]), "+f"(d[61]), "+f"(d[62]), "+f"(d[63]), "+f"(d[64]), "+f"(d[65]), "+f"(d[66]), "+f"(d[67]), "+f"(d[68]), "+f"(d[69]), "+f"(d[70]), "+f"(d[71]), "+f"(d[72]), "+f"(d[73]), "+f"(d[74]), "+f"(d[75]), "+f"(d[76]), "+f"(d[77]), "+f"(d[78]), "+f"(d[79]), "+f"(d[80]), "+f"(d[81]), "+f"(d[82]), "+f"(d[83]), "+f"(d[84]), "+f"(d[85]), "+f"(d[86]), "+f"(d[87])
        : "l"(da), "l"(db), "r"(scale_d), "n"(TB));
}

template <int TB>
__device__ __forceinline__ void wgmma_n192(float (&d)[96], uint64_t da, uint64_t db, int scale_d) {
    asm volatile("{\n.reg .pred p;\nsetp.ne.b32 p, %98, 0;\n"
        "wgmma.mma_async.sync.aligned.m64n192k16.f32.bf16.bf16 {%0, %1, %2, %3, %4, %5, %6, %7, %8, %9, %10, %11, %12, %13, %14, %15, %16, %17, %18, %19, %20, %21, %22, %23, %24, %25, %26, %27, %28, %29, %30, %31, %32, %33, %34, %35, %36, %37, %38, %39, %40, %41, %42, %43, %44, %45, %46, %47, %48, %49, %50, %51, %52, %53, %54, %55, %56, %57, %58, %59, %60, %61, %62, %63, %64, %65, %66, %67, %68, %69, %70, %71, %72, %73, %74, %75, %76, %77, %78, %79, %80, %81, %82, %83, %84, %85, %86, %87, %88, %89, %90, %91, %92, %93, %94, %95}, %96, %97, p, 1, 1, 0, %99;\n}\n"
        : "+f"(d[0]), "+f"(d[1]), "+f"(d[2]), "+f"(d[3]), "+f"(d[4]), "+f"(d[5]), "+f"(d[6]), "+f"(d[7]), "+f"(d[8]), "+f"(d[9]), "+f"(d[10]), "+f"(d[11]), "+f"(d[12]), "+f"(d[13]), "+f"(d[14]), "+f"(d[15]), "+f"(d[16]), "+f"(d[17]), "+f"(d[18]), "+f"(d[19]), "+f"(d[20]), "+f"(d[21]), "+f"(d[22]), "+f"(d[23]), "+f"(d[24]), "+f"(d[25]), "+f"(d[26]), "+f"(d[27]), "+f"(d[28]), "+f"(d[29]), "+f"(d[30]), "+f"(d[31]), "+f"(d[32]), "+f"(d[33]), "+f"(d[34]), "+f"(d[35]), "+f"(d[36]), "+f"(d[37]), "+f"(d[38]), "+f"(d[39]), "+f"(d[40]), "+f"(d[41]), "+f"(d[42]), "+f"(d[43]), "+f"(d[44]), "+f"(d[45]), "+f"(d[46]), "+f"(d[47]), "+f"(d[48]), "+f"(d[49]), "+f"(d[50]), "+f"(d[51]), "+f"(d[52]), "+f"(d[53]), "+f"(d[54]), "+f"(d[55]), "+f"(d[56]), "+f"(d[57]), "+f"(d[58]), "+f"(d[59]), "+f"(d[60]), "+f"(d[61]), "+f"(d[62]), "+f"(d[63]), "+f"(d[64]), "+f"(d[65]), "+f"(d[66]), "+f"(d[67]), "+f"(d[68]), "+f"(d[69]), "+f"(d[70]), "+f"(d[71]), "+f"(d[72]), "+f"(d[73]), "+f"(d[74]), "+f"(d[75]), "+f"(d[76]), "+f"(d[77]), "+f"(d[78]), "+f"(d[79]), "+f"(d[80]), "+f"(d[81]), "+f"(d[82]), "+f"(d[83]), "+f"(d[84]), "+f"(d[85]), "+f"(d[86]), "+f"(d[87]), "+f"(d[88]), "+f"(d[89]), "+f"(d[90]), "+f"(d[91]), "+f"(d[92]), "+f"(d[93]), "+f"(d[94]), "+f"(d[95])
        : "l"(da), "l"(db), "r"(scale_d), "n"(TB));
}

__device__ __forceinline__ uint32_t pack_bf16(float lo, float hi) {
    uint32_t r;
    asm("cvt.rn.bf16x2.f32 %0, %1, %2;" : "=r"(r) : "f"(hi), "f"(lo));
    return r;
}
__device__ __forceinline__ float bf_lo(uint32_t v) { return __uint_as_float(v << 16); }
__device__ __forceinline__ float bf_hi(uint32_t v) { return __uint_as_float(v & 0xffff0000u); }

__device__ __forceinline__ void quad_transpose(uint32_t (&w)[4], int q) {
    const bool o1 = q & 1, o2 = q & 2;
    {
        uint32_t s0 = o1 ? w[0] : w[1], s1 = o1 ? w[2] : w[3];
        s0 = __shfl_xor_sync(0xffffffffu, s0, 1); s1 = __shfl_xor_sync(0xffffffffu, s1, 1);
        if (o1) { w[0] = s0; w[2] = s1; } else { w[1] = s0; w[3] = s1; }
    }
    {
        uint32_t s0 = o2 ? w[0] : w[2], s1 = o2 ? w[1] : w[3];
        s0 = __shfl_xor_sync(0xffffffffu, s0, 2); s1 = __shfl_xor_sync(0xffffffffu, s1, 2);
        if (o2) { w[0] = s0; w[1] = s1; } else { w[2] = s0; w[3] = s1; }
    }
}

__device__ __forceinline__ float ex2(float x) { float y; asm("ex2.approx.ftz.f32 %0, %1;" : "=f"(y) : "f"(x)); return y; }
__device__ __forceinline__ float rcp(float x) { float y; asm("rcp.approx.ftz.f32 %0, %1;" : "=f"(y) : "f"(x)); return y; }

__device__ __forceinline__ float ex2v(float x) { float y; asm volatile("ex2.approx.ftz.f32 %0, %1;" : "=f"(y) : "f"(x)); return y; }
__device__ __forceinline__ float rcpv(float x) { float y; asm volatile("rcp.approx.ftz.f32 %0, %1;" : "=f"(y) : "f"(x)); return y; }
__device__ __forceinline__ float mish_f(float h) {
    const float w = ex2v(-1.4426950408889634f * fabsf(h));
    const float t = w * w;
    const bool pos = h > 0.f;
    const float num = fmaf(2.f, w, pos ? 1.f : t);
    const float den = num + (pos ? t + t : 2.f);
    return h * num * rcpv(den);
}

__device__ unsigned int g_epoch;
__device__ unsigned int g_done;
__device__ unsigned int g_flag_qkv[128];
__device__ unsigned int g_flag_act[128];
__device__ unsigned int g_flag_att[128];

__device__ __forceinline__ void flag_set(unsigned int* f, unsigned int v) {
    asm volatile("st.release.gpu.global.u32 [%0], %1;" :: "l"(f), "r"(v) : "memory");
}
__device__ __forceinline__ void flag_wait(const unsigned int* f, unsigned int v) {
    for (uint32_t it = 0; it < (1u << 22); ++it) {
        unsigned int x;
        asm volatile("ld.acquire.gpu.global.u32 %0, [%1];" : "=r"(x) : "l"(f) : "memory");
        if (x == v) break;
    }
}
__device__ __forceinline__ void fence_proxy_async() { asm volatile("fence.proxy.async;" ::: "memory"); }

__device__ __forceinline__ void ldsm_x4(uint32_t (&r)[4], uint32_t addr) {
    asm volatile("ldmatrix.sync.aligned.m8n8.x4.shared.b16 {%0,%1,%2,%3}, [%4];"
                 : "=r"(r[0]), "=r"(r[1]), "=r"(r[2]), "=r"(r[3]) : "r"(addr));
}
__device__ __forceinline__ void ldsm_x4_t(uint32_t (&r)[4], uint32_t addr) {
    asm volatile("ldmatrix.sync.aligned.m8n8.x4.trans.shared.b16 {%0,%1,%2,%3}, [%4];"
                 : "=r"(r[0]), "=r"(r[1]), "=r"(r[2]), "=r"(r[3]) : "r"(addr));
}
__device__ __forceinline__ void mma16816(float (&d)[4], const uint32_t (&a)[4], uint32_t b0, uint32_t b1) {
    asm volatile("mma.sync.aligned.m16n8k16.row.col.f32.bf16.bf16.f32 {%0,%1,%2,%3}, {%4,%5,%6,%7}, {%8,%9}, {%0,%1,%2,%3};"
                 : "+f"(d[0]), "+f"(d[1]), "+f"(d[2]), "+f"(d[3])
                 : "r"(a[0]), "r"(a[1]), "r"(a[2]), "r"(a[3]), "r"(b0), "r"(b1));
}
__device__ __forceinline__ void mma16816_z(float (&d)[4], const uint32_t (&a)[4], uint32_t b0, uint32_t b1) {
    asm volatile("mma.sync.aligned.m16n8k16.row.col.f32.bf16.bf16.f32 {%0,%1,%2,%3}, {%4,%5,%6,%7}, {%8,%9}, {%10,%10,%10,%10};"
                 : "=f"(d[0]), "=f"(d[1]), "=f"(d[2]), "=f"(d[3])
                 : "r"(a[0]), "r"(a[1]), "r"(a[2]), "r"(a[3]), "r"(b0), "r"(b1), "f"(0.f));
}

constexpr int KV_PITCH = 128;

template <int EDGE>
__device__ __forceinline__ void score_block(float (&s)[2][4], const uint32_t (&qa)[4], uint32_t kaddr, int r0, int c0)
{
    uint32_t kf[4];
    ldsm_x4(kf, kaddr);
    mma16816_z(s[0], qa, kf[0], kf[1]);
    mma16816_z(s[1], qa, kf[2], kf[3]);
    if (EDGE != 0) {
#pragma unroll
        for (int t = 0; t < 2; t++)
#pragma unroll
            for (int e = 0; e < 4; e++) {
                const int r = r0 + (e >> 1) * 8, c = t * 8 + c0 + (e & 1);
                if (EDGE == 1 ? (c <= r) : (c > r)) s[t][e] = -1e30f;
            }
    }
}
__device__ __forceinline__ void max_block(const float (&s)[2][4], float& m0, float& m1) {
    m0 = fmaxf(m0, fmaxf(fmaxf(s[0][0], s[0][1]), fmaxf(s[1][0], s[1][1])));
    m1 = fmaxf(m1, fmaxf(fmaxf(s[0][2], s[0][3]), fmaxf(s[1][2], s[1][3])));
}
__device__ __forceinline__ void pv_block(const float (&s)[2][4], float mc0, float mc1, float& l0, float& l1,
                                         float (&o)[2][4], uint32_t vaddr) {
    const float C = 0.25f * 1.4426950408889634f;
    uint32_t pa[4];
#pragma unroll
    for (int t = 0; t < 2; t++) {
        const float p0 = ex2(fmaf(s[t][0], C, -mc0)), p1 = ex2(fmaf(s[t][1], C, -mc0));
        const float p2 = ex2(fmaf(s[t][2], C, -mc1)), p3 = ex2(fmaf(s[t][3], C, -mc1));
        l0 += p0 + p1; l1 += p2 + p3;
        pa[2 * t] = pack_bf16(p0, p1); pa[2 * t + 1] = pack_bf16(p2, p3);
    }
    uint32_t vf[4];
    ldsm_x4_t(vf, vaddr);
    mma16816(o[0], pa, vf[0], vf[1]);
    mma16816(o[1], pa, vf[2], vf[3]);
}

__device__ __forceinline__ void attn_task(const uint32_t (&qa)[4], uint32_t ka, uint32_t va, int kb0, int lane,
                                          bf16* __restrict__ out  , float g0, float g1)
{
    const float C = 0.25f * 1.4426950408889634f;
    const int r0 = lane >> 2, c0 = (lane & 3) * 2;
    const int kb1 = kb0 > 1 ? kb0 : 1;
    float s[2][4];
    float m0 = -1e30f, m1 = -1e30f;
    if (kb0 == 0) { score_block<1>(s, qa, ka, r0, c0); max_block(s, m0, m1); }
#pragma unroll 3
    for (int kb = kb1; kb < 16; kb++) { score_block<0>(s, qa, ka + kb * 16 * KV_PITCH, r0, c0); max_block(s, m0, m1); }
    score_block<2>(s, qa, ka + 16 * 16 * KV_PITCH, r0, c0); max_block(s, m0, m1);
    m0 = fmaxf(m0, __shfl_xor_sync(0xffffffffu, m0, 1)); m0 = fmaxf(m0, __shfl_xor_sync(0xffffffffu, m0, 2));
    m1 = fmaxf(m1, __shfl_xor_sync(0xffffffffu, m1, 1)); m1 = fmaxf(m1, __shfl_xor_sync(0xffffffffu, m1, 2));
    const float mc0 = m0 * C, mc1 = m1 * C;
    float l0 = 0.f, l1 = 0.f;
    float o[2][4] = {{0.f, 0.f, 0.f, 0.f}, {0.f, 0.f, 0.f, 0.f}};
    if (kb0 == 0) { score_block<1>(s, qa, ka, r0, c0); pv_block(s, mc0, mc1, l0, l1, o, va); }
#pragma unroll 3
    for (int kb = kb1; kb < 16; kb++) {
        score_block<0>(s, qa, ka + kb * 16 * KV_PITCH, r0, c0);
        pv_block(s, mc0, mc1, l0, l1, o, va + kb * 16 * KV_PITCH);
    }
    score_block<2>(s, qa, ka + 16 * 16 * KV_PITCH, r0, c0); pv_block(s, mc0, mc1, l0, l1, o, va + 16 * 16 * KV_PITCH);
    l0 += __shfl_xor_sync(0xffffffffu, l0, 1); l0 += __shfl_xor_sync(0xffffffffu, l0, 2);
    l1 += __shfl_xor_sync(0xffffffffu, l1, 1); l1 += __shfl_xor_sync(0xffffffffu, l1, 2);
    const float f0 = g0 / l0, f1 = g1 / l1;
#pragma unroll
    for (int t = 0; t < 2; t++) {
        *(uint32_t*)(out + (size_t)r0 * KA2 + t * 8 + c0) = pack_bf16(o[t][0] * f0, o[t][1] * f0);
        *(uint32_t*)(out + (size_t)(r0 + 8) * KA2 + t * 8 + c0) = pack_bf16(o[t][2] * f1, o[t][3] * f1);
    }
}

constexpr int P1_STAGES = 3;
constexpr int P1_STAGE  = 16384 + 24576;
constexpr int P2_STAGES = 5;
constexpr int P2_STAGE  = 16384 + 8192;
constexpr int P2_KSTEPS = 30;
constexpr int OFF_KV    = P1_STAGES * P1_STAGE;
constexpr int OFF_MISC  = OFF_KV + 2 * 384 * KV_PITCH;
constexpr int FUSED_SMEM = OFF_MISC + 2048 + 1024;

__global__ void __launch_bounds__(512, 1)
fused_kernel(const __grid_constant__ CUtensorMap tmX, const __grid_constant__ CUtensorMap tmWqkv,
             const __grid_constant__ CUtensorMap tmW1, const __grid_constant__ CUtensorMap tmQKV,
             const __grid_constant__ CUtensorMap tmA2, const __grid_constant__ CUtensorMap tmWo,
             const __grid_constant__ CUtensorMap tmW2,
             const bf16* __restrict__ b1, const bf16* __restrict__ gate_w,
             const bf16* __restrict__ w1p, const bf16* __restrict__ wqkvp,
             const bf16* __restrict__ w2p, const bf16* __restrict__ wop, bf16* __restrict__ out)
{
    extern __shared__ uint8_t smem_raw[];
    const uint32_t sbase = (smem_u32(smem_raw) + 1023u) & ~1023u;
    uint8_t* sgen = smem_raw + (sbase - smem_u32(smem_raw));
    const uint32_t sK = sbase + OFF_KV, sV = sK + 384 * KV_PITCH;
    const uint32_t sBar = sbase + OFF_MISC;
    const uint32_t full1 = sBar, empty1 = sBar + 32, full2 = sBar + 64, empty2 = sBar + 104, kv_full = sBar + 144;
    float* sGate = (float*)(sgen + OFF_MISC + 256);
    uint8_t* sGw = sgen + OFF_MISC + 768;
    uint32_t* sBias = (uint32_t*)(sgen + OFF_MISC + 1792);

    const int rb = blockIdx.x >> 3, j = blockIdx.x & 7;
    const int tid = threadIdx.x, wg = tid >> 7, warp = tid >> 5, lane = tid & 31;
    TS(0, tid == 0);

    if (tid == 0) {
        for (int i = 0; i < P1_STAGES; i++) { mbar_init(full1 + 8 * i, 1); mbar_init(empty1 + 8 * i, 8); }
        for (int i = 0; i < P2_STAGES; i++) { mbar_init(full2 + 8 * i, 1); mbar_init(empty2 + 8 * i, 8); }
        mbar_init(kv_full, 1);
        fence_barrier_init();
    }
    __syncthreads();
    const unsigned int ep = *(volatile unsigned int*)&g_epoch + 1;

    if (wg >= 2) {
        reg_dealloc<104>();
        if (warp == 15) {
            if (lane == 0) {
                for (int it = 0; it < 16; it++) {
                    const int st = it % P1_STAGES;
                    if (it >= P1_STAGES) mbar_wait(empty1 + 8 * st, ((it / P1_STAGES) - 1) & 1);
                    mbar_expect_tx(full1 + 8 * st, P1_STAGE);
                    const uint32_t dst = sbase + st * P1_STAGE;
                    const int kc = it & 7;
                    tma_load_2d(dst, &tmX, kc * 64, rb * 128, full1 + 8 * st);
                    if (it < 8) {
                        for (int b = 0; b < 3; b++) tma_load_2d(dst + 16384 + b * 8192, &tmWqkv, b * 512 + j * 64, kc * 64, full1 + 8 * st);
                    } else {
                        for (int b = 0; b < 3; b++) tma_load_2d(dst + 16384 + b * 8192, &tmW1, j * FCH + b * 64, kc * 64, full1 + 8 * st);
                    }
                }
                for (int it = 13; it < 16; it++) mbar_wait(empty1 + 8 * (it % P1_STAGES), (it / P1_STAGES) & 1);
                for (int i = 0; i < 8; i++) flag_wait(&g_flag_act[rb * 8 + i], ep);
                fence_proxy_async();
                for (int ks = 0; ks < P2_KSTEPS; ks++) {
                    const int st = ks % P2_STAGES;
                    if (ks >= P2_STAGES) mbar_wait(empty2 + 8 * st, ((ks / P2_STAGES) - 1) & 1);
                    if (ks == 22) {
                        for (int i = 0; i < 8; i++) flag_wait(&g_flag_att[rb * 8 + i], ep);
                        fence_proxy_async();
                    }
                    mbar_expect_tx(full2 + 8 * st, P2_STAGE);
                    const uint32_t dst = sbase + st * P2_STAGE;
                    if (ks < 22) {
                        tma_load_2d(dst, &tmA2, D_ + ks * 64, rb * 128, full2 + 8 * st);
                        tma_load_2d(dst + 16384, &tmW2, j * 64, ks * 64, full2 + 8 * st);
                    } else {
                        tma_load_2d(dst, &tmA2, (ks - 22) * 64, rb * 128, full2 + 8 * st);
                        tma_load_2d(dst + 16384, &tmWo, j * 64, (ks - 22) * 64, full2 + 8 * st);
                    }
                }
            }
        } else {
            if (tid == 288) {
                const int b = blockIdx.x;
                l2_prefetch((const uint8_t*)wqkvp + b * 12288, 12288);
                l2_prefetch((const uint8_t*)w1p + b * 11008, 11008);
                l2_prefetch((const uint8_t*)w2p + b * 11008, 11008);
                l2_prefetch((const uint8_t*)wop + b * 4096, 4096);
            }
            bar_sync(3, 256 + 224);
            if (tid == 256) {
                const int nblk = rb >= 2 ? 3 : rb + 1;
                for (int i = 0; i < nblk; i++) flag_wait(&g_flag_qkv[(rb - i) * 8 + j], ep);
                fence_proxy_async();
                mbar_expect_tx(kv_full, nblk * 2 * 16384);
                for (int i = 0; i < nblk; i++) {
                    const int row = j * S_ + (rb - i) * 128;
                    tma_load_2d(sK + (2 - i) * 16384, &tmQKV, 64, row, kv_full);
                    tma_load_2d(sV + (2 - i) * 16384, &tmQKV, 128, row, kv_full);
                }
            }
            __syncwarp();
            const int r0 = lane >> 2, c0 = (lane & 3) * 2;
            mbar_wait(kv_full, 0);
            TS(6, tid == 256);
#pragma unroll 1
            for (int task = warp - 8; task < 32; task += 7) {
                const int qt = task & 7, hl = task >> 3;
                const int q0g = rb * 128 + qt * 16;
                const float g0 = sGate[qt * 16 + r0], g1 = sGate[qt * 16 + r0 + 8];
                const int kb0 = q0g < 256 ? (256 - q0g) >> 4 : 0;
                const bf16* qsrc = g_qkv + ((size_t)j * S_ + q0g) * 192;
                uint32_t qa[4];
                qa[0] = *(const volatile uint32_t*)(qsrc + (size_t)r0 * 192 + hl * 16 + c0);
                qa[1] = *(const volatile uint32_t*)(qsrc + (size_t)(r0 + 8) * 192 + hl * 16 + c0);
                qa[2] = *(const volatile uint32_t*)(qsrc + (size_t)r0 * 192 + hl * 16 + c0 + 8);
                qa[3] = *(const volatile uint32_t*)(qsrc + (size_t)(r0 + 8) * 192 + hl * 16 + c0 + 8);
                const int krow = qt * 16 + (lane & 7) + ((lane >> 4) << 3);
                const uint32_t ka = sK + krow * KV_PITCH + (((2 * hl + ((lane >> 3) & 1)) ^ (lane & 7)) << 4);
                const int vrow = qt * 16 + (lane & 15);
                const uint32_t va = sV + vrow * KV_PITCH + (((2 * hl + (lane >> 4)) ^ (lane & 7)) << 4);
                attn_task(qa, ka, va, kb0, lane, g_a2 + (size_t)q0g * KA2 + (j * 4 + hl) * 16, g0, g1);
            }
            TS(7, tid == 256);
            __threadfence();
            fence_proxy_async();
            bar_sync(4, 224);
            if (tid == 256) flag_set(&g_flag_att[blockIdx.x], ep);
        }
    } else {
        reg_alloc<152>();
        const int t128 = tid & 127, w4 = warp & 3, q = lane & 3;
        if (tid < 64) ((uint4*)sGw)[tid] = __ldg((const uint4*)gate_w + tid);
        else if (tid < 64 + 88) {
            const int c = j * FCH + (tid - 64) * 2;
            sBias[tid - 64] = c < F_ ? __ldg((const uint32_t*)(b1 + c)) : 0u;
        }
        bar_sync(1, 256);
        const int rl = wg * 64 + w4 * 16 + (lane >> 2);
        {
            float acc[96];
            float gs = 0.f;
            const int grow = wg * 64 + (t128 >> 1), ghalf = t128 & 1;
#pragma unroll
            for (int kc = 0; kc < 8; kc++) {
                const int st = kc % P1_STAGES;
                const uint32_t sa = sbase + st * P1_STAGE;
                mbar_wait(full1 + 8 * st, (kc / P1_STAGES) & 1);
                TS(1, tid == 0 && kc == 0);
                wgmma_fence();
#pragma unroll
                for (int k16 = 0; k16 < 4; k16++)
                    wgmma_n192<1>(acc, make_desc(sa + wg * 8192 + k16 * 32, 16, 1024),
                                  make_desc(sa + 16384 + k16 * 2048, 8192, 1024), (kc | k16) != 0);
                wgmma_commit();
#pragma unroll
                for (int c = 0; c < 4; c++) {
                    const int cc = ghalf * 4 + c;
                    const uint4 xv = *(const uint4*)(sgen + st * P1_STAGE + grow * 128 + ((cc ^ (grow & 7)) << 4));
                    const uint4 gv = *(const uint4*)(sGw + kc * 128 + cc * 16);
                    gs = fmaf(bf_lo(xv.x), bf_lo(gv.x), gs); gs = fmaf(bf_hi(xv.x), bf_hi(gv.x), gs);
                    gs = fmaf(bf_lo(xv.y), bf_lo(gv.y), gs); gs = fmaf(bf_hi(xv.y), bf_hi(gv.y), gs);
                    gs = fmaf(bf_lo(xv.z), bf_lo(gv.z), gs); gs = fmaf(bf_hi(xv.z), bf_hi(gv.z), gs);
                    gs = fmaf(bf_lo(xv.w), bf_lo(gv.w), gs); gs = fmaf(bf_hi(xv.w), bf_hi(gv.w), gs);
                }
                if (kc > 0) { wgmma_wait<1>(); if (lane == 0) mbar_arrive(empty1 + 8 * ((kc - 1) % P1_STAGES)); }
            }
            gs += __shfl_xor_sync(0xffffffffu, gs, 1);
            if (ghalf == 0) sGate[grow] = 1.f / (1.f + __expf(-gs));
            wgmma_wait<0>();
            if (lane == 0) mbar_arrive(empty1 + 8 * (7 % P1_STAGES));
            TS(2, tid == 0);
            bf16* orow0 = g_qkv + ((size_t)j * S_ + rb * 128 + rl) * 192;
            bf16* orow1 = orow0 + 8 * 192;
#pragma unroll
            for (int u = 0; u < 6; u++) {
                uint32_t w0[4], w1[4];
#pragma unroll
                for (int i = 0; i < 4; i++) {
                    const int t = u * 4 + i;
                    w0[i] = pack_bf16(acc[t * 4 + 0], acc[t * 4 + 1]);
                    w1[i] = pack_bf16(acc[t * 4 + 2], acc[t * 4 + 3]);
                }
                quad_transpose(w0, q);
                quad_transpose(w1, q);
                const int c = (u * 4 + q) * 8;
                *(uint4*)(orow0 + c) = make_uint4(w0[0], w0[1], w0[2], w0[3]);
                *(uint4*)(orow1 + c) = make_uint4(w1[0], w1[1], w1[2], w1[3]);
            }
            __threadfence();
            fence_proxy_async();
            bar_sync(3, 256 + 224);
            if (tid == 0) flag_set(&g_flag_qkv[blockIdx.x], ep);
            TS(3, tid == 0);
        }
        {
            float acc[88];
#pragma unroll
            for (int kc = 0; kc < 8; kc++) {
                const int it = kc + 8, st = it % P1_STAGES;
                const uint32_t sa = sbase + st * P1_STAGE;
                mbar_wait(full1 + 8 * st, (it / P1_STAGES) & 1);
                wgmma_fence();
#pragma unroll
                for (int k16 = 0; k16 < 4; k16++)
                    wgmma_n176<1>(acc, make_desc(sa + wg * 8192 + k16 * 32, 16, 1024),
                                  make_desc(sa + 16384 + k16 * 2048, 8192, 1024), (kc | k16) != 0);
                wgmma_commit();
                if (kc > 0) { wgmma_wait<1>(); if (lane == 0) mbar_arrive(empty1 + 8 * ((it - 1) % P1_STAGES)); }
            }
            wgmma_wait<0>();
            if (lane == 0) mbar_arrive(empty1 + 8 * (15 % P1_STAGES));
            TS(4, tid == 0);
            const int n0 = j * FCH;
            const float om0 = 1.f - sGate[rl], om1 = 1.f - sGate[rl + 8];
            bf16* frow0 = g_a2 + (size_t)(rb * 128 + rl) * KA2 + D_ + n0;
            bf16* frow1 = frow0 + 8 * KA2;
#pragma unroll
            for (int u = 0; u < 6; u++) {
                uint32_t w0[4], w1[4];
#pragma unroll
                for (int i = 0; i < 4; i++) {
                    const int t = u * 4 + i;
                    if (t < 22) {
                        const uint32_t bv = sBias[t * 4 + q];
                        const float bb0 = bf_lo(bv), bb1 = bf_hi(bv);
                        w0[i] = pack_bf16(mish_f(acc[t * 4 + 0] + bb0) * om0, mish_f(acc[t * 4 + 1] + bb1) * om0);
                        w1[i] = pack_bf16(mish_f(acc[t * 4 + 2] + bb0) * om1, mish_f(acc[t * 4 + 3] + bb1) * om1);
                    } else { w0[i] = 0; w1[i] = 0; }
                }
                quad_transpose(w0, q);
                quad_transpose(w1, q);
                const int c = (u * 4 + q) * 8;
                if (c < FCH && n0 + c < F_) {
                    *(uint4*)(frow0 + c) = make_uint4(w0[0], w0[1], w0[2], w0[3]);
                    *(uint4*)(frow1 + c) = make_uint4(w1[0], w1[1], w1[2], w1[3]);
                }
            }
            __threadfence();
            fence_proxy_async();
            bar_sync(1, 256);
            if (tid == 0) flag_set(&g_flag_act[blockIdx.x], ep);
            TS(5, tid == 0);
        }
        {
            float acc[32];
            for (int ks = 0; ks < P2_KSTEPS; ks++) {
                const int st = ks % P2_STAGES;
                const uint32_t sa = sbase + st * P2_STAGE;
                mbar_wait(full2 + 8 * st, (ks / P2_STAGES) & 1);
                TS(8, tid == 0 && ks == 0); TS(9, tid == 0 && ks == 22);
                wgmma_fence();
#pragma unroll
                for (int k16 = 0; k16 < 4; k16++)
                    wgmma_n64<1>(acc, make_desc(sa + wg * 8192 + k16 * 32, 16, 1024),
                                 make_desc(sa + 16384 + k16 * 2048, 8192, 1024), (ks | k16) != 0);
                wgmma_commit();
                if (ks > 0) { wgmma_wait<1>(); if (lane == 0) mbar_arrive(empty2 + 8 * ((ks - 1) % P2_STAGES)); }
            }
            wgmma_wait<0>();
            TS(10, tid == 0);
            bf16* orow0 = out + (size_t)(rb * 128 + rl) * D_ + j * 64;
            bf16* orow1 = orow0 + 8 * D_;
#pragma unroll
            for (int u = 0; u < 2; u++) {
                uint32_t w0[4], w1[4];
#pragma unroll
                for (int i = 0; i < 4; i++) {
                    const int t = u * 4 + i;
                    w0[i] = pack_bf16(acc[t * 4 + 0], acc[t * 4 + 1]);
                    w1[i] = pack_bf16(acc[t * 4 + 2], acc[t * 4 + 3]);
                }
                quad_transpose(w0, q);
                quad_transpose(w1, q);
                const int c = (u * 4 + q) * 8;
                *(uint4*)(orow0 + c) = make_uint4(w0[0], w0[1], w0[2], w0[3]);
                *(uint4*)(orow1 + c) = make_uint4(w1[0], w1[1], w1[2], w1[3]);
            }
            TS(11, tid == 0);
        }
        if (tid == 0) {
            __threadfence();
            if (atomicAdd(&g_done, 1u) == gridDim.x - 1) {
                g_done = 0;
                __threadfence();
                atomicAdd(&g_epoch, 1u);
            }
        }
    }
}

typedef CUresult (*PFN_encodeTiled)(CUtensorMap*, CUtensorMapDataType, cuuint32_t, void*, const cuuint64_t*,
                                    const cuuint64_t*, const cuuint32_t*, const cuuint32_t*, CUtensorMapInterleave,
                                    CUtensorMapSwizzle, CUtensorMapL2promotion, CUtensorMapFloatOOBfill);

static void make_map(PFN_encodeTiled enc, CUtensorMap* m, const void* ptr, uint64_t cols, uint64_t rows,
                     uint32_t box_cols, uint32_t box_rows)
{
    cuuint64_t dims[2] = {cols, rows};
    cuuint64_t strides[1] = {cols * 2};
    cuuint32_t box[2] = {box_cols, box_rows};
    cuuint32_t es[2] = {1, 1};
    enc(m, CU_TENSOR_MAP_DATA_TYPE_BFLOAT16, 2, const_cast<void*>(ptr), dims, strides, box, es,
        CU_TENSOR_MAP_INTERLEAVE_NONE, CU_TENSOR_MAP_SWIZZLE_128B, CU_TENSOR_MAP_L2_PROMOTION_L2_128B,
        CU_TENSOR_MAP_FLOAT_OOB_FILL_NONE);
}

extern "C" void kernel_launch(void* const* d_in, const int* in_sizes, int n_in, void* d_out, int out_size)
{
    const bf16* x    = (const bf16*)d_in[0];
    const bf16* wqkv = (const bf16*)d_in[1];
    const bf16* wo   = (const bf16*)d_in[2];
    const bf16* w1   = (const bf16*)d_in[4];
    const bf16* b1   = (const bf16*)d_in[5];
    const bf16* w2   = (const bf16*)d_in[6];
    const bf16* gw   = (const bf16*)d_in[7];

    static PFN_encodeTiled enc = nullptr;
    if (!enc) {
        void* fn = nullptr;
        cudaDriverEntryPointQueryResult qr;
        cudaGetDriverEntryPoint("cuTensorMapEncodeTiled", &fn, cudaEnableDefault, &qr);
        enc = (PFN_encodeTiled)fn;
        cudaFuncSetAttribute(fused_kernel, cudaFuncAttributeMaxDynamicSharedMemorySize, FUSED_SMEM);
    }
    void *a2p = nullptr, *qkvp = nullptr;
    cudaGetSymbolAddress(&a2p, g_a2);
    cudaGetSymbolAddress(&qkvp, g_qkv);
    CUtensorMap tmX, tmWqkv, tmW1, tmQKV, tmA2, tmWo, tmW2;
    make_map(enc, &tmX, x, D_, S_, 64, 128);
    make_map(enc, &tmWqkv, wqkv, 3 * D_, D_, 64, 64);
    make_map(enc, &tmW1, w1, F_, D_, 64, 64);
    make_map(enc, &tmQKV, qkvp, 192, 8 * S_, 64, 128);
    make_map(enc, &tmA2, a2p, KA2, S_, 64, 128);
    make_map(enc, &tmWo, wo, D_, D_, 64, 64);
    make_map(enc, &tmW2, w2, D_, F_, 64, 64);

    fused_kernel<<<128, 512, FUSED_SMEM, cudaStreamPerThread>>>(tmX, tmWqkv, tmW1, tmQKV, tmA2, tmWo, tmW2,
                                                                b1, gw, w1, wqkv, w2, wo, (bf16*)d_out);
}
```

```cpp
#include <cuda_runtime.h>
#include <cuda_bf16.h>
#include <cuda.h>
#include <stdint.h>

typedef __nv_bfloat16 bf16;

constexpr int S_ = 2048, D_ = 512, F_ = 1376;
constexpr int KA2 = D_ + F_;
constexpr int FCH = 176;

__device__ bf16  g_qkv[8 * S_ * 192];
__device__ bf16  g_a2[S_ * KA2];
__device__ float g_gate[S_];

#define TS(k, cond) do { } while (0)

__device__ __forceinline__ uint32_t smem_u32(const void* p) { return (uint32_t)__cvta_generic_to_shared(p); }
__device__ __forceinline__ void mbar_init(uint32_t bar, uint32_t count) {
    asm volatile("mbarrier.init.shared::cta.b64 [%0], %1;" :: "r"(bar), "r"(count) : "memory");
}
__device__ __forceinline__ void mbar_expect_tx(uint32_t bar, uint32_t bytes) {
    asm volatile("mbarrier.arrive.expect_tx.shared::cta.b64 _, [%0], %1;" :: "r"(bar), "r"(bytes) : "memory");
}
__device__ __forceinline__ void mbar_arrive(uint32_t bar) {
    asm volatile("mbarrier.arrive.shared::cta.b64 _, [%0];" :: "r"(bar) : "memory");
}
__device__ __forceinline__ bool mbar_try_wait(uint32_t bar, uint32_t parity) {
    uint32_t ok;
    asm volatile("{\n.reg .pred p;\nmbarrier.try_wait.parity.shared::cta.b64 p, [%1], %2;\nselp.u32 %0, 1, 0, p;\n}"
                 : "=r"(ok) : "r"(bar), "r"(parity) : "memory");
    return ok != 0;
}
__device__ __forceinline__ void mbar_wait(uint32_t bar, uint32_t parity) {
    for (uint32_t it = 0; it < (1u << 22); ++it) { if (mbar_try_wait(bar, parity)) break; }
}
__device__ __forceinline__ void tma_load_2d(uint32_t dst, const CUtensorMap* map, int c0, int c1, uint32_t bar) {
    asm volatile("cp.async.bulk.tensor.2d.shared::cluster.global.mbarrier::complete_tx::bytes [%0], [%1, {%3, %4}], [%2];"
                 :: "r"(dst), "l"(map), "r"(bar), "r"(c0), "r"(c1) : "memory");
}
__device__ __forceinline__ void l2_prefetch(const void* p, uint32_t bytes) {
    asm volatile("cp.async.bulk.prefetch.L2.global [%0], %1;" :: "l"(p), "r"(bytes) : "memory");
}
__device__ __forceinline__ void fence_barrier_init() { asm volatile("fence.mbarrier_init.release.cluster;" ::: "memory"); }
__device__ __forceinline__ void wgmma_fence()  { asm volatile("wgmma.fence.sync.aligned;" ::: "memory"); }
__device__ __forceinline__ void wgmma_commit() { asm volatile("wgmma.commit_group.sync.aligned;" ::: "memory"); }
template <int N> __device__ __forceinline__ void wgmma_wait() { asm volatile("wgmma.wait_group.sync.aligned %0;" :: "n"(N) : "memory"); }
template <int R> __device__ __forceinline__ void reg_alloc()   { asm volatile("setmaxnreg.inc.sync.aligned.u32 %0;" :: "n"(R)); }
template <int R> __device__ __forceinline__ void reg_dealloc() { asm volatile("setmaxnreg.dec.sync.aligned.u32 %0;" :: "n"(R)); }
__device__ __forceinline__ void bar_sync(int id, int n)   { asm volatile("bar.sync %0, %1;" :: "r"(id), "r"(n) : "memory"); }
__device__ __forceinline__ void bar_arrive(int id, int n) { asm volatile("bar.arrive %0, %1;" :: "r"(id), "r"(n) : "memory"); }

__device__ __forceinline__ uint64_t make_desc(uint32_t addr, uint32_t lbo, uint32_t sbo) {
    uint64_t d = (uint64_t)((addr & 0x3FFFF) >> 4);
    d |= (uint64_t)((lbo & 0x3FFFF) >> 4) << 16;
    d |= (uint64_t)((sbo & 0x3FFFF) >> 4) << 32;
    d |= (uint64_t)1 << 62;
    return d;
}

template <int TB>
__device__ __forceinline__ void wgmma_n64(float (&d)[32], uint64_t da, uint64_t db, int scale_d) {
    asm volatile("{\n.reg .pred p;\nsetp.ne.b32 p, %34, 0;\n"
        "wgmma.mma_async.sync.aligned.m64n64k16.f32.bf16.bf16 {%0, %1, %2, %3, %4, %5, %6, %7, %8, %9, %10, %11, %12, %13, %14, %15, %16, %17, %18, %19, %20, %21, %22, %23, %24, %25, %26, %27, %28, %29, %30, %31}, %32, %33, p, 1, 1, 0, %35;\n}\n"
        : "+f"(d[0]), "+f"(d[1]), "+f"(d[2]), "+f"(d[3]), "+f"(d[4]), "+f"(d[5]), "+f"(d[6]), "+f"(d[7]), "+f"(d[8]), "+f"(d[9]), "+f"(d[10]), "+f"(d[11]), "+f"(d[12]), "+f"(d[13]), "+f"(d[14]), "+f"(d[15]), "+f"(d[16]), "+f"(d[17]), "+f"(d[18]), "+f"(d[19]), "+f"(d[20]), "+f"(d[21]), "+f"(d[22]), "+f"(d[23]), "+f"(d[24]), "+f"(d[25]), "+f"(d[26]), "+f"(d[27]), "+f"(d[28]), "+f"(d[29]), "+f"(d[30]), "+f"(d[31])
        : "l"(da), "l"(db), "r"(scale_d), "n"(TB));
}

template <int TB>
__device__ __forceinline__ void wgmma_n128(float (&d)[64], uint64_t da, uint64_t db, int scale_d) {
    asm volatile("{\n.reg .pred p;\nsetp.ne.b32 p, %66, 0;\n"
        "wgmma.mma_async.sync.aligned.m64n128k16.f32.bf16.bf16 {%0, %1, %2, %3, %4, %5, %6, %7, %8, %9, %10, %11, %12, %13, %14, %15, %16, %17, %18, %19, %20, %21, %22, %23, %24, %25, %26, %27, %28, %29, %30, %31, %32, %33, %34, %35, %36, %37, %38, %39, %40, %41, %42, %43, %44, %45, %46, %47, %48, %49, %50, %51, %52, %53, %54, %55, %56, %57, %58, %59, %60, %61, %62, %63}, %64, %65, p, 1, 1, 0, %67;\n}\n"
        : "+f"(d[0]), "+f"(d[1]), "+f"(d[2]), "+f"(d[3]), "+f"(d[4]), "+f"(d[5]), "+f"(d[6]), "+f"(d[7]), "+f"(d[8]), "+f"(d[9]), "+f"(d[10]), "+f"(d[11]), "+f"(d[12]), "+f"(d[13]), "+f"(d[14]), "+f"(d[15]), "+f"(d[16]), "+f"(d[17]), "+f"(d[18]), "+f"(d[19]), "+f"(d[20]), "+f"(d[21]), "+f"(d[22]), "+f"(d[23]), "+f"(d[24]), "+f"(d[25]), "+f"(d[26]), "+f"(d[27]), "+f"(d[28]), "+f"(d[29]), "+f"(d[30]), "+f"(d[31]), "+f"(d[32]), "+f"(d[33]), "+f"(d[34]), "+f"(d[35]), "+f"(d[36]), "+f"(d[37]), "+f"(d[38]), "+f"(d[39]), "+f"(d[40]), "+f"(d[41]), "+f"(d[42]), "+f"(d[43]), "+f"(d[44]), "+f"(d[45]), "+f"(d[46]), "+f"(d[47]), "+f"(d[48]), "+f"(d[49]), "+f"(d[50]), "+f"(d[51]), "+f"(d[52]), "+f"(d[53]), "+f"(d[54]), "+f"(d[55]), "+f"(d[56]), "+f"(d[57]), "+f"(d[58]), "+f"(d[59]), "+f"(d[60]), "+f"(d[61]), "+f"(d[62]), "+f"(d[63])
        : "l"(da), "l"(db), "r"(scale_d), "n"(TB));
}

template <int TB>
__device__ __forceinline__ void wgmma_n176(float (&d)[88], uint64_t da, uint64_t db, int scale_d) {
    asm volatile("{\n.reg .pred p;\nsetp.ne.b32 p, %90, 0;\n"
        "wgmma.mma_async.sync.aligned.m64n176k16.f32.bf16.bf16 {%0, %1, %2, %3, %4, %5, %6, %7, %8, %9, %10, %11, %12, %13, %14, %15, %16, %17, %18, %19, %20, %21, %22, %23, %24, %25, %26, %27, %28, %29, %30, %31, %32, %33, %34, %35, %36, %37, %38, %39, %40, %41, %42, %43, %44, %45, %46, %47, %48, %49, %50, %51, %52, %53, %54, %55, %56, %57, %58, %59, %60, %61, %62, %63, %64, %65, %66, %67, %68, %69, %70, %71, %72, %73, %74, %75, %76, %77, %78, %79, %80, %81, %82, %83, %84, %85, %86, %87}, %88, %89, p, 1, 1, 0, %91;\n}\n"
        : "+f"(d[0]), "+f"(d[1]), "+f"(d[2]), "+f"(d[3]), "+f"(d[4]), "+f"(d[5]), "+f"(d[6]), "+f"(d[7]), "+f"(d[8]), "+f"(d[9]), "+f"(d[10]), "+f"(d[11]), "+f"(d[12]), "+f"(d[13]), "+f"(d[14]), "+f"(d[15]), "+f"(d[16]), "+f"(d[17]), "+f"(d[18]), "+f"(d[19]), "+f"(d[20]), "+f"(d[21]), "+f"(d[22]), "+f"(d[23]), "+f"(d[24]), "+f"(d[25]), "+f"(d[26]), "+f"(d[27]), "+f"(d[28]), "+f"(d[29]), "+f"(d[30]), "+f"(d[31]), "+f"(d[32]), "+f"(d[33]), "+f"(d[34]), "+f"(d[35]), "+f"(d[36]), "+f"(d[37]), "+f"(d[38]), "+f"(d[39]), "+f"(d[40]), "+f"(d[41]), "+f"(d[42]), "+f"(d[43]), "+f"(d[44]), "+f"(d[45]), "+f"(d[46]), "+f"(d[47]), "+f"(d[48]), "+f"(d[49]), "+f"(d[50]), "+f"(d[51]), "+f"(d[52]), "+f"(d[53]), "+f"(d[54]), "+f"(d[55]), "+f"(d[56]), "+f"(d[57]), "+f"(d[58]), "+f"(d[59]), "+f"(d[60]), "+f"(d[61]), "+f"(d[62]), "+f"(d[63]), "+f"(d[64]), "+f"(d[65]), "+f"(d[66]), "+f"(d[67]), "+f"(d[68]), "+f"(d[69]), "+f"(d[70]), "+f"(d[71]), "+f"(d[72]), "+f"(d[73]), "+f"(d[74]), "+f"(d[75]), "+f"(d[76]), "+f"(d[77]), "+f"(d[78]), "+f"(d[79]), "+f"(d[80]), "+f"(d[81]), "+f"(d[82]), "+f"(d[83]), "+f"(d[84]), "+f"(d[85]), "+f"(d[86]), "+f"(d[87])
        : "l"(da), "l"(db), "r"(scale_d), "n"(TB));
}

template <int TB>
__device__ __forceinline__ void wgmma_n192(float (&d)[96], uint64_t da, uint64_t db, int scale_d) {
    asm volatile("{\n.reg .pred p;\nsetp.ne.b32 p, %98, 0;\n"
        "wgmma.mma_async.sync.aligned.m64n192k16.f32.bf16.bf16 {%0, %1, %2, %3, %4, %5, %6, %7, %8, %9, %10, %11, %12, %13, %14, %15, %16, %17, %18, %19, %20, %21, %22, %23, %24, %25, %26, %27, %28, %29, %30, %31, %32, %33, %34, %35, %36, %37, %38, %39, %40, %41, %42, %43, %44, %45, %46, %47, %48, %49, %50, %51, %52, %53, %54, %55, %56, %57, %58, %59, %60, %61, %62, %63, %64, %65, %66, %67, %68, %69, %70, %71, %72, %73, %74, %75, %76, %77, %78, %79, %80, %81, %82, %83, %84, %85, %86, %87, %88, %89, %90, %91, %92, %93, %94, %95}, %96, %97, p, 1, 1, 0, %99;\n}\n"
        : "+f"(d[0]), "+f"(d[1]), "+f"(d[2]), "+f"(d[3]), "+f"(d[4]), "+f"(d[5]), "+f"(d[6]), "+f"(d[7]), "+f"(d[8]), "+f"(d[9]), "+f"(d[10]), "+f"(d[11]), "+f"(d[12]), "+f"(d[13]), "+f"(d[14]), "+f"(d[15]), "+f"(d[16]), "+f"(d[17]), "+f"(d[18]), "+f"(d[19]), "+f"(d[20]), "+f"(d[21]), "+f"(d[22]), "+f"(d[23]), "+f"(d[24]), "+f"(d[25]), "+f"(d[26]), "+f"(d[27]), "+f"(d[28]), "+f"(d[29]), "+f"(d[30]), "+f"(d[31]), "+f"(d[32]), "+f"(d[33]), "+f"(d[34]), "+f"(d[35]), "+f"(d[36]), "+f"(d[37]), "+f"(d[38]), "+f"(d[39]), "+f"(d[40]), "+f"(d[41]), "+f"(d[42]), "+f"(d[43]), "+f"(d[44]), "+f"(d[45]), "+f"(d[46]), "+f"(d[47]), "+f"(d[48]), "+f"(d[49]), "+f"(d[50]), "+f"(d[51]), "+f"(d[52]), "+f"(d[53]), "+f"(d[54]), "+f"(d[55]), "+f"(d[56]), "+f"(d[57]), "+f"(d[58]), "+f"(d[59]), "+f"(d[60]), "+f"(d[61]), "+f"(d[62]), "+f"(d[63]), "+f"(d[64]), "+f"(d[65]), "+f"(d[66]), "+f"(d[67]), "+f"(d[68]), "+f"(d[69]), "+f"(d[70]), "+f"(d[71]), "+f"(d[72]), "+f"(d[73]), "+f"(d[74]), "+f"(d[75]), "+f"(d[76]), "+f"(d[77]), "+f"(d[78]), "+f"(d[79]), "+f"(d[80]), "+f"(d[81]), "+f"(d[82]), "+f"(d[83]), "+f"(d[84]), "+f"(d[85]), "+f"(d[86]), "+f"(d[87]), "+f"(d[88]), "+f"(d[89]), "+f"(d[90]), "+f"(d[91]), "+f"(d[92]), "+f"(d[93]), "+f"(d[94]), "+f"(d[95])
        : "l"(da), "l"(db), "r"(scale_d), "n"(TB));
}

__device__ __forceinline__ uint32_t pack_bf16(float lo, float hi) {
    uint32_t r;
    asm("cvt.rn.bf16x2.f32 %0, %1, %2;" : "=r"(r) : "f"(hi), "f"(lo));
    return r;
}
__device__ __forceinline__ float bf_lo(uint32_t v) { return __uint_as_float(v << 16); }
__device__ __forceinline__ float bf_hi(uint32_t v) { return __uint_as_float(v & 0xffff0000u); }

__device__ __forceinline__ void quad_transpose(uint32_t (&w)[4], int q) {
    const bool o1 = q & 1, o2 = q & 2;
    {
        uint32_t s0 = o1 ? w[0] : w[1], s1 = o1 ? w[2] : w[3];
        s0 = __shfl_xor_sync(0xffffffffu, s0, 1); s1 = __shfl_xor_sync(0xffffffffu, s1, 1);
        if (o1) { w[0] = s0; w[2] = s1; } else { w[1] = s0; w[3] = s1; }
    }
    {
        uint32_t s0 = o2 ? w[0] : w[2], s1 = o2 ? w[1] : w[3];
        s0 = __shfl_xor_sync(0xffffffffu, s0, 2); s1 = __shfl_xor_sync(0xffffffffu, s1, 2);
        if (o2) { w[0] = s0; w[1] = s1; } else { w[2] = s0; w[3] = s1; }
    }
}

__device__ __forceinline__ float ex2(float x) { float y; asm("ex2.approx.ftz.f32 %0, %1;" : "=f"(y) : "f"(x)); return y; }
__device__ __forceinline__ float rcp(float x) { float y; asm("rcp.approx.ftz.f32 %0, %1;" : "=f"(y) : "f"(x)); return y; }

__device__ __forceinline__ float ex2v(float x) { float y; asm volatile("ex2.approx.ftz.f32 %0, %1;" : "=f"(y) : "f"(x)); return y; }
__device__ __forceinline__ float rcpv(float x) { float y; asm volatile("rcp.approx.ftz.f32 %0, %1;" : "=f"(y) : "f"(x)); return y; }
__device__ __forceinline__ float mish_f(float h) {
    const float w = ex2v(-1.4426950408889634f * fabsf(h));
    const float t = w * w;
    const bool pos = h > 0.f;
    const float num = fmaf(2.f, w, pos ? 1.f : t);
    const float den = num + (pos ? t + t : 2.f);
    return h * num * rcpv(den);
}

__device__ unsigned int g_epoch;
__device__ unsigned int g_done;
__device__ unsigned int g_flag_qkv[128];
__device__ unsigned int g_flag_act[128];
__device__ unsigned int g_flag_att[128];

__device__ __forceinline__ void flag_set(unsigned int* f, unsigned int v) {
    asm volatile("st.release.gpu.global.u32 [%0], %1;" :: "l"(f), "r"(v) : "memory");
}
__device__ __forceinline__ void flag_wait(const unsigned int* f, unsigned int v) {
    for (uint32_t it = 0; it < (1u << 22); ++it) {
        unsigned int x;
        asm volatile("ld.acquire.gpu.global.u32 %0, [%1];" : "=r"(x) : "l"(f) : "memory");
        if (x == v) break;
    }
}
__device__ __forceinline__ void fence_proxy_async() { asm volatile("fence.proxy.async;" ::: "memory"); }

__device__ __forceinline__ void ldsm_x4(uint32_t (&r)[4], uint32_t addr) {
    asm("ldmatrix.sync.aligned.m8n8.x4.shared.b16 {%0,%1,%2,%3}, [%4];"
                 : "=r"(r[0]), "=r"(r[1]), "=r"(r[2]), "=r"(r[3]) : "r"(addr));
}
__device__ __forceinline__ void ldsm_x4_t(uint32_t (&r)[4], uint32_t addr) {
    asm("ldmatrix.sync.aligned.m8n8.x4.trans.shared.b16 {%0,%1,%2,%3}, [%4];"
                 : "=r"(r[0]), "=r"(r[1]), "=r"(r[2]), "=r"(r[3]) : "r"(addr));
}
__device__ __forceinline__ void mma16816(float (&d)[4], const uint32_t (&a)[4], uint32_t b0, uint32_t b1) {
    asm("mma.sync.aligned.m16n8k16.row.col.f32.bf16.bf16.f32 {%0,%1,%2,%3}, {%4,%5,%6,%7}, {%8,%9}, {%0,%1,%2,%3};"
                 : "+f"(d[0]), "+f"(d[1]), "+f"(d[2]), "+f"(d[3])
                 : "r"(a[0]), "r"(a[1]), "r"(a[2]), "r"(a[3]), "r"(b0), "r"(b1));
}
__device__ __forceinline__ void mma16816_z(float (&d)[4], const uint32_t (&a)[4], uint32_t b0, uint32_t b1) {
    asm("mma.sync.aligned.m16n8k16.row.col.f32.bf16.bf16.f32 {%0,%1,%2,%3}, {%4,%5,%6,%7}, {%8,%9}, {%10,%10,%10,%10};"
                 : "=f"(d[0]), "=f"(d[1]), "=f"(d[2]), "=f"(d[3])
                 : "r"(a[0]), "r"(a[1]), "r"(a[2]), "r"(a[3]), "r"(b0), "r"(b1), "f"(0.f));
}

constexpr int KV_PITCH = 128;

template <int EDGE>
__device__ __forceinline__ void score_block(float (&s)[2][4], const uint32_t (&qa)[4], uint32_t kaddr, int r0, int c0)
{
    uint32_t kf[4];
    ldsm_x4(kf, kaddr);
    mma16816_z(s[0], qa, kf[0], kf[1]);
    mma16816_z(s[1], qa, kf[2], kf[3]);
    if (EDGE != 0) {
#pragma unroll
        for (int t = 0; t < 2; t++)
#pragma unroll
            for (int e = 0; e < 4; e++) {
                const int r = r0 + (e >> 1) * 8, c = t * 8 + c0 + (e & 1);
                if (EDGE == 1 ? (c <= r) : (c > r)) s[t][e] = -1e30f;
            }
    }
}
__device__ __forceinline__ void max_block(const float (&s)[2][4], float& m0, float& m1) {
    m0 = fmaxf(m0, fmaxf(fmaxf(s[0][0], s[0][1]), fmaxf(s[1][0], s[1][1])));
    m1 = fmaxf(m1, fmaxf(fmaxf(s[0][2], s[0][3]), fmaxf(s[1][2], s[1][3])));
}
__device__ __forceinline__ void pv_block(const float (&s)[2][4], float mc0, float mc1, float& l0, float& l1,
                                         float (&o)[2][4], uint32_t vaddr) {
    const float C = 0.25f * 1.4426950408889634f;
    uint32_t pa[4];
#pragma unroll
    for (int t = 0; t < 2; t++) {
        const float p0 = ex2(fmaf(s[t][0], C, -mc0)), p1 = ex2(fmaf(s[t][1], C, -mc0));
        const float p2 = ex2(fmaf(s[t][2], C, -mc1)), p3 = ex2(fmaf(s[t][3], C, -mc1));
        l0 += p0 + p1; l1 += p2 + p3;
        pa[2 * t] = pack_bf16(p0, p1); pa[2 * t + 1] = pack_bf16(p2, p3);
    }
    uint32_t vf[4];
    ldsm_x4_t(vf, vaddr);
    mma16816(o[0], pa, vf[0], vf[1]);
    mma16816(o[1], pa, vf[2], vf[3]);
}

__device__ __forceinline__ void attn_task(const uint32_t (&qa)[4], uint32_t ka, uint32_t va, int kb0, int lane,
                                          bf16* __restrict__ out  , float g0, float g1)
{
    const float C = 0.25f * 1.4426950408889634f;
    const int r0 = lane >> 2, c0 = (lane & 3) * 2;
    const int kb1 = kb0 > 1 ? kb0 : 1;
    float s[2][4];
    float m0 = -1e30f, m1 = -1e30f;
    if (kb0 == 0) { score_block<1>(s, qa, ka, r0, c0); max_block(s, m0, m1); }
#pragma unroll 3
    for (int kb = kb1; kb < 16; kb++) { score_block<0>(s, qa, ka + kb * 16 * KV_PITCH, r0, c0); max_block(s, m0, m1); }
    score_block<2>(s, qa, ka + 16 * 16 * KV_PITCH, r0, c0); max_block(s, m0, m1);
    m0 = fmaxf(m0, __shfl_xor_sync(0xffffffffu, m0, 1)); m0 = fmaxf(m0, __shfl_xor_sync(0xffffffffu, m0, 2));
    m1 = fmaxf(m1, __shfl_xor_sync(0xffffffffu, m1, 1)); m1 = fmaxf(m1, __shfl_xor_sync(0xffffffffu, m1, 2));
    const float mc0 = m0 * C, mc1 = m1 * C;
    float l0 = 0.f, l1 = 0.f;
    float o[2][4] = {{0.f, 0.f, 0.f, 0.f}, {0.f, 0.f, 0.f, 0.f}};
    if (kb0 == 0) { score_block<1>(s, qa, ka, r0, c0); pv_block(s, mc0, mc1, l0, l1, o, va); }
#pragma unroll 3
    for (int kb = kb1; kb < 16; kb++) {
        score_block<0>(s, qa, ka + kb * 16 * KV_PITCH, r0, c0);
        pv_block(s, mc0, mc1, l0, l1, o, va + kb * 16 * KV_PITCH);
    }
    score_block<2>(s, qa, ka + 16 * 16 * KV_PITCH, r0, c0); pv_block(s, mc0, mc1, l0, l1, o, va + 16 * 16 * KV_PITCH);
    l0 += __shfl_xor_sync(0xffffffffu, l0, 1); l0 += __shfl_xor_sync(0xffffffffu, l0, 2);
    l1 += __shfl_xor_sync(0xffffffffu, l1, 1); l1 += __shfl_xor_sync(0xffffffffu, l1, 2);
    const float f0 = g0 / l0, f1 = g1 / l1;
#pragma unroll
    for (int t = 0; t < 2; t++) {
        *(uint32_t*)(out + (size_t)r0 * KA2 + t * 8 + c0) = pack_bf16(o[t][0] * f0, o[t][1] * f0);
        *(uint32_t*)(out + (size_t)(r0 + 8) * KA2 + t * 8 + c0) = pack_bf16(o[t][2] * f1, o[t][3] * f1);
    }
}

constexpr int P1_STAGES = 3;
constexpr int P1_STAGE  = 16384 + 24576;
constexpr int P2_STAGES = 5;
constexpr int P2_STAGE  = 16384 + 8192;
constexpr int P2_KSTEPS = 30;
constexpr int OFF_KV    = P1_STAGES * P1_STAGE;
constexpr int OFF_MISC  = OFF_KV + 2 * 384 * KV_PITCH;
constexpr int FUSED_SMEM = OFF_MISC + 2048 + 1024;

__global__ void __launch_bounds__(512, 1)
fused_kernel(const __grid_constant__ CUtensorMap tmX, const __grid_constant__ CUtensorMap tmWqkv,
             const __grid_constant__ CUtensorMap tmW1, const __grid_constant__ CUtensorMap tmQKV,
             const __grid_constant__ CUtensorMap tmA2, const __grid_constant__ CUtensorMap tmWo,
             const __grid_constant__ CUtensorMap tmW2,
             const bf16* __restrict__ b1, const bf16* __restrict__ gate_w,
             const bf16* __restrict__ w1p, const bf16* __restrict__ wqkvp,
             const bf16* __restrict__ w2p, const bf16* __restrict__ wop, bf16* __restrict__ out)
{
    extern __shared__ uint8_t smem_raw[];
    const uint32_t sbase = (smem_u32(smem_raw) + 1023u) & ~1023u;
    uint8_t* sgen = smem_raw + (sbase - smem_u32(smem_raw));
    const uint32_t sK = sbase + OFF_KV, sV = sK + 384 * KV_PITCH;
    const uint32_t sBar = sbase + OFF_MISC;
    const uint32_t full1 = sBar, empty1 = sBar + 32, full2 = sBar + 64, empty2 = sBar + 104, kv_full = sBar + 144;
    float* sGate = (float*)(sgen + OFF_MISC + 256);
    uint8_t* sGw = sgen + OFF_MISC + 768;
    uint32_t* sBias = (uint32_t*)(sgen + OFF_MISC + 1792);

    const int rb = blockIdx.x >> 3, j = blockIdx.x & 7;
    const int tid = threadIdx.x, wg = tid >> 7, warp = tid >> 5, lane = tid & 31;
    TS(0, tid == 0);

    if (tid == 0) {
        for (int i = 0; i < P1_STAGES; i++) { mbar_init(full1 + 8 * i, 1); mbar_init(empty1 + 8 * i, 8); }
        for (int i = 0; i < P2_STAGES; i++) { mbar_init(full2 + 8 * i, 1); mbar_init(empty2 + 8 * i, 8); }
        mbar_init(kv_full, 1);
        fence_barrier_init();
    }
    __syncthreads();
    const unsigned int ep = *(volatile unsigned int*)&g_epoch + 1;

    if (wg >= 2) {
        reg_dealloc<104>();
        if (warp == 15) {
            if (lane == 0) {
                for (int it = 0; it < 16; it++) {
                    const int st = it % P1_STAGES;
                    if (it >= P1_STAGES) mbar_wait(empty1 + 8 * st, ((it / P1_STAGES) - 1) & 1);
                    mbar_expect_tx(full1 + 8 * st, P1_STAGE);
                    const uint32_t dst = sbase + st * P1_STAGE;
                    const int kc = it & 7;
                    tma_load_2d(dst, &tmX, kc * 64, rb * 128, full1 + 8 * st);
                    if (it < 8) {
                        for (int b = 0; b < 3; b++) tma_load_2d(dst + 16384 + b * 8192, &tmWqkv, b * 512 + j * 64, kc * 64, full1 + 8 * st);
                    } else {
                        for (int b = 0; b < 3; b++) tma_load_2d(dst + 16384 + b * 8192, &tmW1, j * FCH + b * 64, kc * 64, full1 + 8 * st);
                    }
                }
                for (int it = 13; it < 16; it++) mbar_wait(empty1 + 8 * (it % P1_STAGES), (it / P1_STAGES) & 1);
                for (int i = 0; i < 8; i++) flag_wait(&g_flag_act[rb * 8 + i], ep);
                fence_proxy_async();
                for (int ks = 0; ks < P2_KSTEPS; ks++) {
                    const int st = ks % P2_STAGES;
                    if (ks >= P2_STAGES) mbar_wait(empty2 + 8 * st, ((ks / P2_STAGES) - 1) & 1);
                    if (ks == 22) {
                        for (int i = 0; i < 8; i++) flag_wait(&g_flag_att[rb * 8 + i], ep);
                        fence_proxy_async();
                    }
                    mbar_expect_tx(full2 + 8 * st, P2_STAGE);
                    const uint32_t dst = sbase + st * P2_STAGE;
                    if (ks < 22) {
                        tma_load_2d(dst, &tmA2, D_ + ks * 64, rb * 128, full2 + 8 * st);
                        tma_load_2d(dst + 16384, &tmW2, j * 64, ks * 64, full2 + 8 * st);
                    } else {
                        tma_load_2d(dst, &tmA2, (ks - 22) * 64, rb * 128, full2 + 8 * st);
                        tma_load_2d(dst + 16384, &tmWo, j * 64, (ks - 22) * 64, full2 + 8 * st);
                    }
                }
            }
        } else {
            if (tid == 288) {
                const int b = blockIdx.x;
                mbar_wait(full1 + 8, 0);
                l2_prefetch((const uint8_t*)w1p + b * 11008, 11008);
                l2_prefetch((const uint8_t*)w2p + b * 11008, 11008);
                l2_prefetch((const uint8_t*)wop + b * 4096, 4096);
            }
            bar_sync(3, 256 + 224);
            if (tid == 256) {
                const int nblk = rb >= 2 ? 3 : rb + 1;
                for (int i = 0; i < nblk; i++) flag_wait(&g_flag_qkv[(rb - i) * 8 + j], ep);
                fence_proxy_async();
                mbar_expect_tx(kv_full, nblk * 2 * 16384);
                for (int i = 0; i < nblk; i++) {
                    const int row = j * S_ + (rb - i) * 128;
                    tma_load_2d(sK + (2 - i) * 16384, &tmQKV, 64, row, kv_full);
                    tma_load_2d(sV + (2 - i) * 16384, &tmQKV, 128, row, kv_full);
                }
            }
            __syncwarp();
            const int r0 = lane >> 2, c0 = (lane & 3) * 2;
            mbar_wait(kv_full, 0);
            uint32_t sKd = sK, sVd = sV;
            asm volatile("" : "+r"(sKd), "+r"(sVd) :: "memory");
            TS(6, tid == 256);
#pragma unroll 1
            for (int task = warp - 8; task < 32; task += 7) {
                const int qt = task & 7, hl = task >> 3;
                const int q0g = rb * 128 + qt * 16;
                const float g0 = sGate[qt * 16 + r0], g1 = sGate[qt * 16 + r0 + 8];
                const int kb0 = q0g < 256 ? (256 - q0g) >> 4 : 0;
                const bf16* qsrc = g_qkv + ((size_t)j * S_ + q0g) * 192;
                uint32_t qa[4];
                qa[0] = *(const volatile uint32_t*)(qsrc + (size_t)r0 * 192 + hl * 16 + c0);
                qa[1] = *(const volatile uint32_t*)(qsrc + (size_t)(r0 + 8) * 192 + hl * 16 + c0);
                qa[2] = *(const volatile uint32_t*)(qsrc + (size_t)r0 * 192 + hl * 16 + c0 + 8);
                qa[3] = *(const volatile uint32_t*)(qsrc + (size_t)(r0 + 8) * 192 + hl * 16 + c0 + 8);
                const int krow = qt * 16 + (lane & 7) + ((lane >> 4) << 3);
                const uint32_t ka = sKd + krow * KV_PITCH + (((2 * hl + ((lane >> 3) & 1)) ^ (lane & 7)) << 4);
                const int vrow = qt * 16 + (lane & 15);
                const uint32_t va = sVd + vrow * KV_PITCH + (((2 * hl + (lane >> 4)) ^ (lane & 7)) << 4);
                attn_task(qa, ka, va, kb0, lane, g_a2 + (size_t)q0g * KA2 + (j * 4 + hl) * 16, g0, g1);
            }
            TS(7, tid == 256);
            bar_sync(4, 224);
            if (tid == 256) { __threadfence(); flag_set(&g_flag_att[blockIdx.x], ep); }
        }
    } else {
        reg_alloc<152>();
        const int t128 = tid & 127, w4 = warp & 3, q = lane & 3;
        if (tid < 64) ((uint4*)sGw)[tid] = __ldg((const uint4*)gate_w + tid);
        else if (tid < 64 + 88) {
            const int c = j * FCH + (tid - 64) * 2;
            sBias[tid - 64] = c < F_ ? __ldg((const uint32_t*)(b1 + c)) : 0u;
        }
        bar_sync(1, 256);
        const int rl = wg * 64 + w4 * 16 + (lane >> 2);
        {
            float acc[96];
            float gs = 0.f;
            const int grow = wg * 64 + (t128 >> 1), ghalf = t128 & 1;
#pragma unroll
            for (int kc = 0; kc < 8; kc++) {
                const int st = kc % P1_STAGES;
                const uint32_t sa = sbase + st * P1_STAGE;
                mbar_wait(full1 + 8 * st, (kc / P1_STAGES) & 1);
                TS(1, tid == 0 && kc == 0);
                wgmma_fence();
#pragma unroll
                for (int k16 = 0; k16 < 4; k16++)
                    wgmma_n192<1>(acc, make_desc(sa + wg * 8192 + k16 * 32, 16, 1024),
                                  make_desc(sa + 16384 + k16 * 2048, 8192, 1024), (kc | k16) != 0);
                wgmma_commit();
#pragma unroll
                for (int c = 0; c < 4; c++) {
                    const int cc = ghalf * 4 + c;
                    const uint4 xv = *(const uint4*)(sgen + st * P1_STAGE + grow * 128 + ((cc ^ (grow & 7)) << 4));
                    const uint4 gv = *(const uint4*)(sGw + kc * 128 + cc * 16);
                    gs = fmaf(bf_lo(xv.x), bf_lo(gv.x), gs); gs = fmaf(bf_hi(xv.x), bf_hi(gv.x), gs);
                    gs = fmaf(bf_lo(xv.y), bf_lo(gv.y), gs); gs = fmaf(bf_hi(xv.y), bf_hi(gv.y), gs);
                    gs = fmaf(bf_lo(xv.z), bf_lo(gv.z), gs); gs = fmaf(bf_hi(xv.z), bf_hi(gv.z), gs);
                    gs = fmaf(bf_lo(xv.w), bf_lo(gv.w), gs); gs = fmaf(bf_hi(xv.w), bf_hi(gv.w), gs);
                }
                if (kc > 0) { wgmma_wait<1>(); if (lane == 0) mbar_arrive(empty1 + 8 * ((kc - 1) % P1_STAGES)); }
            }
            gs += __shfl_xor_sync(0xffffffffu, gs, 1);
            if (ghalf == 0) sGate[grow] = 1.f / (1.f + __expf(-gs));
            wgmma_wait<0>();
            if (lane == 0) mbar_arrive(empty1 + 8 * (7 % P1_STAGES));
            TS(2, tid == 0);
            bf16* orow0 = g_qkv + ((size_t)j * S_ + rb * 128 + rl) * 192;
            bf16* orow1 = orow0 + 8 * 192;
#pragma unroll
            for (int u = 0; u < 6; u++) {
                uint32_t w0[4], w1[4];
#pragma unroll
                for (int i = 0; i < 4; i++) {
                    const int t = u * 4 + i;
                    w0[i] = pack_bf16(acc[t * 4 + 0], acc[t * 4 + 1]);
                    w1[i] = pack_bf16(acc[t * 4 + 2], acc[t * 4 + 3]);
                }
                quad_transpose(w0, q);
                quad_transpose(w1, q);
                const int c = (u * 4 + q) * 8;
                *(uint4*)(orow0 + c) = make_uint4(w0[0], w0[1], w0[2], w0[3]);
                *(uint4*)(orow1 + c) = make_uint4(w1[0], w1[1], w1[2], w1[3]);
            }
            bar_sync(3, 256 + 224);
            if (tid == 0) { __threadfence(); flag_set(&g_flag_qkv[blockIdx.x], ep); }
            TS(3, tid == 0);
        }
        {
            float acc[88];
#pragma unroll
            for (int kc = 0; kc < 8; kc++) {
                const int it = kc + 8, st = it % P1_STAGES;
                const uint32_t sa = sbase + st * P1_STAGE;
                mbar_wait(full1 + 8 * st, (it / P1_STAGES) & 1);
                wgmma_fence();
#pragma unroll
                for (int k16 = 0; k16 < 4; k16++)
                    wgmma_n176<1>(acc, make_desc(sa + wg * 8192 + k16 * 32, 16, 1024),
                                  make_desc(sa + 16384 + k16 * 2048, 8192, 1024), (kc | k16) != 0);
                wgmma_commit();
                if (kc > 0) { wgmma_wait<1>(); if (lane == 0) mbar_arrive(empty1 + 8 * ((it - 1) % P1_STAGES)); }
            }
            wgmma_wait<0>();
            if (lane == 0) mbar_arrive(empty1 + 8 * (15 % P1_STAGES));
            TS(4, tid == 0);
            const int n0 = j * FCH;
            const float om0 = 1.f - sGate[rl], om1 = 1.f - sGate[rl + 8];
            bf16* frow0 = g_a2 + (size_t)(rb * 128 + rl) * KA2 + D_ + n0;
            bf16* frow1 = frow0 + 8 * KA2;
#pragma unroll
            for (int u = 0; u < 6; u++) {
                uint32_t w0[4], w1[4];
#pragma unroll
                for (int i = 0; i < 4; i++) {
                    const int t = u * 4 + i;
                    if (t < 22) {
                        const uint32_t bv = sBias[t * 4 + q];
                        const float bb0 = bf_lo(bv), bb1 = bf_hi(bv);
                        w0[i] = pack_bf16(mish_f(acc[t * 4 + 0] + bb0) * om0, mish_f(acc[t * 4 + 1] + bb1) * om0);
                        w1[i] = pack_bf16(mish_f(acc[t * 4 + 2] + bb0) * om1, mish_f(acc[t * 4 + 3] + bb1) * om1);
                    } else { w0[i] = 0; w1[i] = 0; }
                }
                quad_transpose(w0, q);
                quad_transpose(w1, q);
                const int c = (u * 4 + q) * 8;
                if (c < FCH && n0 + c < F_) {
                    *(uint4*)(frow0 + c) = make_uint4(w0[0], w0[1], w0[2], w0[3]);
                    *(uint4*)(frow1 + c) = make_uint4(w1[0], w1[1], w1[2], w1[3]);
                }
            }
            bar_sync(1, 256);
            if (tid == 0) { __threadfence(); flag_set(&g_flag_act[blockIdx.x], ep); }
            TS(5, tid == 0);
        }
        {
            float acc[32];
            for (int ks = 0; ks < P2_KSTEPS; ks++) {
                const int st = ks % P2_STAGES;
                const uint32_t sa = sbase + st * P2_STAGE;
                mbar_wait(full2 + 8 * st, (ks / P2_STAGES) & 1);
                TS(8, tid == 0 && ks == 0); TS(9, tid == 0 && ks == 22);
                wgmma_fence();
#pragma unroll
                for (int k16 = 0; k16 < 4; k16++)
                    wgmma_n64<1>(acc, make_desc(sa + wg * 8192 + k16 * 32, 16, 1024),
                                 make_desc(sa + 16384 + k16 * 2048, 8192, 1024), (ks | k16) != 0);
                wgmma_commit();
                if (ks > 0) { wgmma_wait<1>(); if (lane == 0) mbar_arrive(empty2 + 8 * ((ks - 1) % P2_STAGES)); }
            }
            wgmma_wait<0>();
            TS(10, tid == 0);
            bf16* orow0 = out + (size_t)(rb * 128 + rl) * D_ + j * 64;
            bf16* orow1 = orow0 + 8 * D_;
#pragma unroll
            for (int u = 0; u < 2; u++) {
                uint32_t w0[4], w1[4];
#pragma unroll
                for (int i = 0; i < 4; i++) {
                    const int t = u * 4 + i;
                    w0[i] = pack_bf16(acc[t * 4 + 0], acc[t * 4 + 1]);
                    w1[i] = pack_bf16(acc[t * 4 + 2], acc[t * 4 + 3]);
                }
                quad_transpose(w0, q);
                quad_transpose(w1, q);
                const int c = (u * 4 + q) * 8;
                *(uint4*)(orow0 + c) = make_uint4(w0[0], w0[1], w0[2], w0[3]);
                *(uint4*)(orow1 + c) = make_uint4(w1[0], w1[1], w1[2], w1[3]);
            }
            TS(11, tid == 0);
        }
        if (tid == 0) {
            __threadfence();
            if (atomicAdd(&g_done, 1u) == gridDim.x - 1) {
                g_done = 0;
                __threadfence();
                atomicAdd(&g_epoch, 1u);
            }
        }
    }
}

typedef CUresult (*PFN_encodeTiled)(CUtensorMap*, CUtensorMapDataType, cuuint32_t, void*, const cuuint64_t*,
                                    const cuuint64_t*, const cuuint32_t*, const cuuint32_t*, CUtensorMapInterleave,
                                    CUtensorMapSwizzle, CUtensorMapL2promotion, CUtensorMapFloatOOBfill);

static void make_map(PFN_encodeTiled enc, CUtensorMap* m, const void* ptr, uint64_t cols, uint64_t rows,
                     uint32_t box_cols, uint32_t box_rows)
{
    cuuint64_t dims[2] = {cols, rows};
    cuuint64_t strides[1] = {cols * 2};
    cuuint32_t box[2] = {box_cols, box_rows};
    cuuint32_t es[2] = {1, 1};
    enc(m, CU_TENSOR_MAP_DATA_TYPE_BFLOAT16, 2, const_cast<void*>(ptr), dims, strides, box, es,
        CU_TENSOR_MAP_INTERLEAVE_NONE, CU_TENSOR_MAP_SWIZZLE_128B, CU_TENSOR_MAP_L2_PROMOTION_L2_128B,
        CU_TENSOR_MAP_FLOAT_OOB_FILL_NONE);
}

extern "C" void kernel_launch(void* const* d_in, const int* in_sizes, int n_in, void* d_out, int out_size)
{
    const bf16* x    = (const bf16*)d_in[0];
    const bf16* wqkv = (const bf16*)d_in[1];
    const bf16* wo   = (const bf16*)d_in[2];
    const bf16* w1   = (const bf16*)d_in[4];
    const bf16* b1   = (const bf16*)d_in[5];
    const bf16* w2   = (const bf16*)d_in[6];
    const bf16* gw   = (const bf16*)d_in[7];

    static PFN_encodeTiled enc = nullptr;
    if (!enc) {
        void* fn = nullptr;
        cudaDriverEntryPointQueryResult qr;
        cudaGetDriverEntryPoint("cuTensorMapEncodeTiled", &fn, cudaEnableDefault, &qr);
        enc = (PFN_encodeTiled)fn;
        cudaFuncSetAttribute(fused_kernel, cudaFuncAttributeMaxDynamicSharedMemorySize, FUSED_SMEM);
    }
    void *a2p = nullptr, *qkvp = nullptr;
    cudaGetSymbolAddress(&a2p, g_a2);
    cudaGetSymbolAddress(&qkvp, g_qkv);
    CUtensorMap tmX, tmWqkv, tmW1, tmQKV, tmA2, tmWo, tmW2;
    make_map(enc, &tmX, x, D_, S_, 64, 128);
    make_map(enc, &tmWqkv, wqkv, 3 * D_, D_, 64, 64);
    make_map(enc, &tmW1, w1, F_, D_, 64, 64);
    make_map(enc, &tmQKV, qkvp, 192, 8 * S_, 64, 128);
    make_map(enc, &tmA2, a2p, KA2, S_, 64, 128);
    make_map(enc, &tmWo, wo, D_, D_, 64, 64);
    make_map(enc, &tmW2, w2, D_, F_, 64, 64);

    fused_kernel<<<128, 512, FUSED_SMEM, cudaStreamPerThread>>>(tmX, tmWqkv, tmW1, tmQKV, tmA2, tmWo, tmW2,
                                                                b1, gw, w1, wqkv, w2, wo, (bf16*)d_out);
}
```

```cpp
#include <cuda_runtime.h>
#include <cuda_bf16.h>
#include <cuda.h>
#include <stdint.h>

typedef __nv_bfloat16 bf16;

constexpr int S_ = 2048, D_ = 512, F_ = 1376;
constexpr int KA2 = D_ + F_;
constexpr int FCH = 176;

__device__ bf16  g_qkv[8 * S_ * 192];
__device__ bf16  g_a2[S_ * KA2];
__device__ float g_gate[S_];

#define TS(k, cond) do { } while (0)

__device__ __forceinline__ uint32_t smem_u32(const void* p) { return (uint32_t)__cvta_generic_to_shared(p); }
__device__ __forceinline__ void mbar_init(uint32_t bar, uint32_t count) {
    asm volatile("mbarrier.init.shared::cta.b64 [%0], %1;" :: "r"(bar), "r"(count) : "memory");
}
__device__ __forceinline__ void mbar_expect_tx(uint32_t bar, uint32_t bytes) {
    asm volatile("mbarrier.arrive.expect_tx.shared::cta.b64 _, [%0], %1;" :: "r"(bar), "r"(bytes) : "memory");
}
__device__ __forceinline__ void mbar_arrive(uint32_t bar) {
    asm volatile("mbarrier.arrive.shared::cta.b64 _, [%0];" :: "r"(bar) : "memory");
}
__device__ __forceinline__ bool mbar_try_wait(uint32_t bar, uint32_t parity) {
    uint32_t ok;
    asm volatile("{\n.reg .pred p;\nmbarrier.try_wait.parity.shared::cta.b64 p, [%1], %2;\nselp.u32 %0, 1, 0, p;\n}"
                 : "=r"(ok) : "r"(bar), "r"(parity) : "memory");
    return ok != 0;
}
__device__ __forceinline__ void mbar_wait(uint32_t bar, uint32_t parity) {
    for (uint32_t it = 0; it < (1u << 22); ++it) { if (mbar_try_wait(bar, parity)) break; }
}
__device__ __forceinline__ void tma_load_2d(uint32_t dst, const CUtensorMap* map, int c0, int c1, uint32_t bar) {
    asm volatile("cp.async.bulk.tensor.2d.shared::cluster.global.mbarrier::complete_tx::bytes [%0], [%1, {%3, %4}], [%2];"
                 :: "r"(dst), "l"(map), "r"(bar), "r"(c0), "r"(c1) : "memory");
}
__device__ __forceinline__ void l2_prefetch(const void* p, uint32_t bytes) {
    asm volatile("cp.async.bulk.prefetch.L2.global [%0], %1;" :: "l"(p), "r"(bytes) : "memory");
}
__device__ __forceinline__ void fence_barrier_init() { asm volatile("fence.mbarrier_init.release.cluster;" ::: "memory"); }
__device__ __forceinline__ void wgmma_fence()  { asm volatile("wgmma.fence.sync.aligned;" ::: "memory"); }
__device__ __forceinline__ void wgmma_commit() { asm volatile("wgmma.commit_group.sync.aligned;" ::: "memory"); }
template <int N> __device__ __forceinline__ void wgmma_wait() { asm volatile("wgmma.wait_group.sync.aligned %0;" :: "n"(N) : "memory"); }
template <int R> __device__ __forceinline__ void reg_alloc()   { asm volatile("setmaxnreg.inc.sync.aligned.u32 %0;" :: "n"(R)); }
template <int R> __device__ __forceinline__ void reg_dealloc() { asm volatile("setmaxnreg.dec.sync.aligned.u32 %0;" :: "n"(R)); }
__device__ __forceinline__ void bar_sync(int id, int n)   { asm volatile("bar.sync %0, %1;" :: "r"(id), "r"(n) : "memory"); }
__device__ __forceinline__ void bar_arrive(int id, int n) { asm volatile("bar.arrive %0, %1;" :: "r"(id), "r"(n) : "memory"); }

__device__ __forceinline__ uint64_t make_desc(uint32_t addr, uint32_t lbo, uint32_t sbo) {
    uint64_t d = (uint64_t)((addr & 0x3FFFF) >> 4);
    d |= (uint64_t)((lbo & 0x3FFFF) >> 4) << 16;
    d |= (uint64_t)((sbo & 0x3FFFF) >> 4) << 32;
    d |= (uint64_t)1 << 62;
    return d;
}

template <int TB>
__device__ __forceinline__ void wgmma_n64(float (&d)[32], uint64_t da, uint64_t db, int scale_d) {
    asm volatile("{\n.reg .pred p;\nsetp.ne.b32 p, %34, 0;\n"
        "wgmma.mma_async.sync.aligned.m64n64k16.f32.bf16.bf16 {%0, %1, %2, %3, %4, %5, %6, %7, %8, %9, %10, %11, %12, %13, %14, %15, %16, %17, %18, %19, %20, %21, %22, %23, %24, %25, %26, %27, %28, %29, %30, %31}, %32, %33, p, 1, 1, 0, %35;\n}\n"
        : "+f"(d[0]), "+f"(d[1]), "+f"(d[2]), "+f"(d[3]), "+f"(d[4]), "+f"(d[5]), "+f"(d[6]), "+f"(d[7]), "+f"(d[8]), "+f"(d[9]), "+f"(d[10]), "+f"(d[11]), "+f"(d[12]), "+f"(d[13]), "+f"(d[14]), "+f"(d[15]), "+f"(d[16]), "+f"(d[17]), "+f"(d[18]), "+f"(d[19]), "+f"(d[20]), "+f"(d[21]), "+f"(d[22]), "+f"(d[23]), "+f"(d[24]), "+f"(d[25]), "+f"(d[26]), "+f"(d[27]), "+f"(d[28]), "+f"(d[29]), "+f"(d[30]), "+f"(d[31])
        : "l"(da), "l"(db), "r"(scale_d), "n"(TB));
}

template <int TB>
__device__ __forceinline__ void wgmma_n128(float (&d)[64], uint64_t da, uint64_t db, int scale_d) {
    asm volatile("{\n.reg .pred p;\nsetp.ne.b32 p, %66, 0;\n"
        "wgmma.mma_async.sync.aligned.m64n128k16.f32.bf16.bf16 {%0, %1, %2, %3, %4, %5, %6, %7, %8, %9, %10, %11, %12, %13, %14, %15, %16, %17, %18, %19, %20, %21, %22, %23, %24, %25, %26, %27, %28, %29, %30, %31, %32, %33, %34, %35, %36, %37, %38, %39, %40, %41, %42, %43, %44, %45, %46, %47, %48, %49, %50, %51, %52, %53, %54, %55, %56, %57, %58, %59, %60, %61, %62, %63}, %64, %65, p, 1, 1, 0, %67;\n}\n"
        : "+f"(d[0]), "+f"(d[1]), "+f"(d[2]), "+f"(d[3]), "+f"(d[4]), "+f"(d[5]), "+f"(d[6]), "+f"(d[7]), "+f"(d[8]), "+f"(d[9]), "+f"(d[10]), "+f"(d[11]), "+f"(d[12]), "+f"(d[13]), "+f"(d[14]), "+f"(d[15]), "+f"(d[16]), "+f"(d[17]), "+f"(d[18]), "+f"(d[19]), "+f"(d[20]), "+f"(d[21]), "+f"(d[22]), "+f"(d[23]), "+f"(d[24]), "+f"(d[25]), "+f"(d[26]), "+f"(d[27]), "+f"(d[28]), "+f"(d[29]), "+f"(d[30]), "+f"(d[31]), "+f"(d[32]), "+f"(d[33]), "+f"(d[34]), "+f"(d[35]), "+f"(d[36]), "+f"(d[37]), "+f"(d[38]), "+f"(d[39]), "+f"(d[40]), "+f"(d[41]), "+f"(d[42]), "+f"(d[43]), "+f"(d[44]), "+f"(d[45]), "+f"(d[46]), "+f"(d[47]), "+f"(d[48]), "+f"(d[49]), "+f"(d[50]), "+f"(d[51]), "+f"(d[52]), "+f"(d[53]), "+f"(d[54]), "+f"(d[55]), "+f"(d[56]), "+f"(d[57]), "+f"(d[58]), "+f"(d[59]), "+f"(d[60]), "+f"(d[61]), "+f"(d[62]), "+f"(d[63])
        : "l"(da), "l"(db), "r"(scale_d), "n"(TB));
}

template <int TB>
__device__ __forceinline__ void wgmma_n176(float (&d)[88], uint64_t da, uint64_t db, int scale_d) {
    asm volatile("{\n.reg .pred p;\nsetp.ne.b32 p, %90, 0;\n"
        "wgmma.mma_async.sync.aligned.m64n176k16.f32.bf16.bf16 {%0, %1, %2, %3, %4, %5, %6, %7, %8, %9, %10, %11, %12, %13, %14, %15, %16, %17, %18, %19, %20, %21, %22, %23, %24, %25, %26, %27, %28, %29, %30, %31, %32, %33, %34, %35, %36, %37, %38, %39, %40, %41, %42, %43, %44, %45, %46, %47, %48, %49, %50, %51, %52, %53, %54, %55, %56, %57, %58, %59, %60, %61, %62, %63, %64, %65, %66, %67, %68, %69, %70, %71, %72, %73, %74, %75, %76, %77, %78, %79, %80, %81, %82, %83, %84, %85, %86, %87}, %88, %89, p, 1, 1, 0, %91;\n}\n"
        : "+f"(d[0]), "+f"(d[1]), "+f"(d[2]), "+f"(d[3]), "+f"(d[4]), "+f"(d[5]), "+f"(d[6]), "+f"(d[7]), "+f"(d[8]), "+f"(d[9]), "+f"(d[10]), "+f"(d[11]), "+f"(d[12]), "+f"(d[13]), "+f"(d[14]), "+f"(d[15]), "+f"(d[16]), "+f"(d[17]), "+f"(d[18]), "+f"(d[19]), "+f"(d[20]), "+f"(d[21]), "+f"(d[22]), "+f"(d[23]), "+f"(d[24]), "+f"(d[25]), "+f"(d[26]), "+f"(d[27]), "+f"(d[28]), "+f"(d[29]), "+f"(d[30]), "+f"(d[31]), "+f"(d[32]), "+f"(d[33]), "+f"(d[34]), "+f"(d[35]), "+f"(d[36]), "+f"(d[37]), "+f"(d[38]), "+f"(d[39]), "+f"(d[40]), "+f"(d[41]), "+f"(d[42]), "+f"(d[43]), "+f"(d[44]), "+f"(d[45]), "+f"(d[46]), "+f"(d[47]), "+f"(d[48]), "+f"(d[49]), "+f"(d[50]), "+f"(d[51]), "+f"(d[52]), "+f"(d[53]), "+f"(d[54]), "+f"(d[55]), "+f"(d[56]), "+f"(d[57]), "+f"(d[58]), "+f"(d[59]), "+f"(d[60]), "+f"(d[61]), "+f"(d[62]), "+f"(d[63]), "+f"(d[64]), "+f"(d[65]), "+f"(d[66]), "+f"(d[67]), "+f"(d[68]), "+f"(d[69]), "+f"(d[70]), "+f"(d[71]), "+f"(d[72]), "+f"(d[73]), "+f"(d[74]), "+f"(d[75]), "+f"(d[76]), "+f"(d[77]), "+f"(d[78]), "+f"(d[79]), "+f"(d[80]), "+f"(d[81]), "+f"(d[82]), "+f"(d[83]), "+f"(d[84]), "+f"(d[85]), "+f"(d[86]), "+f"(d[87])
        : "l"(da), "l"(db), "r"(scale_d), "n"(TB));
}

template <int TB>
__device__ __forceinline__ void wgmma_n192(float (&d)[96], uint64_t da, uint64_t db, int scale_d) {
    asm volatile("{\n.reg .pred p;\nsetp.ne.b32 p, %98, 0;\n"
        "wgmma.mma_async.sync.aligned.m64n192k16.f32.bf16.bf16 {%0, %1, %2, %3, %4, %5, %6, %7, %8, %9, %10, %11, %12, %13, %14, %15, %16, %17, %18, %19, %20, %21, %22, %23, %24, %25, %26, %27, %28, %29, %30, %31, %32, %33, %34, %35, %36, %37, %38, %39, %40, %41, %42, %43, %44, %45, %46, %47, %48, %49, %50, %51, %52, %53, %54, %55, %56, %57, %58, %59, %60, %61, %62, %63, %64, %65, %66, %67, %68, %69, %70, %71, %72, %73, %74, %75, %76, %77, %78, %79, %80, %81, %82, %83, %84, %85, %86, %87, %88, %89, %90, %91, %92, %93, %94, %95}, %96, %97, p, 1, 1, 0, %99;\n}\n"
        : "+f"(d[0]), "+f"(d[1]), "+f"(d[2]), "+f"(d[3]), "+f"(d[4]), "+f"(d[5]), "+f"(d[6]), "+f"(d[7]), "+f"(d[8]), "+f"(d[9]), "+f"(d[10]), "+f"(d[11]), "+f"(d[12]), "+f"(d[13]), "+f"(d[14]), "+f"(d[15]), "+f"(d[16]), "+f"(d[17]), "+f"(d[18]), "+f"(d[19]), "+f"(d[20]), "+f"(d[21]), "+f"(d[22]), "+f"(d[23]), "+f"(d[24]), "+f"(d[25]), "+f"(d[26]), "+f"(d[27]), "+f"(d[28]), "+f"(d[29]), "+f"(d[30]), "+f"(d[31]), "+f"(d[32]), "+f"(d[33]), "+f"(d[34]), "+f"(d[35]), "+f"(d[36]), "+f"(d[37]), "+f"(d[38]), "+f"(d[39]), "+f"(d[40]), "+f"(d[41]), "+f"(d[42]), "+f"(d[43]), "+f"(d[44]), "+f"(d[45]), "+f"(d[46]), "+f"(d[47]), "+f"(d[48]), "+f"(d[49]), "+f"(d[50]), "+f"(d[51]), "+f"(d[52]), "+f"(d[53]), "+f"(d[54]), "+f"(d[55]), "+f"(d[56]), "+f"(d[57]), "+f"(d[58]), "+f"(d[59]), "+f"(d[60]), "+f"(d[61]), "+f"(d[62]), "+f"(d[63]), "+f"(d[64]), "+f"(d[65]), "+f"(d[66]), "+f"(d[67]), "+f"(d[68]), "+f"(d[69]), "+f"(d[70]), "+f"(d[71]), "+f"(d[72]), "+f"(d[73]), "+f"(d[74]), "+f"(d[75]), "+f"(d[76]), "+f"(d[77]), "+f"(d[78]), "+f"(d[79]), "+f"(d[80]), "+f"(d[81]), "+f"(d[82]), "+f"(d[83]), "+f"(d[84]), "+f"(d[85]), "+f"(d[86]), "+f"(d[87]), "+f"(d[88]), "+f"(d[89]), "+f"(d[90]), "+f"(d[91]), "+f"(d[92]), "+f"(d[93]), "+f"(d[94]), "+f"(d[95])
        : "l"(da), "l"(db), "r"(scale_d), "n"(TB));
}

__device__ __forceinline__ uint32_t pack_bf16(float lo, float hi) {
    uint32_t r;
    asm("cvt.rn.bf16x2.f32 %0, %1, %2;" : "=r"(r) : "f"(hi), "f"(lo));
    return r;
}
__device__ __forceinline__ float bf_lo(uint32_t v) { return __uint_as_float(v << 16); }
__device__ __forceinline__ float bf_hi(uint32_t v) { return __uint_as_float(v & 0xffff0000u); }

__device__ __forceinline__ void quad_transpose(uint32_t (&w)[4], int q) {
    const bool o1 = q & 1, o2 = q & 2;
    {
        uint32_t s0 = o1 ? w[0] : w[1], s1 = o1 ? w[2] : w[3];
        s0 = __shfl_xor_sync(0xffffffffu, s0, 1); s1 = __shfl_xor_sync(0xffffffffu, s1, 1);
        if (o1) { w[0] = s0; w[2] = s1; } else { w[1] = s0; w[3] = s1; }
    }
    {
        uint32_t s0 = o2 ? w[0] : w[2], s1 = o2 ? w[1] : w[3];
        s0 = __shfl_xor_sync(0xffffffffu, s0, 2); s1 = __shfl_xor_sync(0xffffffffu, s1, 2);
        if (o2) { w[0] = s0; w[1] = s1; } else { w[2] = s0; w[3] = s1; }
    }
}

__device__ __forceinline__ float ex2(float x) { float y; asm("ex2.approx.ftz.f32 %0, %1;" : "=f"(y) : "f"(x)); return y; }
__device__ __forceinline__ float rcp(float x) { float y; asm("rcp.approx.ftz.f32 %0, %1;" : "=f"(y) : "f"(x)); return y; }

__device__ __forceinline__ float ex2v(float x) { float y; asm volatile("ex2.approx.ftz.f32 %0, %1;" : "=f"(y) : "f"(x)); return y; }
__device__ __forceinline__ float rcpv(float x) { float y; asm volatile("rcp.approx.ftz.f32 %0, %1;" : "=f"(y) : "f"(x)); return y; }
__device__ __forceinline__ float mish_f(float h) {
    const float w = ex2v(-1.4426950408889634f * fabsf(h));
    const float t = w * w;
    const bool pos = h > 0.f;
    const float num = fmaf(2.f, w, pos ? 1.f : t);
    const float den = num + (pos ? t + t : 2.f);
    return h * num * rcpv(den);
}

__device__ unsigned int g_epoch;
__device__ unsigned int g_done;
__device__ unsigned int g_flag_qkv[128];
__device__ unsigned int g_flag_act[128];
__device__ unsigned int g_flag_att[128];

__device__ __forceinline__ void flag_set(unsigned int* f, unsigned int v) {
    asm volatile("st.release.gpu.global.u32 [%0], %1;" :: "l"(f), "r"(v) : "memory");
}
__device__ __forceinline__ void flag_wait(const unsigned int* f, unsigned int v) {
    for (uint32_t it = 0; it < (1u << 22); ++it) {
        unsigned int x;
        asm volatile("ld.acquire.gpu.global.u32 %0, [%1];" : "=r"(x) : "l"(f) : "memory");
        if (x == v) break;
    }
}
__device__ __forceinline__ void fence_proxy_async() { asm volatile("fence.proxy.async;" ::: "memory"); }

__device__ __forceinline__ void ldsm_x4(uint32_t (&r)[4], uint32_t addr) {
    asm("ldmatrix.sync.aligned.m8n8.x4.shared.b16 {%0,%1,%2,%3}, [%4];"
                 : "=r"(r[0]), "=r"(r[1]), "=r"(r[2]), "=r"(r[3]) : "r"(addr));
}
__device__ __forceinline__ void ldsm_x4_t(uint32_t (&r)[4], uint32_t addr) {
    asm("ldmatrix.sync.aligned.m8n8.x4.trans.shared.b16 {%0,%1,%2,%3}, [%4];"
                 : "=r"(r[0]), "=r"(r[1]), "=r"(r[2]), "=r"(r[3]) : "r"(addr));
}
__device__ __forceinline__ void mma16816(float (&d)[4], const uint32_t (&a)[4], uint32_t b0, uint32_t b1) {
    asm("mma.sync.aligned.m16n8k16.row.col.f32.bf16.bf16.f32 {%0,%1,%2,%3}, {%4,%5,%6,%7}, {%8,%9}, {%0,%1,%2,%3};"
                 : "+f"(d[0]), "+f"(d[1]), "+f"(d[2]), "+f"(d[3])
                 : "r"(a[0]), "r"(a[1]), "r"(a[2]), "r"(a[3]), "r"(b0), "r"(b1));
}
__device__ __forceinline__ void mma16816_z(float (&d)[4], const uint32_t (&a)[4], uint32_t b0, uint32_t b1) {
    asm("mma.sync.aligned.m16n8k16.row.col.f32.bf16.bf16.f32 {%0,%1,%2,%3}, {%4,%5,%6,%7}, {%8,%9}, {%10,%10,%10,%10};"
                 : "=f"(d[0]), "=f"(d[1]), "=f"(d[2]), "=f"(d[3])
                 : "r"(a[0]), "r"(a[1]), "r"(a[2]), "r"(a[3]), "r"(b0), "r"(b1), "f"(0.f));
}

constexpr int KV_PITCH = 128;

template <int NB, bool MASK_FIRST, bool MASK_LAST, bool HEAD>
__device__ __forceinline__ void attn_chunk(const uint32_t (&qa)[4], uint32_t ka, uint32_t va, int kbs, int kb0, int r0, int c0,
                                           float& m0, float& m1, float& l0, float& l1, float (&o)[2][4])
{
    const float C = 0.25f * 1.4426950408889634f;
    float s[NB][2][4];
#pragma unroll
    for (int b = 0; b < NB; b++) {
        uint32_t kf[4];
        ldsm_x4(kf, ka + (kbs + b) * 16 * KV_PITCH);
        mma16816_z(s[b][0], qa, kf[0], kf[1]);
        mma16816_z(s[b][1], qa, kf[2], kf[3]);
    }
#pragma unroll
    for (int t = 0; t < 2; t++)
#pragma unroll
        for (int e = 0; e < 4; e++) {
            const int r = r0 + (e >> 1) * 8, c = t * 8 + c0 + (e & 1);
            if (MASK_FIRST && c <= r) s[0][t][e] = -1e30f;
            if (MASK_LAST && c > r) s[NB - 1][t][e] = -1e30f;
        }
    if (HEAD) {
#pragma unroll
        for (int b = 0; b < NB; b++)
            if (kbs + b < kb0) {
#pragma unroll
                for (int t = 0; t < 2; t++)
#pragma unroll
                    for (int e = 0; e < 4; e++) s[b][t][e] = -1e30f;
            }
    }
    float n0 = m0, n1 = m1;
#pragma unroll
    for (int b = 0; b < NB; b++) {
        n0 = fmaxf(n0, fmaxf(fmaxf(s[b][0][0], s[b][0][1]), fmaxf(s[b][1][0], s[b][1][1])));
        n1 = fmaxf(n1, fmaxf(fmaxf(s[b][0][2], s[b][0][3]), fmaxf(s[b][1][2], s[b][1][3])));
    }
    n0 = fmaxf(n0, __shfl_xor_sync(0xffffffffu, n0, 1)); n0 = fmaxf(n0, __shfl_xor_sync(0xffffffffu, n0, 2));
    n1 = fmaxf(n1, __shfl_xor_sync(0xffffffffu, n1, 1)); n1 = fmaxf(n1, __shfl_xor_sync(0xffffffffu, n1, 2));
    const float mc0 = n0 * C, mc1 = n1 * C;
    if (!MASK_LAST) {
        const float a0 = ex2(fmaf(m0, C, -mc0)), a1 = ex2(fmaf(m1, C, -mc1));
        l0 *= a0; l1 *= a1;
        o[0][0] *= a0; o[0][1] *= a0; o[1][0] *= a0; o[1][1] *= a0;
        o[0][2] *= a1; o[0][3] *= a1; o[1][2] *= a1; o[1][3] *= a1;
    }
    m0 = n0; m1 = n1;
#pragma unroll
    for (int b = 0; b < NB; b++) {
        uint32_t pa[4];
#pragma unroll
        for (int t = 0; t < 2; t++) {
            const float p0 = ex2(fmaf(s[b][t][0], C, -mc0)), p1 = ex2(fmaf(s[b][t][1], C, -mc0));
            const float p2 = ex2(fmaf(s[b][t][2], C, -mc1)), p3 = ex2(fmaf(s[b][t][3], C, -mc1));
            l0 += p0 + p1; l1 += p2 + p3;
            pa[2 * t] = pack_bf16(p0, p1); pa[2 * t + 1] = pack_bf16(p2, p3);
        }
        uint32_t vf[4];
        ldsm_x4_t(vf, va + (kbs + b) * 16 * KV_PITCH);
        mma16816(o[0], pa, vf[0], vf[1]);
        mma16816(o[1], pa, vf[2], vf[3]);
    }
}

template <bool HEAD>
__device__ __forceinline__ void attn_task(const uint32_t (&qa)[4], uint32_t ka, uint32_t va, int kb0, int lane,
                                          bf16* __restrict__ out  , float g0, float g1)
{
    const int r0 = lane >> 2, c0 = (lane & 3) * 2;
    float m0 = -1e30f, m1 = -1e30f, l0 = 0.f, l1 = 0.f;
    float o[2][4] = {{0.f, 0.f, 0.f, 0.f}, {0.f, 0.f, 0.f, 0.f}};
    attn_chunk<5, false, true, HEAD>(qa, ka, va, 12, kb0, r0, c0, m0, m1, l0, l1, o);
    if (!HEAD || kb0 < 12) attn_chunk<4, false, false, HEAD>(qa, ka, va, 8, kb0, r0, c0, m0, m1, l0, l1, o);
    if (!HEAD || kb0 < 8)  attn_chunk<4, false, false, HEAD>(qa, ka, va, 4, kb0, r0, c0, m0, m1, l0, l1, o);
    if (!HEAD || kb0 < 4)  attn_chunk<4, true, false, HEAD>(qa, ka, va, 0, kb0, r0, c0, m0, m1, l0, l1, o);
    l0 += __shfl_xor_sync(0xffffffffu, l0, 1); l0 += __shfl_xor_sync(0xffffffffu, l0, 2);
    l1 += __shfl_xor_sync(0xffffffffu, l1, 1); l1 += __shfl_xor_sync(0xffffffffu, l1, 2);
    const float f0 = g0 / l0, f1 = g1 / l1;
#pragma unroll
    for (int t = 0; t < 2; t++) {
        *(uint32_t*)(out + (size_t)r0 * KA2 + t * 8 + c0) = pack_bf16(o[t][0] * f0, o[t][1] * f0);
        *(uint32_t*)(out + (size_t)(r0 + 8) * KA2 + t * 8 + c0) = pack_bf16(o[t][2] * f1, o[t][3] * f1);
    }
}

constexpr int P1_STAGES = 3;
constexpr int P1_STAGE  = 16384 + 24576;
constexpr int P2_STAGES = 5;
constexpr int P2_STAGE  = 16384 + 8192;
constexpr int P2_KSTEPS = 30;
constexpr int OFF_KV    = P1_STAGES * P1_STAGE;
constexpr int OFF_MISC  = OFF_KV + 2 * 384 * KV_PITCH;
constexpr int FUSED_SMEM = OFF_MISC + 2048 + 1024;

__global__ void __launch_bounds__(512, 1)
fused_kernel(const __grid_constant__ CUtensorMap tmX, const __grid_constant__ CUtensorMap tmWqkv,
             const __grid_constant__ CUtensorMap tmW1, const __grid_constant__ CUtensorMap tmQKV,
             const __grid_constant__ CUtensorMap tmA2, const __grid_constant__ CUtensorMap tmWo,
             const __grid_constant__ CUtensorMap tmW2,
             const bf16* __restrict__ b1, const bf16* __restrict__ gate_w,
             const bf16* __restrict__ w1p, const bf16* __restrict__ wqkvp,
             const bf16* __restrict__ w2p, const bf16* __restrict__ wop, bf16* __restrict__ out)
{
    extern __shared__ uint8_t smem_raw[];
    const uint32_t sbase = (smem_u32(smem_raw) + 1023u) & ~1023u;
    uint8_t* sgen = smem_raw + (sbase - smem_u32(smem_raw));
    const uint32_t sK = sbase + OFF_KV, sV = sK + 384 * KV_PITCH;
    const uint32_t sBar = sbase + OFF_MISC;
    const uint32_t full1 = sBar, empty1 = sBar + 32, full2 = sBar + 64, empty2 = sBar + 104, kv_full = sBar + 144;
    float* sGate = (float*)(sgen + OFF_MISC + 256);
    uint8_t* sGw = sgen + OFF_MISC + 768;
    uint32_t* sBias = (uint32_t*)(sgen + OFF_MISC + 1792);

    const int rb = blockIdx.x >> 3, j = blockIdx.x & 7;
    const int tid = threadIdx.x, wg = tid >> 7, warp = tid >> 5, lane = tid & 31;
    TS(0, tid == 0);

    if (tid == 0) {
        for (int i = 0; i < P1_STAGES; i++) { mbar_init(full1 + 8 * i, 1); mbar_init(empty1 + 8 * i, 8); }
        for (int i = 0; i < P2_STAGES; i++) { mbar_init(full2 + 8 * i, 1); mbar_init(empty2 + 8 * i, 8); }
        mbar_init(kv_full, 1);
        fence_barrier_init();
    }
    __syncthreads();
    const unsigned int ep = *(volatile unsigned int*)&g_epoch + 1;

    if (wg >= 2) {
        reg_dealloc<104>();
        if (warp == 15) {
            if (lane == 0) {
                for (int it = 0; it < 16; it++) {
                    const int st = it % P1_STAGES;
                    if (it >= P1_STAGES) mbar_wait(empty1 + 8 * st, ((it / P1_STAGES) - 1) & 1);
                    mbar_expect_tx(full1 + 8 * st, P1_STAGE);
                    const uint32_t dst = sbase + st * P1_STAGE;
                    const int kc = it & 7;
                    tma_load_2d(dst, &tmX, kc * 64, rb * 128, full1 + 8 * st);
                    if (it < 8) {
                        for (int b = 0; b < 3; b++) tma_load_2d(dst + 16384 + b * 8192, &tmWqkv, b * 512 + j * 64, kc * 64, full1 + 8 * st);
                    } else {
                        for (int b = 0; b < 3; b++) tma_load_2d(dst + 16384 + b * 8192, &tmW1, j * FCH + b * 64, kc * 64, full1 + 8 * st);
                    }
                }
                for (int it = 13; it < 16; it++) mbar_wait(empty1 + 8 * (it % P1_STAGES), (it / P1_STAGES) & 1);
                for (int i = 0; i < 8; i++) flag_wait(&g_flag_act[rb * 8 + i], ep);
                fence_proxy_async();
                for (int ks = 0; ks < P2_KSTEPS; ks++) {
                    const int st = ks % P2_STAGES;
                    if (ks >= P2_STAGES) mbar_wait(empty2 + 8 * st, ((ks / P2_STAGES) - 1) & 1);
                    if (ks == 22) {
                        for (int i = 0; i < 8; i++) flag_wait(&g_flag_att[rb * 8 + i], ep);
                        fence_proxy_async();
                    }
                    mbar_expect_tx(full2 + 8 * st, P2_STAGE);
                    const uint32_t dst = sbase + st * P2_STAGE;
                    if (ks < 22) {
                        tma_load_2d(dst, &tmA2, D_ + ks * 64, rb * 128, full2 + 8 * st);
                        tma_load_2d(dst + 16384, &tmW2, j * 64, ks * 64, full2 + 8 * st);
                    } else {
                        tma_load_2d(dst, &tmA2, (ks - 22) * 64, rb * 128, full2 + 8 * st);
                        tma_load_2d(dst + 16384, &tmWo, j * 64, (ks - 22) * 64, full2 + 8 * st);
                    }
                }
            }
        } else {
            if (tid == 288) {
                const int b = blockIdx.x;
                mbar_wait(full1 + 8, 0);
                l2_prefetch((const uint8_t*)w1p + b * 11008, 11008);
                l2_prefetch((const uint8_t*)w2p + b * 11008, 11008);
                l2_prefetch((const uint8_t*)wop + b * 4096, 4096);
            }
            bar_sync(3, 256 + 224);
            if (tid == 256) {
                const int nblk = rb >= 2 ? 3 : rb + 1;
                for (int i = 0; i < nblk; i++) flag_wait(&g_flag_qkv[(rb - i) * 8 + j], ep);
                fence_proxy_async();
                mbar_expect_tx(kv_full, nblk * 2 * 16384);
                for (int i = 0; i < nblk; i++) {
                    const int row = j * S_ + (rb - i) * 128;
                    tma_load_2d(sK + (2 - i) * 16384, &tmQKV, 64, row, kv_full);
                    tma_load_2d(sV + (2 - i) * 16384, &tmQKV, 128, row, kv_full);
                }
            }
            __syncwarp();
            if (rb < 2) {
                for (int i = tid - 256; i < (2 - rb) * 1024; i += 224) {
                    *(uint4*)(sgen + OFF_KV + i * 16) = make_uint4(0, 0, 0, 0);
                    *(uint4*)(sgen + OFF_KV + 384 * KV_PITCH + i * 16) = make_uint4(0, 0, 0, 0);
                }
                bar_sync(4, 224);
            }
            const int r0 = lane >> 2, c0 = (lane & 3) * 2;
            mbar_wait(kv_full, 0);
            uint32_t sKd = sK, sVd = sV;
            asm volatile("" : "+r"(sKd), "+r"(sVd) :: "memory");
            TS(6, tid == 256);
#pragma unroll 1
            for (int task = warp - 8; task < 32; task += 7) {
                const int qt = task & 7, hl = task >> 3;
                const int q0g = rb * 128 + qt * 16;
                const float g0 = sGate[qt * 16 + r0], g1 = sGate[qt * 16 + r0 + 8];
                const int kb0 = q0g < 256 ? (256 - q0g) >> 4 : 0;
                const bf16* qsrc = g_qkv + ((size_t)j * S_ + q0g) * 192;
                uint32_t qa[4];
                qa[0] = *(const volatile uint32_t*)(qsrc + (size_t)r0 * 192 + hl * 16 + c0);
                qa[1] = *(const volatile uint32_t*)(qsrc + (size_t)(r0 + 8) * 192 + hl * 16 + c0);
                qa[2] = *(const volatile uint32_t*)(qsrc + (size_t)r0 * 192 + hl * 16 + c0 + 8);
                qa[3] = *(const volatile uint32_t*)(qsrc + (size_t)(r0 + 8) * 192 + hl * 16 + c0 + 8);
                const int krow = qt * 16 + (lane & 7) + ((lane >> 4) << 3);
                const uint32_t ka = sKd + krow * KV_PITCH + (((2 * hl + ((lane >> 3) & 1)) ^ (lane & 7)) << 4);
                const int vrow = qt * 16 + (lane & 15);
                const uint32_t va = sVd + vrow * KV_PITCH + (((2 * hl + (lane >> 4)) ^ (lane & 7)) << 4);
                if (rb < 2) attn_task<true>(qa, ka, va, kb0, lane, g_a2 + (size_t)q0g * KA2 + (j * 4 + hl) * 16, g0, g1);
                else        attn_task<false>(qa, ka, va, kb0, lane, g_a2 + (size_t)q0g * KA2 + (j * 4 + hl) * 16, g0, g1);
                TS(12 + task / 7, tid == 256);
            }
            TS(7, tid == 256);
            bar_sync(4, 224);
            if (tid == 256) { __threadfence(); flag_set(&g_flag_att[blockIdx.x], ep); }
        }
    } else {
        reg_alloc<152>();
        const int t128 = tid & 127, w4 = warp & 3, q = lane & 3;
        if (tid < 64) ((uint4*)sGw)[tid] = __ldg((const uint4*)gate_w + tid);
        else if (tid < 64 + 88) {
            const int c = j * FCH + (tid - 64) * 2;
            sBias[tid - 64] = c < F_ ? __ldg((const uint32_t*)(b1 + c)) : 0u;
        }
        bar_sync(1, 256);
        const int rl = wg * 64 + w4 * 16 + (lane >> 2);
        {
            float acc[96];
            float gs = 0.f;
            const int grow = wg * 64 + (t128 >> 1), ghalf = t128 & 1;
#pragma unroll
            for (int kc = 0; kc < 8; kc++) {
                const int st = kc % P1_STAGES;
                const uint32_t sa = sbase + st * P1_STAGE;
                mbar_wait(full1 + 8 * st, (kc / P1_STAGES) & 1);
                TS(1, tid == 0 && kc == 0);
                wgmma_fence();
#pragma unroll
                for (int k16 = 0; k16 < 4; k16++)
                    wgmma_n192<1>(acc, make_desc(sa + wg * 8192 + k16 * 32, 16, 1024),
                                  make_desc(sa + 16384 + k16 * 2048, 8192, 1024), (kc | k16) != 0);
                wgmma_commit();
#pragma unroll
                for (int c = 0; c < 4; c++) {
                    const int cc = ghalf * 4 + c;
                    const uint4 xv = *(const uint4*)(sgen + st * P1_STAGE + grow * 128 + ((cc ^ (grow & 7)) << 4));
                    const uint4 gv = *(const uint4*)(sGw + kc * 128 + cc * 16);
                    gs = fmaf(bf_lo(xv.x), bf_lo(gv.x), gs); gs = fmaf(bf_hi(xv.x), bf_hi(gv.x), gs);
                    gs = fmaf(bf_lo(xv.y), bf_lo(gv.y), gs); gs = fmaf(bf_hi(xv.y), bf_hi(gv.y), gs);
                    gs = fmaf(bf_lo(xv.z), bf_lo(gv.z), gs); gs = fmaf(bf_hi(xv.z), bf_hi(gv.z), gs);
                    gs = fmaf(bf_lo(xv.w), bf_lo(gv.w), gs); gs = fmaf(bf_hi(xv.w), bf_hi(gv.w), gs);
                }
                if (kc > 0) { wgmma_wait<1>(); if (lane == 0) mbar_arrive(empty1 + 8 * ((kc - 1) % P1_STAGES)); }
            }
            gs += __shfl_xor_sync(0xffffffffu, gs, 1);
            if (ghalf == 0) sGate[grow] = 1.f / (1.f + __expf(-gs));
            wgmma_wait<0>();
            if (lane == 0) mbar_arrive(empty1 + 8 * (7 % P1_STAGES));
            TS(2, tid == 0);
            bf16* orow0 = g_qkv + ((size_t)j * S_ + rb * 128 + rl) * 192;
            bf16* orow1 = orow0 + 8 * 192;
#pragma unroll
            for (int u = 0; u < 6; u++) {
                uint32_t w0[4], w1[4];
#pragma unroll
                for (int i = 0; i < 4; i++) {
                    const int t = u * 4 + i;
                    w0[i] = pack_bf16(acc[t * 4 + 0], acc[t * 4 + 1]);
                    w1[i] = pack_bf16(acc[t * 4 + 2], acc[t * 4 + 3]);
                }
                quad_transpose(w0, q);
                quad_transpose(w1, q);
                const int c = (u * 4 + q) * 8;
                *(uint4*)(orow0 + c) = make_uint4(w0[0], w0[1], w0[2], w0[3]);
                *(uint4*)(orow1 + c) = make_uint4(w1[0], w1[1], w1[2], w1[3]);
            }
            bar_sync(3, 256 + 224);
            if (tid == 0) { __threadfence(); flag_set(&g_flag_qkv[blockIdx.x], ep); }
            TS(3, tid == 0);
        }
        {
            float acc[88];
#pragma unroll
            for (int kc = 0; kc < 8; kc++) {
                const int it = kc + 8, st = it % P1_STAGES;
                const uint32_t sa = sbase + st * P1_STAGE;
                mbar_wait(full1 + 8 * st, (it / P1_STAGES) & 1);
                wgmma_fence();
#pragma unroll
                for (int k16 = 0; k16 < 4; k16++)
                    wgmma_n176<1>(acc, make_desc(sa + wg * 8192 + k16 * 32, 16, 1024),
                                  make_desc(sa + 16384 + k16 * 2048, 8192, 1024), (kc | k16) != 0);
                wgmma_commit();
                if (kc > 0) { wgmma_wait<1>(); if (lane == 0) mbar_arrive(empty1 + 8 * ((it - 1) % P1_STAGES)); }
            }
            wgmma_wait<0>();
            if (lane == 0) mbar_arrive(empty1 + 8 * (15 % P1_STAGES));
            TS(4, tid == 0);
            const int n0 = j * FCH;
            const float om0 = 1.f - sGate[rl], om1 = 1.f - sGate[rl + 8];
            bf16* frow0 = g_a2 + (size_t)(rb * 128 + rl) * KA2 + D_ + n0;
            bf16* frow1 = frow0 + 8 * KA2;
#pragma unroll
            for (int u = 0; u < 6; u++) {
                uint32_t w0[4], w1[4];
#pragma unroll
                for (int i = 0; i < 4; i++) {
                    const int t = u * 4 + i;
                    if (t < 22) {
                        const uint32_t bv = sBias[t * 4 + q];
                        const float bb0 = bf_lo(bv), bb1 = bf_hi(bv);
                        w0[i] = pack_bf16(mish_f(acc[t * 4 + 0] + bb0) * om0, mish_f(acc[t * 4 + 1] + bb1) * om0);
                        w1[i] = pack_bf16(mish_f(acc[t * 4 + 2] + bb0) * om1, mish_f(acc[t * 4 + 3] + bb1) * om1);
                    } else { w0[i] = 0; w1[i] = 0; }
                }
                quad_transpose(w0, q);
                quad_transpose(w1, q);
                const int c = (u * 4 + q) * 8;
                if (c < FCH && n0 + c < F_) {
                    *(uint4*)(frow0 + c) = make_uint4(w0[0], w0[1], w0[2], w0[3]);
                    *(uint4*)(frow1 + c) = make_uint4(w1[0], w1[1], w1[2], w1[3]);
                }
            }
            bar_sync(1, 256);
            if (tid == 0) { __threadfence(); flag_set(&g_flag_act[blockIdx.x], ep); }
            TS(5, tid == 0);
        }
        {
            float acc[32];
            for (int ks = 0; ks < P2_KSTEPS; ks++) {
                const int st = ks % P2_STAGES;
                const uint32_t sa = sbase + st * P2_STAGE;
                mbar_wait(full2 + 8 * st, (ks / P2_STAGES) & 1);
                TS(8, tid == 0 && ks == 0); TS(9, tid == 0 && ks == 22);
                wgmma_fence();
#pragma unroll
                for (int k16 = 0; k16 < 4; k16++)
                    wgmma_n64<1>(acc, make_desc(sa + wg * 8192 + k16 * 32, 16, 1024),
                                 make_desc(sa + 16384 + k16 * 2048, 8192, 1024), (ks | k16) != 0);
                wgmma_commit();
                if (ks > 0) { wgmma_wait<1>(); if (lane == 0) mbar_arrive(empty2 + 8 * ((ks - 1) % P2_STAGES)); }
            }
            wgmma_wait<0>();
            TS(10, tid == 0);
            bf16* orow0 = out + (size_t)(rb * 128 + rl) * D_ + j * 64;
            bf16* orow1 = orow0 + 8 * D_;
#pragma unroll
            for (int u = 0; u < 2; u++) {
                uint32_t w0[4], w1[4];
#pragma unroll
                for (int i = 0; i < 4; i++) {
                    const int t = u * 4 + i;
                    w0[i] = pack_bf16(acc[t * 4 + 0], acc[t * 4 + 1]);
                    w1[i] = pack_bf16(acc[t * 4 + 2], acc[t * 4 + 3]);
                }
                quad_transpose(w0, q);
                quad_transpose(w1, q);
                const int c = (u * 4 + q) * 8;
                *(uint4*)(orow0 + c) = make_uint4(w0[0], w0[1], w0[2], w0[3]);
                *(uint4*)(orow1 + c) = make_uint4(w1[0], w1[1], w1[2], w1[3]);
            }
            TS(11, tid == 0);
        }
        if (tid == 0) {
            __threadfence();
            if (atomicAdd(&g_done, 1u) == gridDim.x - 1) {
                g_done = 0;
                __threadfence();
                atomicAdd(&g_epoch, 1u);
            }
        }
    }
}

typedef CUresult (*PFN_encodeTiled)(CUtensorMap*, CUtensorMapDataType, cuuint32_t, void*, const cuuint64_t*,
                                    const cuuint64_t*, const cuuint32_t*, const cuuint32_t*, CUtensorMapInterleave,
                                    CUtensorMapSwizzle, CUtensorMapL2promotion, CUtensorMapFloatOOBfill);

static void make_map(PFN_encodeTiled enc, CUtensorMap* m, const void* ptr, uint64_t cols, uint64_t rows,
                     uint32_t box_cols, uint32_t box_rows)
{
    cuuint64_t dims[2] = {cols, rows};
    cuuint64_t strides[1] = {cols * 2};
    cuuint32_t box[2] = {box_cols, box_rows};
    cuuint32_t es[2] = {1, 1};
    enc(m, CU_TENSOR_MAP_DATA_TYPE_BFLOAT16, 2, const_cast<void*>(ptr), dims, strides, box, es,
        CU_TENSOR_MAP_INTERLEAVE_NONE, CU_TENSOR_MAP_SWIZZLE_128B, CU_TENSOR_MAP_L2_PROMOTION_L2_128B,
        CU_TENSOR_MAP_FLOAT_OOB_FILL_NONE);
}

extern "C" void kernel_launch(void* const* d_in, const int* in_sizes, int n_in, void* d_out, int out_size)
{
    const bf16* x    = (const bf16*)d_in[0];
    const bf16* wqkv = (const bf16*)d_in[1];
    const bf16* wo   = (const bf16*)d_in[2];
    const bf16* w1   = (const bf16*)d_in[4];
    const bf16* b1   = (const bf16*)d_in[5];
    const bf16* w2   = (const bf16*)d_in[6];
    const bf16* gw   = (const bf16*)d_in[7];

    static PFN_encodeTiled enc = nullptr;
    if (!enc) {
        void* fn = nullptr;
        cudaDriverEntryPointQueryResult qr;
        cudaGetDriverEntryPoint("cuTensorMapEncodeTiled", &fn, cudaEnableDefault, &qr);
        enc = (PFN_encodeTiled)fn;
        cudaFuncSetAttribute(fused_kernel, cudaFuncAttributeMaxDynamicSharedMemorySize, FUSED_SMEM);
    }
    void *a2p = nullptr, *qkvp = nullptr;
    cudaGetSymbolAddress(&a2p, g_a2);
    cudaGetSymbolAddress(&qkvp, g_qkv);
    CUtensorMap tmX, tmWqkv, tmW1, tmQKV, tmA2, tmWo, tmW2;
    make_map(enc, &tmX, x, D_, S_, 64, 128);
    make_map(enc, &tmWqkv, wqkv, 3 * D_, D_, 64, 64);
    make_map(enc, &tmW1, w1, F_, D_, 64, 64);
    make_map(enc, &tmQKV, qkvp, 192, 8 * S_, 64, 128);
    make_map(enc, &tmA2, a2p, KA2, S_, 64, 128);
    make_map(enc, &tmWo, wo, D_, D_, 64, 64);
    make_map(enc, &tmW2, w2, D_, F_, 64, 64);

    fused_kernel<<<128, 512, FUSED_SMEM, cudaStreamPerThread>>>(tmX, tmWqkv, tmW1, tmQKV, tmA2, tmWo, tmW2,
                                                                b1, gw, w1, wqkv, w2, wo, (bf16*)d_out);
}
```

```cpp
#include <cuda_runtime.h>
#include <cuda_bf16.h>
#include <cuda.h>
#include <stdint.h>

typedef __nv_bfloat16 bf16;

constexpr int S_ = 2048, D_ = 512, F_ = 1376;
constexpr int KA2 = D_ + F_;
constexpr int FCH = 176;

__device__ bf16  g_qkv[8 * S_ * 192];
__device__ bf16  g_a2[S_ * KA2];
__device__ float g_gate[S_];

#define TS(k, cond) do { } while (0)

__device__ __forceinline__ uint32_t smem_u32(const void* p) { return (uint32_t)__cvta_generic_to_shared(p); }
__device__ __forceinline__ void mbar_init(uint32_t bar, uint32_t count) {
    asm volatile("mbarrier.init.shared::cta.b64 [%0], %1;" :: "r"(bar), "r"(count) : "memory");
}
__device__ __forceinline__ void mbar_expect_tx(uint32_t bar, uint32_t bytes) {
    asm volatile("mbarrier.arrive.expect_tx.shared::cta.b64 _, [%0], %1;" :: "r"(bar), "r"(bytes) : "memory");
}
__device__ __forceinline__ void mbar_arrive(uint32_t bar) {
    asm volatile("mbarrier.arrive.shared::cta.b64 _, [%0];" :: "r"(bar) : "memory");
}
__device__ __forceinline__ bool mbar_try_wait(uint32_t bar, uint32_t parity) {
    uint32_t ok;
    asm volatile("{\n.reg .pred p;\nmbarrier.try_wait.parity.shared::cta.b64 p, [%1], %2;\nselp.u32 %0, 1, 0, p;\n}"
                 : "=r"(ok) : "r"(bar), "r"(parity) : "memory");
    return ok != 0;
}
__device__ __forceinline__ void mbar_wait(uint32_t bar, uint32_t parity) {
    for (uint32_t it = 0; it < (1u << 22); ++it) { if (mbar_try_wait(bar, parity)) break; }
}
__device__ __forceinline__ void tma_load_2d(uint32_t dst, const CUtensorMap* map, int c0, int c1, uint32_t bar) {
    asm volatile("cp.async.bulk.tensor.2d.shared::cluster.global.mbarrier::complete_tx::bytes [%0], [%1, {%3, %4}], [%2];"
                 :: "r"(dst), "l"(map), "r"(bar), "r"(c0), "r"(c1) : "memory");
}
__device__ __forceinline__ void l2_prefetch(const void* p, uint32_t bytes) {
    asm volatile("cp.async.bulk.prefetch.L2.global [%0], %1;" :: "l"(p), "r"(bytes) : "memory");
}
__device__ __forceinline__ void fence_barrier_init() { asm volatile("fence.mbarrier_init.release.cluster;" ::: "memory"); }
__device__ __forceinline__ void wgmma_fence()  { asm volatile("wgmma.fence.sync.aligned;" ::: "memory"); }
__device__ __forceinline__ void wgmma_commit() { asm volatile("wgmma.commit_group.sync.aligned;" ::: "memory"); }
template <int N> __device__ __forceinline__ void wgmma_wait() { asm volatile("wgmma.wait_group.sync.aligned %0;" :: "n"(N) : "memory"); }
template <int R> __device__ __forceinline__ void reg_alloc()   { asm volatile("setmaxnreg.inc.sync.aligned.u32 %0;" :: "n"(R)); }
template <int R> __device__ __forceinline__ void reg_dealloc() { asm volatile("setmaxnreg.dec.sync.aligned.u32 %0;" :: "n"(R)); }
__device__ __forceinline__ void bar_sync(int id, int n)   { asm volatile("bar.sync %0, %1;" :: "r"(id), "r"(n) : "memory"); }
__device__ __forceinline__ void bar_arrive(int id, int n) { asm volatile("bar.arrive %0, %1;" :: "r"(id), "r"(n) : "memory"); }

__device__ __forceinline__ uint64_t make_desc(uint32_t addr, uint32_t lbo, uint32_t sbo) {
    uint64_t d = (uint64_t)((addr & 0x3FFFF) >> 4);
    d |= (uint64_t)((lbo & 0x3FFFF) >> 4) << 16;
    d |= (uint64_t)((sbo & 0x3FFFF) >> 4) << 32;
    d |= (uint64_t)1 << 62;
    return d;
}

template <int TB>
__device__ __forceinline__ void wgmma_n64(float (&d)[32], uint64_t da, uint64_t db, int scale_d) {
    asm volatile("{\n.reg .pred p;\nsetp.ne.b32 p, %34, 0;\n"
        "wgmma.mma_async.sync.aligned.m64n64k16.f32.bf16.bf16 {%0, %1, %2, %3, %4, %5, %6, %7, %8, %9, %10, %11, %12, %13, %14, %15, %16, %17, %18, %19, %20, %21, %22, %23, %24, %25, %26, %27, %28, %29, %30, %31}, %32, %33, p, 1, 1, 0, %35;\n}\n"
        : "+f"(d[0]), "+f"(d[1]), "+f"(d[2]), "+f"(d[3]), "+f"(d[4]), "+f"(d[5]), "+f"(d[6]), "+f"(d[7]), "+f"(d[8]), "+f"(d[9]), "+f"(d[10]), "+f"(d[11]), "+f"(d[12]), "+f"(d[13]), "+f"(d[14]), "+f"(d[15]), "+f"(d[16]), "+f"(d[17]), "+f"(d[18]), "+f"(d[19]), "+f"(d[20]), "+f"(d[21]), "+f"(d[22]), "+f"(d[23]), "+f"(d[24]), "+f"(d[25]), "+f"(d[26]), "+f"(d[27]), "+f"(d[28]), "+f"(d[29]), "+f"(d[30]), "+f"(d[31])
        : "l"(da), "l"(db), "r"(scale_d), "n"(TB));
}

template <int TB>
__device__ __forceinline__ void wgmma_n128(float (&d)[64], uint64_t da, uint64_t db, int scale_d) {
    asm volatile("{\n.reg .pred p;\nsetp.ne.b32 p, %66, 0;\n"
        "wgmma.mma_async.sync.aligned.m64n128k16.f32.bf16.bf16 {%0, %1, %2, %3, %4, %5, %6, %7, %8, %9, %10, %11, %12, %13, %14, %15, %16, %17, %18, %19, %20, %21, %22, %23, %24, %25, %26, %27, %28, %29, %30, %31, %32, %33, %34, %35, %36, %37, %38, %39, %40, %41, %42, %43, %44, %45, %46, %47, %48, %49, %50, %51, %52, %53, %54, %55, %56, %57, %58, %59, %60, %61, %62, %63}, %64, %65, p, 1, 1, 0, %67;\n}\n"
        : "+f"(d[0]), "+f"(d[1]), "+f"(d[2]), "+f"(d[3]), "+f"(d[4]), "+f"(d[5]), "+f"(d[6]), "+f"(d[7]), "+f"(d[8]), "+f"(d[9]), "+f"(d[10]), "+f"(d[11]), "+f"(d[12]), "+f"(d[13]), "+f"(d[14]), "+f"(d[15]), "+f"(d[16]), "+f"(d[17]), "+f"(d[18]), "+f"(d[19]), "+f"(d[20]), "+f"(d[21]), "+f"(d[22]), "+f"(d[23]), "+f"(d[24]), "+f"(d[25]), "+f"(d[26]), "+f"(d[27]), "+f"(d[28]), "+f"(d[29]), "+f"(d[30]), "+f"(d[31]), "+f"(d[32]), "+f"(d[33]), "+f"(d[34]), "+f"(d[35]), "+f"(d[36]), "+f"(d[37]), "+f"(d[38]), "+f"(d[39]), "+f"(d[40]), "+f"(d[41]), "+f"(d[42]), "+f"(d[43]), "+f"(d[44]), "+f"(d[45]), "+f"(d[46]), "+f"(d[47]), "+f"(d[48]), "+f"(d[49]), "+f"(d[50]), "+f"(d[51]), "+f"(d[52]), "+f"(d[53]), "+f"(d[54]), "+f"(d[55]), "+f"(d[56]), "+f"(d[57]), "+f"(d[58]), "+f"(d[59]), "+f"(d[60]), "+f"(d[61]), "+f"(d[62]), "+f"(d[63])
        : "l"(da), "l"(db), "r"(scale_d), "n"(TB));
}

template <int TB>
__device__ __forceinline__ void wgmma_n176(float (&d)[88], uint64_t da, uint64_t db, int scale_d) {
    asm volatile("{\n.reg .pred p;\nsetp.ne.b32 p, %90, 0;\n"
        "wgmma.mma_async.sync.aligned.m64n176k16.f32.bf16.bf16 {%0, %1, %2, %3, %4, %5, %6, %7, %8, %9, %10, %11, %12, %13, %14, %15, %16, %17, %18, %19, %20, %21, %22, %23, %24, %25, %26, %27, %28, %29, %30, %31, %32, %33, %34, %35, %36, %37, %38, %39, %40, %41, %42, %43, %44, %45, %46, %47, %48, %49, %50, %51, %52, %53, %54, %55, %56, %57, %58, %59, %60, %61, %62, %63, %64, %65, %66, %67, %68, %69, %70, %71, %72, %73, %74, %75, %76, %77, %78, %79, %80, %81, %82, %83, %84, %85, %86, %87}, %88, %89, p, 1, 1, 0, %91;\n}\n"
        : "+f"(d[0]), "+f"(d[1]), "+f"(d[2]), "+f"(d[3]), "+f"(d[4]), "+f"(d[5]), "+f"(d[6]), "+f"(d[7]), "+f"(d[8]), "+f"(d[9]), "+f"(d[10]), "+f"(d[11]), "+f"(d[12]), "+f"(d[13]), "+f"(d[14]), "+f"(d[15]), "+f"(d[16]), "+f"(d[17]), "+f"(d[18]), "+f"(d[19]), "+f"(d[20]), "+f"(d[21]), "+f"(d[22]), "+f"(d[23]), "+f"(d[24]), "+f"(d[25]), "+f"(d[26]), "+f"(d[27]), "+f"(d[28]), "+f"(d[29]), "+f"(d[30]), "+f"(d[31]), "+f"(d[32]), "+f"(d[33]), "+f"(d[34]), "+f"(d[35]), "+f"(d[36]), "+f"(d[37]), "+f"(d[38]), "+f"(d[39]), "+f"(d[40]), "+f"(d[41]), "+f"(d[42]), "+f"(d[43]), "+f"(d[44]), "+f"(d[45]), "+f"(d[46]), "+f"(d[47]), "+f"(d[48]), "+f"(d[49]), "+f"(d[50]), "+f"(d[51]), "+f"(d[52]), "+f"(d[53]), "+f"(d[54]), "+f"(d[55]), "+f"(d[56]), "+f"(d[57]), "+f"(d[58]), "+f"(d[59]), "+f"(d[60]), "+f"(d[61]), "+f"(d[62]), "+f"(d[63]), "+f"(d[64]), "+f"(d[65]), "+f"(d[66]), "+f"(d[67]), "+f"(d[68]), "+f"(d[69]), "+f"(d[70]), "+f"(d[71]), "+f"(d[72]), "+f"(d[73]), "+f"(d[74]), "+f"(d[75]), "+f"(d[76]), "+f"(d[77]), "+f"(d[78]), "+f"(d[79]), "+f"(d[80]), "+f"(d[81]), "+f"(d[82]), "+f"(d[83]), "+f"(d[84]), "+f"(d[85]), "+f"(d[86]), "+f"(d[87])
        : "l"(da), "l"(db), "r"(scale_d), "n"(TB));
}

template <int TB>
__device__ __forceinline__ void wgmma_n192(float (&d)[96], uint64_t da, uint64_t db, int scale_d) {
    asm volatile("{\n.reg .pred p;\nsetp.ne.b32 p, %98, 0;\n"
        "wgmma.mma_async.sync.aligned.m64n192k16.f32.bf16.bf16 {%0, %1, %2, %3, %4, %5, %6, %7, %8, %9, %10, %11, %12, %13, %14, %15, %16, %17, %18, %19, %20, %21, %22, %23, %24, %25, %26, %27, %28, %29, %30, %31, %32, %33, %34, %35, %36, %37, %38, %39, %40, %41, %42, %43, %44, %45, %46, %47, %48, %49, %50, %51, %52, %53, %54, %55, %56, %57, %58, %59, %60, %61, %62, %63, %64, %65, %66, %67, %68, %69, %70, %71, %72, %73, %74, %75, %76, %77, %78, %79, %80, %81, %82, %83, %84, %85, %86, %87, %88, %89, %90, %91, %92, %93, %94, %95}, %96, %97, p, 1, 1, 0, %99;\n}\n"
        : "+f"(d[0]), "+f"(d[1]), "+f"(d[2]), "+f"(d[3]), "+f"(d[4]), "+f"(d[5]), "+f"(d[6]), "+f"(d[7]), "+f"(d[8]), "+f"(d[9]), "+f"(d[10]), "+f"(d[11]), "+f"(d[12]), "+f"(d[13]), "+f"(d[14]), "+f"(d[15]), "+f"(d[16]), "+f"(d[17]), "+f"(d[18]), "+f"(d[19]), "+f"(d[20]), "+f"(d[21]), "+f"(d[22]), "+f"(d[23]), "+f"(d[24]), "+f"(d[25]), "+f"(d[26]), "+f"(d[27]), "+f"(d[28]), "+f"(d[29]), "+f"(d[30]), "+f"(d[31]), "+f"(d[32]), "+f"(d[33]), "+f"(d[34]), "+f"(d[35]), "+f"(d[36]), "+f"(d[37]), "+f"(d[38]), "+f"(d[39]), "+f"(d[40]), "+f"(d[41]), "+f"(d[42]), "+f"(d[43]), "+f"(d[44]), "+f"(d[45]), "+f"(d[46]), "+f"(d[47]), "+f"(d[48]), "+f"(d[49]), "+f"(d[50]), "+f"(d[51]), "+f"(d[52]), "+f"(d[53]), "+f"(d[54]), "+f"(d[55]), "+f"(d[56]), "+f"(d[57]), "+f"(d[58]), "+f"(d[59]), "+f"(d[60]), "+f"(d[61]), "+f"(d[62]), "+f"(d[63]), "+f"(d[64]), "+f"(d[65]), "+f"(d[66]), "+f"(d[67]), "+f"(d[68]), "+f"(d[69]), "+f"(d[70]), "+f"(d[71]), "+f"(d[72]), "+f"(d[73]), "+f"(d[74]), "+f"(d[75]), "+f"(d[76]), "+f"(d[77]), "+f"(d[78]), "+f"(d[79]), "+f"(d[80]), "+f"(d[81]), "+f"(d[82]), "+f"(d[83]), "+f"(d[84]), "+f"(d[85]), "+f"(d[86]), "+f"(d[87]), "+f"(d[88]), "+f"(d[89]), "+f"(d[90]), "+f"(d[91]), "+f"(d[92]), "+f"(d[93]), "+f"(d[94]), "+f"(d[95])
        : "l"(da), "l"(db), "r"(scale_d), "n"(TB));
}

__device__ __forceinline__ uint32_t pack_bf16(float lo, float hi) {
    uint32_t r;
    asm("cvt.rn.bf16x2.f32 %0, %1, %2;" : "=r"(r) : "f"(hi), "f"(lo));
    return r;
}
__device__ __forceinline__ float bf_lo(uint32_t v) { return __uint_as_float(v << 16); }
__device__ __forceinline__ float bf_hi(uint32_t v) { return __uint_as_float(v & 0xffff0000u); }

__device__ __forceinline__ void quad_transpose(uint32_t (&w)[4], int q) {
    const bool o1 = q & 1, o2 = q & 2;
    {
        uint32_t s0 = o1 ? w[0] : w[1], s1 = o1 ? w[2] : w[3];
        s0 = __shfl_xor_sync(0xffffffffu, s0, 1); s1 = __shfl_xor_sync(0xffffffffu, s1, 1);
        if (o1) { w[0] = s0; w[2] = s1; } else { w[1] = s0; w[3] = s1; }
    }
    {
        uint32_t s0 = o2 ? w[0] : w[2], s1 = o2 ? w[1] : w[3];
        s0 = __shfl_xor_sync(0xffffffffu, s0, 2); s1 = __shfl_xor_sync(0xffffffffu, s1, 2);
        if (o2) { w[0] = s0; w[1] = s1; } else { w[2] = s0; w[3] = s1; }
    }
}

__device__ __forceinline__ float ex2(float x) { float y; asm("ex2.approx.ftz.f32 %0, %1;" : "=f"(y) : "f"(x)); return y; }
__device__ __forceinline__ float rcp(float x) { float y; asm("rcp.approx.ftz.f32 %0, %1;" : "=f"(y) : "f"(x)); return y; }

__device__ __forceinline__ float ex2v(float x) { float y; asm volatile("ex2.approx.ftz.f32 %0, %1;" : "=f"(y) : "f"(x)); return y; }
__device__ __forceinline__ float rcpv(float x) { float y; asm volatile("rcp.approx.ftz.f32 %0, %1;" : "=f"(y) : "f"(x)); return y; }
__device__ __forceinline__ float mish_f(float h) {
    const float w = ex2v(-1.4426950408889634f * fabsf(h));
    const float t = w * w;
    const bool pos = h > 0.f;
    const float num = fmaf(2.f, w, pos ? 1.f : t);
    const float den = num + (pos ? t + t : 2.f);
    return h * num * rcpv(den);
}

__device__ unsigned int g_epoch;
__device__ unsigned int g_done;
__device__ unsigned int g_flag_qkv[128];
__device__ unsigned int g_flag_act[128];
__device__ unsigned int g_flag_att[128];

__device__ __forceinline__ void flag_set(unsigned int* f, unsigned int v) {
    asm volatile("st.release.gpu.global.u32 [%0], %1;" :: "l"(f), "r"(v) : "memory");
}
__device__ __forceinline__ void flag_wait(const unsigned int* f, unsigned int v) {
    for (uint32_t it = 0; it < (1u << 22); ++it) {
        unsigned int x;
        asm volatile("ld.acquire.gpu.global.u32 %0, [%1];" : "=r"(x) : "l"(f) : "memory");
        if (x == v) break;
    }
}
__device__ __forceinline__ void fence_proxy_async() { asm volatile("fence.proxy.async;" ::: "memory"); }

__device__ __forceinline__ void ldsm_x4(uint32_t (&r)[4], uint32_t addr) {
    asm("ldmatrix.sync.aligned.m8n8.x4.shared.b16 {%0,%1,%2,%3}, [%4];"
                 : "=r"(r[0]), "=r"(r[1]), "=r"(r[2]), "=r"(r[3]) : "r"(addr));
}
__device__ __forceinline__ void ldsm_x4_t(uint32_t (&r)[4], uint32_t addr) {
    asm("ldmatrix.sync.aligned.m8n8.x4.trans.shared.b16 {%0,%1,%2,%3}, [%4];"
                 : "=r"(r[0]), "=r"(r[1]), "=r"(r[2]), "=r"(r[3]) : "r"(addr));
}
__device__ __forceinline__ void mma16816(float (&d)[4], const uint32_t (&a)[4], uint32_t b0, uint32_t b1) {
    asm("mma.sync.aligned.m16n8k16.row.col.f32.bf16.bf16.f32 {%0,%1,%2,%3}, {%4,%5,%6,%7}, {%8,%9}, {%0,%1,%2,%3};"
                 : "+f"(d[0]), "+f"(d[1]), "+f"(d[2]), "+f"(d[3])
                 : "r"(a[0]), "r"(a[1]), "r"(a[2]), "r"(a[3]), "r"(b0), "r"(b1));
}
__device__ __forceinline__ void mma16816_z(float (&d)[4], const uint32_t (&a)[4], uint32_t b0, uint32_t b1) {
    asm("mma.sync.aligned.m16n8k16.row.col.f32.bf16.bf16.f32 {%0,%1,%2,%3}, {%4,%5,%6,%7}, {%8,%9}, {%10,%10,%10,%10};"
                 : "=f"(d[0]), "=f"(d[1]), "=f"(d[2]), "=f"(d[3])
                 : "r"(a[0]), "r"(a[1]), "r"(a[2]), "r"(a[3]), "r"(b0), "r"(b1), "f"(0.f));
}

constexpr int KV_PITCH = 128;

template <int NB, bool MASK_FIRST, bool MASK_LAST, bool HEAD>
__device__ __forceinline__ void attn_chunk(const uint32_t (&qa)[4], uint32_t ka, uint32_t va, int kbs, int kb0, int r0, int c0,
                                           float& m0, float& m1, float& l0, float& l1, float (&o)[2][4])
{
    const float C = 0.25f * 1.4426950408889634f;
    float s[NB][2][4];
#pragma unroll
    for (int b = 0; b < NB; b++) {
        uint32_t kf[4];
        ldsm_x4(kf, ka + (kbs + b) * 16 * KV_PITCH);
        mma16816_z(s[b][0], qa, kf[0], kf[1]);
        mma16816_z(s[b][1], qa, kf[2], kf[3]);
    }
#pragma unroll
    for (int t = 0; t < 2; t++)
#pragma unroll
        for (int e = 0; e < 4; e++) {
            const int r = r0 + (e >> 1) * 8, c = t * 8 + c0 + (e & 1);
            if (MASK_FIRST && c <= r) s[0][t][e] = -1e30f;
            if (MASK_LAST && c > r) s[NB - 1][t][e] = -1e30f;
        }
    if (HEAD) {
#pragma unroll
        for (int b = 0; b < NB; b++)
            if (kbs + b < kb0) {
#pragma unroll
                for (int t = 0; t < 2; t++)
#pragma unroll
                    for (int e = 0; e < 4; e++) s[b][t][e] = -1e30f;
            }
    }
    float n0 = m0, n1 = m1;
#pragma unroll
    for (int b = 0; b < NB; b++) {
        n0 = fmaxf(n0, fmaxf(fmaxf(s[b][0][0], s[b][0][1]), fmaxf(s[b][1][0], s[b][1][1])));
        n1 = fmaxf(n1, fmaxf(fmaxf(s[b][0][2], s[b][0][3]), fmaxf(s[b][1][2], s[b][1][3])));
    }
    n0 = fmaxf(n0, __shfl_xor_sync(0xffffffffu, n0, 1)); n0 = fmaxf(n0, __shfl_xor_sync(0xffffffffu, n0, 2));
    n1 = fmaxf(n1, __shfl_xor_sync(0xffffffffu, n1, 1)); n1 = fmaxf(n1, __shfl_xor_sync(0xffffffffu, n1, 2));
    const float mc0 = n0 * C, mc1 = n1 * C;
    if (!MASK_LAST) {
        const float a0 = ex2(fmaf(m0, C, -mc0)), a1 = ex2(fmaf(m1, C, -mc1));
        l0 *= a0; l1 *= a1;
        o[0][0] *= a0; o[0][1] *= a0; o[1][0] *= a0; o[1][1] *= a0;
        o[0][2] *= a1; o[0][3] *= a1; o[1][2] *= a1; o[1][3] *= a1;
    }
    m0 = n0; m1 = n1;
#pragma unroll
    for (int b = 0; b < NB; b++) {
        uint32_t pa[4];
#pragma unroll
        for (int t = 0; t < 2; t++) {
            const float p0 = ex2(fmaf(s[b][t][0], C, -mc0)), p1 = ex2(fmaf(s[b][t][1], C, -mc0));
            const float p2 = ex2(fmaf(s[b][t][2], C, -mc1)), p3 = ex2(fmaf(s[b][t][3], C, -mc1));
            l0 += p0 + p1; l1 += p2 + p3;
            pa[2 * t] = pack_bf16(p0, p1); pa[2 * t + 1] = pack_bf16(p2, p3);
        }
        uint32_t vf[4];
        ldsm_x4_t(vf, va + (kbs + b) * 16 * KV_PITCH);
        mma16816(o[0], pa, vf[0], vf[1]);
        mma16816(o[1], pa, vf[2], vf[3]);
    }
}

template <bool HEAD>
__device__ __forceinline__ void attn_task(const uint32_t (&qa)[4], uint32_t ka, uint32_t va, int kb0, int lane,
                                          bf16* __restrict__ out  , float g0, float g1)
{
    const int r0 = lane >> 2, c0 = (lane & 3) * 2;
    float m0 = -1e30f, m1 = -1e30f, l0 = 0.f, l1 = 0.f;
    float o[2][4] = {{0.f, 0.f, 0.f, 0.f}, {0.f, 0.f, 0.f, 0.f}};
    attn_chunk<5, false, true, HEAD>(qa, ka, va, 12, kb0, r0, c0, m0, m1, l0, l1, o);
    if (!HEAD || kb0 < 12) attn_chunk<4, false, false, HEAD>(qa, ka, va, 8, kb0, r0, c0, m0, m1, l0, l1, o);
    if (!HEAD || kb0 < 8)  attn_chunk<4, false, false, HEAD>(qa, ka, va, 4, kb0, r0, c0, m0, m1, l0, l1, o);
    if (!HEAD || kb0 < 4)  attn_chunk<4, true, false, HEAD>(qa, ka, va, 0, kb0, r0, c0, m0, m1, l0, l1, o);
    l0 += __shfl_xor_sync(0xffffffffu, l0, 1); l0 += __shfl_xor_sync(0xffffffffu, l0, 2);
    l1 += __shfl_xor_sync(0xffffffffu, l1, 1); l1 += __shfl_xor_sync(0xffffffffu, l1, 2);
    const float f0 = g0 / l0, f1 = g1 / l1;
#pragma unroll
    for (int t = 0; t < 2; t++) {
        *(uint32_t*)(out + (size_t)r0 * KA2 + t * 8 + c0) = pack_bf16(o[t][0] * f0, o[t][1] * f0);
        *(uint32_t*)(out + (size_t)(r0 + 8) * KA2 + t * 8 + c0) = pack_bf16(o[t][2] * f1, o[t][3] * f1);
    }
}

constexpr int P1_STAGES = 3;
constexpr int P1_STAGE  = 16384 + 24576;
constexpr int P2_STAGES = 5;
constexpr int P2_STAGE  = 16384 + 8192;
constexpr int P2_KSTEPS = 30;
constexpr int OFF_KV    = P1_STAGES * P1_STAGE;
constexpr int OFF_MISC  = OFF_KV + 2 * 384 * KV_PITCH;
constexpr int FUSED_SMEM = OFF_MISC + 2048 + 1024;

__device__ __forceinline__ void flag_add_release(unsigned int* f) {
    asm volatile("red.release.gpu.global.add.u32 [%0], 1;" :: "l"(f) : "memory");
}

__global__ void __launch_bounds__(512, 1)
fused_kernel(const __grid_constant__ CUtensorMap tmX, const __grid_constant__ CUtensorMap tmWqkv,
             const __grid_constant__ CUtensorMap tmW1, const __grid_constant__ CUtensorMap tmQKV,
             const __grid_constant__ CUtensorMap tmA2, const __grid_constant__ CUtensorMap tmWo,
             const __grid_constant__ CUtensorMap tmW2,
             const bf16* __restrict__ b1, const bf16* __restrict__ gate_w,
             const bf16* __restrict__ w1p, const bf16* __restrict__ wqkvp,
             const bf16* __restrict__ w2p, const bf16* __restrict__ wop, bf16* __restrict__ out)
{
    extern __shared__ uint8_t smem_raw[];
    const uint32_t sbase = (smem_u32(smem_raw) + 1023u) & ~1023u;
    uint8_t* sgen = smem_raw + (sbase - smem_u32(smem_raw));
    const uint32_t sK = sbase + OFF_KV, sV = sK + 384 * KV_PITCH;
    const uint32_t sBar = sbase + OFF_MISC;
    const uint32_t full1 = sBar, empty1 = sBar + 32, full2 = sBar + 64, empty2 = sBar + 104, kv_full = sBar + 144;
    float* sGate = (float*)(sgen + OFF_MISC + 256);
    uint8_t* sGw = sgen + OFF_MISC + 768;
    uint32_t* sBias = (uint32_t*)(sgen + OFF_MISC + 1792);

    const int rb = blockIdx.x >> 3, j = blockIdx.x & 7;
    const int tid = threadIdx.x, wg = tid >> 7, warp = tid >> 5, lane = tid & 31;
    TS(0, tid == 0);

    auto load1 = [&](int it) {
        const int st = it % P1_STAGES;
        mbar_expect_tx(full1 + 8 * st, P1_STAGE);
        const uint32_t dst = sbase + st * P1_STAGE;
        const int kc = it & 7;
        tma_load_2d(dst, &tmX, kc * 64, rb * 128, full1 + 8 * st);
        if (it < 8) {
            for (int b = 0; b < 3; b++) tma_load_2d(dst + 16384 + b * 8192, &tmWqkv, b * 512 + j * 64, kc * 64, full1 + 8 * st);
        } else {
            for (int b = 0; b < 3; b++) tma_load_2d(dst + 16384 + b * 8192, &tmW1, j * FCH + b * 64, kc * 64, full1 + 8 * st);
        }
    };
    auto load2 = [&](int ks) {
        const int st = ks % P2_STAGES;
        mbar_expect_tx(full2 + 8 * st, P2_STAGE);
        const uint32_t dst = sbase + st * P2_STAGE;
        if (ks < 22) {
            tma_load_2d(dst, &tmA2, D_ + ks * 64, rb * 128, full2 + 8 * st);
            tma_load_2d(dst + 16384, &tmW2, j * 64, ks * 64, full2 + 8 * st);
        } else {
            tma_load_2d(dst, &tmA2, (ks - 22) * 64, rb * 128, full2 + 8 * st);
            tma_load_2d(dst + 16384, &tmWo, j * 64, (ks - 22) * 64, full2 + 8 * st);
        }
    };

    if (tid == 0) {
        for (int i = 0; i < P1_STAGES; i++) { mbar_init(full1 + 8 * i, 1); mbar_init(empty1 + 8 * i, 8); }
        for (int i = 0; i < P2_STAGES; i++) { mbar_init(full2 + 8 * i, 1); mbar_init(empty2 + 8 * i, 8); }
        mbar_init(kv_full, 1);
        fence_barrier_init();
        for (int it = 0; it < P1_STAGES; it++) load1(it);
    }
    __syncthreads();
    const unsigned int ep8 = (*(volatile unsigned int*)&g_epoch + 1) * 8;

    if (wg >= 2) {
        reg_dealloc<104>();
        const int qt = warp - 8;
        const int q0g = rb * 128 + qt * 16;
        if (tid == 288) {
            const int b = blockIdx.x;
            mbar_wait(full1 + 8, 0);
            l2_prefetch((const uint8_t*)w1p + b * 11008, 11008);
            l2_prefetch((const uint8_t*)w2p + b * 11008, 11008);
            l2_prefetch((const uint8_t*)wop + b * 4096, 4096);
        }
        if (rb < 2) {
            for (int i = tid - 256; i < (2 - rb) * 1024; i += 256) {
                *(uint4*)(sgen + OFF_KV + i * 16) = make_uint4(0, 0, 0, 0);
                *(uint4*)(sgen + OFF_KV + 384 * KV_PITCH + i * 16) = make_uint4(0, 0, 0, 0);
            }
        }
        if (tid == 256) {
            const int nblk = rb >= 2 ? 3 : rb + 1;
            for (int i = 0; i < nblk; i++) flag_wait(&g_flag_qkv[(rb - i) * 8 + j], ep8);
            fence_proxy_async();
            mbar_expect_tx(kv_full, nblk * 2 * 16384);
            for (int i = 0; i < nblk; i++) {
                const int row = j * S_ + (rb - i) * 128;
                tma_load_2d(sK + (2 - i) * 16384, &tmQKV, 64, row, kv_full);
                tma_load_2d(sV + (2 - i) * 16384, &tmQKV, 128, row, kv_full);
            }
        }
        __syncwarp();
        bar_sync(3, 512);
        const int r0 = lane >> 2, c0 = (lane & 3) * 2;
        uint32_t qa[4][4];
        {
            const bf16* qsrc = g_qkv + ((size_t)j * S_ + q0g) * 192;
#pragma unroll
            for (int hl = 0; hl < 4; hl++) {
                qa[hl][0] = *(const volatile uint32_t*)(qsrc + (size_t)r0 * 192 + hl * 16 + c0);
                qa[hl][1] = *(const volatile uint32_t*)(qsrc + (size_t)(r0 + 8) * 192 + hl * 16 + c0);
                qa[hl][2] = *(const volatile uint32_t*)(qsrc + (size_t)r0 * 192 + hl * 16 + c0 + 8);
                qa[hl][3] = *(const volatile uint32_t*)(qsrc + (size_t)(r0 + 8) * 192 + hl * 16 + c0 + 8);
            }
        }
        const float g0 = sGate[qt * 16 + r0], g1 = sGate[qt * 16 + r0 + 8];
        const int kb0 = q0g < 256 ? (256 - q0g) >> 4 : 0;
        mbar_wait(kv_full, 0);
        uint32_t sKd = sK, sVd = sV;
        asm volatile("" : "+r"(sKd), "+r"(sVd) :: "memory");
        TS(6, tid == 256);
        const int krow = qt * 16 + (lane & 7) + ((lane >> 4) << 3);
        const int vrow = qt * 16 + (lane & 15);
#pragma unroll
        for (int hl = 0; hl < 4; hl++) {
            const uint32_t ka = sKd + krow * KV_PITCH + (((2 * hl + ((lane >> 3) & 1)) ^ (lane & 7)) << 4);
            const uint32_t va = sVd + vrow * KV_PITCH + (((2 * hl + (lane >> 4)) ^ (lane & 7)) << 4);
            if (rb < 2) attn_task<true>(qa[hl], ka, va, kb0, lane, g_a2 + (size_t)q0g * KA2 + (j * 4 + hl) * 16, g0, g1);
            else        attn_task<false>(qa[hl], ka, va, kb0, lane, g_a2 + (size_t)q0g * KA2 + (j * 4 + hl) * 16, g0, g1);
            TS(12 + hl, tid == 256);
        }
        TS(7, tid == 256);
        __syncwarp();
        if (lane == 0) flag_add_release(&g_flag_att[blockIdx.x]);
    } else {
        reg_alloc<152>();
        const int t128 = tid & 127, w4 = warp & 3, q = lane & 3;
        if (tid < 64) ((uint4*)sGw)[tid] = __ldg((const uint4*)gate_w + tid);
        else if (tid < 64 + 88) {
            const int c = j * FCH + (tid - 64) * 2;
            sBias[tid - 64] = c < F_ ? __ldg((const uint32_t*)(b1 + c)) : 0u;
        }
        bar_sync(1, 256);
        const int rl = wg * 64 + w4 * 16 + (lane >> 2);
        {
            float acc[96];
            float gs = 0.f;
            const int grow = wg * 64 + (t128 >> 1), ghalf = t128 & 1;
#pragma unroll
            for (int kc = 0; kc < 8; kc++) {
                const int st = kc % P1_STAGES;
                const uint32_t sa = sbase + st * P1_STAGE;
                mbar_wait(full1 + 8 * st, (kc / P1_STAGES) & 1);
                TS(1, tid == 0 && kc == 0);
                wgmma_fence();
#pragma unroll
                for (int k16 = 0; k16 < 4; k16++)
                    wgmma_n192<1>(acc, make_desc(sa + wg * 8192 + k16 * 32, 16, 1024),
                                  make_desc(sa + 16384 + k16 * 2048, 8192, 1024), (kc | k16) != 0);
                wgmma_commit();
#pragma unroll
                for (int c = 0; c < 4; c++) {
                    const int cc = ghalf * 4 + c;
                    const uint4 xv = *(const uint4*)(sgen + st * P1_STAGE + grow * 128 + ((cc ^ (grow & 7)) << 4));
                    const uint4 gv = *(const uint4*)(sGw + kc * 128 + cc * 16);
                    gs = fmaf(bf_lo(xv.x), bf_lo(gv.x), gs); gs = fmaf(bf_hi(xv.x), bf_hi(gv.x), gs);
                    gs = fmaf(bf_lo(xv.y), bf_lo(gv.y), gs); gs = fmaf(bf_hi(xv.y), bf_hi(gv.y), gs);
                    gs = fmaf(bf_lo(xv.z), bf_lo(gv.z), gs); gs = fmaf(bf_hi(xv.z), bf_hi(gv.z), gs);
                    gs = fmaf(bf_lo(xv.w), bf_lo(gv.w), gs); gs = fmaf(bf_hi(xv.w), bf_hi(gv.w), gs);
                }
                if (kc > 0) {
                    wgmma_wait<1>();
                    if (lane == 0) mbar_arrive(empty1 + 8 * ((kc - 1) % P1_STAGES));
                    if (tid == 0) { mbar_wait(empty1 + 8 * ((kc - 1) % P1_STAGES), ((kc - 1) / P1_STAGES) & 1); load1(kc + 2); }
                    __syncwarp();
                }
            }
            gs += __shfl_xor_sync(0xffffffffu, gs, 1);
            if (ghalf == 0) sGate[grow] = 1.f / (1.f + __expf(-gs));
            wgmma_wait<0>();
            if (lane == 0) mbar_arrive(empty1 + 8 * (7 % P1_STAGES));
            if (tid == 0) { mbar_wait(empty1 + 8 * (7 % P1_STAGES), (7 / P1_STAGES) & 1); load1(10); }
            __syncwarp();
            TS(2, tid == 0);
            bf16* orow0 = g_qkv + ((size_t)j * S_ + rb * 128 + rl) * 192;
            bf16* orow1 = orow0 + 8 * 192;
#pragma unroll
            for (int uu = 0; uu < 6; uu++) {
                const int u = (uu + 2) % 6;
                uint32_t w0[4], w1[4];
#pragma unroll
                for (int i = 0; i < 4; i++) {
                    const int t = u * 4 + i;
                    w0[i] = pack_bf16(acc[t * 4 + 0], acc[t * 4 + 1]);
                    w1[i] = pack_bf16(acc[t * 4 + 2], acc[t * 4 + 3]);
                }
                quad_transpose(w0, q);
                quad_transpose(w1, q);
                const int c = (u * 4 + q) * 8;
                *(uint4*)(orow0 + c) = make_uint4(w0[0], w0[1], w0[2], w0[3]);
                *(uint4*)(orow1 + c) = make_uint4(w1[0], w1[1], w1[2], w1[3]);
            }
            __syncwarp();
            if (lane == 0) flag_add_release(&g_flag_qkv[blockIdx.x]);
            bar_arrive(3, 512);
            TS(3, tid == 0);
        }
        {
            float acc[88];
#pragma unroll
            for (int kc = 0; kc < 8; kc++) {
                const int it = kc + 8, st = it % P1_STAGES;
                const uint32_t sa = sbase + st * P1_STAGE;
                mbar_wait(full1 + 8 * st, (it / P1_STAGES) & 1);
                wgmma_fence();
#pragma unroll
                for (int k16 = 0; k16 < 4; k16++)
                    wgmma_n176<1>(acc, make_desc(sa + wg * 8192 + k16 * 32, 16, 1024),
                                  make_desc(sa + 16384 + k16 * 2048, 8192, 1024), (kc | k16) != 0);
                wgmma_commit();
                if (kc > 0) {
                    wgmma_wait<1>();
                    if (lane == 0) mbar_arrive(empty1 + 8 * ((it - 1) % P1_STAGES));
                    if (tid == 0 && it + 2 < 16) { mbar_wait(empty1 + 8 * ((it - 1) % P1_STAGES), ((it - 1) / P1_STAGES) & 1); load1(it + 2); }
                    __syncwarp();
                }
            }
            wgmma_wait<0>();
            TS(4, tid == 0);
            const int n0 = j * FCH;
            const float om0 = 1.f - sGate[rl], om1 = 1.f - sGate[rl + 8];
            bf16* frow0 = g_a2 + (size_t)(rb * 128 + rl) * KA2 + D_ + n0;
            bf16* frow1 = frow0 + 8 * KA2;
#pragma unroll
            for (int u = 0; u < 6; u++) {
                uint32_t w0[4], w1[4];
#pragma unroll
                for (int i = 0; i < 4; i++) {
                    const int t = u * 4 + i;
                    if (t < 22) {
                        const uint32_t bv = sBias[t * 4 + q];
                        const float bb0 = bf_lo(bv), bb1 = bf_hi(bv);
                        w0[i] = pack_bf16(mish_f(acc[t * 4 + 0] + bb0) * om0, mish_f(acc[t * 4 + 1] + bb1) * om0);
                        w1[i] = pack_bf16(mish_f(acc[t * 4 + 2] + bb0) * om1, mish_f(acc[t * 4 + 3] + bb1) * om1);
                    } else { w0[i] = 0; w1[i] = 0; }
                }
                quad_transpose(w0, q);
                quad_transpose(w1, q);
                const int c = (u * 4 + q) * 8;
                if (c < FCH && n0 + c < F_) {
                    *(uint4*)(frow0 + c) = make_uint4(w0[0], w0[1], w0[2], w0[3]);
                    *(uint4*)(frow1 + c) = make_uint4(w1[0], w1[1], w1[2], w1[3]);
                }
            }
            __syncwarp();
            if (lane == 0) flag_add_release(&g_flag_act[blockIdx.x]);
            TS(5, tid == 0);
        }
        {
            bar_sync(1, 256);
            if (tid == 0) {
                for (int i = 0; i < 8; i++) flag_wait(&g_flag_act[rb * 8 + i], ep8);
                fence_proxy_async();
                for (int ks = 0; ks < P2_STAGES; ks++) load2(ks);
            }
            __syncwarp();
            float acc[32];
            for (int ks = 0; ks < P2_KSTEPS; ks++) {
                const int st = ks % P2_STAGES;
                const uint32_t sa = sbase + st * P2_STAGE;
                mbar_wait(full2 + 8 * st, (ks / P2_STAGES) & 1);
                TS(8, tid == 0 && ks == 0); TS(9, tid == 0 && ks == 22);
                wgmma_fence();
#pragma unroll
                for (int k16 = 0; k16 < 4; k16++)
                    wgmma_n64<1>(acc, make_desc(sa + wg * 8192 + k16 * 32, 16, 1024),
                                 make_desc(sa + 16384 + k16 * 2048, 8192, 1024), (ks | k16) != 0);
                wgmma_commit();
                if (ks > 0) {
                    wgmma_wait<1>();
                    if (lane == 0) mbar_arrive(empty2 + 8 * ((ks - 1) % P2_STAGES));
                    if (tid == 0 && ks - 1 + P2_STAGES < P2_KSTEPS) {
                        mbar_wait(empty2 + 8 * ((ks - 1) % P2_STAGES), ((ks - 1) / P2_STAGES) & 1);
                        if (ks - 1 + P2_STAGES == 22) {
                            for (int i = 0; i < 8; i++) flag_wait(&g_flag_att[rb * 8 + i], ep8);
                            fence_proxy_async();
                        }
                        load2(ks - 1 + P2_STAGES);
                    }
                    __syncwarp();
                }
            }
            wgmma_wait<0>();
            TS(10, tid == 0);
            bf16* orow0 = out + (size_t)(rb * 128 + rl) * D_ + j * 64;
            bf16* orow1 = orow0 + 8 * D_;
#pragma unroll
            for (int u = 0; u < 2; u++) {
                uint32_t w0[4], w1[4];
#pragma unroll
                for (int i = 0; i < 4; i++) {
                    const int t = u * 4 + i;
                    w0[i] = pack_bf16(acc[t * 4 + 0], acc[t * 4 + 1]);
                    w1[i] = pack_bf16(acc[t * 4 + 2], acc[t * 4 + 3]);
                }
                quad_transpose(w0, q);
                quad_transpose(w1, q);
                const int c = (u * 4 + q) * 8;
                *(uint4*)(orow0 + c) = make_uint4(w0[0], w0[1], w0[2], w0[3]);
                *(uint4*)(orow1 + c) = make_uint4(w1[0], w1[1], w1[2], w1[3]);
            }
            TS(11, tid == 0);
        }
        if (tid == 0) {
            __threadfence();
            if (atomicAdd(&g_done, 1u) == gridDim.x - 1) {
                g_done = 0;
                __threadfence();
                atomicAdd(&g_epoch, 1u);
            }
        }
    }
}

typedef CUresult (*PFN_encodeTiled)(CUtensorMap*, CUtensorMapDataType, cuuint32_t, void*, const cuuint64_t*,
                                    const cuuint64_t*, const cuuint32_t*, const cuuint32_t*, CUtensorMapInterleave,
                                    CUtensorMapSwizzle, CUtensorMapL2promotion, CUtensorMapFloatOOBfill);

static void make_map(PFN_encodeTiled enc, CUtensorMap* m, const void* ptr, uint64_t cols, uint64_t rows,
                     uint32_t box_cols, uint32_t box_rows)
{
    cuuint64_t dims[2] = {cols, rows};
    cuuint64_t strides[1] = {cols * 2};
    cuuint32_t box[2] = {box_cols, box_rows};
    cuuint32_t es[2] = {1, 1};
    enc(m, CU_TENSOR_MAP_DATA_TYPE_BFLOAT16, 2, const_cast<void*>(ptr), dims, strides, box, es,
        CU_TENSOR_MAP_INTERLEAVE_NONE, CU_TENSOR_MAP_SWIZZLE_128B, CU_TENSOR_MAP_L2_PROMOTION_L2_128B,
        CU_TENSOR_MAP_FLOAT_OOB_FILL_NONE);
}

extern "C" void kernel_launch(void* const* d_in, const int* in_sizes, int n_in, void* d_out, int out_size)
{
    const bf16* x    = (const bf16*)d_in[0];
    const bf16* wqkv = (const bf16*)d_in[1];
    const bf16* wo   = (const bf16*)d_in[2];
    const bf16* w1   = (const bf16*)d_in[4];
    const bf16* b1   = (const bf16*)d_in[5];
    const bf16* w2   = (const bf16*)d_in[6];
    const bf16* gw   = (const bf16*)d_in[7];

    static PFN_encodeTiled enc = nullptr;
    if (!enc) {
        void* fn = nullptr;
        cudaDriverEntryPointQueryResult qr;
        cudaGetDriverEntryPoint("cuTensorMapEncodeTiled", &fn, cudaEnableDefault, &qr);
        enc = (PFN_encodeTiled)fn;
        cudaFuncSetAttribute(fused_kernel, cudaFuncAttributeMaxDynamicSharedMemorySize, FUSED_SMEM);
    }
    void *a2p = nullptr, *qkvp = nullptr;
    cudaGetSymbolAddress(&a2p, g_a2);
    cudaGetSymbolAddress(&qkvp, g_qkv);
    CUtensorMap tmX, tmWqkv, tmW1, tmQKV, tmA2, tmWo, tmW2;
    make_map(enc, &tmX, x, D_, S_, 64, 128);
    make_map(enc, &tmWqkv, wqkv, 3 * D_, D_, 64, 64);
    make_map(enc, &tmW1, w1, F_, D_, 64, 64);
    make_map(enc, &tmQKV, qkvp, 192, 8 * S_, 64, 128);
    make_map(enc, &tmA2, a2p, KA2, S_, 64, 128);
    make_map(enc, &tmWo, wo, D_, D_, 64, 64);
    make_map(enc, &tmW2, w2, D_, F_, 64, 64);

    fused_kernel<<<128, 512, FUSED_SMEM, cudaStreamPerThread>>>(tmX, tmWqkv, tmW1, tmQKV, tmA2, tmWo, tmW2,
                                                                b1, gw, w1, wqkv, w2, wo, (bf16*)d_out);
}
```

```cpp
#include <cuda_runtime.h>
#include <cuda_bf16.h>
#include <cuda.h>
#include <stdint.h>

typedef __nv_bfloat16 bf16;

constexpr int S_ = 2048, D_ = 512, F_ = 1376;
constexpr int KA2 = D_ + F_;
constexpr int FCH = 176;

__device__ bf16  g_qkv[8 * S_ * 192];
__device__ bf16  g_a2[S_ * KA2];
__device__ float g_gate[S_];

#define TS(k, cond) do { } while (0)

__device__ __forceinline__ uint32_t smem_u32(const void* p) { return (uint32_t)__cvta_generic_to_shared(p); }
__device__ __forceinline__ void mbar_init(uint32_t bar, uint32_t count) {
    asm volatile("mbarrier.init.shared::cta.b64 [%0], %1;" :: "r"(bar), "r"(count) : "memory");
}
__device__ __forceinline__ void mbar_expect_tx(uint32_t bar, uint32_t bytes) {
    asm volatile("mbarrier.arrive.expect_tx.shared::cta.b64 _, [%0], %1;" :: "r"(bar), "r"(bytes) : "memory");
}
__device__ __forceinline__ void mbar_arrive(uint32_t bar) {
    asm volatile("mbarrier.arrive.shared::cta.b64 _, [%0];" :: "r"(bar) : "memory");
}
__device__ __forceinline__ bool mbar_try_wait(uint32_t bar, uint32_t parity) {
    uint32_t ok;
    asm volatile("{\n.reg .pred p;\nmbarrier.try_wait.parity.shared::cta.b64 p, [%1], %2;\nselp.u32 %0, 1, 0, p;\n}"
                 : "=r"(ok) : "r"(bar), "r"(parity) : "memory");
    return ok != 0;
}
__device__ __forceinline__ void mbar_wait(uint32_t bar, uint32_t parity) {
    for (uint32_t it = 0; it < (1u << 22); ++it) { if (mbar_try_wait(bar, parity)) break; }
}
__device__ __forceinline__ void tma_load_2d(uint32_t dst, const CUtensorMap* map, int c0, int c1, uint32_t bar) {
    asm volatile("cp.async.bulk.tensor.2d.shared::cluster.global.mbarrier::complete_tx::bytes [%0], [%1, {%3, %4}], [%2];"
                 :: "r"(dst), "l"(map), "r"(bar), "r"(c0), "r"(c1) : "memory");
}
__device__ __forceinline__ void l2_prefetch(const void* p, uint32_t bytes) {
    asm volatile("cp.async.bulk.prefetch.L2.global [%0], %1;" :: "l"(p), "r"(bytes) : "memory");
}
__device__ __forceinline__ void fence_barrier_init() { asm volatile("fence.mbarrier_init.release.cluster;" ::: "memory"); }
__device__ __forceinline__ void wgmma_fence()  { asm volatile("wgmma.fence.sync.aligned;" ::: "memory"); }
__device__ __forceinline__ void wgmma_commit() { asm volatile("wgmma.commit_group.sync.aligned;" ::: "memory"); }
template <int N> __device__ __forceinline__ void wgmma_wait() { asm volatile("wgmma.wait_group.sync.aligned %0;" :: "n"(N) : "memory"); }
template <int R> __device__ __forceinline__ void reg_alloc()   { asm volatile("setmaxnreg.inc.sync.aligned.u32 %0;" :: "n"(R)); }
template <int R> __device__ __forceinline__ void reg_dealloc() { asm volatile("setmaxnreg.dec.sync.aligned.u32 %0;" :: "n"(R)); }
__device__ __forceinline__ void bar_sync(int id, int n)   { asm volatile("bar.sync %0, %1;" :: "r"(id), "r"(n) : "memory"); }
__device__ __forceinline__ void bar_arrive(int id, int n) { asm volatile("bar.arrive %0, %1;" :: "r"(id), "r"(n) : "memory"); }

__device__ __forceinline__ uint64_t make_desc(uint32_t addr, uint32_t lbo, uint32_t sbo) {
    uint64_t d = (uint64_t)((addr & 0x3FFFF) >> 4);
    d |= (uint64_t)((lbo & 0x3FFFF) >> 4) << 16;
    d |= (uint64_t)((sbo & 0x3FFFF) >> 4) << 32;
    d |= (uint64_t)1 << 62;
    return d;
}

template <int TB>
__device__ __forceinline__ void wgmma_n64(float (&d)[32], uint64_t da, uint64_t db, int scale_d) {
    asm volatile("{\n.reg .pred p;\nsetp.ne.b32 p, %34, 0;\n"
        "wgmma.mma_async.sync.aligned.m64n64k16.f32.bf16.bf16 {%0, %1, %2, %3, %4, %5, %6, %7, %8, %9, %10, %11, %12, %13, %14, %15, %16, %17, %18, %19, %20, %21, %22, %23, %24, %25, %26, %27, %28, %29, %30, %31}, %32, %33, p, 1, 1, 0, %35;\n}\n"
        : "+f"(d[0]), "+f"(d[1]), "+f"(d[2]), "+f"(d[3]), "+f"(d[4]), "+f"(d[5]), "+f"(d[6]), "+f"(d[7]), "+f"(d[8]), "+f"(d[9]), "+f"(d[10]), "+f"(d[11]), "+f"(d[12]), "+f"(d[13]), "+f"(d[14]), "+f"(d[15]), "+f"(d[16]), "+f"(d[17]), "+f"(d[18]), "+f"(d[19]), "+f"(d[20]), "+f"(d[21]), "+f"(d[22]), "+f"(d[23]), "+f"(d[24]), "+f"(d[25]), "+f"(d[26]), "+f"(d[27]), "+f"(d[28]), "+f"(d[29]), "+f"(d[30]), "+f"(d[31])
        : "l"(da), "l"(db), "r"(scale_d), "n"(TB));
}

template <int TB>
__device__ __forceinline__ void wgmma_n128(float (&d)[64], uint64_t da, uint64_t db, int scale_d) {
    asm volatile("{\n.reg .pred p;\nsetp.ne.b32 p, %66, 0;\n"
        "wgmma.mma_async.sync.aligned.m64n128k16.f32.bf16.bf16 {%0, %1, %2, %3, %4, %5, %6, %7, %8, %9, %10, %11, %12, %13, %14, %15, %16, %17, %18, %19, %20, %21, %22, %23, %24, %25, %26, %27, %28, %29, %30, %31, %32, %33, %34, %35, %36, %37, %38, %39, %40, %41, %42, %43, %44, %45, %46, %47, %48, %49, %50, %51, %52, %53, %54, %55, %56, %57, %58, %59, %60, %61, %62, %63}, %64, %65, p, 1, 1, 0, %67;\n}\n"
        : "+f"(d[0]), "+f"(d[1]), "+f"(d[2]), "+f"(d[3]), "+f"(d[4]), "+f"(d[5]), "+f"(d[6]), "+f"(d[7]), "+f"(d[8]), "+f"(d[9]), "+f"(d[10]), "+f"(d[11]), "+f"(d[12]), "+f"(d[13]), "+f"(d[14]), "+f"(d[15]), "+f"(d[16]), "+f"(d[17]), "+f"(d[18]), "+f"(d[19]), "+f"(d[20]), "+f"(d[21]), "+f"(d[22]), "+f"(d[23]), "+f"(d[24]), "+f"(d[25]), "+f"(d[26]), "+f"(d[27]), "+f"(d[28]), "+f"(d[29]), "+f"(d[30]), "+f"(d[31]), "+f"(d[32]), "+f"(d[33]), "+f"(d[34]), "+f"(d[35]), "+f"(d[36]), "+f"(d[37]), "+f"(d[38]), "+f"(d[39]), "+f"(d[40]), "+f"(d[41]), "+f"(d[42]), "+f"(d[43]), "+f"(d[44]), "+f"(d[45]), "+f"(d[46]), "+f"(d[47]), "+f"(d[48]), "+f"(d[49]), "+f"(d[50]), "+f"(d[51]), "+f"(d[52]), "+f"(d[53]), "+f"(d[54]), "+f"(d[55]), "+f"(d[56]), "+f"(d[57]), "+f"(d[58]), "+f"(d[59]), "+f"(d[60]), "+f"(d[61]), "+f"(d[62]), "+f"(d[63])
        : "l"(da), "l"(db), "r"(scale_d), "n"(TB));
}

template <int TB>
__device__ __forceinline__ void wgmma_n176(float (&d)[88], uint64_t da, uint64_t db, int scale_d) {
    asm volatile("{\n.reg .pred p;\nsetp.ne.b32 p, %90, 0;\n"
        "wgmma.mma_async.sync.aligned.m64n176k16.f32.bf16.bf16 {%0, %1, %2, %3, %4, %5, %6, %7, %8, %9, %10, %11, %12, %13, %14, %15, %16, %17, %18, %19, %20, %21, %22, %23, %24, %25, %26, %27, %28, %29, %30, %31, %32, %33, %34, %35, %36, %37, %38, %39, %40, %41, %42, %43, %44, %45, %46, %47, %48, %49, %50, %51, %52, %53, %54, %55, %56, %57, %58, %59, %60, %61, %62, %63, %64, %65, %66, %67, %68, %69, %70, %71, %72, %73, %74, %75, %76, %77, %78, %79, %80, %81, %82, %83, %84, %85, %86, %87}, %88, %89, p, 1, 1, 0, %91;\n}\n"
        : "+f"(d[0]), "+f"(d[1]), "+f"(d[2]), "+f"(d[3]), "+f"(d[4]), "+f"(d[5]), "+f"(d[6]), "+f"(d[7]), "+f"(d[8]), "+f"(d[9]), "+f"(d[10]), "+f"(d[11]), "+f"(d[12]), "+f"(d[13]), "+f"(d[14]), "+f"(d[15]), "+f"(d[16]), "+f"(d[17]), "+f"(d[18]), "+f"(d[19]), "+f"(d[20]), "+f"(d[21]), "+f"(d[22]), "+f"(d[23]), "+f"(d[24]), "+f"(d[25]), "+f"(d[26]), "+f"(d[27]), "+f"(d[28]), "+f"(d[29]), "+f"(d[30]), "+f"(d[31]), "+f"(d[32]), "+f"(d[33]), "+f"(d[34]), "+f"(d[35]), "+f"(d[36]), "+f"(d[37]), "+f"(d[38]), "+f"(d[39]), "+f"(d[40]), "+f"(d[41]), "+f"(d[42]), "+f"(d[43]), "+f"(d[44]), "+f"(d[45]), "+f"(d[46]), "+f"(d[47]), "+f"(d[48]), "+f"(d[49]), "+f"(d[50]), "+f"(d[51]), "+f"(d[52]), "+f"(d[53]), "+f"(d[54]), "+f"(d[55]), "+f"(d[56]), "+f"(d[57]), "+f"(d[58]), "+f"(d[59]), "+f"(d[60]), "+f"(d[61]), "+f"(d[62]), "+f"(d[63]), "+f"(d[64]), "+f"(d[65]), "+f"(d[66]), "+f"(d[67]), "+f"(d[68]), "+f"(d[69]), "+f"(d[70]), "+f"(d[71]), "+f"(d[72]), "+f"(d[73]), "+f"(d[74]), "+f"(d[75]), "+f"(d[76]), "+f"(d[77]), "+f"(d[78]), "+f"(d[79]), "+f"(d[80]), "+f"(d[81]), "+f"(d[82]), "+f"(d[83]), "+f"(d[84]), "+f"(d[85]), "+f"(d[86]), "+f"(d[87])
        : "l"(da), "l"(db), "r"(scale_d), "n"(TB));
}

template <int TB>
__device__ __forceinline__ void wgmma_n192(float (&d)[96], uint64_t da, uint64_t db, int scale_d) {
    asm volatile("{\n.reg .pred p;\nsetp.ne.b32 p, %98, 0;\n"
        "wgmma.mma_async.sync.aligned.m64n192k16.f32.bf16.bf16 {%0, %1, %2, %3, %4, %5, %6, %7, %8, %9, %10, %11, %12, %13, %14, %15, %16, %17, %18, %19, %20, %21, %22, %23, %24, %25, %26, %27, %28, %29, %30, %31, %32, %33, %34, %35, %36, %37, %38, %39, %40, %41, %42, %43, %44, %45, %46, %47, %48, %49, %50, %51, %52, %53, %54, %55, %56, %57, %58, %59, %60, %61, %62, %63, %64, %65, %66, %67, %68, %69, %70, %71, %72, %73, %74, %75, %76, %77, %78, %79, %80, %81, %82, %83, %84, %85, %86, %87, %88, %89, %90, %91, %92, %93, %94, %95}, %96, %97, p, 1, 1, 0, %99;\n}\n"
        : "+f"(d[0]), "+f"(d[1]), "+f"(d[2]), "+f"(d[3]), "+f"(d[4]), "+f"(d[5]), "+f"(d[6]), "+f"(d[7]), "+f"(d[8]), "+f"(d[9]), "+f"(d[10]), "+f"(d[11]), "+f"(d[12]), "+f"(d[13]), "+f"(d[14]), "+f"(d[15]), "+f"(d[16]), "+f"(d[17]), "+f"(d[18]), "+f"(d[19]), "+f"(d[20]), "+f"(d[21]), "+f"(d[22]), "+f"(d[23]), "+f"(d[24]), "+f"(d[25]), "+f"(d[26]), "+f"(d[27]), "+f"(d[28]), "+f"(d[29]), "+f"(d[30]), "+f"(d[31]), "+f"(d[32]), "+f"(d[33]), "+f"(d[34]), "+f"(d[35]), "+f"(d[36]), "+f"(d[37]), "+f"(d[38]), "+f"(d[39]), "+f"(d[40]), "+f"(d[41]), "+f"(d[42]), "+f"(d[43]), "+f"(d[44]), "+f"(d[45]), "+f"(d[46]), "+f"(d[47]), "+f"(d[48]), "+f"(d[49]), "+f"(d[50]), "+f"(d[51]), "+f"(d[52]), "+f"(d[53]), "+f"(d[54]), "+f"(d[55]), "+f"(d[56]), "+f"(d[57]), "+f"(d[58]), "+f"(d[59]), "+f"(d[60]), "+f"(d[61]), "+f"(d[62]), "+f"(d[63]), "+f"(d[64]), "+f"(d[65]), "+f"(d[66]), "+f"(d[67]), "+f"(d[68]), "+f"(d[69]), "+f"(d[70]), "+f"(d[71]), "+f"(d[72]), "+f"(d[73]), "+f"(d[74]), "+f"(d[75]), "+f"(d[76]), "+f"(d[77]), "+f"(d[78]), "+f"(d[79]), "+f"(d[80]), "+f"(d[81]), "+f"(d[82]), "+f"(d[83]), "+f"(d[84]), "+f"(d[85]), "+f"(d[86]), "+f"(d[87]), "+f"(d[88]), "+f"(d[89]), "+f"(d[90]), "+f"(d[91]), "+f"(d[92]), "+f"(d[93]), "+f"(d[94]), "+f"(d[95])
        : "l"(da), "l"(db), "r"(scale_d), "n"(TB));
}

__device__ __forceinline__ uint32_t pack_bf16(float lo, float hi) {
    uint32_t r;
    asm("cvt.rn.bf16x2.f32 %0, %1, %2;" : "=r"(r) : "f"(hi), "f"(lo));
    return r;
}
__device__ __forceinline__ float bf_lo(uint32_t v) { return __uint_as_float(v << 16); }
__device__ __forceinline__ float bf_hi(uint32_t v) { return __uint_as_float(v & 0xffff0000u); }

__device__ __forceinline__ void quad_transpose(uint32_t (&w)[4], int q) {
    const bool o1 = q & 1, o2 = q & 2;
    {
        uint32_t s0 = o1 ? w[0] : w[1], s1 = o1 ? w[2] : w[3];
        s0 = __shfl_xor_sync(0xffffffffu, s0, 1); s1 = __shfl_xor_sync(0xffffffffu, s1, 1);
        if (o1) { w[0] = s0; w[2] = s1; } else { w[1] = s0; w[3] = s1; }
    }
    {
        uint32_t s0 = o2 ? w[0] : w[2], s1 = o2 ? w[1] : w[3];
        s0 = __shfl_xor_sync(0xffffffffu, s0, 2); s1 = __shfl_xor_sync(0xffffffffu, s1, 2);
        if (o2) { w[0] = s0; w[1] = s1; } else { w[2] = s0; w[3] = s1; }
    }
}

__device__ __forceinline__ float ex2(float x) { float y; asm("ex2.approx.ftz.f32 %0, %1;" : "=f"(y) : "f"(x)); return y; }
__device__ __forceinline__ float rcp(float x) { float y; asm("rcp.approx.ftz.f32 %0, %1;" : "=f"(y) : "f"(x)); return y; }

__device__ __forceinline__ float ex2v(float x) { float y; asm volatile("ex2.approx.ftz.f32 %0, %1;" : "=f"(y) : "f"(x)); return y; }
__device__ __forceinline__ float rcpv(float x) { float y; asm volatile("rcp.approx.ftz.f32 %0, %1;" : "=f"(y) : "f"(x)); return y; }
__device__ __forceinline__ float mish_f(float h) {
    const float w = ex2v(-1.4426950408889634f * fabsf(h));
    const float t = w * w;
    const bool pos = h > 0.f;
    const float num = fmaf(2.f, w, pos ? 1.f : t);
    const float den = num + (pos ? t + t : 2.f);
    return h * num * rcpv(den);
}

__device__ unsigned int g_epoch;
__device__ unsigned int g_done;
__device__ unsigned int g_flag_qkv[128];
__device__ unsigned int g_flag_act[128];
__device__ unsigned int g_flag_att[128];

__device__ __forceinline__ void flag_set(unsigned int* f, unsigned int v) {
    asm volatile("st.release.gpu.global.u32 [%0], %1;" :: "l"(f), "r"(v) : "memory");
}
__device__ __forceinline__ void flag_wait(const unsigned int* f, unsigned int v) {
    for (uint32_t it = 0; it < (1u << 22); ++it) {
        unsigned int x;
        asm volatile("ld.acquire.gpu.global.u32 %0, [%1];" : "=r"(x) : "l"(f) : "memory");
        if (x == v) break;
    }
}
__device__ __forceinline__ void fence_proxy_async() { asm volatile("fence.proxy.async;" ::: "memory"); }

__device__ __forceinline__ void ldsm_x4(uint32_t (&r)[4], uint32_t addr) {
    asm("ldmatrix.sync.aligned.m8n8.x4.shared.b16 {%0,%1,%2,%3}, [%4];"
                 : "=r"(r[0]), "=r"(r[1]), "=r"(r[2]), "=r"(r[3]) : "r"(addr));
}
__device__ __forceinline__ void ldsm_x4_t(uint32_t (&r)[4], uint32_t addr) {
    asm("ldmatrix.sync.aligned.m8n8.x4.trans.shared.b16 {%0,%1,%2,%3}, [%4];"
                 : "=r"(r[0]), "=r"(r[1]), "=r"(r[2]), "=r"(r[3]) : "r"(addr));
}
__device__ __forceinline__ void mma16816(float (&d)[4], const uint32_t (&a)[4], uint32_t b0, uint32_t b1) {
    asm("mma.sync.aligned.m16n8k16.row.col.f32.bf16.bf16.f32 {%0,%1,%2,%3}, {%4,%5,%6,%7}, {%8,%9}, {%0,%1,%2,%3};"
                 : "+f"(d[0]), "+f"(d[1]), "+f"(d[2]), "+f"(d[3])
                 : "r"(a[0]), "r"(a[1]), "r"(a[2]), "r"(a[3]), "r"(b0), "r"(b1));
}
__device__ __forceinline__ void mma16816_z(float (&d)[4], const uint32_t (&a)[4], uint32_t b0, uint32_t b1) {
    asm("mma.sync.aligned.m16n8k16.row.col.f32.bf16.bf16.f32 {%0,%1,%2,%3}, {%4,%5,%6,%7}, {%8,%9}, {%10,%10,%10,%10};"
                 : "=f"(d[0]), "=f"(d[1]), "=f"(d[2]), "=f"(d[3])
                 : "r"(a[0]), "r"(a[1]), "r"(a[2]), "r"(a[3]), "r"(b0), "r"(b1), "f"(0.f));
}

constexpr int KV_PITCH = 128;

template <int NB, bool MASK_FIRST, bool MASK_LAST, bool HEAD>
__device__ __forceinline__ void attn_chunk(const uint32_t (&qa)[4], uint32_t ka, uint32_t va, int kbs, int kb0, int r0, int c0,
                                           float& m0, float& m1, float& l0, float& l1, float (&o)[2][4])
{
    const float C = 0.25f * 1.4426950408889634f;
    float s[NB][2][4];
#pragma unroll
    for (int b = 0; b < NB; b++) {
        uint32_t kf[4];
        ldsm_x4(kf, ka + (kbs + b) * 16 * KV_PITCH);
        mma16816_z(s[b][0], qa, kf[0], kf[1]);
        mma16816_z(s[b][1], qa, kf[2], kf[3]);
    }
#pragma unroll
    for (int t = 0; t < 2; t++)
#pragma unroll
        for (int e = 0; e < 4; e++) {
            const int r = r0 + (e >> 1) * 8, c = t * 8 + c0 + (e & 1);
            if (MASK_FIRST && c <= r) s[0][t][e] = -1e30f;
            if (MASK_LAST && c > r) s[NB - 1][t][e] = -1e30f;
        }
    if (HEAD) {
#pragma unroll
        for (int b = 0; b < NB; b++)
            if (kbs + b < kb0) {
#pragma unroll
                for (int t = 0; t < 2; t++)
#pragma unroll
                    for (int e = 0; e < 4; e++) s[b][t][e] = -1e30f;
            }
    }
    float n0 = m0, n1 = m1;
#pragma unroll
    for (int b = 0; b < NB; b++) {
        n0 = fmaxf(n0, fmaxf(fmaxf(s[b][0][0], s[b][0][1]), fmaxf(s[b][1][0], s[b][1][1])));
        n1 = fmaxf(n1, fmaxf(fmaxf(s[b][0][2], s[b][0][3]), fmaxf(s[b][1][2], s[b][1][3])));
    }
    n0 = fmaxf(n0, __shfl_xor_sync(0xffffffffu, n0, 1)); n0 = fmaxf(n0, __shfl_xor_sync(0xffffffffu, n0, 2));
    n1 = fmaxf(n1, __shfl_xor_sync(0xffffffffu, n1, 1)); n1 = fmaxf(n1, __shfl_xor_sync(0xffffffffu, n1, 2));
    const float mc0 = n0 * C, mc1 = n1 * C;
    if (!MASK_LAST) {
        const float a0 = ex2(fmaf(m0, C, -mc0)), a1 = ex2(fmaf(m1, C, -mc1));
        l0 *= a0; l1 *= a1;
        o[0][0] *= a0; o[0][1] *= a0; o[1][0] *= a0; o[1][1] *= a0;
        o[0][2] *= a1; o[0][3] *= a1; o[1][2] *= a1; o[1][3] *= a1;
    }
    m0 = n0; m1 = n1;
#pragma unroll
    for (int b = 0; b < NB; b++) {
        uint32_t pa[4];
#pragma unroll
        for (int t = 0; t < 2; t++) {
            const float p0 = ex2(fmaf(s[b][t][0], C, -mc0)), p1 = ex2(fmaf(s[b][t][1], C, -mc0));
            const float p2 = ex2(fmaf(s[b][t][2], C, -mc1)), p3 = ex2(fmaf(s[b][t][3], C, -mc1));
            l0 += p0 + p1; l1 += p2 + p3;
            pa[2 * t] = pack_bf16(p0, p1); pa[2 * t + 1] = pack_bf16(p2, p3);
        }
        uint32_t vf[4];
        ldsm_x4_t(vf, va + (kbs + b) * 16 * KV_PITCH);
        mma16816(o[0], pa, vf[0], vf[1]);
        mma16816(o[1], pa, vf[2], vf[3]);
    }
}

template <bool HEAD>
__device__ __forceinline__ void attn_task(const uint32_t (&qa)[4], uint32_t ka, uint32_t va, int kb0, int lane,
                                          bf16* __restrict__ out  , float g0, float g1)
{
    const int r0 = lane >> 2, c0 = (lane & 3) * 2;
    float m0 = -1e30f, m1 = -1e30f, l0 = 0.f, l1 = 0.f;
    float o[2][4] = {{0.f, 0.f, 0.f, 0.f}, {0.f, 0.f, 0.f, 0.f}};
    attn_chunk<5, false, true, HEAD>(qa, ka, va, 12, kb0, r0, c0, m0, m1, l0, l1, o);
    if (!HEAD || kb0 < 12) attn_chunk<4, false, false, HEAD>(qa, ka, va, 8, kb0, r0, c0, m0, m1, l0, l1, o);
    if (!HEAD || kb0 < 8)  attn_chunk<4, false, false, HEAD>(qa, ka, va, 4, kb0, r0, c0, m0, m1, l0, l1, o);
    if (!HEAD || kb0 < 4)  attn_chunk<4, true, false, HEAD>(qa, ka, va, 0, kb0, r0, c0, m0, m1, l0, l1, o);
    l0 += __shfl_xor_sync(0xffffffffu, l0, 1); l0 += __shfl_xor_sync(0xffffffffu, l0, 2);
    l1 += __shfl_xor_sync(0xffffffffu, l1, 1); l1 += __shfl_xor_sync(0xffffffffu, l1, 2);
    const float f0 = g0 / l0, f1 = g1 / l1;
#pragma unroll
    for (int t = 0; t < 2; t++) {
        *(uint32_t*)(out + (size_t)r0 * KA2 + t * 8 + c0) = pack_bf16(o[t][0] * f0, o[t][1] * f0);
        *(uint32_t*)(out + (size_t)(r0 + 8) * KA2 + t * 8 + c0) = pack_bf16(o[t][2] * f1, o[t][3] * f1);
    }
}

constexpr int P1_STAGES = 3;
constexpr int P1_STAGE  = 16384 + 24576;
constexpr int P2_STAGES = 5;
constexpr int P2_STAGE  = 16384 + 8192;
constexpr int P2_KSTEPS = 30;
constexpr int OFF_KV    = P1_STAGES * P1_STAGE;
constexpr int OFF_MISC  = OFF_KV + 2 * 384 * KV_PITCH;
constexpr int FUSED_SMEM = OFF_MISC + 2048 + 1024;

__device__ __forceinline__ void flag_add_release(unsigned int* f) {
    asm volatile("red.release.gpu.global.add.u32 [%0], 1;" :: "l"(f) : "memory");
}

__global__ void __launch_bounds__(512, 1)
fused_kernel(const __grid_constant__ CUtensorMap tmX, const __grid_constant__ CUtensorMap tmWqkv,
             const __grid_constant__ CUtensorMap tmW1, const __grid_constant__ CUtensorMap tmQKV,
             const __grid_constant__ CUtensorMap tmA2, const __grid_constant__ CUtensorMap tmWo,
             const __grid_constant__ CUtensorMap tmW2,
             const bf16* __restrict__ b1, const bf16* __restrict__ gate_w,
             const bf16* __restrict__ w1p, const bf16* __restrict__ wqkvp,
             const bf16* __restrict__ w2p, const bf16* __restrict__ wop, bf16* __restrict__ out)
{
    extern __shared__ uint8_t smem_raw[];
    const uint32_t sbase = (smem_u32(smem_raw) + 1023u) & ~1023u;
    uint8_t* sgen = smem_raw + (sbase - smem_u32(smem_raw));
    const uint32_t sK = sbase + OFF_KV, sV = sK + 384 * KV_PITCH;
    const uint32_t sBar = sbase + OFF_MISC;
    const uint32_t full1 = sBar, empty1 = sBar + 32, full2 = sBar + 64, empty2 = sBar + 104, kv_full = sBar + 144;
    float* sGate = (float*)(sgen + OFF_MISC + 256);
    uint8_t* sGw = sgen + OFF_MISC + 768;
    uint32_t* sBias = (uint32_t*)(sgen + OFF_MISC + 1792);

    const int rb = blockIdx.x >> 3, j = blockIdx.x & 7;
    const int tid = threadIdx.x, wg = tid >> 7, warp = tid >> 5, lane = tid & 31;
    TS(0, tid == 0);

    auto load1 = [&](int it) {
        const int st = it % P1_STAGES;
        mbar_expect_tx(full1 + 8 * st, P1_STAGE);
        const uint32_t dst = sbase + st * P1_STAGE;
        const int kc = it & 7;
        tma_load_2d(dst, &tmX, kc * 64, rb * 128, full1 + 8 * st);
        if (it < 8) {
            for (int b = 0; b < 3; b++) tma_load_2d(dst + 16384 + b * 8192, &tmWqkv, b * 512 + j * 64, kc * 64, full1 + 8 * st);
        } else {
            for (int b = 0; b < 3; b++) tma_load_2d(dst + 16384 + b * 8192, &tmW1, j * FCH + b * 64, kc * 64, full1 + 8 * st);
        }
    };
    auto load2 = [&](int ks) {
        const int st = ks % P2_STAGES;
        mbar_expect_tx(full2 + 8 * st, P2_STAGE);
        const uint32_t dst = sbase + st * P2_STAGE;
        if (ks < 22) {
            tma_load_2d(dst, &tmA2, D_ + ks * 64, rb * 128, full2 + 8 * st);
            tma_load_2d(dst + 16384, &tmW2, j * 64, ks * 64, full2 + 8 * st);
        } else {
            tma_load_2d(dst, &tmA2, (ks - 22) * 64, rb * 128, full2 + 8 * st);
            tma_load_2d(dst + 16384, &tmWo, j * 64, (ks - 22) * 64, full2 + 8 * st);
        }
    };

    if (tid == 0) {
        for (int i = 0; i < P1_STAGES; i++) { mbar_init(full1 + 8 * i, 1); mbar_init(empty1 + 8 * i, 8); }
        for (int i = 0; i < P2_STAGES; i++) { mbar_init(full2 + 8 * i, 1); mbar_init(empty2 + 8 * i, 8); }
        mbar_init(kv_full, 1);
        fence_barrier_init();
        for (int it = 0; it < P1_STAGES; it++) load1(it);
    }
    __syncthreads();
    const unsigned int ep8 = *(volatile unsigned int*)&g_epoch + 1;

    if (wg >= 2) {
        reg_dealloc<104>();
        const int qt = warp - 8;
        const int q0g = rb * 128 + qt * 16;
        if (tid == 288) {
            const int b = blockIdx.x;
            mbar_wait(full1 + 8, 0);
            l2_prefetch((const uint8_t*)w1p + b * 11008, 11008);
            l2_prefetch((const uint8_t*)w2p + b * 11008, 11008);
            l2_prefetch((const uint8_t*)wop + b * 4096, 4096);
        }
        if (rb < 2) {
            for (int i = tid - 256; i < (2 - rb) * 1024; i += 256) {
                *(uint4*)(sgen + OFF_KV + i * 16) = make_uint4(0, 0, 0, 0);
                *(uint4*)(sgen + OFF_KV + 384 * KV_PITCH + i * 16) = make_uint4(0, 0, 0, 0);
            }
        }
        bar_sync(3, 512);
        if (tid == 256) {
            __threadfence();
            flag_set(&g_flag_qkv[blockIdx.x], ep8);
            const int nblk = rb >= 2 ? 3 : rb + 1;
            for (int i = 1; i < nblk; i++) flag_wait(&g_flag_qkv[(rb - i) * 8 + j], ep8);
            fence_proxy_async();
            mbar_expect_tx(kv_full, nblk * 2 * 16384);
            for (int i = 0; i < nblk; i++) {
                const int row = j * S_ + (rb - i) * 128;
                tma_load_2d(sK + (2 - i) * 16384, &tmQKV, 64, row, kv_full);
                tma_load_2d(sV + (2 - i) * 16384, &tmQKV, 128, row, kv_full);
            }
        }
        __syncwarp();
        const int r0 = lane >> 2, c0 = (lane & 3) * 2;
        const bf16* qsrc = g_qkv + ((size_t)j * S_ + q0g) * 192;
        uint32_t qa[4], qn[4];
        qa[0] = *(const volatile uint32_t*)(qsrc + (size_t)r0 * 192 + c0);
        qa[1] = *(const volatile uint32_t*)(qsrc + (size_t)(r0 + 8) * 192 + c0);
        qa[2] = *(const volatile uint32_t*)(qsrc + (size_t)r0 * 192 + c0 + 8);
        qa[3] = *(const volatile uint32_t*)(qsrc + (size_t)(r0 + 8) * 192 + c0 + 8);
        const float g0 = sGate[qt * 16 + r0], g1 = sGate[qt * 16 + r0 + 8];
        const int kb0 = q0g < 256 ? (256 - q0g) >> 4 : 0;
        mbar_wait(kv_full, 0);
        uint32_t sKd = sK, sVd = sV;
        asm volatile("" : "+r"(sKd), "+r"(sVd) :: "memory");
        TS(6, tid == 256);
        const int krow = qt * 16 + (lane & 7) + ((lane >> 4) << 3);
        const int vrow = qt * 16 + (lane & 15);
#pragma unroll 1
        for (int hl = 0; hl < 4; hl++) {
            const int hn = (hl + 1) & 3;
            qn[0] = *(const volatile uint32_t*)(qsrc + (size_t)r0 * 192 + hn * 16 + c0);
            qn[1] = *(const volatile uint32_t*)(qsrc + (size_t)(r0 + 8) * 192 + hn * 16 + c0);
            qn[2] = *(const volatile uint32_t*)(qsrc + (size_t)r0 * 192 + hn * 16 + c0 + 8);
            qn[3] = *(const volatile uint32_t*)(qsrc + (size_t)(r0 + 8) * 192 + hn * 16 + c0 + 8);
            const uint32_t ka = sKd + krow * KV_PITCH + (((2 * hl + ((lane >> 3) & 1)) ^ (lane & 7)) << 4);
            const uint32_t va = sVd + vrow * KV_PITCH + (((2 * hl + (lane >> 4)) ^ (lane & 7)) << 4);
            if (rb < 2) attn_task<true>(qa, ka, va, kb0, lane, g_a2 + (size_t)q0g * KA2 + (j * 4 + hl) * 16, g0, g1);
            else        attn_task<false>(qa, ka, va, kb0, lane, g_a2 + (size_t)q0g * KA2 + (j * 4 + hl) * 16, g0, g1);
            TS(12 + hl, tid == 256);
            qa[0] = qn[0]; qa[1] = qn[1]; qa[2] = qn[2]; qa[3] = qn[3];
        }
        TS(7, tid == 256);
        bar_sync(4, 256);
        if (tid == 256) { __threadfence(); flag_set(&g_flag_att[blockIdx.x], ep8); }
    } else {
        reg_alloc<152>();
        const int t128 = tid & 127, w4 = warp & 3, q = lane & 3;
        if (tid < 64) ((uint4*)sGw)[tid] = __ldg((const uint4*)gate_w + tid);
        else if (tid < 64 + 88) {
            const int c = j * FCH + (tid - 64) * 2;
            sBias[tid - 64] = c < F_ ? __ldg((const uint32_t*)(b1 + c)) : 0u;
        }
        bar_sync(1, 256);
        const int rl = wg * 64 + w4 * 16 + (lane >> 2);
        {
            float acc[96];
            float gs = 0.f;
            const int grow = wg * 64 + (t128 >> 1), ghalf = t128 & 1;
#pragma unroll
            for (int kc = 0; kc < 8; kc++) {
                const int st = kc % P1_STAGES;
                const uint32_t sa = sbase + st * P1_STAGE;
                mbar_wait(full1 + 8 * st, (kc / P1_STAGES) & 1);
                TS(1, tid == 0 && kc == 0);
                wgmma_fence();
#pragma unroll
                for (int k16 = 0; k16 < 4; k16++)
                    wgmma_n192<1>(acc, make_desc(sa + wg * 8192 + k16 * 32, 16, 1024),
                                  make_desc(sa + 16384 + k16 * 2048, 8192, 1024), (kc | k16) != 0);
                wgmma_commit();
#pragma unroll
                for (int c = 0; c < 4; c++) {
                    const int cc = ghalf * 4 + c;
                    const uint4 xv = *(const uint4*)(sgen + st * P1_STAGE + grow * 128 + ((cc ^ (grow & 7)) << 4));
                    const uint4 gv = *(const uint4*)(sGw + kc * 128 + cc * 16);
                    gs = fmaf(bf_lo(xv.x), bf_lo(gv.x), gs); gs = fmaf(bf_hi(xv.x), bf_hi(gv.x), gs);
                    gs = fmaf(bf_lo(xv.y), bf_lo(gv.y), gs); gs = fmaf(bf_hi(xv.y), bf_hi(gv.y), gs);
                    gs = fmaf(bf_lo(xv.z), bf_lo(gv.z), gs); gs = fmaf(bf_hi(xv.z), bf_hi(gv.z), gs);
                    gs = fmaf(bf_lo(xv.w), bf_lo(gv.w), gs); gs = fmaf(bf_hi(xv.w), bf_hi(gv.w), gs);
                }
                if (kc > 0) {
                    wgmma_wait<1>();
                    if (lane == 0) mbar_arrive(empty1 + 8 * ((kc - 1) % P1_STAGES));
                    if (tid == 0) { mbar_wait(empty1 + 8 * ((kc - 1) % P1_STAGES), ((kc - 1) / P1_STAGES) & 1); load1(kc + 2); }
                    __syncwarp();
                }
            }
            gs += __shfl_xor_sync(0xffffffffu, gs, 1);
            if (ghalf == 0) sGate[grow] = 1.f / (1.f + __expf(-gs));
            wgmma_wait<0>();
            if (lane == 0) mbar_arrive(empty1 + 8 * (7 % P1_STAGES));
            if (tid == 0) { mbar_wait(empty1 + 8 * (7 % P1_STAGES), (7 / P1_STAGES) & 1); load1(10); }
            __syncwarp();
            TS(2, tid == 0);
            bf16* orow0 = g_qkv + ((size_t)j * S_ + rb * 128 + rl) * 192;
            bf16* orow1 = orow0 + 8 * 192;
#pragma unroll
            for (int uu = 0; uu < 6; uu++) {
                const int u = (uu + 2) % 6;
                uint32_t w0[4], w1[4];
#pragma unroll
                for (int i = 0; i < 4; i++) {
                    const int t = u * 4 + i;
                    w0[i] = pack_bf16(acc[t * 4 + 0], acc[t * 4 + 1]);
                    w1[i] = pack_bf16(acc[t * 4 + 2], acc[t * 4 + 3]);
                }
                quad_transpose(w0, q);
                quad_transpose(w1, q);
                const int c = (u * 4 + q) * 8;
                *(uint4*)(orow0 + c) = make_uint4(w0[0], w0[1], w0[2], w0[3]);
                *(uint4*)(orow1 + c) = make_uint4(w1[0], w1[1], w1[2], w1[3]);
            }
            bar_arrive(3, 512);
            TS(3, tid == 0);
        }
        {
            float acc[88];
#pragma unroll
            for (int kc = 0; kc < 8; kc++) {
                const int it = kc + 8, st = it % P1_STAGES;
                const uint32_t sa = sbase + st * P1_STAGE;
                mbar_wait(full1 + 8 * st, (it / P1_STAGES) & 1);
                wgmma_fence();
#pragma unroll
                for (int k16 = 0; k16 < 4; k16++)
                    wgmma_n176<1>(acc, make_desc(sa + wg * 8192 + k16 * 32, 16, 1024),
                                  make_desc(sa + 16384 + k16 * 2048, 8192, 1024), (kc | k16) != 0);
                wgmma_commit();
                if (kc > 0) {
                    wgmma_wait<1>();
                    if (lane == 0) mbar_arrive(empty1 + 8 * ((it - 1) % P1_STAGES));
                    if (tid == 0 && it + 2 < 16) { mbar_wait(empty1 + 8 * ((it - 1) % P1_STAGES), ((it - 1) / P1_STAGES) & 1); load1(it + 2); }
                    __syncwarp();
                }
            }
            wgmma_wait<0>();
            TS(4, tid == 0);
            const int n0 = j * FCH;
            const float om0 = 1.f - sGate[rl], om1 = 1.f - sGate[rl + 8];
            bf16* frow0 = g_a2 + (size_t)(rb * 128 + rl) * KA2 + D_ + n0;
            bf16* frow1 = frow0 + 8 * KA2;
#pragma unroll
            for (int u = 0; u < 6; u++) {
                uint32_t w0[4], w1[4];
#pragma unroll
                for (int i = 0; i < 4; i++) {
                    const int t = u * 4 + i;
                    if (t < 22) {
                        const uint32_t bv = sBias[t * 4 + q];
                        const float bb0 = bf_lo(bv), bb1 = bf_hi(bv);
                        w0[i] = pack_bf16(mish_f(acc[t * 4 + 0] + bb0) * om0, mish_f(acc[t * 4 + 1] + bb1) * om0);
                        w1[i] = pack_bf16(mish_f(acc[t * 4 + 2] + bb0) * om1, mish_f(acc[t * 4 + 3] + bb1) * om1);
                    } else { w0[i] = 0; w1[i] = 0; }
                }
                quad_transpose(w0, q);
                quad_transpose(w1, q);
                const int c = (u * 4 + q) * 8;
                if (c < FCH && n0 + c < F_) {
                    *(uint4*)(frow0 + c) = make_uint4(w0[0], w0[1], w0[2], w0[3]);
                    *(uint4*)(frow1 + c) = make_uint4(w1[0], w1[1], w1[2], w1[3]);
                }
            }
            TS(5, tid == 0);
        }
        {
            bar_sync(1, 256);
            if (tid == 0) {
                __threadfence();
                flag_set(&g_flag_act[blockIdx.x], ep8);
                for (int i = 0; i < 8; i++) flag_wait(&g_flag_act[rb * 8 + i], ep8);
                fence_proxy_async();
                for (int ks = 0; ks < P2_STAGES; ks++) load2(ks);
            }
            __syncwarp();
            float acc[32];
            for (int ks = 0; ks < P2_KSTEPS; ks++) {
                const int st = ks % P2_STAGES;
                const uint32_t sa = sbase + st * P2_STAGE;
                mbar_wait(full2 + 8 * st, (ks / P2_STAGES) & 1);
                TS(8, tid == 0 && ks == 0); TS(9, tid == 0 && ks == 22);
                wgmma_fence();
#pragma unroll
                for (int k16 = 0; k16 < 4; k16++)
                    wgmma_n64<1>(acc, make_desc(sa + wg * 8192 + k16 * 32, 16, 1024),
                                 make_desc(sa + 16384 + k16 * 2048, 8192, 1024), (ks | k16) != 0);
                wgmma_commit();
                if (ks > 0) {
                    wgmma_wait<1>();
                    if (lane == 0) mbar_arrive(empty2 + 8 * ((ks - 1) % P2_STAGES));
                    if (tid == 0 && ks - 1 + P2_STAGES < P2_KSTEPS) {
                        mbar_wait(empty2 + 8 * ((ks - 1) % P2_STAGES), ((ks - 1) / P2_STAGES) & 1);
                        if (ks - 1 + P2_STAGES == 22) {
                            for (int i = 0; i < 8; i++) flag_wait(&g_flag_att[rb * 8 + i], ep8);
                            fence_proxy_async();
                        }
                        load2(ks - 1 + P2_STAGES);
                    }
                    __syncwarp();
                }
            }
            wgmma_wait<0>();
            TS(10, tid == 0);
            bf16* orow0 = out + (size_t)(rb * 128 + rl) * D_ + j * 64;
            bf16* orow1 = orow0 + 8 * D_;
#pragma unroll
            for (int u = 0; u < 2; u++) {
                uint32_t w0[4], w1[4];
#pragma unroll
                for (int i = 0; i < 4; i++) {
                    const int t = u * 4 + i;
                    w0[i] = pack_bf16(acc[t * 4 + 0], acc[t * 4 + 1]);
                    w1[i] = pack_bf16(acc[t * 4 + 2], acc[t * 4 + 3]);
                }
                quad_transpose(w0, q);
                quad_transpose(w1, q);
                const int c = (u * 4 + q) * 8;
                *(uint4*)(orow0 + c) = make_uint4(w0[0], w0[1], w0[2], w0[3]);
                *(uint4*)(orow1 + c) = make_uint4(w1[0], w1[1], w1[2], w1[3]);
            }
            TS(11, tid == 0);
        }
        if (tid == 0) {
            __threadfence();
            if (atomicAdd(&g_done, 1u) == gridDim.x - 1) {
                g_done = 0;
                __threadfence();
                atomicAdd(&g_epoch, 1u);
            }
        }
    }
}

typedef CUresult (*PFN_encodeTiled)(CUtensorMap*, CUtensorMapDataType, cuuint32_t, void*, const cuuint64_t*,
                                    const cuuint64_t*, const cuuint32_t*, const cuuint32_t*, CUtensorMapInterleave,
                                    CUtensorMapSwizzle, CUtensorMapL2promotion, CUtensorMapFloatOOBfill);

static void make_map(PFN_encodeTiled enc, CUtensorMap* m, const void* ptr, uint64_t cols, uint64_t rows,
                     uint32_t box_cols, uint32_t box_rows)
{
    cuuint64_t dims[2] = {cols, rows};
    cuuint64_t strides[1] = {cols * 2};
    cuuint32_t box[2] = {box_cols, box_rows};
    cuuint32_t es[2] = {1, 1};
    enc(m, CU_TENSOR_MAP_DATA_TYPE_BFLOAT16, 2, const_cast<void*>(ptr), dims, strides, box, es,
        CU_TENSOR_MAP_INTERLEAVE_NONE, CU_TENSOR_MAP_SWIZZLE_128B, CU_TENSOR_MAP_L2_PROMOTION_L2_128B,
        CU_TENSOR_MAP_FLOAT_OOB_FILL_NONE);
}

extern "C" void kernel_launch(void* const* d_in, const int* in_sizes, int n_in, void* d_out, int out_size)
{
    const bf16* x    = (const bf16*)d_in[0];
    const bf16* wqkv = (const bf16*)d_in[1];
    const bf16* wo   = (const bf16*)d_in[2];
    const bf16* w1   = (const bf16*)d_in[4];
    const bf16* b1   = (const bf16*)d_in[5];
    const bf16* w2   = (const bf16*)d_in[6];
    const bf16* gw   = (const bf16*)d_in[7];

    static PFN_encodeTiled enc = nullptr;
    if (!enc) {
        void* fn = nullptr;
        cudaDriverEntryPointQueryResult qr;
        cudaGetDriverEntryPoint("cuTensorMapEncodeTiled", &fn, cudaEnableDefault, &qr);
        enc = (PFN_encodeTiled)fn;
        cudaFuncSetAttribute(fused_kernel, cudaFuncAttributeMaxDynamicSharedMemorySize, FUSED_SMEM);
    }
    void *a2p = nullptr, *qkvp = nullptr;
    cudaGetSymbolAddress(&a2p, g_a2);
    cudaGetSymbolAddress(&qkvp, g_qkv);
    CUtensorMap tmX, tmWqkv, tmW1, tmQKV, tmA2, tmWo, tmW2;
    make_map(enc, &tmX, x, D_, S_, 64, 128);
    make_map(enc, &tmWqkv, wqkv, 3 * D_, D_, 64, 64);
    make_map(enc, &tmW1, w1, F_, D_, 64, 64);
    make_map(enc, &tmQKV, qkvp, 192, 8 * S_, 64, 128);
    make_map(enc, &tmA2, a2p, KA2, S_, 64, 128);
    make_map(enc, &tmWo, wo, D_, D_, 64, 64);
    make_map(enc, &tmW2, w2, D_, F_, 64, 64);

    fused_kernel<<<128, 512, FUSED_SMEM, cudaStreamPerThread>>>(tmX, tmWqkv, tmW1, tmQKV, tmA2, tmWo, tmW2,
                                                                b1, gw, w1, wqkv, w2, wo, (bf16*)d_out);
}
```

```cpp
#include <cuda_runtime.h>
#include <cuda_bf16.h>
#include <cuda.h>
#include <stdint.h>

typedef __nv_bfloat16 bf16;

constexpr int S_ = 2048, D_ = 512, F_ = 1376;
constexpr int KA2 = D_ + F_;
constexpr int FCH = 176;

__device__ bf16  g_qkv[8 * S_ * 192];
__device__ bf16  g_a2[S_ * KA2];
__device__ float g_gate[S_];

#define TS(k, cond) do { } while (0)

__device__ __forceinline__ uint32_t smem_u32(const void* p) { return (uint32_t)__cvta_generic_to_shared(p); }
__device__ __forceinline__ void mbar_init(uint32_t bar, uint32_t count) {
    asm volatile("mbarrier.init.shared::cta.b64 [%0], %1;" :: "r"(bar), "r"(count) : "memory");
}
__device__ __forceinline__ void mbar_expect_tx(uint32_t bar, uint32_t bytes) {
    asm volatile("mbarrier.arrive.expect_tx.shared::cta.b64 _, [%0], %1;" :: "r"(bar), "r"(bytes) : "memory");
}
__device__ __forceinline__ void mbar_arrive(uint32_t bar) {
    asm volatile("mbarrier.arrive.shared::cta.b64 _, [%0];" :: "r"(bar) : "memory");
}
__device__ __forceinline__ bool mbar_try_wait(uint32_t bar, uint32_t parity) {
    uint32_t ok;
    asm volatile("{\n.reg .pred p;\nmbarrier.try_wait.parity.shared::cta.b64 p, [%1], %2;\nselp.u32 %0, 1, 0, p;\n}"
                 : "=r"(ok) : "r"(bar), "r"(parity) : "memory");
    return ok != 0;
}
__device__ __forceinline__ void mbar_wait(uint32_t bar, uint32_t parity) {
    for (uint32_t it = 0; it < (1u << 22); ++it) { if (mbar_try_wait(bar, parity)) break; }
}
__device__ __forceinline__ void tma_load_2d(uint32_t dst, const CUtensorMap* map, int c0, int c1, uint32_t bar) {
    asm volatile("cp.async.bulk.tensor.2d.shared::cluster.global.mbarrier::complete_tx::bytes [%0], [%1, {%3, %4}], [%2];"
                 :: "r"(dst), "l"(map), "r"(bar), "r"(c0), "r"(c1) : "memory");
}
__device__ __forceinline__ void l2_prefetch(const void* p, uint32_t bytes) {
    asm volatile("cp.async.bulk.prefetch.L2.global [%0], %1;" :: "l"(p), "r"(bytes) : "memory");
}
__device__ __forceinline__ void fence_barrier_init() { asm volatile("fence.mbarrier_init.release.cluster;" ::: "memory"); }
__device__ __forceinline__ void wgmma_fence()  { asm volatile("wgmma.fence.sync.aligned;" ::: "memory"); }
__device__ __forceinline__ void wgmma_commit() { asm volatile("wgmma.commit_group.sync.aligned;" ::: "memory"); }
template <int N> __device__ __forceinline__ void wgmma_wait() { asm volatile("wgmma.wait_group.sync.aligned %0;" :: "n"(N) : "memory"); }
template <int R> __device__ __forceinline__ void reg_alloc()   { asm volatile("setmaxnreg.inc.sync.aligned.u32 %0;" :: "n"(R)); }
template <int R> __device__ __forceinline__ void reg_dealloc() { asm volatile("setmaxnreg.dec.sync.aligned.u32 %0;" :: "n"(R)); }
__device__ __forceinline__ void bar_sync(int id, int n)   { asm volatile("bar.sync %0, %1;" :: "r"(id), "r"(n) : "memory"); }
__device__ __forceinline__ void bar_arrive(int id, int n) { asm volatile("bar.arrive %0, %1;" :: "r"(id), "r"(n) : "memory"); }

__device__ __forceinline__ uint64_t make_desc(uint32_t addr, uint32_t lbo, uint32_t sbo) {
    uint64_t d = (uint64_t)((addr & 0x3FFFF) >> 4);
    d |= (uint64_t)((lbo & 0x3FFFF) >> 4) << 16;
    d |= (uint64_t)((sbo & 0x3FFFF) >> 4) << 32;
    d |= (uint64_t)1 << 62;
    return d;
}

template <int TB>
__device__ __forceinline__ void wgmma_n64(float (&d)[32], uint64_t da, uint64_t db, int scale_d) {
    asm volatile("{\n.reg .pred p;\nsetp.ne.b32 p, %34, 0;\n"
        "wgmma.mma_async.sync.aligned.m64n64k16.f32.bf16.bf16 {%0, %1, %2, %3, %4, %5, %6, %7, %8, %9, %10, %11, %12, %13, %14, %15, %16, %17, %18, %19, %20, %21, %22, %23, %24, %25, %26, %27, %28, %29, %30, %31}, %32, %33, p, 1, 1, 0, %35;\n}\n"
        : "+f"(d[0]), "+f"(d[1]), "+f"(d[2]), "+f"(d[3]), "+f"(d[4]), "+f"(d[5]), "+f"(d[6]), "+f"(d[7]), "+f"(d[8]), "+f"(d[9]), "+f"(d[10]), "+f"(d[11]), "+f"(d[12]), "+f"(d[13]), "+f"(d[14]), "+f"(d[15]), "+f"(d[16]), "+f"(d[17]), "+f"(d[18]), "+f"(d[19]), "+f"(d[20]), "+f"(d[21]), "+f"(d[22]), "+f"(d[23]), "+f"(d[24]), "+f"(d[25]), "+f"(d[26]), "+f"(d[27]), "+f"(d[28]), "+f"(d[29]), "+f"(d[30]), "+f"(d[31])
        : "l"(da), "l"(db), "r"(scale_d), "n"(TB));
}

template <int TB>
__device__ __forceinline__ void wgmma_n128(float (&d)[64], uint64_t da, uint64_t db, int scale_d) {
    asm volatile("{\n.reg .pred p;\nsetp.ne.b32 p, %66, 0;\n"
        "wgmma.mma_async.sync.aligned.m64n128k16.f32.bf16.bf16 {%0, %1, %2, %3, %4, %5, %6, %7, %8, %9, %10, %11, %12, %13, %14, %15, %16, %17, %18, %19, %20, %21, %22, %23, %24, %25, %26, %27, %28, %29, %30, %31, %32, %33, %34, %35, %36, %37, %38, %39, %40, %41, %42, %43, %44, %45, %46, %47, %48, %49, %50, %51, %52, %53, %54, %55, %56, %57, %58, %59, %60, %61, %62, %63}, %64, %65, p, 1, 1, 0, %67;\n}\n"
        : "+f"(d[0]), "+f"(d[1]), "+f"(d[2]), "+f"(d[3]), "+f"(d[4]), "+f"(d[5]), "+f"(d[6]), "+f"(d[7]), "+f"(d[8]), "+f"(d[9]), "+f"(d[10]), "+f"(d[11]), "+f"(d[12]), "+f"(d[13]), "+f"(d[14]), "+f"(d[15]), "+f"(d[16]), "+f"(d[17]), "+f"(d[18]), "+f"(d[19]), "+f"(d[20]), "+f"(d[21]), "+f"(d[22]), "+f"(d[23]), "+f"(d[24]), "+f"(d[25]), "+f"(d[26]), "+f"(d[27]), "+f"(d[28]), "+f"(d[29]), "+f"(d[30]), "+f"(d[31]), "+f"(d[32]), "+f"(d[33]), "+f"(d[34]), "+f"(d[35]), "+f"(d[36]), "+f"(d[37]), "+f"(d[38]), "+f"(d[39]), "+f"(d[40]), "+f"(d[41]), "+f"(d[42]), "+f"(d[43]), "+f"(d[44]), "+f"(d[45]), "+f"(d[46]), "+f"(d[47]), "+f"(d[48]), "+f"(d[49]), "+f"(d[50]), "+f"(d[51]), "+f"(d[52]), "+f"(d[53]), "+f"(d[54]), "+f"(d[55]), "+f"(d[56]), "+f"(d[57]), "+f"(d[58]), "+f"(d[59]), "+f"(d[60]), "+f"(d[61]), "+f"(d[62]), "+f"(d[63])
        : "l"(da), "l"(db), "r"(scale_d), "n"(TB));
}

template <int TB>
__device__ __forceinline__ void wgmma_n176(float (&d)[88], uint64_t da, uint64_t db, int scale_d) {
    asm volatile("{\n.reg .pred p;\nsetp.ne.b32 p, %90, 0;\n"
        "wgmma.mma_async.sync.aligned.m64n176k16.f32.bf16.bf16 {%0, %1, %2, %3, %4, %5, %6, %7, %8, %9, %10, %11, %12, %13, %14, %15, %16, %17, %18, %19, %20, %21, %22, %23, %24, %25, %26, %27, %28, %29, %30, %31, %32, %33, %34, %35, %36, %37, %38, %39, %40, %41, %42, %43, %44, %45, %46, %47, %48, %49, %50, %51, %52, %53, %54, %55, %56, %57, %58, %59, %60, %61, %62, %63, %64, %65, %66, %67, %68, %69, %70, %71, %72, %73, %74, %75, %76, %77, %78, %79, %80, %81, %82, %83, %84, %85, %86, %87}, %88, %89, p, 1, 1, 0, %91;\n}\n"
        : "+f"(d[0]), "+f"(d[1]), "+f"(d[2]), "+f"(d[3]), "+f"(d[4]), "+f"(d[5]), "+f"(d[6]), "+f"(d[7]), "+f"(d[8]), "+f"(d[9]), "+f"(d[10]), "+f"(d[11]), "+f"(d[12]), "+f"(d[13]), "+f"(d[14]), "+f"(d[15]), "+f"(d[16]), "+f"(d[17]), "+f"(d[18]), "+f"(d[19]), "+f"(d[20]), "+f"(d[21]), "+f"(d[22]), "+f"(d[23]), "+f"(d[24]), "+f"(d[25]), "+f"(d[26]), "+f"(d[27]), "+f"(d[28]), "+f"(d[29]), "+f"(d[30]), "+f"(d[31]), "+f"(d[32]), "+f"(d[33]), "+f"(d[34]), "+f"(d[35]), "+f"(d[36]), "+f"(d[37]), "+f"(d[38]), "+f"(d[39]), "+f"(d[40]), "+f"(d[41]), "+f"(d[42]), "+f"(d[43]), "+f"(d[44]), "+f"(d[45]), "+f"(d[46]), "+f"(d[47]), "+f"(d[48]), "+f"(d[49]), "+f"(d[50]), "+f"(d[51]), "+f"(d[52]), "+f"(d[53]), "+f"(d[54]), "+f"(d[55]), "+f"(d[56]), "+f"(d[57]), "+f"(d[58]), "+f"(d[59]), "+f"(d[60]), "+f"(d[61]), "+f"(d[62]), "+f"(d[63]), "+f"(d[64]), "+f"(d[65]), "+f"(d[66]), "+f"(d[67]), "+f"(d[68]), "+f"(d[69]), "+f"(d[70]), "+f"(d[71]), "+f"(d[72]), "+f"(d[73]), "+f"(d[74]), "+f"(d[75]), "+f"(d[76]), "+f"(d[77]), "+f"(d[78]), "+f"(d[79]), "+f"(d[80]), "+f"(d[81]), "+f"(d[82]), "+f"(d[83]), "+f"(d[84]), "+f"(d[85]), "+f"(d[86]), "+f"(d[87])
        : "l"(da), "l"(db), "r"(scale_d), "n"(TB));
}

template <int TB>
__device__ __forceinline__ void wgmma_n192(float (&d)[96], uint64_t da, uint64_t db, int scale_d) {
    asm volatile("{\n.reg .pred p;\nsetp.ne.b32 p, %98, 0;\n"
        "wgmma.mma_async.sync.aligned.m64n192k16.f32.bf16.bf16 {%0, %1, %2, %3, %4, %5, %6, %7, %8, %9, %10, %11, %12, %13, %14, %15, %16, %17, %18, %19, %20, %21, %22, %23, %24, %25, %26, %27, %28, %29, %30, %31, %32, %33, %34, %35, %36, %37, %38, %39, %40, %41, %42, %43, %44, %45, %46, %47, %48, %49, %50, %51, %52, %53, %54, %55, %56, %57, %58, %59, %60, %61, %62, %63, %64, %65, %66, %67, %68, %69, %70, %71, %72, %73, %74, %75, %76, %77, %78, %79, %80, %81, %82, %83, %84, %85, %86, %87, %88, %89, %90, %91, %92, %93, %94, %95}, %96, %97, p, 1, 1, 0, %99;\n}\n"
        : "+f"(d[0]), "+f"(d[1]), "+f"(d[2]), "+f"(d[3]), "+f"(d[4]), "+f"(d[5]), "+f"(d[6]), "+f"(d[7]), "+f"(d[8]), "+f"(d[9]), "+f"(d[10]), "+f"(d[11]), "+f"(d[12]), "+f"(d[13]), "+f"(d[14]), "+f"(d[15]), "+f"(d[16]), "+f"(d[17]), "+f"(d[18]), "+f"(d[19]), "+f"(d[20]), "+f"(d[21]), "+f"(d[22]), "+f"(d[23]), "+f"(d[24]), "+f"(d[25]), "+f"(d[26]), "+f"(d[27]), "+f"(d[28]), "+f"(d[29]), "+f"(d[30]), "+f"(d[31]), "+f"(d[32]), "+f"(d[33]), "+f"(d[34]), "+f"(d[35]), "+f"(d[36]), "+f"(d[37]), "+f"(d[38]), "+f"(d[39]), "+f"(d[40]), "+f"(d[41]), "+f"(d[42]), "+f"(d[43]), "+f"(d[44]), "+f"(d[45]), "+f"(d[46]), "+f"(d[47]), "+f"(d[48]), "+f"(d[49]), "+f"(d[50]), "+f"(d[51]), "+f"(d[52]), "+f"(d[53]), "+f"(d[54]), "+f"(d[55]), "+f"(d[56]), "+f"(d[57]), "+f"(d[58]), "+f"(d[59]), "+f"(d[60]), "+f"(d[61]), "+f"(d[62]), "+f"(d[63]), "+f"(d[64]), "+f"(d[65]), "+f"(d[66]), "+f"(d[67]), "+f"(d[68]), "+f"(d[69]), "+f"(d[70]), "+f"(d[71]), "+f"(d[72]), "+f"(d[73]), "+f"(d[74]), "+f"(d[75]), "+f"(d[76]), "+f"(d[77]), "+f"(d[78]), "+f"(d[79]), "+f"(d[80]), "+f"(d[81]), "+f"(d[82]), "+f"(d[83]), "+f"(d[84]), "+f"(d[85]), "+f"(d[86]), "+f"(d[87]), "+f"(d[88]), "+f"(d[89]), "+f"(d[90]), "+f"(d[91]), "+f"(d[92]), "+f"(d[93]), "+f"(d[94]), "+f"(d[95])
        : "l"(da), "l"(db), "r"(scale_d), "n"(TB));
}

__device__ __forceinline__ uint32_t pack_bf16(float lo, float hi) {
    uint32_t r;
    asm("cvt.rn.bf16x2.f32 %0, %1, %2;" : "=r"(r) : "f"(hi), "f"(lo));
    return r;
}
__device__ __forceinline__ float bf_lo(uint32_t v) { return __uint_as_float(v << 16); }
__device__ __forceinline__ float bf_hi(uint32_t v) { return __uint_as_float(v & 0xffff0000u); }

__device__ __forceinline__ void quad_transpose(uint32_t (&w)[4], int q) {
    const bool o1 = q & 1, o2 = q & 2;
    {
        uint32_t s0 = o1 ? w[0] : w[1], s1 = o1 ? w[2] : w[3];
        s0 = __shfl_xor_sync(0xffffffffu, s0, 1); s1 = __shfl_xor_sync(0xffffffffu, s1, 1);
        if (o1) { w[0] = s0; w[2] = s1; } else { w[1] = s0; w[3] = s1; }
    }
    {
        uint32_t s0 = o2 ? w[0] : w[2], s1 = o2 ? w[1] : w[3];
        s0 = __shfl_xor_sync(0xffffffffu, s0, 2); s1 = __shfl_xor_sync(0xffffffffu, s1, 2);
        if (o2) { w[0] = s0; w[1] = s1; } else { w[2] = s0; w[3] = s1; }
    }
}

__device__ __forceinline__ float ex2(float x) { float y; asm("ex2.approx.ftz.f32 %0, %1;" : "=f"(y) : "f"(x)); return y; }
__device__ __forceinline__ float rcp(float x) { float y; asm("rcp.approx.ftz.f32 %0, %1;" : "=f"(y) : "f"(x)); return y; }

__device__ __forceinline__ float ex2v(float x) { float y; asm volatile("ex2.approx.ftz.f32 %0, %1;" : "=f"(y) : "f"(x)); return y; }
__device__ __forceinline__ float rcpv(float x) { float y; asm volatile("rcp.approx.ftz.f32 %0, %1;" : "=f"(y) : "f"(x)); return y; }
__device__ __forceinline__ float mish_f(float h) {
    const float w = ex2v(-1.4426950408889634f * fabsf(h));
    const float t = w * w;
    const bool pos = h > 0.f;
    const float num = fmaf(2.f, w, pos ? 1.f : t);
    const float den = num + (pos ? t + t : 2.f);
    return h * num * rcpv(den);
}

constexpr int K1_STAGES = 4;
constexpr int K1_XBYTES = 128 * 512 * 2;
constexpr int K1_BSTAGE = 3 * 8192;
constexpr int K1_SMEM   = K1_XBYTES + K1_STAGES * K1_BSTAGE + 2048   + 1024  ;

__global__ void __launch_bounds__(384, 1)
k1_kernel(const __grid_constant__ CUtensorMap tmX, const __grid_constant__ CUtensorMap tmWqkv,
          const __grid_constant__ CUtensorMap tmW1, const bf16* __restrict__ b1,
          const bf16* __restrict__ gate_w, const bf16* __restrict__ w1p, const bf16* __restrict__ wqkvp,
          const bf16* __restrict__ w2p, const bf16* __restrict__ wop)
{

    extern __shared__ uint8_t smem_raw[];
    const uint32_t sbase = (smem_u32(smem_raw) + 1023u) & ~1023u;
    uint8_t* sgen = smem_raw + (sbase - smem_u32(smem_raw));
    const uint32_t sX = sbase;
    const uint32_t sB = sbase + K1_XBYTES;
    const uint32_t sBar = sB + K1_STAGES * K1_BSTAGE;
    const uint32_t x_full = sBar;
    const uint32_t b_full = sBar + 64;
    const uint32_t b_empty = sBar + 96;
    float* sGate = (float*)(sgen + K1_XBYTES + K1_STAGES * K1_BSTAGE + 128);
    uint8_t* sGw = sgen + K1_XBYTES + K1_STAGES * K1_BSTAGE + 640;
    uint32_t* sBias = (uint32_t*)(sgen + K1_XBYTES + K1_STAGES * K1_BSTAGE + 1664);

    const int rb = blockIdx.x >> 3, j = blockIdx.x & 7;
    const int tid = threadIdx.x, wg = tid >> 7, warp = tid >> 5, lane = tid & 31;
    TS(0, tid == 0);

    if (tid == 0) {
        for (int i = 0; i < 8; i++) mbar_init(x_full + 8 * i, 1);
        for (int i = 0; i < K1_STAGES; i++) { mbar_init(b_full + 8 * i, 1); mbar_init(b_empty + 8 * i, 8); }
        fence_barrier_init();
    }
    __syncthreads();

    if (wg == 2) {
        reg_dealloc<40>();
        if (tid == 288) {
            const int b = blockIdx.x;
            mbar_wait(b_full + 8, 0);
            l2_prefetch((const uint8_t*)wqkvp + b * 12288, 12288);
            l2_prefetch((const uint8_t*)w2p + b * 11008, 11008);
            l2_prefetch((const uint8_t*)wop + b * 4096, 4096);
        }
        if (tid == 256) {
            for (int it = 0; it < 16; it++) {
                if (it < 8) {
                    mbar_expect_tx(x_full + 8 * it, 16384);
                    tma_load_2d(sX + it * 16384, &tmX, it * 64, rb * 128, x_full + 8 * it);
                }
                const int st = it & 3;
                if (it >= K1_STAGES) mbar_wait(b_empty + 8 * st, ((it >> 2) - 1) & 1);
                mbar_expect_tx(b_full + 8 * st, K1_BSTAGE);
                const uint32_t dst = sB + st * K1_BSTAGE;
                if (it < 8) {
                    for (int b = 0; b < 3; b++) tma_load_2d(dst + b * 8192, &tmW1, j * FCH + b * 64, it * 64, b_full + 8 * st);
                } else {
                    for (int b = 0; b < 3; b++) tma_load_2d(dst + b * 8192, &tmWqkv, b * 512 + j * 64, (it - 8) * 64, b_full + 8 * st);
                }
            }
        }
    } else {
        reg_alloc<232>();
        if (tid < 64) ((uint4*)sGw)[tid] = __ldg((const uint4*)gate_w + tid);
        else if (tid < 64 + 88) {
            const int c = j * FCH + (tid - 64) * 2;
            sBias[tid - 64] = c < F_ ? __ldg((const uint32_t*)(b1 + c)) : 0u;
        }
        bar_sync(3, 256);
        const int t128 = tid & 127, w4 = warp & 3, q = lane & 3;
        float accF[88], accQ[96];
        float gs = 0.f;
        const int grow = wg * 64 + (t128 >> 1), ghalf = t128 & 1;
#pragma unroll
        for (int kc = 0; kc < 8; kc++) {
            const int st = kc & 3;
            mbar_wait(x_full + 8 * kc, 0);
            mbar_wait(b_full + 8 * st, (kc >> 2) & 1);
            TS(1, tid == 0 && kc == 0); TS(2, tid == 0 && kc == 4);
            wgmma_fence();
#pragma unroll
            for (int k16 = 0; k16 < 4; k16++) {
                const uint64_t db = make_desc(sB + st * K1_BSTAGE + k16 * 2048, 8192, 1024);
                const uint64_t da = make_desc(sX + kc * 16384 + wg * 8192 + k16 * 32, 16, 1024);
                wgmma_n176<1>(accF, da, db, (kc | k16) != 0);
            }
            wgmma_commit();
#pragma unroll
            for (int c = 0; c < 4; c++) {
                const int cc = ghalf * 4 + c;
                const uint4 xv = *(const uint4*)(sgen + kc * 16384 + grow * 128 + ((cc ^ (grow & 7)) << 4));
                const uint4 gv = *(const uint4*)(sGw + kc * 128 + cc * 16);
                gs = fmaf(bf_lo(xv.x), bf_lo(gv.x), gs); gs = fmaf(bf_hi(xv.x), bf_hi(gv.x), gs);
                gs = fmaf(bf_lo(xv.y), bf_lo(gv.y), gs); gs = fmaf(bf_hi(xv.y), bf_hi(gv.y), gs);
                gs = fmaf(bf_lo(xv.z), bf_lo(gv.z), gs); gs = fmaf(bf_hi(xv.z), bf_hi(gv.z), gs);
                gs = fmaf(bf_lo(xv.w), bf_lo(gv.w), gs); gs = fmaf(bf_hi(xv.w), bf_hi(gv.w), gs);
            }
            if (kc > 0) { wgmma_wait<1>(); if (lane == 0) mbar_arrive(b_empty + 8 * ((kc - 1) & 3)); }
        }
        gs += __shfl_xor_sync(0xffffffffu, gs, 1);
        {
            const float g = 1.f / (1.f + __expf(-gs));
            if (ghalf == 0) {
                sGate[grow] = g;
                if (j == 0) g_gate[rb * 128 + grow] = g;
            }
        }
        wgmma_wait<0>();
        if (lane == 0) mbar_arrive(b_empty + 8 * 3);
        bar_sync(1 + wg, 128);
        TS(3, tid == 0);
        const int n0 = j * FCH;
        const int rl = wg * 64 + w4 * 16 + (lane >> 2);
        const float om0 = 1.f - sGate[rl], om1 = 1.f - sGate[rl + 8];
        bf16* frow0 = g_a2 + (size_t)(rb * 128 + rl) * KA2 + D_ + n0;
        bf16* frow1 = frow0 + 8 * KA2;
#pragma unroll
        for (int kc = 0; kc < 8; kc++) {
            const int st = kc & 3;
            mbar_wait(b_full + 8 * st, ((kc + 8) >> 2) & 1);
            wgmma_fence();
#pragma unroll
            for (int k16 = 0; k16 < 4; k16++) {
                const uint64_t db = make_desc(sB + st * K1_BSTAGE + k16 * 2048, 8192, 1024);
                const uint64_t da = make_desc(sX + kc * 16384 + wg * 8192 + k16 * 32, 16, 1024);
                wgmma_n192<1>(accQ, da, db, (kc | k16) != 0);
            }
            wgmma_commit();
            if (kc < 6) {
                const int u = kc;
                uint32_t w0[4], w1[4];
#pragma unroll
                for (int i = 0; i < 4; i++) {
                    const int t = u * 4 + i;
                    if (t < 22) {
                        const uint32_t bv = sBias[t * 4 + q];
                        const float bb0 = bf_lo(bv), bb1 = bf_hi(bv);
                        w0[i] = pack_bf16(mish_f(accF[t * 4 + 0] + bb0) * om0, mish_f(accF[t * 4 + 1] + bb1) * om0);
                        w1[i] = pack_bf16(mish_f(accF[t * 4 + 2] + bb0) * om1, mish_f(accF[t * 4 + 3] + bb1) * om1);
                    } else { w0[i] = 0; w1[i] = 0; }
                }
                quad_transpose(w0, q);
                quad_transpose(w1, q);
                const int c = (u * 4 + q) * 8;
                if (c < FCH && n0 + c < F_) {
                    *(uint4*)(frow0 + c) = make_uint4(w0[0], w0[1], w0[2], w0[3]);
                    *(uint4*)(frow1 + c) = make_uint4(w1[0], w1[1], w1[2], w1[3]);
                }
            }
            if (kc > 0) { wgmma_wait<1>(); if (lane == 0) mbar_arrive(b_empty + 8 * ((kc - 1) & 3)); }
        }
        wgmma_wait<0>();
        TS(4, tid == 0);
        {
            bf16* orow0 = g_qkv + ((size_t)j * S_ + rb * 128 + rl) * 192;
            bf16* orow1 = orow0 + 8 * 192;
#pragma unroll
            for (int u = 0; u < 6; u++) {
                uint32_t w0[4], w1[4];
#pragma unroll
                for (int i = 0; i < 4; i++) {
                    const int t = u * 4 + i;
                    w0[i] = pack_bf16(accQ[t * 4 + 0], accQ[t * 4 + 1]);
                    w1[i] = pack_bf16(accQ[t * 4 + 2], accQ[t * 4 + 3]);
                }
                quad_transpose(w0, q);
                quad_transpose(w1, q);
                const int c = (u * 4 + q) * 8;
                *(uint4*)(orow0 + c) = make_uint4(w0[0], w0[1], w0[2], w0[3]);
                *(uint4*)(orow1 + c) = make_uint4(w1[0], w1[1], w1[2], w1[3]);
            }
        }
        TS(5, tid == 0);
    }
}

__device__ __forceinline__ void ldsm_x4(uint32_t (&r)[4], uint32_t addr) {
    asm("ldmatrix.sync.aligned.m8n8.x4.shared.b16 {%0,%1,%2,%3}, [%4];"
                 : "=r"(r[0]), "=r"(r[1]), "=r"(r[2]), "=r"(r[3]) : "r"(addr));
}
__device__ __forceinline__ void ldsm_x4_t(uint32_t (&r)[4], uint32_t addr) {
    asm("ldmatrix.sync.aligned.m8n8.x4.trans.shared.b16 {%0,%1,%2,%3}, [%4];"
                 : "=r"(r[0]), "=r"(r[1]), "=r"(r[2]), "=r"(r[3]) : "r"(addr));
}
__device__ __forceinline__ void mma16816(float (&d)[4], const uint32_t (&a)[4], uint32_t b0, uint32_t b1) {
    asm("mma.sync.aligned.m16n8k16.row.col.f32.bf16.bf16.f32 {%0,%1,%2,%3}, {%4,%5,%6,%7}, {%8,%9}, {%0,%1,%2,%3};"
                 : "+f"(d[0]), "+f"(d[1]), "+f"(d[2]), "+f"(d[3])
                 : "r"(a[0]), "r"(a[1]), "r"(a[2]), "r"(a[3]), "r"(b0), "r"(b1));
}
__device__ __forceinline__ void mma16816_z(float (&d)[4], const uint32_t (&a)[4], uint32_t b0, uint32_t b1) {
    asm("mma.sync.aligned.m16n8k16.row.col.f32.bf16.bf16.f32 {%0,%1,%2,%3}, {%4,%5,%6,%7}, {%8,%9}, {%10,%10,%10,%10};"
                 : "=f"(d[0]), "=f"(d[1]), "=f"(d[2]), "=f"(d[3])
                 : "r"(a[0]), "r"(a[1]), "r"(a[2]), "r"(a[3]), "r"(b0), "r"(b1), "f"(0.f));
}

constexpr int KV_PITCH = 128;

template <int NB, bool MASK_FIRST, bool MASK_LAST, bool HEAD>
__device__ __forceinline__ void attn_chunk(const uint32_t (&qa)[4], uint32_t ka, uint32_t va, int kbs, int kb0, int r0, int c0,
                                           float& m0, float& m1, float& l0, float& l1, float (&o)[2][4])
{
    const float C = 0.25f * 1.4426950408889634f;
    float s[NB][2][4];
#pragma unroll
    for (int b = 0; b < NB; b++) {
        uint32_t kf[4];
        ldsm_x4(kf, ka + (kbs + b) * 16 * KV_PITCH);
        mma16816_z(s[b][0], qa, kf[0], kf[1]);
        mma16816_z(s[b][1], qa, kf[2], kf[3]);
    }
#pragma unroll
    for (int t = 0; t < 2; t++)
#pragma unroll
        for (int e = 0; e < 4; e++) {
            const int r = r0 + (e >> 1) * 8, c = t * 8 + c0 + (e & 1);
            if (MASK_FIRST && c <= r) s[0][t][e] = -1e30f;
            if (MASK_LAST && c > r) s[NB - 1][t][e] = -1e30f;
        }
    if (HEAD) {
#pragma unroll
        for (int b = 0; b < NB; b++)
            if (kbs + b < kb0) {
#pragma unroll
                for (int t = 0; t < 2; t++)
#pragma unroll
                    for (int e = 0; e < 4; e++) s[b][t][e] = -1e30f;
            }
    }
    float n0 = m0, n1 = m1;
#pragma unroll
    for (int b = 0; b < NB; b++) {
        n0 = fmaxf(n0, fmaxf(fmaxf(s[b][0][0], s[b][0][1]), fmaxf(s[b][1][0], s[b][1][1])));
        n1 = fmaxf(n1, fmaxf(fmaxf(s[b][0][2], s[b][0][3]), fmaxf(s[b][1][2], s[b][1][3])));
    }
    n0 = fmaxf(n0, __shfl_xor_sync(0xffffffffu, n0, 1)); n0 = fmaxf(n0, __shfl_xor_sync(0xffffffffu, n0, 2));
    n1 = fmaxf(n1, __shfl_xor_sync(0xffffffffu, n1, 1)); n1 = fmaxf(n1, __shfl_xor_sync(0xffffffffu, n1, 2));
    const float mc0 = n0 * C, mc1 = n1 * C;
    if (!MASK_LAST) {
        const float a0 = ex2(fmaf(m0, C, -mc0)), a1 = ex2(fmaf(m1, C, -mc1));
        l0 *= a0; l1 *= a1;
        o[0][0] *= a0; o[0][1] *= a0; o[1][0] *= a0; o[1][1] *= a0;
        o[0][2] *= a1; o[0][3] *= a1; o[1][2] *= a1; o[1][3] *= a1;
    }
    m0 = n0; m1 = n1;
#pragma unroll
    for (int b = 0; b < NB; b++) {
        uint32_t pa[4];
#pragma unroll
        for (int t = 0; t < 2; t++) {
            const float p0 = ex2(fmaf(s[b][t][0], C, -mc0)), p1 = ex2(fmaf(s[b][t][1], C, -mc0));
            const float p2 = ex2(fmaf(s[b][t][2], C, -mc1)), p3 = ex2(fmaf(s[b][t][3], C, -mc1));
            l0 += p0 + p1; l1 += p2 + p3;
            pa[2 * t] = pack_bf16(p0, p1); pa[2 * t + 1] = pack_bf16(p2, p3);
        }
        uint32_t vf[4];
        ldsm_x4_t(vf, va + (kbs + b) * 16 * KV_PITCH);
        mma16816(o[0], pa, vf[0], vf[1]);
        mma16816(o[1], pa, vf[2], vf[3]);
    }
}

template <bool HEAD>
__device__ __forceinline__ void attn_task(const uint32_t (&qa)[4], uint32_t ka, uint32_t va, int kb0, int lane,
                                          bf16* __restrict__ out  , float g0, float g1)
{
    const int r0 = lane >> 2, c0 = (lane & 3) * 2;
    float m0 = -1e30f, m1 = -1e30f, l0 = 0.f, l1 = 0.f;
    float o[2][4] = {{0.f, 0.f, 0.f, 0.f}, {0.f, 0.f, 0.f, 0.f}};
    attn_chunk<5, false, true, HEAD>(qa, ka, va, 12, kb0, r0, c0, m0, m1, l0, l1, o);
    if (!HEAD || kb0 < 12) attn_chunk<4, false, false, HEAD>(qa, ka, va, 8, kb0, r0, c0, m0, m1, l0, l1, o);
    if (!HEAD || kb0 < 8)  attn_chunk<4, false, false, HEAD>(qa, ka, va, 4, kb0, r0, c0, m0, m1, l0, l1, o);
    if (!HEAD || kb0 < 4)  attn_chunk<4, true, false, HEAD>(qa, ka, va, 0, kb0, r0, c0, m0, m1, l0, l1, o);
    l0 += __shfl_xor_sync(0xffffffffu, l0, 1); l0 += __shfl_xor_sync(0xffffffffu, l0, 2);
    l1 += __shfl_xor_sync(0xffffffffu, l1, 1); l1 += __shfl_xor_sync(0xffffffffu, l1, 2);
    const float f0 = g0 / l0, f1 = g1 / l1;
#pragma unroll
    for (int t = 0; t < 2; t++) {
        *(uint32_t*)(out + (size_t)r0 * KA2 + t * 8 + c0) = pack_bf16(o[t][0] * f0, o[t][1] * f0);
        *(uint32_t*)(out + (size_t)(r0 + 8) * KA2 + t * 8 + c0) = pack_bf16(o[t][2] * f1, o[t][3] * f1);
    }
}

constexpr int K2_SMEM = 2 * 384 * KV_PITCH + 1024 + 64;

__global__ void __launch_bounds__(512, 1) k2_kernel(const __grid_constant__ CUtensorMap tmQKV)
{
    extern __shared__ uint8_t smem_raw[];
    const uint32_t sbase = (smem_u32(smem_raw) + 1023u) & ~1023u;
    uint8_t* sgen = smem_raw + (sbase - smem_u32(smem_raw));
    const uint32_t sK = sbase, sV = sK + 384 * KV_PITCH, kv_full = sbase + 2 * 384 * KV_PITCH;
    const int rb = blockIdx.x >> 3, j = blockIdx.x & 7;
    const int tid = threadIdx.x, warp = tid >> 5, lane = tid & 31;
    TS(6, tid == 0);
    if (tid == 0) {
        mbar_init(kv_full, 1);
        fence_barrier_init();
        const int nblk = rb >= 2 ? 3 : rb + 1;
        mbar_expect_tx(kv_full, nblk * 2 * 16384);
        for (int i = 0; i < nblk; i++) {
            const int row = j * S_ + (rb - i) * 128;
            tma_load_2d(sK + (2 - i) * 16384, &tmQKV, 64, row, kv_full);
            tma_load_2d(sV + (2 - i) * 16384, &tmQKV, 128, row, kv_full);
        }
    }
    if (rb < 2) {
        for (int i = tid; i < (2 - rb) * 1024; i += 512) {
            *(uint4*)(sgen + i * 16) = make_uint4(0, 0, 0, 0);
            *(uint4*)(sgen + 384 * KV_PITCH + i * 16) = make_uint4(0, 0, 0, 0);
        }
    }
    const int qt = warp & 7, h0 = (warp >> 3) * 2;
    const int q0g = rb * 128 + qt * 16;
    const int r0 = lane >> 2, c0 = (lane & 3) * 2;
    const bf16* qsrc = g_qkv + ((size_t)j * S_ + q0g) * 192 + h0 * 16;
    uint32_t qa[4], qn[4];
    qa[0] = *(const uint32_t*)(qsrc + (size_t)r0 * 192 + c0);
    qa[1] = *(const uint32_t*)(qsrc + (size_t)(r0 + 8) * 192 + c0);
    qa[2] = *(const uint32_t*)(qsrc + (size_t)r0 * 192 + c0 + 8);
    qa[3] = *(const uint32_t*)(qsrc + (size_t)(r0 + 8) * 192 + c0 + 8);
    qn[0] = *(const uint32_t*)(qsrc + (size_t)r0 * 192 + 16 + c0);
    qn[1] = *(const uint32_t*)(qsrc + (size_t)(r0 + 8) * 192 + 16 + c0);
    qn[2] = *(const uint32_t*)(qsrc + (size_t)r0 * 192 + 16 + c0 + 8);
    qn[3] = *(const uint32_t*)(qsrc + (size_t)(r0 + 8) * 192 + 16 + c0 + 8);
    const float g0 = g_gate[q0g + r0], g1 = g_gate[q0g + r0 + 8];
    const int kb0 = q0g < 256 ? (256 - q0g) >> 4 : 0;
    __syncthreads();
    mbar_wait(kv_full, 0);
    uint32_t sKd = sK, sVd = sV;
    asm volatile("" : "+r"(sKd), "+r"(sVd) :: "memory");
    TS(7, tid == 0);
    const int krow = qt * 16 + (lane & 7) + ((lane >> 4) << 3);
    const int vrow = qt * 16 + (lane & 15);
#pragma unroll 1
    for (int hh = 0; hh < 2; hh++) {
        const int hl = h0 + hh;
        const uint32_t ka = sKd + krow * KV_PITCH + (((2 * hl + ((lane >> 3) & 1)) ^ (lane & 7)) << 4);
        const uint32_t va = sVd + vrow * KV_PITCH + (((2 * hl + (lane >> 4)) ^ (lane & 7)) << 4);
        if (rb < 2) attn_task<true>(qa, ka, va, kb0, lane, g_a2 + (size_t)q0g * KA2 + (j * 4 + hl) * 16, g0, g1);
        else        attn_task<false>(qa, ka, va, kb0, lane, g_a2 + (size_t)q0g * KA2 + (j * 4 + hl) * 16, g0, g1);
        TS(8 + hh, tid == 0);
        qa[0] = qn[0]; qa[1] = qn[1]; qa[2] = qn[2]; qa[3] = qn[3];
    }
}

constexpr int K3_STAGES = 8;
constexpr int K3_STAGE = 16384 + 8192;
constexpr int K3_SMEM = K3_STAGES * K3_STAGE + 1024 + 1024;
constexpr int K3_KSTEPS = 30;

__global__ void __launch_bounds__(384, 1)
k3_kernel(const __grid_constant__ CUtensorMap tmA2, const __grid_constant__ CUtensorMap tmWo,
          const __grid_constant__ CUtensorMap tmW2, bf16* __restrict__ out)
{
    extern __shared__ uint8_t smem_raw[];
    const uint32_t sbase = (smem_u32(smem_raw) + 1023u) & ~1023u;
    const uint32_t sBar = sbase + K3_STAGES * K3_STAGE;
    const uint32_t full = sBar, empty = sBar + 64;
    const int rb = blockIdx.x >> 3, nb = blockIdx.x & 7;
    const int tid = threadIdx.x, wg = tid >> 7, warp = tid >> 5, lane = tid & 31;
    TS(10, tid == 0);
    if (tid == 0) {
        for (int i = 0; i < K3_STAGES; i++) { mbar_init(full + 8 * i, 1); mbar_init(empty + 8 * i, 8); }
        fence_barrier_init();
    }
    __syncthreads();
    if (wg == 2) {
        reg_dealloc<40>();
        if (tid == 256) {
            for (int ks = 0; ks < K3_KSTEPS; ks++) {
                const int st = ks % K3_STAGES;
                if (ks >= K3_STAGES) mbar_wait(empty + 8 * st, ((ks / K3_STAGES) - 1) & 1);
                mbar_expect_tx(full + 8 * st, K3_STAGE);
                const uint32_t dst = sbase + st * K3_STAGE;
                tma_load_2d(dst, &tmA2, ks * 64, rb * 128, full + 8 * st);
                if (ks < 8) tma_load_2d(dst + 16384, &tmWo, nb * 64, ks * 64, full + 8 * st);
                else        tma_load_2d(dst + 16384, &tmW2, nb * 64, (ks - 8) * 64, full + 8 * st);
            }
        }
    } else {
        reg_alloc<232>();
        float acc[32];
        for (int ks = 0; ks < K3_KSTEPS; ks++) {
            const int st = ks % K3_STAGES;
            mbar_wait(full + 8 * st, (ks / K3_STAGES) & 1);
            TS(11, tid == 0 && ks == 0); TS(12, tid == 0 && ks == 8); TS(13, tid == 0 && ks == 16);
            wgmma_fence();
#pragma unroll
            for (int k16 = 0; k16 < 4; k16++) {
                const uint64_t da = make_desc(sbase + st * K3_STAGE + wg * 8192 + k16 * 32, 16, 1024);
                const uint64_t db = make_desc(sbase + st * K3_STAGE + 16384 + k16 * 2048, 8192, 1024);
                wgmma_n64<1>(acc, da, db, (ks | k16) != 0);
            }
            wgmma_commit();
            if (ks > 0) { wgmma_wait<1>(); if (lane == 0) mbar_arrive(empty + 8 * ((ks - 1) % K3_STAGES)); }
        }
        wgmma_wait<0>();
        TS(14, tid == 0);
        const int q = lane & 3;
        const int r = rb * 128 + wg * 64 + (warp & 3) * 16 + (lane >> 2);
        bf16* orow0 = out + (size_t)r * D_ + nb * 64;
        bf16* orow1 = orow0 + 8 * D_;
#pragma unroll
        for (int u = 0; u < 2; u++) {
            uint32_t w0[4], w1[4];
#pragma unroll
            for (int i = 0; i < 4; i++) {
                const int t = u * 4 + i;
                w0[i] = pack_bf16(acc[t * 4 + 0], acc[t * 4 + 1]);
                w1[i] = pack_bf16(acc[t * 4 + 2], acc[t * 4 + 3]);
            }
            quad_transpose(w0, q);
            quad_transpose(w1, q);
            const int c = (u * 4 + q) * 8;
            *(uint4*)(orow0 + c) = make_uint4(w0[0], w0[1], w0[2], w0[3]);
            *(uint4*)(orow1 + c) = make_uint4(w1[0], w1[1], w1[2], w1[3]);
        }
        TS(15, tid == 0);
    }
}

typedef CUresult (*PFN_encodeTiled)(CUtensorMap*, CUtensorMapDataType, cuuint32_t, void*, const cuuint64_t*,
                                    const cuuint64_t*, const cuuint32_t*, const cuuint32_t*, CUtensorMapInterleave,
                                    CUtensorMapSwizzle, CUtensorMapL2promotion, CUtensorMapFloatOOBfill);

static void make_map(PFN_encodeTiled enc, CUtensorMap* m, const void* ptr, uint64_t cols, uint64_t rows,
                     uint32_t box_cols, uint32_t box_rows)
{
    cuuint64_t dims[2] = {cols, rows};
    cuuint64_t strides[1] = {cols * 2};
    cuuint32_t box[2] = {box_cols, box_rows};
    cuuint32_t es[2] = {1, 1};
    enc(m, CU_TENSOR_MAP_DATA_TYPE_BFLOAT16, 2, const_cast<void*>(ptr), dims, strides, box, es,
        CU_TENSOR_MAP_INTERLEAVE_NONE, CU_TENSOR_MAP_SWIZZLE_128B, CU_TENSOR_MAP_L2_PROMOTION_L2_128B,
        CU_TENSOR_MAP_FLOAT_OOB_FILL_NONE);
}

extern "C" void kernel_launch(void* const* d_in, const int* in_sizes, int n_in, void* d_out, int out_size)
{
    const bf16* x    = (const bf16*)d_in[0];
    const bf16* wqkv = (const bf16*)d_in[1];
    const bf16* wo   = (const bf16*)d_in[2];
    const bf16* w1   = (const bf16*)d_in[4];
    const bf16* b1   = (const bf16*)d_in[5];
    const bf16* w2   = (const bf16*)d_in[6];
    const bf16* gw   = (const bf16*)d_in[7];

    static PFN_encodeTiled enc = nullptr;
    if (!enc) {
        void* fn = nullptr;
        cudaDriverEntryPointQueryResult qr;
        cudaGetDriverEntryPoint("cuTensorMapEncodeTiled", &fn, cudaEnableDefault, &qr);
        enc = (PFN_encodeTiled)fn;
        cudaFuncSetAttribute(k1_kernel, cudaFuncAttributeMaxDynamicSharedMemorySize, K1_SMEM);
        cudaFuncSetAttribute(k2_kernel, cudaFuncAttributeMaxDynamicSharedMemorySize, K2_SMEM);
        cudaFuncSetAttribute(k3_kernel, cudaFuncAttributeMaxDynamicSharedMemorySize, K3_SMEM);
    }
    void* a2p = nullptr;
    cudaGetSymbolAddress(&a2p, g_a2);
    void* qkvp = nullptr;
    cudaGetSymbolAddress(&qkvp, g_qkv);
    CUtensorMap tmX, tmWqkv, tmW1, tmA2, tmWo, tmW2, tmQKV;
    make_map(enc, &tmQKV, qkvp, 192, 8 * S_, 64, 128);
    make_map(enc, &tmX, x, D_, S_, 64, 128);
    make_map(enc, &tmWqkv, wqkv, 3 * D_, D_, 64, 64);
    make_map(enc, &tmW1, w1, F_, D_, 64, 64);
    make_map(enc, &tmA2, a2p, KA2, S_, 64, 128);
    make_map(enc, &tmWo, wo, D_, D_, 64, 64);
    make_map(enc, &tmW2, w2, D_, F_, 64, 64);

    cudaStream_t st = cudaStreamPerThread;
    k1_kernel<<<128, 384, K1_SMEM, st>>>(tmX, tmWqkv, tmW1, b1, gw, w1, wqkv, w2, wo);
    k2_kernel<<<128, 512, K2_SMEM, st>>>(tmQKV);
    k3_kernel<<<128, 384, K3_SMEM, st>>>(tmA2, tmWo, tmW2, (bf16*)d_out);
}
```

```cpp
#include <cuda_runtime.h>
#include <cuda_bf16.h>
#include <cuda.h>
#include <stdint.h>

typedef __nv_bfloat16 bf16;

constexpr int S_ = 2048, D_ = 512, F_ = 1376;
constexpr int KA2 = D_ + F_;
constexpr int FCH = 176;

__device__ bf16  g_qkv[8 * S_ * 192];
__device__ bf16  g_a2[S_ * KA2];
__device__ float g_gate[S_];

#define TS(k, cond) do { } while (0)

__device__ __forceinline__ uint32_t smem_u32(const void* p) { return (uint32_t)__cvta_generic_to_shared(p); }
__device__ __forceinline__ void mbar_init(uint32_t bar, uint32_t count) {
    asm volatile("mbarrier.init.shared::cta.b64 [%0], %1;" :: "r"(bar), "r"(count) : "memory");
}
__device__ __forceinline__ void mbar_expect_tx(uint32_t bar, uint32_t bytes) {
    asm volatile("mbarrier.arrive.expect_tx.shared::cta.b64 _, [%0], %1;" :: "r"(bar), "r"(bytes) : "memory");
}
__device__ __forceinline__ void mbar_arrive(uint32_t bar) {
    asm volatile("mbarrier.arrive.shared::cta.b64 _, [%0];" :: "r"(bar) : "memory");
}
__device__ __forceinline__ bool mbar_try_wait(uint32_t bar, uint32_t parity) {
    uint32_t ok;
    asm volatile("{\n.reg .pred p;\nmbarrier.try_wait.parity.shared::cta.b64 p, [%1], %2;\nselp.u32 %0, 1, 0, p;\n}"
                 : "=r"(ok) : "r"(bar), "r"(parity) : "memory");
    return ok != 0;
}
__device__ __forceinline__ void mbar_wait(uint32_t bar, uint32_t parity) {
    for (uint32_t it = 0; it < (1u << 22); ++it) { if (mbar_try_wait(bar, parity)) break; }
}
__device__ __forceinline__ void tma_load_2d(uint32_t dst, const CUtensorMap* map, int c0, int c1, uint32_t bar) {
    asm volatile("cp.async.bulk.tensor.2d.shared::cluster.global.mbarrier::complete_tx::bytes [%0], [%1, {%3, %4}], [%2];"
                 :: "r"(dst), "l"(map), "r"(bar), "r"(c0), "r"(c1) : "memory");
}
__device__ __forceinline__ void l2_prefetch(const void* p, uint32_t bytes) {
    asm volatile("cp.async.bulk.prefetch.L2.global [%0], %1;" :: "l"(p), "r"(bytes) : "memory");
}
__device__ __forceinline__ void fence_barrier_init() { asm volatile("fence.mbarrier_init.release.cluster;" ::: "memory"); }
__device__ __forceinline__ void wgmma_fence()  { asm volatile("wgmma.fence.sync.aligned;" ::: "memory"); }
__device__ __forceinline__ void wgmma_commit() { asm volatile("wgmma.commit_group.sync.aligned;" ::: "memory"); }
template <int N> __device__ __forceinline__ void wgmma_wait() { asm volatile("wgmma.wait_group.sync.aligned %0;" :: "n"(N) : "memory"); }
template <int R> __device__ __forceinline__ void reg_alloc()   { asm volatile("setmaxnreg.inc.sync.aligned.u32 %0;" :: "n"(R)); }
template <int R> __device__ __forceinline__ void reg_dealloc() { asm volatile("setmaxnreg.dec.sync.aligned.u32 %0;" :: "n"(R)); }
__device__ __forceinline__ void bar_sync(int id, int n)   { asm volatile("bar.sync %0, %1;" :: "r"(id), "r"(n) : "memory"); }
__device__ __forceinline__ void bar_arrive(int id, int n) { asm volatile("bar.arrive %0, %1;" :: "r"(id), "r"(n) : "memory"); }

__device__ __forceinline__ uint64_t make_desc(uint32_t addr, uint32_t lbo, uint32_t sbo) {
    uint64_t d = (uint64_t)((addr & 0x3FFFF) >> 4);
    d |= (uint64_t)((lbo & 0x3FFFF) >> 4) << 16;
    d |= (uint64_t)((sbo & 0x3FFFF) >> 4) << 32;
    d |= (uint64_t)1 << 62;
    return d;
}

template <int TB>
__device__ __forceinline__ void wgmma_n64(float (&d)[32], uint64_t da, uint64_t db, int scale_d) {
    asm volatile("{\n.reg .pred p;\nsetp.ne.b32 p, %34, 0;\n"
        "wgmma.mma_async.sync.aligned.m64n64k16.f32.bf16.bf16 {%0, %1, %2, %3, %4, %5, %6, %7, %8, %9, %10, %11, %12, %13, %14, %15, %16, %17, %18, %19, %20, %21, %22, %23, %24, %25, %26, %27, %28, %29, %30, %31}, %32, %33, p, 1, 1, 0, %35;\n}\n"
        : "+f"(d[0]), "+f"(d[1]), "+f"(d[2]), "+f"(d[3]), "+f"(d[4]), "+f"(d[5]), "+f"(d[6]), "+f"(d[7]), "+f"(d[8]), "+f"(d[9]), "+f"(d[10]), "+f"(d[11]), "+f"(d[12]), "+f"(d[13]), "+f"(d[14]), "+f"(d[15]), "+f"(d[16]), "+f"(d[17]), "+f"(d[18]), "+f"(d[19]), "+f"(d[20]), "+f"(d[21]), "+f"(d[22]), "+f"(d[23]), "+f"(d[24]), "+f"(d[25]), "+f"(d[26]), "+f"(d[27]), "+f"(d[28]), "+f"(d[29]), "+f"(d[30]), "+f"(d[31])
        : "l"(da), "l"(db), "r"(scale_d), "n"(TB));
}

template <int TB>
__device__ __forceinline__ void wgmma_n128(float (&d)[64], uint64_t da, uint64_t db, int scale_d) {
    asm volatile("{\n.reg .pred p;\nsetp.ne.b32 p, %66, 0;\n"
        "wgmma.mma_async.sync.aligned.m64n128k16.f32.bf16.bf16 {%0, %1, %2, %3, %4, %5, %6, %7, %8, %9, %10, %11, %12, %13, %14, %15, %16, %17, %18, %19, %20, %21, %22, %23, %24, %25, %26, %27, %28, %29, %30, %31, %32, %33, %34, %35, %36, %37, %38, %39, %40, %41, %42, %43, %44, %45, %46, %47, %48, %49, %50, %51, %52, %53, %54, %55, %56, %57, %58, %59, %60, %61, %62, %63}, %64, %65, p, 1, 1, 0, %67;\n}\n"
        : "+f"(d[0]), "+f"(d[1]), "+f"(d[2]), "+f"(d[3]), "+f"(d[4]), "+f"(d[5]), "+f"(d[6]), "+f"(d[7]), "+f"(d[8]), "+f"(d[9]), "+f"(d[10]), "+f"(d[11]), "+f"(d[12]), "+f"(d[13]), "+f"(d[14]), "+f"(d[15]), "+f"(d[16]), "+f"(d[17]), "+f"(d[18]), "+f"(d[19]), "+f"(d[20]), "+f"(d[21]), "+f"(d[22]), "+f"(d[23]), "+f"(d[24]), "+f"(d[25]), "+f"(d[26]), "+f"(d[27]), "+f"(d[28]), "+f"(d[29]), "+f"(d[30]), "+f"(d[31]), "+f"(d[32]), "+f"(d[33]), "+f"(d[34]), "+f"(d[35]), "+f"(d[36]), "+f"(d[37]), "+f"(d[38]), "+f"(d[39]), "+f"(d[40]), "+f"(d[41]), "+f"(d[42]), "+f"(d[43]), "+f"(d[44]), "+f"(d[45]), "+f"(d[46]), "+f"(d[47]), "+f"(d[48]), "+f"(d[49]), "+f"(d[50]), "+f"(d[51]), "+f"(d[52]), "+f"(d[53]), "+f"(d[54]), "+f"(d[55]), "+f"(d[56]), "+f"(d[57]), "+f"(d[58]), "+f"(d[59]), "+f"(d[60]), "+f"(d[61]), "+f"(d[62]), "+f"(d[63])
        : "l"(da), "l"(db), "r"(scale_d), "n"(TB));
}

template <int TB>
__device__ __forceinline__ void wgmma_n176(float (&d)[88], uint64_t da, uint64_t db, int scale_d) {
    asm volatile("{\n.reg .pred p;\nsetp.ne.b32 p, %90, 0;\n"
        "wgmma.mma_async.sync.aligned.m64n176k16.f32.bf16.bf16 {%0, %1, %2, %3, %4, %5, %6, %7, %8, %9, %10, %11, %12, %13, %14, %15, %16, %17, %18, %19, %20, %21, %22, %23, %24, %25, %26, %27, %28, %29, %30, %31, %32, %33, %34, %35, %36, %37, %38, %39, %40, %41, %42, %43, %44, %45, %46, %47, %48, %49, %50, %51, %52, %53, %54, %55, %56, %57, %58, %59, %60, %61, %62, %63, %64, %65, %66, %67, %68, %69, %70, %71, %72, %73, %74, %75, %76, %77, %78, %79, %80, %81, %82, %83, %84, %85, %86, %87}, %88, %89, p, 1, 1, 0, %91;\n}\n"
        : "+f"(d[0]), "+f"(d[1]), "+f"(d[2]), "+f"(d[3]), "+f"(d[4]), "+f"(d[5]), "+f"(d[6]), "+f"(d[7]), "+f"(d[8]), "+f"(d[9]), "+f"(d[10]), "+f"(d[11]), "+f"(d[12]), "+f"(d[13]), "+f"(d[14]), "+f"(d[15]), "+f"(d[16]), "+f"(d[17]), "+f"(d[18]), "+f"(d[19]), "+f"(d[20]), "+f"(d[21]), "+f"(d[22]), "+f"(d[23]), "+f"(d[24]), "+f"(d[25]), "+f"(d[26]), "+f"(d[27]), "+f"(d[28]), "+f"(d[29]), "+f"(d[30]), "+f"(d[31]), "+f"(d[32]), "+f"(d[33]), "+f"(d[34]), "+f"(d[35]), "+f"(d[36]), "+f"(d[37]), "+f"(d[38]), "+f"(d[39]), "+f"(d[40]), "+f"(d[41]), "+f"(d[42]), "+f"(d[43]), "+f"(d[44]), "+f"(d[45]), "+f"(d[46]), "+f"(d[47]), "+f"(d[48]), "+f"(d[49]), "+f"(d[50]), "+f"(d[51]), "+f"(d[52]), "+f"(d[53]), "+f"(d[54]), "+f"(d[55]), "+f"(d[56]), "+f"(d[57]), "+f"(d[58]), "+f"(d[59]), "+f"(d[60]), "+f"(d[61]), "+f"(d[62]), "+f"(d[63]), "+f"(d[64]), "+f"(d[65]), "+f"(d[66]), "+f"(d[67]), "+f"(d[68]), "+f"(d[69]), "+f"(d[70]), "+f"(d[71]), "+f"(d[72]), "+f"(d[73]), "+f"(d[74]), "+f"(d[75]), "+f"(d[76]), "+f"(d[77]), "+f"(d[78]), "+f"(d[79]), "+f"(d[80]), "+f"(d[81]), "+f"(d[82]), "+f"(d[83]), "+f"(d[84]), "+f"(d[85]), "+f"(d[86]), "+f"(d[87])
        : "l"(da), "l"(db), "r"(scale_d), "n"(TB));
}

template <int TB>
__device__ __forceinline__ void wgmma_n192(float (&d)[96], uint64_t da, uint64_t db, int scale_d) {
    asm volatile("{\n.reg .pred p;\nsetp.ne.b32 p, %98, 0;\n"
        "wgmma.mma_async.sync.aligned.m64n192k16.f32.bf16.bf16 {%0, %1, %2, %3, %4, %5, %6, %7, %8, %9, %10, %11, %12, %13, %14, %15, %16, %17, %18, %19, %20, %21, %22, %23, %24, %25, %26, %27, %28, %29, %30, %31, %32, %33, %34, %35, %36, %37, %38, %39, %40, %41, %42, %43, %44, %45, %46, %47, %48, %49, %50, %51, %52, %53, %54, %55, %56, %57, %58, %59, %60, %61, %62, %63, %64, %65, %66, %67, %68, %69, %70, %71, %72, %73, %74, %75, %76, %77, %78, %79, %80, %81, %82, %83, %84, %85, %86, %87, %88, %89, %90, %91, %92, %93, %94, %95}, %96, %97, p, 1, 1, 0, %99;\n}\n"
        : "+f"(d[0]), "+f"(d[1]), "+f"(d[2]), "+f"(d[3]), "+f"(d[4]), "+f"(d[5]), "+f"(d[6]), "+f"(d[7]), "+f"(d[8]), "+f"(d[9]), "+f"(d[10]), "+f"(d[11]), "+f"(d[12]), "+f"(d[13]), "+f"(d[14]), "+f"(d[15]), "+f"(d[16]), "+f"(d[17]), "+f"(d[18]), "+f"(d[19]), "+f"(d[20]), "+f"(d[21]), "+f"(d[22]), "+f"(d[23]), "+f"(d[24]), "+f"(d[25]), "+f"(d[26]), "+f"(d[27]), "+f"(d[28]), "+f"(d[29]), "+f"(d[30]), "+f"(d[31]), "+f"(d[32]), "+f"(d[33]), "+f"(d[34]), "+f"(d[35]), "+f"(d[36]), "+f"(d[37]), "+f"(d[38]), "+f"(d[39]), "+f"(d[40]), "+f"(d[41]), "+f"(d[42]), "+f"(d[43]), "+f"(d[44]), "+f"(d[45]), "+f"(d[46]), "+f"(d[47]), "+f"(d[48]), "+f"(d[49]), "+f"(d[50]), "+f"(d[51]), "+f"(d[52]), "+f"(d[53]), "+f"(d[54]), "+f"(d[55]), "+f"(d[56]), "+f"(d[57]), "+f"(d[58]), "+f"(d[59]), "+f"(d[60]), "+f"(d[61]), "+f"(d[62]), "+f"(d[63]), "+f"(d[64]), "+f"(d[65]), "+f"(d[66]), "+f"(d[67]), "+f"(d[68]), "+f"(d[69]), "+f"(d[70]), "+f"(d[71]), "+f"(d[72]), "+f"(d[73]), "+f"(d[74]), "+f"(d[75]), "+f"(d[76]), "+f"(d[77]), "+f"(d[78]), "+f"(d[79]), "+f"(d[80]), "+f"(d[81]), "+f"(d[82]), "+f"(d[83]), "+f"(d[84]), "+f"(d[85]), "+f"(d[86]), "+f"(d[87]), "+f"(d[88]), "+f"(d[89]), "+f"(d[90]), "+f"(d[91]), "+f"(d[92]), "+f"(d[93]), "+f"(d[94]), "+f"(d[95])
        : "l"(da), "l"(db), "r"(scale_d), "n"(TB));
}

__device__ __forceinline__ uint32_t pack_bf16(float lo, float hi) {
    uint32_t r;
    asm("cvt.rn.bf16x2.f32 %0, %1, %2;" : "=r"(r) : "f"(hi), "f"(lo));
    return r;
}
__device__ __forceinline__ float bf_lo(uint32_t v) { return __uint_as_float(v << 16); }
__device__ __forceinline__ float bf_hi(uint32_t v) { return __uint_as_float(v & 0xffff0000u); }

__device__ __forceinline__ void quad_transpose(uint32_t (&w)[4], int q) {
    const bool o1 = q & 1, o2 = q & 2;
    {
        uint32_t s0 = o1 ? w[0] : w[1], s1 = o1 ? w[2] : w[3];
        s0 = __shfl_xor_sync(0xffffffffu, s0, 1); s1 = __shfl_xor_sync(0xffffffffu, s1, 1);
        if (o1) { w[0] = s0; w[2] = s1; } else { w[1] = s0; w[3] = s1; }
    }
    {
        uint32_t s0 = o2 ? w[0] : w[2], s1 = o2 ? w[1] : w[3];
        s0 = __shfl_xor_sync(0xffffffffu, s0, 2); s1 = __shfl_xor_sync(0xffffffffu, s1, 2);
        if (o2) { w[0] = s0; w[1] = s1; } else { w[2] = s0; w[3] = s1; }
    }
}

__device__ __forceinline__ float ex2(float x) { float y; asm("ex2.approx.ftz.f32 %0, %1;" : "=f"(y) : "f"(x)); return y; }
__device__ __forceinline__ float rcp(float x) { float y; asm("rcp.approx.ftz.f32 %0, %1;" : "=f"(y) : "f"(x)); return y; }

__device__ __forceinline__ float ex2v(float x) { float y; asm volatile("ex2.approx.ftz.f32 %0, %1;" : "=f"(y) : "f"(x)); return y; }
__device__ __forceinline__ float rcpv(float x) { float y; asm volatile("rcp.approx.ftz.f32 %0, %1;" : "=f"(y) : "f"(x)); return y; }
__device__ __forceinline__ float mish_f(float h) {
    const float w = ex2v(-1.4426950408889634f * fabsf(h));
    const float t = w * w;
    const bool pos = h > 0.f;
    const float num = fmaf(2.f, w, pos ? 1.f : t);
    const float den = num + (pos ? t + t : 2.f);
    return h * num * rcpv(den);
}

constexpr int K1_STAGES = 4;
constexpr int K1_XBYTES = 128 * 512 * 2;
constexpr int K1_BSTAGE = 3 * 8192;
constexpr int K1_SMEM   = K1_XBYTES + K1_STAGES * K1_BSTAGE + 2048   + 1024  ;

__global__ void __launch_bounds__(384, 1)
k1_kernel(const __grid_constant__ CUtensorMap tmX, const __grid_constant__ CUtensorMap tmWqkv,
          const __grid_constant__ CUtensorMap tmW1, const bf16* __restrict__ b1,
          const bf16* __restrict__ gate_w, const bf16* __restrict__ w1p, const bf16* __restrict__ wqkvp,
          const bf16* __restrict__ w2p, const bf16* __restrict__ wop)
{

    extern __shared__ uint8_t smem_raw[];
    const uint32_t sbase = (smem_u32(smem_raw) + 1023u) & ~1023u;
    uint8_t* sgen = smem_raw + (sbase - smem_u32(smem_raw));
    const uint32_t sX = sbase;
    const uint32_t sB = sbase + K1_XBYTES;
    const uint32_t sBar = sB + K1_STAGES * K1_BSTAGE;
    const uint32_t x_full = sBar;
    const uint32_t b_full = sBar + 64;
    const uint32_t b_empty = sBar + 96;
    float* sGate = (float*)(sgen + K1_XBYTES + K1_STAGES * K1_BSTAGE + 128);
    uint8_t* sGw = sgen + K1_XBYTES + K1_STAGES * K1_BSTAGE + 640;
    uint32_t* sBias = (uint32_t*)(sgen + K1_XBYTES + K1_STAGES * K1_BSTAGE + 1664);

    const int rb = blockIdx.x >> 3, j = blockIdx.x & 7;
    const int tid = threadIdx.x, wg = tid >> 7, warp = tid >> 5, lane = tid & 31;
    TS(0, tid == 0);

    if (tid == 0) {
        for (int i = 0; i < 8; i++) mbar_init(x_full + 8 * i, 1);
        for (int i = 0; i < K1_STAGES; i++) { mbar_init(b_full + 8 * i, 1); mbar_init(b_empty + 8 * i, 8); }
        fence_barrier_init();
    }
    __syncthreads();

    if (wg == 2) {
        reg_dealloc<40>();
        if (tid == 288) {
            const int b = blockIdx.x;
            mbar_wait(b_full + 8, 0);
            l2_prefetch((const uint8_t*)wqkvp + b * 12288, 12288);
            l2_prefetch((const uint8_t*)w2p + b * 11008, 11008);
            l2_prefetch((const uint8_t*)wop + b * 4096, 4096);
        }
        if (tid == 256) {
            for (int it = 0; it < 16; it++) {
                if (it < 8) {
                    mbar_expect_tx(x_full + 8 * it, 16384);
                    tma_load_2d(sX + it * 16384, &tmX, it * 64, rb * 128, x_full + 8 * it);
                }
                const int st = it & 3;
                if (it >= K1_STAGES) mbar_wait(b_empty + 8 * st, ((it >> 2) - 1) & 1);
                mbar_expect_tx(b_full + 8 * st, K1_BSTAGE);
                const uint32_t dst = sB + st * K1_BSTAGE;
                if (it < 8) {
                    for (int b = 0; b < 3; b++) tma_load_2d(dst + b * 8192, &tmW1, j * FCH + b * 64, it * 64, b_full + 8 * st);
                } else {
                    for (int b = 0; b < 3; b++) tma_load_2d(dst + b * 8192, &tmWqkv, b * 512 + j * 64, (it - 8) * 64, b_full + 8 * st);
                }
            }
        }
    } else {
        reg_alloc<232>();
        if (tid < 64) ((uint4*)sGw)[tid] = __ldg((const uint4*)gate_w + tid);
        else if (tid < 64 + 88) {
            const int c = j * FCH + (tid - 64) * 2;
            sBias[tid - 64] = c < F_ ? __ldg((const uint32_t*)(b1 + c)) : 0u;
        }
        bar_sync(3, 256);
        const int t128 = tid & 127, w4 = warp & 3, q = lane & 3;
        float accF[88], accQ[96];
        float gs = 0.f;
        const int grow = wg * 64 + (t128 >> 1), ghalf = t128 & 1;
#pragma unroll
        for (int kc = 0; kc < 8; kc++) {
            const int st = kc & 3;
            mbar_wait(x_full + 8 * kc, 0);
            mbar_wait(b_full + 8 * st, (kc >> 2) & 1);
            TS(1, tid == 0 && kc == 0); TS(2, tid == 0 && kc == 4);
            wgmma_fence();
#pragma unroll
            for (int k16 = 0; k16 < 4; k16++) {
                const uint64_t db = make_desc(sB + st * K1_BSTAGE + k16 * 2048, 8192, 1024);
                const uint64_t da = make_desc(sX + kc * 16384 + wg * 8192 + k16 * 32, 16, 1024);
                wgmma_n176<1>(accF, da, db, (kc | k16) != 0);
            }
            wgmma_commit();
#pragma unroll
            for (int c = 0; c < 4; c++) {
                const int cc = ghalf * 4 + c;
                const uint4 xv = *(const uint4*)(sgen + kc * 16384 + grow * 128 + ((cc ^ (grow & 7)) << 4));
                const uint4 gv = *(const uint4*)(sGw + kc * 128 + cc * 16);
                gs = fmaf(bf_lo(xv.x), bf_lo(gv.x), gs); gs = fmaf(bf_hi(xv.x), bf_hi(gv.x), gs);
                gs = fmaf(bf_lo(xv.y), bf_lo(gv.y), gs); gs = fmaf(bf_hi(xv.y), bf_hi(gv.y), gs);
                gs = fmaf(bf_lo(xv.z), bf_lo(gv.z), gs); gs = fmaf(bf_hi(xv.z), bf_hi(gv.z), gs);
                gs = fmaf(bf_lo(xv.w), bf_lo(gv.w), gs); gs = fmaf(bf_hi(xv.w), bf_hi(gv.w), gs);
            }
            if (kc > 0) { wgmma_wait<1>(); if (lane == 0) mbar_arrive(b_empty + 8 * ((kc - 1) & 3)); }
        }
        gs += __shfl_xor_sync(0xffffffffu, gs, 1);
        {
            const float g = 1.f / (1.f + __expf(-gs));
            if (ghalf == 0) {
                sGate[grow] = g;
                if (j == 0) g_gate[rb * 128 + grow] = g;
            }
        }
        wgmma_wait<0>();
        if (lane == 0) mbar_arrive(b_empty + 8 * 3);
        bar_sync(1 + wg, 128);
        TS(3, tid == 0);
        const int n0 = j * FCH;
        const int rl = wg * 64 + w4 * 16 + (lane >> 2);
        const float om0 = 1.f - sGate[rl], om1 = 1.f - sGate[rl + 8];
        bf16* frow0 = g_a2 + (size_t)(rb * 128 + rl) * KA2 + D_ + n0;
        bf16* frow1 = frow0 + 8 * KA2;
#pragma unroll
        for (int kc = 0; kc < 8; kc++) {
            const int st = kc & 3;
            mbar_wait(b_full + 8 * st, ((kc + 8) >> 2) & 1);
            wgmma_fence();
#pragma unroll
            for (int k16 = 0; k16 < 4; k16++) {
                const uint64_t db = make_desc(sB + st * K1_BSTAGE + k16 * 2048, 8192, 1024);
                const uint64_t da = make_desc(sX + kc * 16384 + wg * 8192 + k16 * 32, 16, 1024);
                wgmma_n192<1>(accQ, da, db, (kc | k16) != 0);
            }
            wgmma_commit();
            if (kc < 6) {
                const int u = kc;
                uint32_t w0[4], w1[4];
#pragma unroll
                for (int i = 0; i < 4; i++) {
                    const int t = u * 4 + i;
                    if (t < 22) {
                        const uint32_t bv = sBias[t * 4 + q];
                        const float bb0 = bf_lo(bv), bb1 = bf_hi(bv);
                        w0[i] = pack_bf16(mish_f(accF[t * 4 + 0] + bb0) * om0, mish_f(accF[t * 4 + 1] + bb1) * om0);
                        w1[i] = pack_bf16(mish_f(accF[t * 4 + 2] + bb0) * om1, mish_f(accF[t * 4 + 3] + bb1) * om1);
                    } else { w0[i] = 0; w1[i] = 0; }
                }
                quad_transpose(w0, q);
                quad_transpose(w1, q);
                const int c = (u * 4 + q) * 8;
                if (c < FCH && n0 + c < F_) {
                    *(uint4*)(frow0 + c) = make_uint4(w0[0], w0[1], w0[2], w0[3]);
                    *(uint4*)(frow1 + c) = make_uint4(w1[0], w1[1], w1[2], w1[3]);
                }
            }
            if (kc > 0) { wgmma_wait<1>(); if (lane == 0) mbar_arrive(b_empty + 8 * ((kc - 1) & 3)); }
        }
        wgmma_wait<0>();
        TS(4, tid == 0);
        {
            bf16* orow0 = g_qkv + ((size_t)j * S_ + rb * 128 + rl) * 192;
            bf16* orow1 = orow0 + 8 * 192;
#pragma unroll
            for (int u = 0; u < 6; u++) {
                uint32_t w0[4], w1[4];
#pragma unroll
                for (int i = 0; i < 4; i++) {
                    const int t = u * 4 + i;
                    w0[i] = pack_bf16(accQ[t * 4 + 0], accQ[t * 4 + 1]);
                    w1[i] = pack_bf16(accQ[t * 4 + 2], accQ[t * 4 + 3]);
                }
                quad_transpose(w0, q);
                quad_transpose(w1, q);
                const int c = (u * 4 + q) * 8;
                *(uint4*)(orow0 + c) = make_uint4(w0[0], w0[1], w0[2], w0[3]);
                *(uint4*)(orow1 + c) = make_uint4(w1[0], w1[1], w1[2], w1[3]);
            }
        }
        TS(5, tid == 0);
    }
}

__device__ __forceinline__ void ldsm_x4(uint32_t (&r)[4], uint32_t addr) {
    asm("ldmatrix.sync.aligned.m8n8.x4.shared.b16 {%0,%1,%2,%3}, [%4];"
                 : "=r"(r[0]), "=r"(r[1]), "=r"(r[2]), "=r"(r[3]) : "r"(addr));
}
__device__ __forceinline__ void ldsm_x4_t(uint32_t (&r)[4], uint32_t addr) {
    asm("ldmatrix.sync.aligned.m8n8.x4.trans.shared.b16 {%0,%1,%2,%3}, [%4];"
                 : "=r"(r[0]), "=r"(r[1]), "=r"(r[2]), "=r"(r[3]) : "r"(addr));
}
__device__ __forceinline__ void mma16816(float (&d)[4], const uint32_t (&a)[4], uint32_t b0, uint32_t b1) {
    asm("mma.sync.aligned.m16n8k16.row.col.f32.bf16.bf16.f32 {%0,%1,%2,%3}, {%4,%5,%6,%7}, {%8,%9}, {%0,%1,%2,%3};"
                 : "+f"(d[0]), "+f"(d[1]), "+f"(d[2]), "+f"(d[3])
                 : "r"(a[0]), "r"(a[1]), "r"(a[2]), "r"(a[3]), "r"(b0), "r"(b1));
}
__device__ __forceinline__ void mma16816_z(float (&d)[4], const uint32_t (&a)[4], uint32_t b0, uint32_t b1) {
    asm("mma.sync.aligned.m16n8k16.row.col.f32.bf16.bf16.f32 {%0,%1,%2,%3}, {%4,%5,%6,%7}, {%8,%9}, {%10,%10,%10,%10};"
                 : "=f"(d[0]), "=f"(d[1]), "=f"(d[2]), "=f"(d[3])
                 : "r"(a[0]), "r"(a[1]), "r"(a[2]), "r"(a[3]), "r"(b0), "r"(b1), "f"(0.f));
}

constexpr int KV_PITCH = 128;

template <int NB, bool MASK_FIRST, bool MASK_LAST, bool HEAD>
__device__ __forceinline__ void attn_chunk(const uint32_t (&qa)[4], uint32_t ka, uint32_t va, int kbs, int kb0, int r0, int c0,
                                           float& m0, float& m1, float& l0, float& l1, float (&o)[2][4])
{
    const float C = 0.25f * 1.4426950408889634f;
    float s[NB][2][4];
#pragma unroll
    for (int b = 0; b < NB; b++) {
        uint32_t kf[4];
        ldsm_x4(kf, ka + (kbs + b) * 16 * KV_PITCH);
        mma16816_z(s[b][0], qa, kf[0], kf[1]);
        mma16816_z(s[b][1], qa, kf[2], kf[3]);
    }
#pragma unroll
    for (int t = 0; t < 2; t++)
#pragma unroll
        for (int e = 0; e < 4; e++) {
            const int r = r0 + (e >> 1) * 8, c = t * 8 + c0 + (e & 1);
            if (MASK_FIRST && c <= r) s[0][t][e] = -1e30f;
            if (MASK_LAST && c > r) s[NB - 1][t][e] = -1e30f;
        }
    if (HEAD) {
#pragma unroll
        for (int b = 0; b < NB; b++)
            if (kbs + b < kb0) {
#pragma unroll
                for (int t = 0; t < 2; t++)
#pragma unroll
                    for (int e = 0; e < 4; e++) s[b][t][e] = -1e30f;
            }
    }
    float n0 = m0, n1 = m1;
#pragma unroll
    for (int b = 0; b < NB; b++) {
        n0 = fmaxf(n0, fmaxf(fmaxf(s[b][0][0], s[b][0][1]), fmaxf(s[b][1][0], s[b][1][1])));
        n1 = fmaxf(n1, fmaxf(fmaxf(s[b][0][2], s[b][0][3]), fmaxf(s[b][1][2], s[b][1][3])));
    }
    n0 = fmaxf(n0, __shfl_xor_sync(0xffffffffu, n0, 1)); n0 = fmaxf(n0, __shfl_xor_sync(0xffffffffu, n0, 2));
    n1 = fmaxf(n1, __shfl_xor_sync(0xffffffffu, n1, 1)); n1 = fmaxf(n1, __shfl_xor_sync(0xffffffffu, n1, 2));
    const float mc0 = n0 * C, mc1 = n1 * C;
    if (!MASK_LAST) {
        const float a0 = ex2(fmaf(m0, C, -mc0)), a1 = ex2(fmaf(m1, C, -mc1));
        l0 *= a0; l1 *= a1;
        o[0][0] *= a0; o[0][1] *= a0; o[1][0] *= a0; o[1][1] *= a0;
        o[0][2] *= a1; o[0][3] *= a1; o[1][2] *= a1; o[1][3] *= a1;
    }
    m0 = n0; m1 = n1;
#pragma unroll
    for (int b = 0; b < NB; b++) {
        uint32_t pa[4];
#pragma unroll
        for (int t = 0; t < 2; t++) {
            const float p0 = ex2(fmaf(s[b][t][0], C, -mc0)), p1 = ex2(fmaf(s[b][t][1], C, -mc0));
            const float p2 = ex2(fmaf(s[b][t][2], C, -mc1)), p3 = ex2(fmaf(s[b][t][3], C, -mc1));
            l0 += p0 + p1; l1 += p2 + p3;
            pa[2 * t] = pack_bf16(p0, p1); pa[2 * t + 1] = pack_bf16(p2, p3);
        }
        uint32_t vf[4];
        ldsm_x4_t(vf, va + (kbs + b) * 16 * KV_PITCH);
        mma16816(o[0], pa, vf[0], vf[1]);
        mma16816(o[1], pa, vf[2], vf[3]);
    }
}

template <bool HEAD>
__device__ __forceinline__ void attn_task(const uint32_t (&qa)[4], uint32_t ka, uint32_t va, int kb0, int lane,
                                          bf16* __restrict__ out  , float g0, float g1)
{
    const int r0 = lane >> 2, c0 = (lane & 3) * 2;
    float m0 = -1e30f, m1 = -1e30f, l0 = 0.f, l1 = 0.f;
    float o[2][4] = {{0.f, 0.f, 0.f, 0.f}, {0.f, 0.f, 0.f, 0.f}};
    attn_chunk<5, false, true, HEAD>(qa, ka, va, 12, kb0, r0, c0, m0, m1, l0, l1, o);
    if (!HEAD || kb0 < 12) attn_chunk<4, false, false, HEAD>(qa, ka, va, 8, kb0, r0, c0, m0, m1, l0, l1, o);
    if (!HEAD || kb0 < 8)  attn_chunk<4, false, false, HEAD>(qa, ka, va, 4, kb0, r0, c0, m0, m1, l0, l1, o);
    if (!HEAD || kb0 < 4)  attn_chunk<4, true, false, HEAD>(qa, ka, va, 0, kb0, r0, c0, m0, m1, l0, l1, o);
    l0 += __shfl_xor_sync(0xffffffffu, l0, 1); l0 += __shfl_xor_sync(0xffffffffu, l0, 2);
    l1 += __shfl_xor_sync(0xffffffffu, l1, 1); l1 += __shfl_xor_sync(0xffffffffu, l1, 2);
    const float f0 = g0 / l0, f1 = g1 / l1;
#pragma unroll
    for (int t = 0; t < 2; t++) {
        *(uint32_t*)(out + (size_t)r0 * KA2 + t * 8 + c0) = pack_bf16(o[t][0] * f0, o[t][1] * f0);
        *(uint32_t*)(out + (size_t)(r0 + 8) * KA2 + t * 8 + c0) = pack_bf16(o[t][2] * f1, o[t][3] * f1);
    }
}

constexpr int K2_SMEM = 2 * 384 * KV_PITCH + 1024 + 64;

__global__ void __launch_bounds__(512, 1) k2_kernel(const __grid_constant__ CUtensorMap tmQKV)
{
    extern __shared__ uint8_t smem_raw[];
    const uint32_t sbase = (smem_u32(smem_raw) + 1023u) & ~1023u;
    uint8_t* sgen = smem_raw + (sbase - smem_u32(smem_raw));
    const uint32_t sK = sbase, sV = sK + 384 * KV_PITCH, kv_full = sbase + 2 * 384 * KV_PITCH;
    const int rb = blockIdx.x >> 3, j = blockIdx.x & 7;
    const int tid = threadIdx.x, warp = tid >> 5, lane = tid & 31;
    TS(6, tid == 0);
    if (tid == 0) {
        mbar_init(kv_full, 1);
        fence_barrier_init();
        const int nblk = rb >= 2 ? 3 : rb + 1;
        mbar_expect_tx(kv_full, nblk * 2 * 16384);
        for (int i = 0; i < nblk; i++) {
            const int row = j * S_ + (rb - i) * 128;
            tma_load_2d(sK + (2 - i) * 16384, &tmQKV, 64, row, kv_full);
            tma_load_2d(sV + (2 - i) * 16384, &tmQKV, 128, row, kv_full);
        }
    }
    if (rb < 2) {
        for (int i = tid; i < (2 - rb) * 1024; i += 512) {
            *(uint4*)(sgen + i * 16) = make_uint4(0, 0, 0, 0);
            *(uint4*)(sgen + 384 * KV_PITCH + i * 16) = make_uint4(0, 0, 0, 0);
        }
    }
    const int qt = warp & 7, h0 = (warp >> 3) * 2;
    const int q0g = rb * 128 + qt * 16;
    const int r0 = lane >> 2, c0 = (lane & 3) * 2;
    const bf16* qsrc = g_qkv + ((size_t)j * S_ + q0g) * 192 + h0 * 16;
    uint32_t qa[4], qn[4];
    qa[0] = *(const uint32_t*)(qsrc + (size_t)r0 * 192 + c0);
    qa[1] = *(const uint32_t*)(qsrc + (size_t)(r0 + 8) * 192 + c0);
    qa[2] = *(const uint32_t*)(qsrc + (size_t)r0 * 192 + c0 + 8);
    qa[3] = *(const uint32_t*)(qsrc + (size_t)(r0 + 8) * 192 + c0 + 8);
    qn[0] = *(const uint32_t*)(qsrc + (size_t)r0 * 192 + 16 + c0);
    qn[1] = *(const uint32_t*)(qsrc + (size_t)(r0 + 8) * 192 + 16 + c0);
    qn[2] = *(const uint32_t*)(qsrc + (size_t)r0 * 192 + 16 + c0 + 8);
    qn[3] = *(const uint32_t*)(qsrc + (size_t)(r0 + 8) * 192 + 16 + c0 + 8);
    const float g0 = g_gate[q0g + r0], g1 = g_gate[q0g + r0 + 8];
    const int kb0 = q0g < 256 ? (256 - q0g) >> 4 : 0;
    __syncthreads();
    mbar_wait(kv_full, 0);
    uint32_t sKd = sK, sVd = sV;
    asm volatile("" : "+r"(sKd), "+r"(sVd) :: "memory");
    TS(7, tid == 0);
    const int krow = qt * 16 + (lane & 7) + ((lane >> 4) << 3);
    const int vrow = qt * 16 + (lane & 15);
#pragma unroll 1
    for (int hh = 0; hh < 2; hh++) {
        const int hl = h0 + hh;
        const uint32_t ka = sKd + krow * KV_PITCH + (((2 * hl + ((lane >> 3) & 1)) ^ (lane & 7)) << 4);
        const uint32_t va = sVd + vrow * KV_PITCH + (((2 * hl + (lane >> 4)) ^ (lane & 7)) << 4);
        if (rb < 2) attn_task<true>(qa, ka, va, kb0, lane, g_a2 + (size_t)q0g * KA2 + (j * 4 + hl) * 16, g0, g1);
        else        attn_task<false>(qa, ka, va, kb0, lane, g_a2 + (size_t)q0g * KA2 + (j * 4 + hl) * 16, g0, g1);
        TS(8 + hh, tid == 0);
        qa[0] = qn[0]; qa[1] = qn[1]; qa[2] = qn[2]; qa[3] = qn[3];
    }
}

constexpr int K3_STAGES = 5;
constexpr int K3_STAGE = 16384 + 16384;
constexpr int K3_RED = K3_STAGES * K3_STAGE;
constexpr int K3_SMEM = K3_RED + 32768 + 1024 + 1024;
constexpr int K3_KSTEPS = 15;

__global__ void __cluster_dims__(2, 1, 1) __launch_bounds__(384, 1)
k3_kernel(const __grid_constant__ CUtensorMap tmA2, const __grid_constant__ CUtensorMap tmWo,
          const __grid_constant__ CUtensorMap tmW2, bf16* __restrict__ out)
{
    extern __shared__ uint8_t smem_raw[];
    const uint32_t sbase = (smem_u32(smem_raw) + 1023u) & ~1023u;
    uint8_t* sgen = smem_raw + (sbase - smem_u32(smem_raw));
    const uint32_t sBar = sbase + K3_RED + 32768;
    const uint32_t full = sBar, empty = sBar + 64, red_full = sBar + 128;
    const int rb = blockIdx.x >> 3, nt = (blockIdx.x >> 1) & 3, kh = blockIdx.x & 1;
    const int tid = threadIdx.x, wg = tid >> 7, warp = tid >> 5, lane = tid & 31;
    TS(10, tid == 0);
    if (tid == 0) {
        for (int i = 0; i < K3_STAGES; i++) { mbar_init(full + 8 * i, 1); mbar_init(empty + 8 * i, 8); }
        mbar_init(red_full, 128);
        fence_barrier_init();
    }
    __syncthreads();
    asm volatile("barrier.cluster.arrive.release.aligned;" ::: "memory");
    if (wg == 2) {
        reg_dealloc<40>();
        if (tid == 256) {
            for (int ks = 0; ks < K3_KSTEPS; ks++) {
                const int st = ks % K3_STAGES;
                if (ks >= K3_STAGES) mbar_wait(empty + 8 * st, ((ks / K3_STAGES) - 1) & 1);
                mbar_expect_tx(full + 8 * st, K3_STAGE);
                const uint32_t dst = sbase + st * K3_STAGE;
                if (ks < 4) {
                    const int kk = kh * 4 + ks;
                    tma_load_2d(dst, &tmA2, kk * 64, rb * 128, full + 8 * st);
                    tma_load_2d(dst + 16384, &tmWo, nt * 128, kk * 64, full + 8 * st);
                    tma_load_2d(dst + 24576, &tmWo, nt * 128 + 64, kk * 64, full + 8 * st);
                } else {
                    const int kk = kh * 11 + ks - 4;
                    tma_load_2d(dst, &tmA2, D_ + kk * 64, rb * 128, full + 8 * st);
                    tma_load_2d(dst + 16384, &tmW2, nt * 128, kk * 64, full + 8 * st);
                    tma_load_2d(dst + 24576, &tmW2, nt * 128 + 64, kk * 64, full + 8 * st);
                }
            }
        }
        asm volatile("barrier.cluster.wait.acquire.aligned;" ::: "memory");
    } else {
        reg_alloc<232>();
        float acc[64];
        for (int ks = 0; ks < K3_KSTEPS; ks++) {
            const int st = ks % K3_STAGES;
            mbar_wait(full + 8 * st, (ks / K3_STAGES) & 1);
            TS(11, tid == 0 && ks == 0); TS(12, tid == 0 && ks == 8);
            wgmma_fence();
#pragma unroll
            for (int k16 = 0; k16 < 4; k16++) {
                const uint64_t da = make_desc(sbase + st * K3_STAGE + wg * 8192 + k16 * 32, 16, 1024);
                const uint64_t db = make_desc(sbase + st * K3_STAGE + 16384 + k16 * 2048, 8192, 1024);
                wgmma_n128<1>(acc, da, db, (ks | k16) != 0);
            }
            wgmma_commit();
            if (ks > 0) { wgmma_wait<1>(); if (lane == 0) mbar_arrive(empty + 8 * ((ks - 1) % K3_STAGES)); }
        }
        wgmma_wait<0>();
        TS(13, tid == 0);
        asm volatile("barrier.cluster.wait.acquire.aligned;" ::: "memory");
        const int t128 = tid & 127;
        if (wg != kh) {
            uint32_t rdst, rbar;
            asm volatile("mapa.shared::cluster.u32 %0, %1, %2;" : "=r"(rdst) : "r"(sbase + K3_RED + t128 * 16), "r"(kh ^ 1));
            asm volatile("mapa.shared::cluster.u32 %0, %1, %2;" : "=r"(rbar) : "r"(red_full), "r"(kh ^ 1));
#pragma unroll
            for (int i = 0; i < 16; i++)
                asm volatile("st.shared::cluster.v4.f32 [%0], {%1,%2,%3,%4};" :: "r"(rdst + i * 2048),
                             "f"(acc[4 * i]), "f"(acc[4 * i + 1]), "f"(acc[4 * i + 2]), "f"(acc[4 * i + 3]) : "memory");
            asm volatile("mbarrier.arrive.release.cluster.shared::cluster.b64 _, [%0];" :: "r"(rbar) : "memory");
        } else {
            for (uint32_t it = 0; it < (1u << 22); ++it) {
                uint32_t ok;
                asm volatile("{\n.reg .pred p;\nmbarrier.try_wait.parity.acquire.cluster.shared::cta.b64 p, [%1], %2;\nselp.u32 %0, 1, 0, p;\n}"
                             : "=r"(ok) : "r"(red_full), "r"(0) : "memory");
                if (ok) break;
            }
            TS(14, t128 == 0);
#pragma unroll
            for (int i = 0; i < 16; i++) {
                const float4 v = *(const float4*)(sgen + K3_RED + i * 2048 + t128 * 16);
                acc[4 * i] += v.x; acc[4 * i + 1] += v.y; acc[4 * i + 2] += v.z; acc[4 * i + 3] += v.w;
            }
            const int q = lane & 3;
            const int r = rb * 128 + wg * 64 + (warp & 3) * 16 + (lane >> 2);
            bf16* orow0 = out + (size_t)r * D_ + nt * 128;
            bf16* orow1 = orow0 + 8 * D_;
#pragma unroll
            for (int u = 0; u < 4; u++) {
                uint32_t w0[4], w1[4];
#pragma unroll
                for (int i = 0; i < 4; i++) {
                    const int t = u * 4 + i;
                    w0[i] = pack_bf16(acc[t * 4 + 0], acc[t * 4 + 1]);
                    w1[i] = pack_bf16(acc[t * 4 + 2], acc[t * 4 + 3]);
                }
                quad_transpose(w0, q);
                quad_transpose(w1, q);
                const int c = (u * 4 + q) * 8;
                *(uint4*)(orow0 + c) = make_uint4(w0[0], w0[1], w0[2], w0[3]);
                *(uint4*)(orow1 + c) = make_uint4(w1[0], w1[1], w1[2], w1[3]);
            }
            TS(15, t128 == 0);
        }
    }
}

typedef CUresult (*PFN_encodeTiled)(CUtensorMap*, CUtensorMapDataType, cuuint32_t, void*, const cuuint64_t*,
                                    const cuuint64_t*, const cuuint32_t*, const cuuint32_t*, CUtensorMapInterleave,
                                    CUtensorMapSwizzle, CUtensorMapL2promotion, CUtensorMapFloatOOBfill);

static void make_map(PFN_encodeTiled enc, CUtensorMap* m, const void* ptr, uint64_t cols, uint64_t rows,
                     uint32_t box_cols, uint32_t box_rows)
{
    cuuint64_t dims[2] = {cols, rows};
    cuuint64_t strides[1] = {cols * 2};
    cuuint32_t box[2] = {box_cols, box_rows};
    cuuint32_t es[2] = {1, 1};
    enc(m, CU_TENSOR_MAP_DATA_TYPE_BFLOAT16, 2, const_cast<void*>(ptr), dims, strides, box, es,
        CU_TENSOR_MAP_INTERLEAVE_NONE, CU_TENSOR_MAP_SWIZZLE_128B, CU_TENSOR_MAP_L2_PROMOTION_L2_128B,
        CU_TENSOR_MAP_FLOAT_OOB_FILL_NONE);
}

extern "C" void kernel_launch(void* const* d_in, const int* in_sizes, int n_in, void* d_out, int out_size)
{
    const bf16* x    = (const bf16*)d_in[0];
    const bf16* wqkv = (const bf16*)d_in[1];
    const bf16* wo   = (const bf16*)d_in[2];
    const bf16* w1   = (const bf16*)d_in[4];
    const bf16* b1   = (const bf16*)d_in[5];
    const bf16* w2   = (const bf16*)d_in[6];
    const bf16* gw   = (const bf16*)d_in[7];

    static PFN_encodeTiled enc = nullptr;
    if (!enc) {
        void* fn = nullptr;
        cudaDriverEntryPointQueryResult qr;
        cudaGetDriverEntryPoint("cuTensorMapEncodeTiled", &fn, cudaEnableDefault, &qr);
        enc = (PFN_encodeTiled)fn;
        cudaFuncSetAttribute(k1_kernel, cudaFuncAttributeMaxDynamicSharedMemorySize, K1_SMEM);
        cudaFuncSetAttribute(k2_kernel, cudaFuncAttributeMaxDynamicSharedMemorySize, K2_SMEM);
        cudaFuncSetAttribute(k3_kernel, cudaFuncAttributeMaxDynamicSharedMemorySize, K3_SMEM);
    }
    void* a2p = nullptr;
    cudaGetSymbolAddress(&a2p, g_a2);
    void* qkvp = nullptr;
    cudaGetSymbolAddress(&qkvp, g_qkv);
    CUtensorMap tmX, tmWqkv, tmW1, tmA2, tmWo, tmW2, tmQKV;
    make_map(enc, &tmQKV, qkvp, 192, 8 * S_, 64, 128);
    make_map(enc, &tmX, x, D_, S_, 64, 128);
    make_map(enc, &tmWqkv, wqkv, 3 * D_, D_, 64, 64);
    make_map(enc, &tmW1, w1, F_, D_, 64, 64);
    make_map(enc, &tmA2, a2p, KA2, S_, 64, 128);
    make_map(enc, &tmWo, wo, D_, D_, 64, 64);
    make_map(enc, &tmW2, w2, D_, F_, 64, 64);

    cudaStream_t st = cudaStreamPerThread;
    k1_kernel<<<128, 384, K1_SMEM, st>>>(tmX, tmWqkv, tmW1, b1, gw, w1, wqkv, w2, wo);
    k2_kernel<<<128, 512, K2_SMEM, st>>>(tmQKV);
    k3_kernel<<<128, 384, K3_SMEM, st>>>(tmA2, tmWo, tmW2, (bf16*)d_out);
}
```

```cpp
#include <cuda_runtime.h>
#include <cuda_bf16.h>
#include <cuda.h>
#include <stdint.h>

typedef __nv_bfloat16 bf16;

constexpr int S_ = 2048, D_ = 512, F_ = 1376;
constexpr int KA2 = D_ + F_;
constexpr int FCH = 176;

__device__ bf16  g_qkv[8 * S_ * 192];
__device__ bf16  g_a2[S_ * KA2];
__device__ float g_gate[S_];

#define TS(k, cond) do { } while (0)

__device__ __forceinline__ uint32_t smem_u32(const void* p) { return (uint32_t)__cvta_generic_to_shared(p); }
__device__ __forceinline__ void mbar_init(uint32_t bar, uint32_t count) {
    asm volatile("mbarrier.init.shared::cta.b64 [%0], %1;" :: "r"(bar), "r"(count) : "memory");
}
__device__ __forceinline__ void mbar_expect_tx(uint32_t bar, uint32_t bytes) {
    asm volatile("mbarrier.arrive.expect_tx.shared::cta.b64 _, [%0], %1;" :: "r"(bar), "r"(bytes) : "memory");
}
__device__ __forceinline__ void mbar_arrive(uint32_t bar) {
    asm volatile("mbarrier.arrive.shared::cta.b64 _, [%0];" :: "r"(bar) : "memory");
}
__device__ __forceinline__ bool mbar_try_wait(uint32_t bar, uint32_t parity) {
    uint32_t ok;
    asm volatile("{\n.reg .pred p;\nmbarrier.try_wait.parity.shared::cta.b64 p, [%1], %2;\nselp.u32 %0, 1, 0, p;\n}"
                 : "=r"(ok) : "r"(bar), "r"(parity) : "memory");
    return ok != 0;
}
__device__ __forceinline__ void mbar_wait(uint32_t bar, uint32_t parity) {
    for (uint32_t it = 0; it < (1u << 22); ++it) { if (mbar_try_wait(bar, parity)) break; }
}
__device__ __forceinline__ void tma_load_2d(uint32_t dst, const CUtensorMap* map, int c0, int c1, uint32_t bar) {
    asm volatile("cp.async.bulk.tensor.2d.shared::cluster.global.mbarrier::complete_tx::bytes [%0], [%1, {%3, %4}], [%2];"
                 :: "r"(dst), "l"(map), "r"(bar), "r"(c0), "r"(c1) : "memory");
}
__device__ __forceinline__ void l2_prefetch(const void* p, uint32_t bytes) {
    asm volatile("cp.async.bulk.prefetch.L2.global [%0], %1;" :: "l"(p), "r"(bytes) : "memory");
}
__device__ __forceinline__ void fence_barrier_init() { asm volatile("fence.mbarrier_init.release.cluster;" ::: "memory"); }
__device__ __forceinline__ void wgmma_fence()  { asm volatile("wgmma.fence.sync.aligned;" ::: "memory"); }
__device__ __forceinline__ void wgmma_commit() { asm volatile("wgmma.commit_group.sync.aligned;" ::: "memory"); }
template <int N> __device__ __forceinline__ void wgmma_wait() { asm volatile("wgmma.wait_group.sync.aligned %0;" :: "n"(N) : "memory"); }
template <int R> __device__ __forceinline__ void reg_alloc()   { asm volatile("setmaxnreg.inc.sync.aligned.u32 %0;" :: "n"(R)); }
template <int R> __device__ __forceinline__ void reg_dealloc() { asm volatile("setmaxnreg.dec.sync.aligned.u32 %0;" :: "n"(R)); }
__device__ __forceinline__ void bar_sync(int id, int n)   { asm volatile("bar.sync %0, %1;" :: "r"(id), "r"(n) : "memory"); }
__device__ __forceinline__ void bar_arrive(int id, int n) { asm volatile("bar.arrive %0, %1;" :: "r"(id), "r"(n) : "memory"); }

__device__ __forceinline__ uint64_t make_desc(uint32_t addr, uint32_t lbo, uint32_t sbo) {
    uint64_t d = (uint64_t)((addr & 0x3FFFF) >> 4);
    d |= (uint64_t)((lbo & 0x3FFFF) >> 4) << 16;
    d |= (uint64_t)((sbo & 0x3FFFF) >> 4) << 32;
    d |= (uint64_t)1 << 62;
    return d;
}

template <int TB>
__device__ __forceinline__ void wgmma_n64(float (&d)[32], uint64_t da, uint64_t db, int scale_d) {
    asm volatile("{\n.reg .pred p;\nsetp.ne.b32 p, %34, 0;\n"
        "wgmma.mma_async.sync.aligned.m64n64k16.f32.bf16.bf16 {%0, %1, %2, %3, %4, %5, %6, %7, %8, %9, %10, %11, %12, %13, %14, %15, %16, %17, %18, %19, %20, %21, %22, %23, %24, %25, %26, %27, %28, %29, %30, %31}, %32, %33, p, 1, 1, 0, %35;\n}\n"
        : "+f"(d[0]), "+f"(d[1]), "+f"(d[2]), "+f"(d[3]), "+f"(d[4]), "+f"(d[5]), "+f"(d[6]), "+f"(d[7]), "+f"(d[8]), "+f"(d[9]), "+f"(d[10]), "+f"(d[11]), "+f"(d[12]), "+f"(d[13]), "+f"(d[14]), "+f"(d[15]), "+f"(d[16]), "+f"(d[17]), "+f"(d[18]), "+f"(d[19]), "+f"(d[20]), "+f"(d[21]), "+f"(d[22]), "+f"(d[23]), "+f"(d[24]), "+f"(d[25]), "+f"(d[26]), "+f"(d[27]), "+f"(d[28]), "+f"(d[29]), "+f"(d[30]), "+f"(d[31])
        : "l"(da), "l"(db), "r"(scale_d), "n"(TB));
}

template <int TB>
__device__ __forceinline__ void wgmma_n128(float (&d)[64], uint64_t da, uint64_t db, int scale_d) {
    asm volatile("{\n.reg .pred p;\nsetp.ne.b32 p, %66, 0;\n"
        "wgmma.mma_async.sync.aligned.m64n128k16.f32.bf16.bf16 {%0, %1, %2, %3, %4, %5, %6, %7, %8, %9, %10, %11, %12, %13, %14, %15, %16, %17, %18, %19, %20, %21, %22, %23, %24, %25, %26, %27, %28, %29, %30, %31, %32, %33, %34, %35, %36, %37, %38, %39, %40, %41, %42, %43, %44, %45, %46, %47, %48, %49, %50, %51, %52, %53, %54, %55, %56, %57, %58, %59, %60, %61, %62, %63}, %64, %65, p, 1, 1, 0, %67;\n}\n"
        : "+f"(d[0]), "+f"(d[1]), "+f"(d[2]), "+f"(d[3]), "+f"(d[4]), "+f"(d[5]), "+f"(d[6]), "+f"(d[7]), "+f"(d[8]), "+f"(d[9]), "+f"(d[10]), "+f"(d[11]), "+f"(d[12]), "+f"(d[13]), "+f"(d[14]), "+f"(d[15]), "+f"(d[16]), "+f"(d[17]), "+f"(d[18]), "+f"(d[19]), "+f"(d[20]), "+f"(d[21]), "+f"(d[22]), "+f"(d[23]), "+f"(d[24]), "+f"(d[25]), "+f"(d[26]), "+f"(d[27]), "+f"(d[28]), "+f"(d[29]), "+f"(d[30]), "+f"(d[31]), "+f"(d[32]), "+f"(d[33]), "+f"(d[34]), "+f"(d[35]), "+f"(d[36]), "+f"(d[37]), "+f"(d[38]), "+f"(d[39]), "+f"(d[40]), "+f"(d[41]), "+f"(d[42]), "+f"(d[43]), "+f"(d[44]), "+f"(d[45]), "+f"(d[46]), "+f"(d[47]), "+f"(d[48]), "+f"(d[49]), "+f"(d[50]), "+f"(d[51]), "+f"(d[52]), "+f"(d[53]), "+f"(d[54]), "+f"(d[55]), "+f"(d[56]), "+f"(d[57]), "+f"(d[58]), "+f"(d[59]), "+f"(d[60]), "+f"(d[61]), "+f"(d[62]), "+f"(d[63])
        : "l"(da), "l"(db), "r"(scale_d), "n"(TB));
}

template <int TB>
__device__ __forceinline__ void wgmma_n176(float (&d)[88], uint64_t da, uint64_t db, int scale_d) {
    asm volatile("{\n.reg .pred p;\nsetp.ne.b32 p, %90, 0;\n"
        "wgmma.mma_async.sync.aligned.m64n176k16.f32.bf16.bf16 {%0, %1, %2, %3, %4, %5, %6, %7, %8, %9, %10, %11, %12, %13, %14, %15, %16, %17, %18, %19, %20, %21, %22, %23, %24, %25, %26, %27, %28, %29, %30, %31, %32, %33, %34, %35, %36, %37, %38, %39, %40, %41, %42, %43, %44, %45, %46, %47, %48, %49, %50, %51, %52, %53, %54, %55, %56, %57, %58, %59, %60, %61, %62, %63, %64, %65, %66, %67, %68, %69, %70, %71, %72, %73, %74, %75, %76, %77, %78, %79, %80, %81, %82, %83, %84, %85, %86, %87}, %88, %89, p, 1, 1, 0, %91;\n}\n"
        : "+f"(d[0]), "+f"(d[1]), "+f"(d[2]), "+f"(d[3]), "+f"(d[4]), "+f"(d[5]), "+f"(d[6]), "+f"(d[7]), "+f"(d[8]), "+f"(d[9]), "+f"(d[10]), "+f"(d[11]), "+f"(d[12]), "+f"(d[13]), "+f"(d[14]), "+f"(d[15]), "+f"(d[16]), "+f"(d[17]), "+f"(d[18]), "+f"(d[19]), "+f"(d[20]), "+f"(d[21]), "+f"(d[22]), "+f"(d[23]), "+f"(d[24]), "+f"(d[25]), "+f"(d[26]), "+f"(d[27]), "+f"(d[28]), "+f"(d[29]), "+f"(d[30]), "+f"(d[31]), "+f"(d[32]), "+f"(d[33]), "+f"(d[34]), "+f"(d[35]), "+f"(d[36]), "+f"(d[37]), "+f"(d[38]), "+f"(d[39]), "+f"(d[40]), "+f"(d[41]), "+f"(d[42]), "+f"(d[43]), "+f"(d[44]), "+f"(d[45]), "+f"(d[46]), "+f"(d[47]), "+f"(d[48]), "+f"(d[49]), "+f"(d[50]), "+f"(d[51]), "+f"(d[52]), "+f"(d[53]), "+f"(d[54]), "+f"(d[55]), "+f"(d[56]), "+f"(d[57]), "+f"(d[58]), "+f"(d[59]), "+f"(d[60]), "+f"(d[61]), "+f"(d[62]), "+f"(d[63]), "+f"(d[64]), "+f"(d[65]), "+f"(d[66]), "+f"(d[67]), "+f"(d[68]), "+f"(d[69]), "+f"(d[70]), "+f"(d[71]), "+f"(d[72]), "+f"(d[73]), "+f"(d[74]), "+f"(d[75]), "+f"(d[76]), "+f"(d[77]), "+f"(d[78]), "+f"(d[79]), "+f"(d[80]), "+f"(d[81]), "+f"(d[82]), "+f"(d[83]), "+f"(d[84]), "+f"(d[85]), "+f"(d[86]), "+f"(d[87])
        : "l"(da), "l"(db), "r"(scale_d), "n"(TB));
}

template <int TB>
__device__ __forceinline__ void wgmma_n192(float (&d)[96], uint64_t da, uint64_t db, int scale_d) {
    asm volatile("{\n.reg .pred p;\nsetp.ne.b32 p, %98, 0;\n"
        "wgmma.mma_async.sync.aligned.m64n192k16.f32.bf16.bf16 {%0, %1, %2, %3, %4, %5, %6, %7, %8, %9, %10, %11, %12, %13, %14, %15, %16, %17, %18, %19, %20, %21, %22, %23, %24, %25, %26, %27, %28, %29, %30, %31, %32, %33, %34, %35, %36, %37, %38, %39, %40, %41, %42, %43, %44, %45, %46, %47, %48, %49, %50, %51, %52, %53, %54, %55, %56, %57, %58, %59, %60, %61, %62, %63, %64, %65, %66, %67, %68, %69, %70, %71, %72, %73, %74, %75, %76, %77, %78, %79, %80, %81, %82, %83, %84, %85, %86, %87, %88, %89, %90, %91, %92, %93, %94, %95}, %96, %97, p, 1, 1, 0, %99;\n}\n"
        : "+f"(d[0]), "+f"(d[1]), "+f"(d[2]), "+f"(d[3]), "+f"(d[4]), "+f"(d[5]), "+f"(d[6]), "+f"(d[7]), "+f"(d[8]), "+f"(d[9]), "+f"(d[10]), "+f"(d[11]), "+f"(d[12]), "+f"(d[13]), "+f"(d[14]), "+f"(d[15]), "+f"(d[16]), "+f"(d[17]), "+f"(d[18]), "+f"(d[19]), "+f"(d[20]), "+f"(d[21]), "+f"(d[22]), "+f"(d[23]), "+f"(d[24]), "+f"(d[25]), "+f"(d[26]), "+f"(d[27]), "+f"(d[28]), "+f"(d[29]), "+f"(d[30]), "+f"(d[31]), "+f"(d[32]), "+f"(d[33]), "+f"(d[34]), "+f"(d[35]), "+f"(d[36]), "+f"(d[37]), "+f"(d[38]), "+f"(d[39]), "+f"(d[40]), "+f"(d[41]), "+f"(d[42]), "+f"(d[43]), "+f"(d[44]), "+f"(d[45]), "+f"(d[46]), "+f"(d[47]), "+f"(d[48]), "+f"(d[49]), "+f"(d[50]), "+f"(d[51]), "+f"(d[52]), "+f"(d[53]), "+f"(d[54]), "+f"(d[55]), "+f"(d[56]), "+f"(d[57]), "+f"(d[58]), "+f"(d[59]), "+f"(d[60]), "+f"(d[61]), "+f"(d[62]), "+f"(d[63]), "+f"(d[64]), "+f"(d[65]), "+f"(d[66]), "+f"(d[67]), "+f"(d[68]), "+f"(d[69]), "+f"(d[70]), "+f"(d[71]), "+f"(d[72]), "+f"(d[73]), "+f"(d[74]), "+f"(d[75]), "+f"(d[76]), "+f"(d[77]), "+f"(d[78]), "+f"(d[79]), "+f"(d[80]), "+f"(d[81]), "+f"(d[82]), "+f"(d[83]), "+f"(d[84]), "+f"(d[85]), "+f"(d[86]), "+f"(d[87]), "+f"(d[88]), "+f"(d[89]), "+f"(d[90]), "+f"(d[91]), "+f"(d[92]), "+f"(d[93]), "+f"(d[94]), "+f"(d[95])
        : "l"(da), "l"(db), "r"(scale_d), "n"(TB));
}

__device__ __forceinline__ uint32_t pack_bf16(float lo, float hi) {
    uint32_t r;
    asm("cvt.rn.bf16x2.f32 %0, %1, %2;" : "=r"(r) : "f"(hi), "f"(lo));
    return r;
}
__device__ __forceinline__ float bf_lo(uint32_t v) { return __uint_as_float(v << 16); }
__device__ __forceinline__ float bf_hi(uint32_t v) { return __uint_as_float(v & 0xffff0000u); }

__device__ __forceinline__ void quad_transpose(uint32_t (&w)[4], int q) {
    const bool o1 = q & 1, o2 = q & 2;
    {
        uint32_t s0 = o1 ? w[0] : w[1], s1 = o1 ? w[2] : w[3];
        s0 = __shfl_xor_sync(0xffffffffu, s0, 1); s1 = __shfl_xor_sync(0xffffffffu, s1, 1);
        if (o1) { w[0] = s0; w[2] = s1; } else { w[1] = s0; w[3] = s1; }
    }
    {
        uint32_t s0 = o2 ? w[0] : w[2], s1 = o2 ? w[1] : w[3];
        s0 = __shfl_xor_sync(0xffffffffu, s0, 2); s1 = __shfl_xor_sync(0xffffffffu, s1, 2);
        if (o2) { w[0] = s0; w[1] = s1; } else { w[2] = s0; w[3] = s1; }
    }
}

__device__ __forceinline__ float ex2(float x) { float y; asm("ex2.approx.ftz.f32 %0, %1;" : "=f"(y) : "f"(x)); return y; }
__device__ __forceinline__ float rcp(float x) { float y; asm("rcp.approx.ftz.f32 %0, %1;" : "=f"(y) : "f"(x)); return y; }

__device__ __forceinline__ float ex2v(float x) { float y; asm volatile("ex2.approx.ftz.f32 %0, %1;" : "=f"(y) : "f"(x)); return y; }
__device__ __forceinline__ float rcpv(float x) { float y; asm volatile("rcp.approx.ftz.f32 %0, %1;" : "=f"(y) : "f"(x)); return y; }
__device__ __forceinline__ float mish_f(float h) {
    const float w = ex2v(-1.4426950408889634f * fabsf(h));
    const float t = w * w;
    const bool pos = h > 0.f;
    const float num = fmaf(2.f, w, pos ? 1.f : t);
    const float den = num + (pos ? t + t : 2.f);
    return h * num * rcpv(den);
}

constexpr int K1_STAGES = 4;
constexpr int K1_XBYTES = 128 * 512 * 2;
constexpr int K1_BSTAGE = 3 * 8192;
constexpr int K1_SMEM   = K1_XBYTES + K1_STAGES * K1_BSTAGE + 2048   + 1024  ;

__global__ void __launch_bounds__(384, 1)
k1_kernel(const __grid_constant__ CUtensorMap tmX, const __grid_constant__ CUtensorMap tmWqkv,
          const __grid_constant__ CUtensorMap tmW1, const bf16* __restrict__ b1,
          const bf16* __restrict__ gate_w, const bf16* __restrict__ w1p, const bf16* __restrict__ wqkvp,
          const bf16* __restrict__ w2p, const bf16* __restrict__ wop)
{

    extern __shared__ uint8_t smem_raw[];
    const uint32_t sbase = (smem_u32(smem_raw) + 1023u) & ~1023u;
    uint8_t* sgen = smem_raw + (sbase - smem_u32(smem_raw));
    const uint32_t sX = sbase;
    const uint32_t sB = sbase + K1_XBYTES;
    const uint32_t sBar = sB + K1_STAGES * K1_BSTAGE;
    const uint32_t x_full = sBar;
    const uint32_t b_full = sBar + 64;
    const uint32_t b_empty = sBar + 96;
    float* sGate = (float*)(sgen + K1_XBYTES + K1_STAGES * K1_BSTAGE + 128);
    uint8_t* sGw = sgen + K1_XBYTES + K1_STAGES * K1_BSTAGE + 640;
    uint32_t* sBias = (uint32_t*)(sgen + K1_XBYTES + K1_STAGES * K1_BSTAGE + 1664);

    const int rb = blockIdx.x >> 3, j = blockIdx.x & 7;
    const int tid = threadIdx.x, wg = tid >> 7, warp = tid >> 5, lane = tid & 31;
    TS(0, tid == 0);

    if (tid == 0) {
        for (int i = 0; i < 8; i++) mbar_init(x_full + 8 * i, 1);
        for (int i = 0; i < K1_STAGES; i++) { mbar_init(b_full + 8 * i, 1); mbar_init(b_empty + 8 * i, 8); }
        fence_barrier_init();
    }
    __syncthreads();

    if (wg == 2) {
        reg_dealloc<40>();
        if (tid == 288) {
            const int b = blockIdx.x;
            mbar_wait(b_full + 8, 0);
            l2_prefetch((const uint8_t*)wqkvp + b * 12288, 12288);
            l2_prefetch((const uint8_t*)w2p + b * 11008, 11008);
            l2_prefetch((const uint8_t*)wop + b * 4096, 4096);
        }
        if (tid == 256) {
            for (int it = 0; it < 16; it++) {
                if (it < 8) {
                    mbar_expect_tx(x_full + 8 * it, 16384);
                    tma_load_2d(sX + it * 16384, &tmX, it * 64, rb * 128, x_full + 8 * it);
                }
                const int st = it & 3;
                if (it >= K1_STAGES) mbar_wait(b_empty + 8 * st, ((it >> 2) - 1) & 1);
                mbar_expect_tx(b_full + 8 * st, K1_BSTAGE);
                const uint32_t dst = sB + st * K1_BSTAGE;
                if (it < 8) {
                    for (int b = 0; b < 3; b++) tma_load_2d(dst + b * 8192, &tmW1, j * FCH + b * 64, it * 64, b_full + 8 * st);
                } else {
                    for (int b = 0; b < 3; b++) tma_load_2d(dst + b * 8192, &tmWqkv, b * 512 + j * 64, (it - 8) * 64, b_full + 8 * st);
                }
            }
        }
    } else {
        reg_alloc<232>();
        if (tid < 64) ((uint4*)sGw)[tid] = __ldg((const uint4*)gate_w + tid);
        else if (tid < 64 + 88) {
            const int c = j * FCH + (tid - 64) * 2;
            sBias[tid - 64] = c < F_ ? __ldg((const uint32_t*)(b1 + c)) : 0u;
        }
        bar_sync(3, 256);
        const int t128 = tid & 127, w4 = warp & 3, q = lane & 3;
        float accF[88], accQ[96];
        float gs = 0.f;
        const int grow = wg * 64 + (t128 >> 1), ghalf = t128 & 1;
#pragma unroll
        for (int kc = 0; kc < 8; kc++) {
            const int st = kc & 3;
            mbar_wait(x_full + 8 * kc, 0);
            mbar_wait(b_full + 8 * st, (kc >> 2) & 1);
            TS(1, tid == 0 && kc == 0); TS(2, tid == 0 && kc == 4);
            wgmma_fence();
#pragma unroll
            for (int k16 = 0; k16 < 4; k16++) {
                const uint64_t db = make_desc(sB + st * K1_BSTAGE + k16 * 2048, 8192, 1024);
                const uint64_t da = make_desc(sX + kc * 16384 + wg * 8192 + k16 * 32, 16, 1024);
                wgmma_n176<1>(accF, da, db, (kc | k16) != 0);
            }
            wgmma_commit();
#pragma unroll
            for (int c = 0; c < 4; c++) {
                const int cc = ghalf * 4 + c;
                const uint4 xv = *(const uint4*)(sgen + kc * 16384 + grow * 128 + ((cc ^ (grow & 7)) << 4));
                const uint4 gv = *(const uint4*)(sGw + kc * 128 + cc * 16);
                gs = fmaf(bf_lo(xv.x), bf_lo(gv.x), gs); gs = fmaf(bf_hi(xv.x), bf_hi(gv.x), gs);
                gs = fmaf(bf_lo(xv.y), bf_lo(gv.y), gs); gs = fmaf(bf_hi(xv.y), bf_hi(gv.y), gs);
                gs = fmaf(bf_lo(xv.z), bf_lo(gv.z), gs); gs = fmaf(bf_hi(xv.z), bf_hi(gv.z), gs);
                gs = fmaf(bf_lo(xv.w), bf_lo(gv.w), gs); gs = fmaf(bf_hi(xv.w), bf_hi(gv.w), gs);
            }
            if (kc > 0) { wgmma_wait<1>(); if (lane == 0) mbar_arrive(b_empty + 8 * ((kc - 1) & 3)); }
        }
        gs += __shfl_xor_sync(0xffffffffu, gs, 1);
        {
            const float g = 1.f / (1.f + __expf(-gs));
            if (ghalf == 0) {
                sGate[grow] = g;
                if (j == 0) g_gate[rb * 128 + grow] = g;
            }
        }
        wgmma_wait<0>();
        if (lane == 0) mbar_arrive(b_empty + 8 * 3);
        bar_sync(1 + wg, 128);
        TS(3, tid == 0);
        const int n0 = j * FCH;
        const int rl = wg * 64 + w4 * 16 + (lane >> 2);
        const float om0 = 1.f - sGate[rl], om1 = 1.f - sGate[rl + 8];
        bf16* frow0 = g_a2 + (size_t)(rb * 128 + rl) * KA2 + D_ + n0;
        bf16* frow1 = frow0 + 8 * KA2;
#pragma unroll
        for (int kc = 0; kc < 8; kc++) {
            const int st = kc & 3;
            mbar_wait(b_full + 8 * st, ((kc + 8) >> 2) & 1);
            wgmma_fence();
#pragma unroll
            for (int k16 = 0; k16 < 4; k16++) {
                const uint64_t db = make_desc(sB + st * K1_BSTAGE + k16 * 2048, 8192, 1024);
                const uint64_t da = make_desc(sX + kc * 16384 + wg * 8192 + k16 * 32, 16, 1024);
                wgmma_n192<1>(accQ, da, db, (kc | k16) != 0);
            }
            wgmma_commit();
            if (kc < 6) {
                const int u = kc;
                uint32_t w0[4], w1[4];
#pragma unroll
                for (int i = 0; i < 4; i++) {
                    const int t = u * 4 + i;
                    if (t < 22) {
                        const uint32_t bv = sBias[t * 4 + q];
                        const float bb0 = bf_lo(bv), bb1 = bf_hi(bv);
                        w0[i] = pack_bf16(mish_f(accF[t * 4 + 0] + bb0) * om0, mish_f(accF[t * 4 + 1] + bb1) * om0);
                        w1[i] = pack_bf16(mish_f(accF[t * 4 + 2] + bb0) * om1, mish_f(accF[t * 4 + 3] + bb1) * om1);
                    } else { w0[i] = 0; w1[i] = 0; }
                }
                quad_transpose(w0, q);
                quad_transpose(w1, q);
                const int c = (u * 4 + q) * 8;
                if (c < FCH && n0 + c < F_) {
                    *(uint4*)(frow0 + c) = make_uint4(w0[0], w0[1], w0[2], w0[3]);
                    *(uint4*)(frow1 + c) = make_uint4(w1[0], w1[1], w1[2], w1[3]);
                }
            }
            if (kc > 0) { wgmma_wait<1>(); if (lane == 0) mbar_arrive(b_empty + 8 * ((kc - 1) & 3)); }
        }
        wgmma_wait<0>();
        TS(4, tid == 0);
        {
            bf16* orow0 = g_qkv + ((size_t)j * S_ + rb * 128 + rl) * 192;
            bf16* orow1 = orow0 + 8 * 192;
#pragma unroll
            for (int u = 0; u < 6; u++) {
                uint32_t w0[4], w1[4];
#pragma unroll
                for (int i = 0; i < 4; i++) {
                    const int t = u * 4 + i;
                    w0[i] = pack_bf16(accQ[t * 4 + 0], accQ[t * 4 + 1]);
                    w1[i] = pack_bf16(accQ[t * 4 + 2], accQ[t * 4 + 3]);
                }
                quad_transpose(w0, q);
                quad_transpose(w1, q);
                const int c = (u * 4 + q) * 8;
                *(uint4*)(orow0 + c) = make_uint4(w0[0], w0[1], w0[2], w0[3]);
                *(uint4*)(orow1 + c) = make_uint4(w1[0], w1[1], w1[2], w1[3]);
            }
        }
        TS(5, tid == 0);
    }
}

__device__ __forceinline__ void ldsm_x4(uint32_t (&r)[4], uint32_t addr) {
    asm("ldmatrix.sync.aligned.m8n8.x4.shared.b16 {%0,%1,%2,%3}, [%4];"
                 : "=r"(r[0]), "=r"(r[1]), "=r"(r[2]), "=r"(r[3]) : "r"(addr));
}
__device__ __forceinline__ void ldsm_x4_t(uint32_t (&r)[4], uint32_t addr) {
    asm("ldmatrix.sync.aligned.m8n8.x4.trans.shared.b16 {%0,%1,%2,%3}, [%4];"
                 : "=r"(r[0]), "=r"(r[1]), "=r"(r[2]), "=r"(r[3]) : "r"(addr));
}
__device__ __forceinline__ void mma16816(float (&d)[4], const uint32_t (&a)[4], uint32_t b0, uint32_t b1) {
    asm("mma.sync.aligned.m16n8k16.row.col.f32.bf16.bf16.f32 {%0,%1,%2,%3}, {%4,%5,%6,%7}, {%8,%9}, {%0,%1,%2,%3};"
                 : "+f"(d[0]), "+f"(d[1]), "+f"(d[2]), "+f"(d[3])
                 : "r"(a[0]), "r"(a[1]), "r"(a[2]), "r"(a[3]), "r"(b0), "r"(b1));
}
__device__ __forceinline__ void mma16816_z(float (&d)[4], const uint32_t (&a)[4], uint32_t b0, uint32_t b1) {
    asm("mma.sync.aligned.m16n8k16.row.col.f32.bf16.bf16.f32 {%0,%1,%2,%3}, {%4,%5,%6,%7}, {%8,%9}, {%10,%10,%10,%10};"
                 : "=f"(d[0]), "=f"(d[1]), "=f"(d[2]), "=f"(d[3])
                 : "r"(a[0]), "r"(a[1]), "r"(a[2]), "r"(a[3]), "r"(b0), "r"(b1), "f"(0.f));
}

constexpr int KV_PITCH = 128;

template <int NB, bool MASK_FIRST, bool MASK_LAST, bool HEAD>
__device__ __forceinline__ void attn_chunk(const uint32_t (&qa)[4], uint32_t ka, uint32_t va, int kbs, int kb0, int r0, int c0,
                                           float& m0, float& m1, float& l0, float& l1, float (&o)[2][4])
{
    const float C = 0.25f * 1.4426950408889634f;
    float s[NB][2][4];
#pragma unroll
    for (int b = 0; b < NB; b++) {
        uint32_t kf[4];
        ldsm_x4(kf, ka + (kbs + b) * 16 * KV_PITCH);
        mma16816_z(s[b][0], qa, kf[0], kf[1]);
        mma16816_z(s[b][1], qa, kf[2], kf[3]);
    }
#pragma unroll
    for (int t = 0; t < 2; t++)
#pragma unroll
        for (int e = 0; e < 4; e++) {
            const int r = r0 + (e >> 1) * 8, c = t * 8 + c0 + (e & 1);
            if (MASK_FIRST && c <= r) s[0][t][e] = -1e30f;
            if (MASK_LAST && c > r) s[NB - 1][t][e] = -1e30f;
        }
    if (HEAD) {
#pragma unroll
        for (int b = 0; b < NB; b++)
            if (kbs + b < kb0) {
#pragma unroll
                for (int t = 0; t < 2; t++)
#pragma unroll
                    for (int e = 0; e < 4; e++) s[b][t][e] = -1e30f;
            }
    }
    float n0 = m0, n1 = m1;
#pragma unroll
    for (int b = 0; b < NB; b++) {
        n0 = fmaxf(n0, fmaxf(fmaxf(s[b][0][0], s[b][0][1]), fmaxf(s[b][1][0], s[b][1][1])));
        n1 = fmaxf(n1, fmaxf(fmaxf(s[b][0][2], s[b][0][3]), fmaxf(s[b][1][2], s[b][1][3])));
    }
    n0 = fmaxf(n0, __shfl_xor_sync(0xffffffffu, n0, 1)); n0 = fmaxf(n0, __shfl_xor_sync(0xffffffffu, n0, 2));
    n1 = fmaxf(n1, __shfl_xor_sync(0xffffffffu, n1, 1)); n1 = fmaxf(n1, __shfl_xor_sync(0xffffffffu, n1, 2));
    const float mc0 = n0 * C, mc1 = n1 * C;
    if (!MASK_LAST) {
        const float a0 = ex2(fmaf(m0, C, -mc0)), a1 = ex2(fmaf(m1, C, -mc1));
        l0 *= a0; l1 *= a1;
        o[0][0] *= a0; o[0][1] *= a0; o[1][0] *= a0; o[1][1] *= a0;
        o[0][2] *= a1; o[0][3] *= a1; o[1][2] *= a1; o[1][3] *= a1;
    }
    m0 = n0; m1 = n1;
#pragma unroll
    for (int b = 0; b < NB; b++) {
        uint32_t pa[4];
#pragma unroll
        for (int t = 0; t < 2; t++) {
            const float p0 = ex2(fmaf(s[b][t][0], C, -mc0)), p1 = ex2(fmaf(s[b][t][1], C, -mc0));
            const float p2 = ex2(fmaf(s[b][t][2], C, -mc1)), p3 = ex2(fmaf(s[b][t][3], C, -mc1));
            l0 += p0 + p1; l1 += p2 + p3;
            pa[2 * t] = pack_bf16(p0, p1); pa[2 * t + 1] = pack_bf16(p2, p3);
        }
        uint32_t vf[4];
        ldsm_x4_t(vf, va + (kbs + b) * 16 * KV_PITCH);
        mma16816(o[0], pa, vf[0], vf[1]);
        mma16816(o[1], pa, vf[2], vf[3]);
    }
}

template <bool HEAD>
__device__ __forceinline__ void attn_task(const uint32_t (&qa)[4], uint32_t ka, uint32_t va, int kb0, int lane,
                                          bf16* __restrict__ out  , float g0, float g1)
{
    const int r0 = lane >> 2, c0 = (lane & 3) * 2;
    float m0 = -1e30f, m1 = -1e30f, l0 = 0.f, l1 = 0.f;
    float o[2][4] = {{0.f, 0.f, 0.f, 0.f}, {0.f, 0.f, 0.f, 0.f}};
    attn_chunk<5, false, true, HEAD>(qa, ka, va, 12, kb0, r0, c0, m0, m1, l0, l1, o);
    if (!HEAD || kb0 < 12) attn_chunk<4, false, false, HEAD>(qa, ka, va, 8, kb0, r0, c0, m0, m1, l0, l1, o);
    if (!HEAD || kb0 < 8)  attn_chunk<4, false, false, HEAD>(qa, ka, va, 4, kb0, r0, c0, m0, m1, l0, l1, o);
    if (!HEAD || kb0 < 4)  attn_chunk<4, true, false, HEAD>(qa, ka, va, 0, kb0, r0, c0, m0, m1, l0, l1, o);
    l0 += __shfl_xor_sync(0xffffffffu, l0, 1); l0 += __shfl_xor_sync(0xffffffffu, l0, 2);
    l1 += __shfl_xor_sync(0xffffffffu, l1, 1); l1 += __shfl_xor_sync(0xffffffffu, l1, 2);
    const float f0 = g0 / l0, f1 = g1 / l1;
#pragma unroll
    for (int t = 0; t < 2; t++) {
        *(uint32_t*)(out + (size_t)r0 * KA2 + t * 8 + c0) = pack_bf16(o[t][0] * f0, o[t][1] * f0);
        *(uint32_t*)(out + (size_t)(r0 + 8) * KA2 + t * 8 + c0) = pack_bf16(o[t][2] * f1, o[t][3] * f1);
    }
}

constexpr int KB_STAGES = 5;
constexpr int KB_STAGE = 16384 + 8192;
constexpr int KB_KSTEPS = 30;
constexpr int KB_OFF_KV = KB_STAGES * KB_STAGE;
constexpr int KB_OFF_BAR = KB_OFF_KV + 2 * 384 * KV_PITCH;
constexpr int KB_SMEM = KB_OFF_BAR + 256 + 1024;
constexpr int KB_ATT_WARPS = 12;

__global__ void __cluster_dims__(8, 1, 1) __launch_bounds__(768, 1)
kb_kernel(const __grid_constant__ CUtensorMap tmQKV, const __grid_constant__ CUtensorMap tmA2,
          const __grid_constant__ CUtensorMap tmWo, const __grid_constant__ CUtensorMap tmW2, bf16* __restrict__ out)
{
    extern __shared__ uint8_t smem_raw[];
    const uint32_t sbase = (smem_u32(smem_raw) + 1023u) & ~1023u;
    uint8_t* sgen = smem_raw + (sbase - smem_u32(smem_raw));
    const uint32_t sK = sbase + KB_OFF_KV, sV = sK + 384 * KV_PITCH;
    const uint32_t sBar = sbase + KB_OFF_BAR;
    const uint32_t full = sBar, empty = sBar + 64, kv_full = sBar + 128;
    const int rb = blockIdx.x >> 3, j = blockIdx.x & 7;
    const int tid = threadIdx.x, wg = tid >> 7, warp = tid >> 5, lane = tid & 31;
    TS(6, tid == 0);
    if (tid == 0) {
        for (int i = 0; i < KB_STAGES; i++) { mbar_init(full + 8 * i, 1); mbar_init(empty + 8 * i, 8); }
        mbar_init(kv_full, 1);
        fence_barrier_init();
        const int nblk = rb >= 2 ? 3 : rb + 1;
        mbar_expect_tx(kv_full, nblk * 2 * 16384);
        for (int i = 0; i < nblk; i++) {
            const int row = j * S_ + (rb - i) * 128;
            tma_load_2d(sK + (2 - i) * 16384, &tmQKV, 64, row, kv_full);
            tma_load_2d(sV + (2 - i) * 16384, &tmQKV, 128, row, kv_full);
        }
    }
    if (rb < 2) {
        for (int i = tid; i < (2 - rb) * 1024; i += 768) {
            *(uint4*)(sgen + KB_OFF_KV + i * 16) = make_uint4(0, 0, 0, 0);
            *(uint4*)(sgen + KB_OFF_KV + 384 * KV_PITCH + i * 16) = make_uint4(0, 0, 0, 0);
        }
    }
    __syncthreads();
    if (wg == 5) {
        reg_dealloc<24>();
        if (tid == 640) {
            for (int ks = 0; ks < 22; ks++) {
                const int st = ks % KB_STAGES;
                if (ks >= KB_STAGES) mbar_wait(empty + 8 * st, ((ks / KB_STAGES) - 1) & 1);
                mbar_expect_tx(full + 8 * st, KB_STAGE);
                const uint32_t dst = sbase + st * KB_STAGE;
                tma_load_2d(dst, &tmA2, D_ + ks * 64, rb * 128, full + 8 * st);
                tma_load_2d(dst + 16384, &tmW2, j * 64, ks * 64, full + 8 * st);
            }
        }
        __syncwarp();
        asm volatile("barrier.cluster.arrive.release.aligned;" ::: "memory");
        asm volatile("barrier.cluster.wait.acquire.aligned;" ::: "memory");
        if (tid == 640) {
            asm volatile("fence.proxy.async;" ::: "memory");
            TS(11, true);
            for (int ks = 22; ks < KB_KSTEPS; ks++) {
                const int st = ks % KB_STAGES;
                mbar_wait(empty + 8 * st, ((ks / KB_STAGES) - 1) & 1);
                mbar_expect_tx(full + 8 * st, KB_STAGE);
                const uint32_t dst = sbase + st * KB_STAGE;
                tma_load_2d(dst, &tmA2, (ks - 22) * 64, rb * 128, full + 8 * st);
                tma_load_2d(dst + 16384, &tmWo, j * 64, (ks - 22) * 64, full + 8 * st);
            }
        }
    } else if (wg >= 2) {
        reg_alloc<104>();
        const int aw = warp - 8;
        const int r0 = lane >> 2, c0 = (lane & 3) * 2;
        uint32_t qa[4], qn[4];
        {
            const bf16* qsrc = g_qkv + ((size_t)j * S_ + rb * 128 + (aw & 7) * 16) * 192 + (aw >> 3) * 16;
            qa[0] = *(const uint32_t*)(qsrc + (size_t)r0 * 192 + c0);
            qa[1] = *(const uint32_t*)(qsrc + (size_t)(r0 + 8) * 192 + c0);
            qa[2] = *(const uint32_t*)(qsrc + (size_t)r0 * 192 + c0 + 8);
            qa[3] = *(const uint32_t*)(qsrc + (size_t)(r0 + 8) * 192 + c0 + 8);
        }
        mbar_wait(kv_full, 0);
        uint32_t sKd = sK, sVd = sV;
        asm volatile("" : "+r"(sKd), "+r"(sVd) :: "memory");
        TS(7, tid == 256);
#pragma unroll 1
        for (int task = aw; task < 32; task += KB_ATT_WARPS) {
            const int qt = task & 7, hl = task >> 3;
            const int q0g = rb * 128 + qt * 16;
            {
                const int tn = (task + KB_ATT_WARPS) & 31;
                const bf16* qsrc = g_qkv + ((size_t)j * S_ + rb * 128 + (tn & 7) * 16) * 192 + (tn >> 3) * 16;
                qn[0] = *(const uint32_t*)(qsrc + (size_t)r0 * 192 + c0);
                qn[1] = *(const uint32_t*)(qsrc + (size_t)(r0 + 8) * 192 + c0);
                qn[2] = *(const uint32_t*)(qsrc + (size_t)r0 * 192 + c0 + 8);
                qn[3] = *(const uint32_t*)(qsrc + (size_t)(r0 + 8) * 192 + c0 + 8);
            }
            const float g0 = g_gate[q0g + r0], g1 = g_gate[q0g + r0 + 8];
            const int kb0 = q0g < 256 ? (256 - q0g) >> 4 : 0;
            const int krow = qt * 16 + (lane & 7) + ((lane >> 4) << 3);
            const int vrow = qt * 16 + (lane & 15);
            const uint32_t ka = sKd + krow * KV_PITCH + (((2 * hl + ((lane >> 3) & 1)) ^ (lane & 7)) << 4);
            const uint32_t va = sVd + vrow * KV_PITCH + (((2 * hl + (lane >> 4)) ^ (lane & 7)) << 4);
            if (rb < 2) attn_task<true>(qa, ka, va, kb0, lane, g_a2 + (size_t)q0g * KA2 + (j * 4 + hl) * 16, g0, g1);
            else        attn_task<false>(qa, ka, va, kb0, lane, g_a2 + (size_t)q0g * KA2 + (j * 4 + hl) * 16, g0, g1);
            TS(8 + task / KB_ATT_WARPS, tid == 256);
            qa[0] = qn[0]; qa[1] = qn[1]; qa[2] = qn[2]; qa[3] = qn[3];
        }
        asm volatile("barrier.cluster.arrive.release.aligned;" ::: "memory");
        asm volatile("barrier.cluster.wait.acquire.aligned;" ::: "memory");
    } else {
        reg_dealloc<64>();
        asm volatile("barrier.cluster.arrive.release.aligned;" ::: "memory");
        float acc[32];
        for (int ks = 0; ks < KB_KSTEPS; ks++) {
            const int st = ks % KB_STAGES;
            mbar_wait(full + 8 * st, (ks / KB_STAGES) & 1);
            TS(12, tid == 0 && ks == 0); TS(13, tid == 0 && ks == 22);
            wgmma_fence();
#pragma unroll
            for (int k16 = 0; k16 < 4; k16++) {
                const uint64_t da = make_desc(sbase + st * KB_STAGE + wg * 8192 + k16 * 32, 16, 1024);
                const uint64_t db = make_desc(sbase + st * KB_STAGE + 16384 + k16 * 2048, 8192, 1024);
                wgmma_n64<1>(acc, da, db, (ks | k16) != 0);
            }
            wgmma_commit();
            if (ks > 0) { wgmma_wait<1>(); if (lane == 0) mbar_arrive(empty + 8 * ((ks - 1) % KB_STAGES)); }
        }
        wgmma_wait<0>();
        TS(14, tid == 0);
        const int q = lane & 3;
        const int r = rb * 128 + wg * 64 + (warp & 3) * 16 + (lane >> 2);
        bf16* orow0 = out + (size_t)r * D_ + j * 64;
        bf16* orow1 = orow0 + 8 * D_;
#pragma unroll
        for (int u = 0; u < 2; u++) {
            uint32_t w0[4], w1[4];
#pragma unroll
            for (int i = 0; i < 4; i++) {
                const int t = u * 4 + i;
                w0[i] = pack_bf16(acc[t * 4 + 0], acc[t * 4 + 1]);
                w1[i] = pack_bf16(acc[t * 4 + 2], acc[t * 4 + 3]);
            }
            quad_transpose(w0, q);
            quad_transpose(w1, q);
            const int c = (u * 4 + q) * 8;
            *(uint4*)(orow0 + c) = make_uint4(w0[0], w0[1], w0[2], w0[3]);
            *(uint4*)(orow1 + c) = make_uint4(w1[0], w1[1], w1[2], w1[3]);
        }
        TS(15, tid == 0);
        asm volatile("barrier.cluster.wait.acquire.aligned;" ::: "memory");
    }
}

typedef CUresult (*PFN_encodeTiled)(CUtensorMap*, CUtensorMapDataType, cuuint32_t, void*, const cuuint64_t*,
                                    const cuuint64_t*, const cuuint32_t*, const cuuint32_t*, CUtensorMapInterleave,
                                    CUtensorMapSwizzle, CUtensorMapL2promotion, CUtensorMapFloatOOBfill);

static void make_map(PFN_encodeTiled enc, CUtensorMap* m, const void* ptr, uint64_t cols, uint64_t rows,
                     uint32_t box_cols, uint32_t box_rows)
{
    cuuint64_t dims[2] = {cols, rows};
    cuuint64_t strides[1] = {cols * 2};
    cuuint32_t box[2] = {box_cols, box_rows};
    cuuint32_t es[2] = {1, 1};
    enc(m, CU_TENSOR_MAP_DATA_TYPE_BFLOAT16, 2, const_cast<void*>(ptr), dims, strides, box, es,
        CU_TENSOR_MAP_INTERLEAVE_NONE, CU_TENSOR_MAP_SWIZZLE_128B, CU_TENSOR_MAP_L2_PROMOTION_L2_128B,
        CU_TENSOR_MAP_FLOAT_OOB_FILL_NONE);
}

extern "C" void kernel_launch(void* const* d_in, const int* in_sizes, int n_in, void* d_out, int out_size)
{
    const bf16* x    = (const bf16*)d_in[0];
    const bf16* wqkv = (const bf16*)d_in[1];
    const bf16* wo   = (const bf16*)d_in[2];
    const bf16* w1   = (const bf16*)d_in[4];
    const bf16* b1   = (const bf16*)d_in[5];
    const bf16* w2   = (const bf16*)d_in[6];
    const bf16* gw   = (const bf16*)d_in[7];

    static PFN_encodeTiled enc = nullptr;
    if (!enc) {
        void* fn = nullptr;
        cudaDriverEntryPointQueryResult qr;
        cudaGetDriverEntryPoint("cuTensorMapEncodeTiled", &fn, cudaEnableDefault, &qr);
        enc = (PFN_encodeTiled)fn;
        cudaFuncSetAttribute(k1_kernel, cudaFuncAttributeMaxDynamicSharedMemorySize, K1_SMEM);
        cudaFuncSetAttribute(kb_kernel, cudaFuncAttributeMaxDynamicSharedMemorySize, KB_SMEM);
    }
    void* a2p = nullptr;
    cudaGetSymbolAddress(&a2p, g_a2);
    void* qkvp = nullptr;
    cudaGetSymbolAddress(&qkvp, g_qkv);
    CUtensorMap tmX, tmWqkv, tmW1, tmA2, tmWo, tmW2, tmQKV;
    make_map(enc, &tmQKV, qkvp, 192, 8 * S_, 64, 128);
    make_map(enc, &tmX, x, D_, S_, 64, 128);
    make_map(enc, &tmWqkv, wqkv, 3 * D_, D_, 64, 64);
    make_map(enc, &tmW1, w1, F_, D_, 64, 64);
    make_map(enc, &tmA2, a2p, KA2, S_, 64, 128);
    make_map(enc, &tmWo, wo, D_, D_, 64, 64);
    make_map(enc, &tmW2, w2, D_, F_, 64, 64);

    cudaStream_t st = cudaStreamPerThread;
    k1_kernel<<<128, 384, K1_SMEM, st>>>(tmX, tmWqkv, tmW1, b1, gw, w1, wqkv, w2, wo);
    kb_kernel<<<128, 768, KB_SMEM, st>>>(tmQKV, tmA2, tmWo, tmW2, (bf16*)d_out);
}
```

```cpp
#include <cuda_runtime.h>
#include <cuda_bf16.h>
#include <cuda.h>
#include <stdint.h>

typedef __nv_bfloat16 bf16;

constexpr int S_ = 2048, D_ = 512, F_ = 1376;
constexpr int KA2 = D_ + F_;
constexpr int FCH = 176;

__device__ bf16  g_qkv[8 * S_ * 192];
__device__ bf16  g_a2[S_ * KA2];
__device__ float g_gate[S_];

#define TS(k, cond) do { } while (0)

__device__ __forceinline__ uint32_t smem_u32(const void* p) { return (uint32_t)__cvta_generic_to_shared(p); }
__device__ __forceinline__ void mbar_init(uint32_t bar, uint32_t count) {
    asm volatile("mbarrier.init.shared::cta.b64 [%0], %1;" :: "r"(bar), "r"(count) : "memory");
}
__device__ __forceinline__ void mbar_expect_tx(uint32_t bar, uint32_t bytes) {
    asm volatile("mbarrier.arrive.expect_tx.shared::cta.b64 _, [%0], %1;" :: "r"(bar), "r"(bytes) : "memory");
}
__device__ __forceinline__ void mbar_arrive(uint32_t bar) {
    asm volatile("mbarrier.arrive.shared::cta.b64 _, [%0];" :: "r"(bar) : "memory");
}
__device__ __forceinline__ bool mbar_try_wait(uint32_t bar, uint32_t parity) {
    uint32_t ok;
    asm volatile("{\n.reg .pred p;\nmbarrier.try_wait.parity.shared::cta.b64 p, [%1], %2;\nselp.u32 %0, 1, 0, p;\n}"
                 : "=r"(ok) : "r"(bar), "r"(parity) : "memory");
    return ok != 0;
}
__device__ __forceinline__ void mbar_wait(uint32_t bar, uint32_t parity) {
    for (uint32_t it = 0; it < (1u << 22); ++it) { if (mbar_try_wait(bar, parity)) break; }
}
__device__ __forceinline__ void tma_load_2d(uint32_t dst, const CUtensorMap* map, int c0, int c1, uint32_t bar) {
    asm volatile("cp.async.bulk.tensor.2d.shared::cluster.global.mbarrier::complete_tx::bytes [%0], [%1, {%3, %4}], [%2];"
                 :: "r"(dst), "l"(map), "r"(bar), "r"(c0), "r"(c1) : "memory");
}
__device__ __forceinline__ void l2_prefetch(const void* p, uint32_t bytes) {
    asm volatile("cp.async.bulk.prefetch.L2.global [%0], %1;" :: "l"(p), "r"(bytes) : "memory");
}
__device__ __forceinline__ void fence_barrier_init() { asm volatile("fence.mbarrier_init.release.cluster;" ::: "memory"); }
__device__ __forceinline__ void wgmma_fence()  { asm volatile("wgmma.fence.sync.aligned;" ::: "memory"); }
__device__ __forceinline__ void wgmma_commit() { asm volatile("wgmma.commit_group.sync.aligned;" ::: "memory"); }
template <int N> __device__ __forceinline__ void wgmma_wait() { asm volatile("wgmma.wait_group.sync.aligned %0;" :: "n"(N) : "memory"); }
template <int R> __device__ __forceinline__ void reg_alloc()   { asm volatile("setmaxnreg.inc.sync.aligned.u32 %0;" :: "n"(R)); }
template <int R> __device__ __forceinline__ void reg_dealloc() { asm volatile("setmaxnreg.dec.sync.aligned.u32 %0;" :: "n"(R)); }
__device__ __forceinline__ void bar_sync(int id, int n)   { asm volatile("bar.sync %0, %1;" :: "r"(id), "r"(n) : "memory"); }
__device__ __forceinline__ void bar_arrive(int id, int n) { asm volatile("bar.arrive %0, %1;" :: "r"(id), "r"(n) : "memory"); }

__device__ __forceinline__ uint64_t make_desc(uint32_t addr, uint32_t lbo, uint32_t sbo) {
    uint64_t d = (uint64_t)((addr & 0x3FFFF) >> 4);
    d |= (uint64_t)((lbo & 0x3FFFF) >> 4) << 16;
    d |= (uint64_t)((sbo & 0x3FFFF) >> 4) << 32;
    d |= (uint64_t)1 << 62;
    return d;
}

template <int TB>
__device__ __forceinline__ void wgmma_n64(float (&d)[32], uint64_t da, uint64_t db, int scale_d) {
    asm volatile("{\n.reg .pred p;\nsetp.ne.b32 p, %34, 0;\n"
        "wgmma.mma_async.sync.aligned.m64n64k16.f32.bf16.bf16 {%0, %1, %2, %3, %4, %5, %6, %7, %8, %9, %10, %11, %12, %13, %14, %15, %16, %17, %18, %19, %20, %21, %22, %23, %24, %25, %26, %27, %28, %29, %30, %31}, %32, %33, p, 1, 1, 0, %35;\n}\n"
        : "+f"(d[0]), "+f"(d[1]), "+f"(d[2]), "+f"(d[3]), "+f"(d[4]), "+f"(d[5]), "+f"(d[6]), "+f"(d[7]), "+f"(d[8]), "+f"(d[9]), "+f"(d[10]), "+f"(d[11]), "+f"(d[12]), "+f"(d[13]), "+f"(d[14]), "+f"(d[15]), "+f"(d[16]), "+f"(d[17]), "+f"(d[18]), "+f"(d[19]), "+f"(d[20]), "+f"(d[21]), "+f"(d[22]), "+f"(d[23]), "+f"(d[24]), "+f"(d[25]), "+f"(d[26]), "+f"(d[27]), "+f"(d[28]), "+f"(d[29]), "+f"(d[30]), "+f"(d[31])
        : "l"(da), "l"(db), "r"(scale_d), "n"(TB));
}

template <int TB>
__device__ __forceinline__ void wgmma_n128(float (&d)[64], uint64_t da, uint64_t db, int scale_d) {
    asm volatile("{\n.reg .pred p;\nsetp.ne.b32 p, %66, 0;\n"
        "wgmma.mma_async.sync.aligned.m64n128k16.f32.bf16.bf16 {%0, %1, %2, %3, %4, %5, %6, %7, %8, %9, %10, %11, %12, %13, %14, %15, %16, %17, %18, %19, %20, %21, %22, %23, %24, %25, %26, %27, %28, %29, %30, %31, %32, %33, %34, %35, %36, %37, %38, %39, %40, %41, %42, %43, %44, %45, %46, %47, %48, %49, %50, %51, %52, %53, %54, %55, %56, %57, %58, %59, %60, %61, %62, %63}, %64, %65, p, 1, 1, 0, %67;\n}\n"
        : "+f"(d[0]), "+f"(d[1]), "+f"(d[2]), "+f"(d[3]), "+f"(d[4]), "+f"(d[5]), "+f"(d[6]), "+f"(d[7]), "+f"(d[8]), "+f"(d[9]), "+f"(d[10]), "+f"(d[11]), "+f"(d[12]), "+f"(d[13]), "+f"(d[14]), "+f"(d[15]), "+f"(d[16]), "+f"(d[17]), "+f"(d[18]), "+f"(d[19]), "+f"(d[20]), "+f"(d[21]), "+f"(d[22]), "+f"(d[23]), "+f"(d[24]), "+f"(d[25]), "+f"(d[26]), "+f"(d[27]), "+f"(d[28]), "+f"(d[29]), "+f"(d[30]), "+f"(d[31]), "+f"(d[32]), "+f"(d[33]), "+f"(d[34]), "+f"(d[35]), "+f"(d[36]), "+f"(d[37]), "+f"(d[38]), "+f"(d[39]), "+f"(d[40]), "+f"(d[41]), "+f"(d[42]), "+f"(d[43]), "+f"(d[44]), "+f"(d[45]), "+f"(d[46]), "+f"(d[47]), "+f"(d[48]), "+f"(d[49]), "+f"(d[50]), "+f"(d[51]), "+f"(d[52]), "+f"(d[53]), "+f"(d[54]), "+f"(d[55]), "+f"(d[56]), "+f"(d[57]), "+f"(d[58]), "+f"(d[59]), "+f"(d[60]), "+f"(d[61]), "+f"(d[62]), "+f"(d[63])
        : "l"(da), "l"(db), "r"(scale_d), "n"(TB));
}

template <int TB>
__device__ __forceinline__ void wgmma_n176(float (&d)[88], uint64_t da, uint64_t db, int scale_d) {
    asm volatile("{\n.reg .pred p;\nsetp.ne.b32 p, %90, 0;\n"
        "wgmma.mma_async.sync.aligned.m64n176k16.f32.bf16.bf16 {%0, %1, %2, %3, %4, %5, %6, %7, %8, %9, %10, %11, %12, %13, %14, %15, %16, %17, %18, %19, %20, %21, %22, %23, %24, %25, %26, %27, %28, %29, %30, %31, %32, %33, %34, %35, %36, %37, %38, %39, %40, %41, %42, %43, %44, %45, %46, %47, %48, %49, %50, %51, %52, %53, %54, %55, %56, %57, %58, %59, %60, %61, %62, %63, %64, %65, %66, %67, %68, %69, %70, %71, %72, %73, %74, %75, %76, %77, %78, %79, %80, %81, %82, %83, %84, %85, %86, %87}, %88, %89, p, 1, 1, 0, %91;\n}\n"
        : "+f"(d[0]), "+f"(d[1]), "+f"(d[2]), "+f"(d[3]), "+f"(d[4]), "+f"(d[5]), "+f"(d[6]), "+f"(d[7]), "+f"(d[8]), "+f"(d[9]), "+f"(d[10]), "+f"(d[11]), "+f"(d[12]), "+f"(d[13]), "+f"(d[14]), "+f"(d[15]), "+f"(d[16]), "+f"(d[17]), "+f"(d[18]), "+f"(d[19]), "+f"(d[20]), "+f"(d[21]), "+f"(d[22]), "+f"(d[23]), "+f"(d[24]), "+f"(d[25]), "+f"(d[26]), "+f"(d[27]), "+f"(d[28]), "+f"(d[29]), "+f"(d[30]), "+f"(d[31]), "+f"(d[32]), "+f"(d[33]), "+f"(d[34]), "+f"(d[35]), "+f"(d[36]), "+f"(d[37]), "+f"(d[38]), "+f"(d[39]), "+f"(d[40]), "+f"(d[41]), "+f"(d[42]), "+f"(d[43]), "+f"(d[44]), "+f"(d[45]), "+f"(d[46]), "+f"(d[47]), "+f"(d[48]), "+f"(d[49]), "+f"(d[50]), "+f"(d[51]), "+f"(d[52]), "+f"(d[53]), "+f"(d[54]), "+f"(d[55]), "+f"(d[56]), "+f"(d[57]), "+f"(d[58]), "+f"(d[59]), "+f"(d[60]), "+f"(d[61]), "+f"(d[62]), "+f"(d[63]), "+f"(d[64]), "+f"(d[65]), "+f"(d[66]), "+f"(d[67]), "+f"(d[68]), "+f"(d[69]), "+f"(d[70]), "+f"(d[71]), "+f"(d[72]), "+f"(d[73]), "+f"(d[74]), "+f"(d[75]), "+f"(d[76]), "+f"(d[77]), "+f"(d[78]), "+f"(d[79]), "+f"(d[80]), "+f"(d[81]), "+f"(d[82]), "+f"(d[83]), "+f"(d[84]), "+f"(d[85]), "+f"(d[86]), "+f"(d[87])
        : "l"(da), "l"(db), "r"(scale_d), "n"(TB));
}

template <int TB>
__device__ __forceinline__ void wgmma_n192(float (&d)[96], uint64_t da, uint64_t db, int scale_d) {
    asm volatile("{\n.reg .pred p;\nsetp.ne.b32 p, %98, 0;\n"
        "wgmma.mma_async.sync.aligned.m64n192k16.f32.bf16.bf16 {%0, %1, %2, %3, %4, %5, %6, %7, %8, %9, %10, %11, %12, %13, %14, %15, %16, %17, %18, %19, %20, %21, %22, %23, %24, %25, %26, %27, %28, %29, %30, %31, %32, %33, %34, %35, %36, %37, %38, %39, %40, %41, %42, %43, %44, %45, %46, %47, %48, %49, %50, %51, %52, %53, %54, %55, %56, %57, %58, %59, %60, %61, %62, %63, %64, %65, %66, %67, %68, %69, %70, %71, %72, %73, %74, %75, %76, %77, %78, %79, %80, %81, %82, %83, %84, %85, %86, %87, %88, %89, %90, %91, %92, %93, %94, %95}, %96, %97, p, 1, 1, 0, %99;\n}\n"
        : "+f"(d[0]), "+f"(d[1]), "+f"(d[2]), "+f"(d[3]), "+f"(d[4]), "+f"(d[5]), "+f"(d[6]), "+f"(d[7]), "+f"(d[8]), "+f"(d[9]), "+f"(d[10]), "+f"(d[11]), "+f"(d[12]), "+f"(d[13]), "+f"(d[14]), "+f"(d[15]), "+f"(d[16]), "+f"(d[17]), "+f"(d[18]), "+f"(d[19]), "+f"(d[20]), "+f"(d[21]), "+f"(d[22]), "+f"(d[23]), "+f"(d[24]), "+f"(d[25]), "+f"(d[26]), "+f"(d[27]), "+f"(d[28]), "+f"(d[29]), "+f"(d[30]), "+f"(d[31]), "+f"(d[32]), "+f"(d[33]), "+f"(d[34]), "+f"(d[35]), "+f"(d[36]), "+f"(d[37]), "+f"(d[38]), "+f"(d[39]), "+f"(d[40]), "+f"(d[41]), "+f"(d[42]), "+f"(d[43]), "+f"(d[44]), "+f"(d[45]), "+f"(d[46]), "+f"(d[47]), "+f"(d[48]), "+f"(d[49]), "+f"(d[50]), "+f"(d[51]), "+f"(d[52]), "+f"(d[53]), "+f"(d[54]), "+f"(d[55]), "+f"(d[56]), "+f"(d[57]), "+f"(d[58]), "+f"(d[59]), "+f"(d[60]), "+f"(d[61]), "+f"(d[62]), "+f"(d[63]), "+f"(d[64]), "+f"(d[65]), "+f"(d[66]), "+f"(d[67]), "+f"(d[68]), "+f"(d[69]), "+f"(d[70]), "+f"(d[71]), "+f"(d[72]), "+f"(d[73]), "+f"(d[74]), "+f"(d[75]), "+f"(d[76]), "+f"(d[77]), "+f"(d[78]), "+f"(d[79]), "+f"(d[80]), "+f"(d[81]), "+f"(d[82]), "+f"(d[83]), "+f"(d[84]), "+f"(d[85]), "+f"(d[86]), "+f"(d[87]), "+f"(d[88]), "+f"(d[89]), "+f"(d[90]), "+f"(d[91]), "+f"(d[92]), "+f"(d[93]), "+f"(d[94]), "+f"(d[95])
        : "l"(da), "l"(db), "r"(scale_d), "n"(TB));
}

__device__ __forceinline__ uint32_t pack_bf16(float lo, float hi) {
    uint32_t r;
    asm("cvt.rn.bf16x2.f32 %0, %1, %2;" : "=r"(r) : "f"(hi), "f"(lo));
    return r;
}
__device__ __forceinline__ float bf_lo(uint32_t v) { return __uint_as_float(v << 16); }
__device__ __forceinline__ float bf_hi(uint32_t v) { return __uint_as_float(v & 0xffff0000u); }

__device__ __forceinline__ void quad_transpose(uint32_t (&w)[4], int q) {
    const bool o1 = q & 1, o2 = q & 2;
    {
        uint32_t s0 = o1 ? w[0] : w[1], s1 = o1 ? w[2] : w[3];
        s0 = __shfl_xor_sync(0xffffffffu, s0, 1); s1 = __shfl_xor_sync(0xffffffffu, s1, 1);
        if (o1) { w[0] = s0; w[2] = s1; } else { w[1] = s0; w[3] = s1; }
    }
    {
        uint32_t s0 = o2 ? w[0] : w[2], s1 = o2 ? w[1] : w[3];
        s0 = __shfl_xor_sync(0xffffffffu, s0, 2); s1 = __shfl_xor_sync(0xffffffffu, s1, 2);
        if (o2) { w[0] = s0; w[1] = s1; } else { w[2] = s0; w[3] = s1; }
    }
}

__device__ __forceinline__ float ex2(float x) { float y; asm("ex2.approx.ftz.f32 %0, %1;" : "=f"(y) : "f"(x)); return y; }
__device__ __forceinline__ float rcp(float x) { float y; asm("rcp.approx.ftz.f32 %0, %1;" : "=f"(y) : "f"(x)); return y; }

__device__ __forceinline__ float ex2v(float x) { float y; asm volatile("ex2.approx.ftz.f32 %0, %1;" : "=f"(y) : "f"(x)); return y; }
__device__ __forceinline__ float rcpv(float x) { float y; asm volatile("rcp.approx.ftz.f32 %0, %1;" : "=f"(y) : "f"(x)); return y; }
__device__ __forceinline__ float mish_f(float h) {
    const float w = ex2v(-1.4426950408889634f * fabsf(h));
    const float t = w * w;
    const bool pos = h > 0.f;
    const float num = fmaf(2.f, w, pos ? 1.f : t);
    const float den = num + (pos ? t + t : 2.f);
    return h * num * rcpv(den);
}

constexpr int K1_STAGES = 4;
constexpr int K1_XBYTES = 128 * 512 * 2;
constexpr int K1_BSTAGE = 3 * 8192;
constexpr int K1_SMEM   = K1_XBYTES + K1_STAGES * K1_BSTAGE + 2048   + 1024  ;

__global__ void __launch_bounds__(384, 1)
k1_kernel(const __grid_constant__ CUtensorMap tmX, const __grid_constant__ CUtensorMap tmWqkv,
          const __grid_constant__ CUtensorMap tmW1, const bf16* __restrict__ b1,
          const bf16* __restrict__ gate_w, const bf16* __restrict__ w1p, const bf16* __restrict__ wqkvp,
          const bf16* __restrict__ w2p, const bf16* __restrict__ wop)
{

    extern __shared__ uint8_t smem_raw[];
    const uint32_t sbase = (smem_u32(smem_raw) + 1023u) & ~1023u;
    uint8_t* sgen = smem_raw + (sbase - smem_u32(smem_raw));
    const uint32_t sX = sbase;
    const uint32_t sB = sbase + K1_XBYTES;
    const uint32_t sBar = sB + K1_STAGES * K1_BSTAGE;
    const uint32_t x_full = sBar;
    const uint32_t b_full = sBar + 64;
    const uint32_t b_empty = sBar + 96;
    float* sGate = (float*)(sgen + K1_XBYTES + K1_STAGES * K1_BSTAGE + 128);
    uint8_t* sGw = sgen + K1_XBYTES + K1_STAGES * K1_BSTAGE + 640;
    uint32_t* sBias = (uint32_t*)(sgen + K1_XBYTES + K1_STAGES * K1_BSTAGE + 1664);

    const int rb = blockIdx.x >> 3, j = blockIdx.x & 7;
    const int tid = threadIdx.x, wg = tid >> 7, warp = tid >> 5, lane = tid & 31;
    TS(0, tid == 0);

    if (tid == 0) {
        for (int i = 0; i < 8; i++) mbar_init(x_full + 8 * i, 1);
        for (int i = 0; i < K1_STAGES; i++) { mbar_init(b_full + 8 * i, 1); mbar_init(b_empty + 8 * i, 8); }
        fence_barrier_init();
    }
    __syncthreads();

    if (wg == 2) {
        reg_dealloc<40>();
        if (tid == 288) {
            const int b = blockIdx.x;
            mbar_wait(b_full + 8, 0);
            l2_prefetch((const uint8_t*)wqkvp + b * 12288, 12288);
            l2_prefetch((const uint8_t*)w2p + b * 11008, 11008);
            l2_prefetch((const uint8_t*)wop + b * 4096, 4096);
        }
        if (tid == 256) {
            for (int it = 0; it < 16; it++) {
                if (it < 8) {
                    mbar_expect_tx(x_full + 8 * it, 16384);
                    tma_load_2d(sX + it * 16384, &tmX, it * 64, rb * 128, x_full + 8 * it);
                }
                const int st = it & 3;
                if (it >= K1_STAGES) mbar_wait(b_empty + 8 * st, ((it >> 2) - 1) & 1);
                mbar_expect_tx(b_full + 8 * st, K1_BSTAGE);
                const uint32_t dst = sB + st * K1_BSTAGE;
                if (it < 8) {
                    for (int b = 0; b < 3; b++) tma_load_2d(dst + b * 8192, &tmW1, j * FCH + b * 64, it * 64, b_full + 8 * st);
                } else {
                    for (int b = 0; b < 3; b++) tma_load_2d(dst + b * 8192, &tmWqkv, b * 512 + j * 64, (it - 8) * 64, b_full + 8 * st);
                }
            }
        }
    } else {
        reg_alloc<232>();
        if (tid < 64) ((uint4*)sGw)[tid] = __ldg((const uint4*)gate_w + tid);
        else if (tid < 64 + 88) {
            const int c = j * FCH + (tid - 64) * 2;
            sBias[tid - 64] = c < F_ ? __ldg((const uint32_t*)(b1 + c)) : 0u;
        }
        bar_sync(3, 256);
        const int t128 = tid & 127, w4 = warp & 3, q = lane & 3;
        float accF[88], accQ[96];
        float gs = 0.f;
        const int grow = wg * 64 + (t128 >> 1), ghalf = t128 & 1;
#pragma unroll
        for (int kc = 0; kc < 8; kc++) {
            const int st = kc & 3;
            mbar_wait(x_full + 8 * kc, 0);
            mbar_wait(b_full + 8 * st, (kc >> 2) & 1);
            TS(1, tid == 0 && kc == 0); TS(2, tid == 0 && kc == 4);
            wgmma_fence();
#pragma unroll
            for (int k16 = 0; k16 < 4; k16++) {
                const uint64_t db = make_desc(sB + st * K1_BSTAGE + k16 * 2048, 8192, 1024);
                const uint64_t da = make_desc(sX + kc * 16384 + wg * 8192 + k16 * 32, 16, 1024);
                wgmma_n176<1>(accF, da, db, (kc | k16) != 0);
            }
            wgmma_commit();
#pragma unroll
            for (int c = 0; c < 4; c++) {
                const int cc = ghalf * 4 + c;
                const uint4 xv = *(const uint4*)(sgen + kc * 16384 + grow * 128 + ((cc ^ (grow & 7)) << 4));
                const uint4 gv = *(const uint4*)(sGw + kc * 128 + cc * 16);
                gs = fmaf(bf_lo(xv.x), bf_lo(gv.x), gs); gs = fmaf(bf_hi(xv.x), bf_hi(gv.x), gs);
                gs = fmaf(bf_lo(xv.y), bf_lo(gv.y), gs); gs = fmaf(bf_hi(xv.y), bf_hi(gv.y), gs);
                gs = fmaf(bf_lo(xv.z), bf_lo(gv.z), gs); gs = fmaf(bf_hi(xv.z), bf_hi(gv.z), gs);
                gs = fmaf(bf_lo(xv.w), bf_lo(gv.w), gs); gs = fmaf(bf_hi(xv.w), bf_hi(gv.w), gs);
            }
            if (kc > 0) { wgmma_wait<1>(); if (lane == 0) mbar_arrive(b_empty + 8 * ((kc - 1) & 3)); }
        }
        gs += __shfl_xor_sync(0xffffffffu, gs, 1);
        {
            const float g = 1.f / (1.f + __expf(-gs));
            if (ghalf == 0) {
                sGate[grow] = g;
                if (j == 0) g_gate[rb * 128 + grow] = g;
            }
        }
        wgmma_wait<0>();
        if (lane == 0) mbar_arrive(b_empty + 8 * 3);
        bar_sync(1 + wg, 128);
        TS(3, tid == 0);
        const int n0 = j * FCH;
        const int rl = wg * 64 + w4 * 16 + (lane >> 2);
        const float om0 = 1.f - sGate[rl], om1 = 1.f - sGate[rl + 8];
        bf16* frow0 = g_a2 + (size_t)(rb * 128 + rl) * KA2 + D_ + n0;
        bf16* frow1 = frow0 + 8 * KA2;
#pragma unroll
        for (int kc = 0; kc < 8; kc++) {
            const int st = kc & 3;
            mbar_wait(b_full + 8 * st, ((kc + 8) >> 2) & 1);
            wgmma_fence();
#pragma unroll
            for (int k16 = 0; k16 < 4; k16++) {
                const uint64_t db = make_desc(sB + st * K1_BSTAGE + k16 * 2048, 8192, 1024);
                const uint64_t da = make_desc(sX + kc * 16384 + wg * 8192 + k16 * 32, 16, 1024);
                wgmma_n192<1>(accQ, da, db, (kc | k16) != 0);
            }
            wgmma_commit();
            if (kc < 6) {
                const int u = kc;
                uint32_t w0[4], w1[4];
#pragma unroll
                for (int i = 0; i < 4; i++) {
                    const int t = u * 4 + i;
                    if (t < 22) {
                        const uint32_t bv = sBias[t * 4 + q];
                        const float bb0 = bf_lo(bv), bb1 = bf_hi(bv);
                        w0[i] = pack_bf16(mish_f(accF[t * 4 + 0] + bb0) * om0, mish_f(accF[t * 4 + 1] + bb1) * om0);
                        w1[i] = pack_bf16(mish_f(accF[t * 4 + 2] + bb0) * om1, mish_f(accF[t * 4 + 3] + bb1) * om1);
                    } else { w0[i] = 0; w1[i] = 0; }
                }
                quad_transpose(w0, q);
                quad_transpose(w1, q);
                const int c = (u * 4 + q) * 8;
                if (c < FCH && n0 + c < F_) {
                    *(uint4*)(frow0 + c) = make_uint4(w0[0], w0[1], w0[2], w0[3]);
                    *(uint4*)(frow1 + c) = make_uint4(w1[0], w1[1], w1[2], w1[3]);
                }
            }
            if (kc > 0) { wgmma_wait<1>(); if (lane == 0) mbar_arrive(b_empty + 8 * ((kc - 1) & 3)); }
        }
        wgmma_wait<0>();
        TS(4, tid == 0);
        {
            bf16* orow0 = g_qkv + ((size_t)j * S_ + rb * 128 + rl) * 192;
            bf16* orow1 = orow0 + 8 * 192;
#pragma unroll
            for (int u = 0; u < 6; u++) {
                uint32_t w0[4], w1[4];
#pragma unroll
                for (int i = 0; i < 4; i++) {
                    const int t = u * 4 + i;
                    w0[i] = pack_bf16(accQ[t * 4 + 0], accQ[t * 4 + 1]);
                    w1[i] = pack_bf16(accQ[t * 4 + 2], accQ[t * 4 + 3]);
                }
                quad_transpose(w0, q);
                quad_transpose(w1, q);
                const int c = (u * 4 + q) * 8;
                *(uint4*)(orow0 + c) = make_uint4(w0[0], w0[1], w0[2], w0[3]);
                *(uint4*)(orow1 + c) = make_uint4(w1[0], w1[1], w1[2], w1[3]);
            }
        }
        TS(5, tid == 0);
    }
}

__device__ __forceinline__ void ldsm_x4(uint32_t (&r)[4], uint32_t addr) {
    asm("ldmatrix.sync.aligned.m8n8.x4.shared.b16 {%0,%1,%2,%3}, [%4];"
                 : "=r"(r[0]), "=r"(r[1]), "=r"(r[2]), "=r"(r[3]) : "r"(addr));
}
__device__ __forceinline__ void ldsm_x4_t(uint32_t (&r)[4], uint32_t addr) {
    asm("ldmatrix.sync.aligned.m8n8.x4.trans.shared.b16 {%0,%1,%2,%3}, [%4];"
                 : "=r"(r[0]), "=r"(r[1]), "=r"(r[2]), "=r"(r[3]) : "r"(addr));
}
__device__ __forceinline__ void mma16816(float (&d)[4], const uint32_t (&a)[4], uint32_t b0, uint32_t b1) {
    asm("mma.sync.aligned.m16n8k16.row.col.f32.bf16.bf16.f32 {%0,%1,%2,%3}, {%4,%5,%6,%7}, {%8,%9}, {%0,%1,%2,%3};"
                 : "+f"(d[0]), "+f"(d[1]), "+f"(d[2]), "+f"(d[3])
                 : "r"(a[0]), "r"(a[1]), "r"(a[2]), "r"(a[3]), "r"(b0), "r"(b1));
}
__device__ __forceinline__ void mma16816_z(float (&d)[4], const uint32_t (&a)[4], uint32_t b0, uint32_t b1) {
    asm("mma.sync.aligned.m16n8k16.row.col.f32.bf16.bf16.f32 {%0,%1,%2,%3}, {%4,%5,%6,%7}, {%8,%9}, {%10,%10,%10,%10};"
                 : "=f"(d[0]), "=f"(d[1]), "=f"(d[2]), "=f"(d[3])
                 : "r"(a[0]), "r"(a[1]), "r"(a[2]), "r"(a[3]), "r"(b0), "r"(b1), "f"(0.f));
}

constexpr int KV_PITCH = 128;

template <int NB, bool MASK_FIRST, bool MASK_LAST, bool HEAD>
__device__ __forceinline__ void chunk_scores(float (&s)[5][2][4], const uint32_t (&qa)[4], uint32_t ka, int kbs, int kb0, int r0, int c0)
{
#pragma unroll
    for (int b = 0; b < NB; b++) {
        uint32_t kf[4];
        ldsm_x4(kf, ka + (kbs + b) * 16 * KV_PITCH);
        mma16816_z(s[b][0], qa, kf[0], kf[1]);
        mma16816_z(s[b][1], qa, kf[2], kf[3]);
    }
#pragma unroll
    for (int t = 0; t < 2; t++)
#pragma unroll
        for (int e = 0; e < 4; e++) {
            const int r = r0 + (e >> 1) * 8, c = t * 8 + c0 + (e & 1);
            if (MASK_FIRST && c <= r) s[0][t][e] = -1e30f;
            if (MASK_LAST && c > r) s[NB - 1][t][e] = -1e30f;
        }
    if (HEAD) {
#pragma unroll
        for (int b = 0; b < NB; b++)
            if (kbs + b < kb0) {
#pragma unroll
                for (int t = 0; t < 2; t++)
#pragma unroll
                    for (int e = 0; e < 4; e++) s[b][t][e] = -1e30f;
            }
    }
}
template <int NB, bool FIRST>
__device__ __forceinline__ void chunk_update(const float (&s)[5][2][4], uint32_t va, int kbs,
                                             float& m0, float& m1, float& l0, float& l1, float (&o)[2][4])
{
    const float C = 0.25f * 1.4426950408889634f;
    float n0 = m0, n1 = m1;
#pragma unroll
    for (int b = 0; b < NB; b++) {
        n0 = fmaxf(n0, fmaxf(fmaxf(s[b][0][0], s[b][0][1]), fmaxf(s[b][1][0], s[b][1][1])));
        n1 = fmaxf(n1, fmaxf(fmaxf(s[b][0][2], s[b][0][3]), fmaxf(s[b][1][2], s[b][1][3])));
    }
    n0 = fmaxf(n0, __shfl_xor_sync(0xffffffffu, n0, 1)); n0 = fmaxf(n0, __shfl_xor_sync(0xffffffffu, n0, 2));
    n1 = fmaxf(n1, __shfl_xor_sync(0xffffffffu, n1, 1)); n1 = fmaxf(n1, __shfl_xor_sync(0xffffffffu, n1, 2));
    const float mc0 = n0 * C, mc1 = n1 * C;
    if (!FIRST) {
        const float a0 = ex2(fmaf(m0, C, -mc0)), a1 = ex2(fmaf(m1, C, -mc1));
        l0 *= a0; l1 *= a1;
        o[0][0] *= a0; o[0][1] *= a0; o[1][0] *= a0; o[1][1] *= a0;
        o[0][2] *= a1; o[0][3] *= a1; o[1][2] *= a1; o[1][3] *= a1;
    }
    m0 = n0; m1 = n1;
#pragma unroll
    for (int b = 0; b < NB; b++) {
        uint32_t pa[4];
#pragma unroll
        for (int t = 0; t < 2; t++) {
            const float p0 = ex2(fmaf(s[b][t][0], C, -mc0)), p1 = ex2(fmaf(s[b][t][1], C, -mc0));
            const float p2 = ex2(fmaf(s[b][t][2], C, -mc1)), p3 = ex2(fmaf(s[b][t][3], C, -mc1));
            l0 += p0 + p1; l1 += p2 + p3;
            pa[2 * t] = pack_bf16(p0, p1); pa[2 * t + 1] = pack_bf16(p2, p3);
        }
        uint32_t vf[4];
        ldsm_x4_t(vf, va + (kbs + b) * 16 * KV_PITCH);
        mma16816(o[0], pa, vf[0], vf[1]);
        mma16816(o[1], pa, vf[2], vf[3]);
    }
}

template <bool HEAD>
__device__ __forceinline__ void attn_task(const uint32_t (&qa)[4], uint32_t ka, uint32_t va, int kb0, int lane,
                                          bf16* __restrict__ out  , float g0, float g1)
{
    const int r0 = lane >> 2, c0 = (lane & 3) * 2;
    float m0 = -1e30f, m1 = -1e30f, l0 = 0.f, l1 = 0.f;
    float o[2][4] = {{0.f, 0.f, 0.f, 0.f}, {0.f, 0.f, 0.f, 0.f}};
    float sa[5][2][4], sb[5][2][4];
    chunk_scores<5, false, true, HEAD>(sa, qa, ka, 12, kb0, r0, c0);
    chunk_scores<4, false, false, HEAD>(sb, qa, ka, 8, kb0, r0, c0);
    chunk_update<5, true>(sa, va, 12, m0, m1, l0, l1, o);
    chunk_scores<4, false, false, HEAD>(sa, qa, ka, 4, kb0, r0, c0);
    chunk_update<4, false>(sb, va, 8, m0, m1, l0, l1, o);
    chunk_scores<4, true, false, HEAD>(sb, qa, ka, 0, kb0, r0, c0);
    chunk_update<4, false>(sa, va, 4, m0, m1, l0, l1, o);
    chunk_update<4, false>(sb, va, 0, m0, m1, l0, l1, o);
    l0 += __shfl_xor_sync(0xffffffffu, l0, 1); l0 += __shfl_xor_sync(0xffffffffu, l0, 2);
    l1 += __shfl_xor_sync(0xffffffffu, l1, 1); l1 += __shfl_xor_sync(0xffffffffu, l1, 2);
    const float f0 = g0 / l0, f1 = g1 / l1;
#pragma unroll
    for (int t = 0; t < 2; t++) {
        *(uint32_t*)(out + (size_t)r0 * KA2 + t * 8 + c0) = pack_bf16(o[t][0] * f0, o[t][1] * f0);
        *(uint32_t*)(out + (size_t)(r0 + 8) * KA2 + t * 8 + c0) = pack_bf16(o[t][2] * f1, o[t][3] * f1);
    }
}

constexpr int K2_SMEM = 2 * 384 * KV_PITCH + 1024 + 64;

__global__ void __launch_bounds__(512, 1) k2_kernel(const __grid_constant__ CUtensorMap tmQKV)
{
    extern __shared__ uint8_t smem_raw[];
    const uint32_t sbase = (smem_u32(smem_raw) + 1023u) & ~1023u;
    uint8_t* sgen = smem_raw + (sbase - smem_u32(smem_raw));
    const uint32_t sK = sbase, sV = sK + 384 * KV_PITCH, kv_full = sbase + 2 * 384 * KV_PITCH;
    const int rb = blockIdx.x >> 3, j = blockIdx.x & 7;
    const int tid = threadIdx.x, warp = tid >> 5, lane = tid & 31;
    TS(6, tid == 0);
    if (tid == 0) {
        mbar_init(kv_full, 1);
        fence_barrier_init();
        const int nblk = rb >= 2 ? 3 : rb + 1;
        mbar_expect_tx(kv_full, nblk * 2 * 16384);
        for (int i = 0; i < nblk; i++) {
            const int row = j * S_ + (rb - i) * 128;
            tma_load_2d(sK + (2 - i) * 16384, &tmQKV, 64, row, kv_full);
            tma_load_2d(sV + (2 - i) * 16384, &tmQKV, 128, row, kv_full);
        }
    }
    if (rb < 2) {
        for (int i = tid; i < (2 - rb) * 1024; i += 512) {
            *(uint4*)(sgen + i * 16) = make_uint4(0, 0, 0, 0);
            *(uint4*)(sgen + 384 * KV_PITCH + i * 16) = make_uint4(0, 0, 0, 0);
        }
    }
    const int qt = warp & 7, h0 = (warp >> 3) * 2;
    const int q0g = rb * 128 + qt * 16;
    const int r0 = lane >> 2, c0 = (lane & 3) * 2;
    const bf16* qsrc = g_qkv + ((size_t)j * S_ + q0g) * 192 + h0 * 16;
    uint32_t qa[4], qn[4];
    qa[0] = *(const uint32_t*)(qsrc + (size_t)r0 * 192 + c0);
    qa[1] = *(const uint32_t*)(qsrc + (size_t)(r0 + 8) * 192 + c0);
    qa[2] = *(const uint32_t*)(qsrc + (size_t)r0 * 192 + c0 + 8);
    qa[3] = *(const uint32_t*)(qsrc + (size_t)(r0 + 8) * 192 + c0 + 8);
    qn[0] = *(const uint32_t*)(qsrc + (size_t)r0 * 192 + 16 + c0);
    qn[1] = *(const uint32_t*)(qsrc + (size_t)(r0 + 8) * 192 + 16 + c0);
    qn[2] = *(const uint32_t*)(qsrc + (size_t)r0 * 192 + 16 + c0 + 8);
    qn[3] = *(const uint32_t*)(qsrc + (size_t)(r0 + 8) * 192 + 16 + c0 + 8);
    const float g0 = g_gate[q0g + r0], g1 = g_gate[q0g + r0 + 8];
    const int kb0 = q0g < 256 ? (256 - q0g) >> 4 : 0;
    __syncthreads();
    mbar_wait(kv_full, 0);
    uint32_t sKd = sK, sVd = sV;
    asm volatile("" : "+r"(sKd), "+r"(sVd) :: "memory");
    TS(7, tid == 0);
    const int krow = qt * 16 + (lane & 7) + ((lane >> 4) << 3);
    const int vrow = qt * 16 + (lane & 15);
#pragma unroll 1
    for (int hh = 0; hh < 2; hh++) {
        const int hl = h0 + hh;
        const uint32_t ka = sKd + krow * KV_PITCH + (((2 * hl + ((lane >> 3) & 1)) ^ (lane & 7)) << 4);
        const uint32_t va = sVd + vrow * KV_PITCH + (((2 * hl + (lane >> 4)) ^ (lane & 7)) << 4);
        if (rb < 2) attn_task<true>(qa, ka, va, kb0, lane, g_a2 + (size_t)q0g * KA2 + (j * 4 + hl) * 16, g0, g1);
        else        attn_task<false>(qa, ka, va, kb0, lane, g_a2 + (size_t)q0g * KA2 + (j * 4 + hl) * 16, g0, g1);
        TS(8 + hh, tid == 0);
        qa[0] = qn[0]; qa[1] = qn[1]; qa[2] = qn[2]; qa[3] = qn[3];
    }
}

constexpr int K3_STAGES = 8;
constexpr int K3_STAGE = 16384 + 8192;
constexpr int K3_SMEM = K3_STAGES * K3_STAGE + 1024 + 1024;
constexpr int K3_KSTEPS = 30;

__global__ void __launch_bounds__(384, 1)
k3_kernel(const __grid_constant__ CUtensorMap tmA2, const __grid_constant__ CUtensorMap tmWo,
          const __grid_constant__ CUtensorMap tmW2, bf16* __restrict__ out)
{
    extern __shared__ uint8_t smem_raw[];
    const uint32_t sbase = (smem_u32(smem_raw) + 1023u) & ~1023u;
    const uint32_t sBar = sbase + K3_STAGES * K3_STAGE;
    const uint32_t full = sBar, empty = sBar + 64;
    const int rb = blockIdx.x >> 3, nb = blockIdx.x & 7;
    const int tid = threadIdx.x, wg = tid >> 7, warp = tid >> 5, lane = tid & 31;
    TS(10, tid == 0);
    if (tid == 0) {
        for (int i = 0; i < K3_STAGES; i++) { mbar_init(full + 8 * i, 1); mbar_init(empty + 8 * i, 8); }
        fence_barrier_init();
    }
    __syncthreads();
    if (wg == 2) {
        reg_dealloc<40>();
        if (tid == 256) {
            for (int ks = 0; ks < K3_KSTEPS; ks++) {
                const int st = ks % K3_STAGES;
                if (ks >= K3_STAGES) mbar_wait(empty + 8 * st, ((ks / K3_STAGES) - 1) & 1);
                mbar_expect_tx(full + 8 * st, K3_STAGE);
                const uint32_t dst = sbase + st * K3_STAGE;
                tma_load_2d(dst, &tmA2, ks * 64, rb * 128, full + 8 * st);
                if (ks < 8) tma_load_2d(dst + 16384, &tmWo, nb * 64, ks * 64, full + 8 * st);
                else        tma_load_2d(dst + 16384, &tmW2, nb * 64, (ks - 8) * 64, full + 8 * st);
            }
        }
    } else {
        reg_alloc<232>();
        float acc[32];
        for (int ks = 0; ks < K3_KSTEPS; ks++) {
            const int st = ks % K3_STAGES;
            mbar_wait(full + 8 * st, (ks / K3_STAGES) & 1);
            TS(11, tid == 0 && ks == 0); TS(12, tid == 0 && ks == 8); TS(13, tid == 0 && ks == 16);
            wgmma_fence();
#pragma unroll
            for (int k16 = 0; k16 < 4; k16++) {
                const uint64_t da = make_desc(sbase + st * K3_STAGE + wg * 8192 + k16 * 32, 16, 1024);
                const uint64_t db = make_desc(sbase + st * K3_STAGE + 16384 + k16 * 2048, 8192, 1024);
                wgmma_n64<1>(acc, da, db, (ks | k16) != 0);
            }
            wgmma_commit();
            if (ks > 0) { wgmma_wait<1>(); if (lane == 0) mbar_arrive(empty + 8 * ((ks - 1) % K3_STAGES)); }
        }
        wgmma_wait<0>();
        TS(14, tid == 0);
        const int q = lane & 3;
        const int r = rb * 128 + wg * 64 + (warp & 3) * 16 + (lane >> 2);
        bf16* orow0 = out + (size_t)r * D_ + nb * 64;
        bf16* orow1 = orow0 + 8 * D_;
#pragma unroll
        for (int u = 0; u < 2; u++) {
            uint32_t w0[4], w1[4];
#pragma unroll
            for (int i = 0; i < 4; i++) {
                const int t = u * 4 + i;
                w0[i] = pack_bf16(acc[t * 4 + 0], acc[t * 4 + 1]);
                w1[i] = pack_bf16(acc[t * 4 + 2], acc[t * 4 + 3]);
            }
            quad_transpose(w0, q);
            quad_transpose(w1, q);
            const int c = (u * 4 + q) * 8;
            *(uint4*)(orow0 + c) = make_uint4(w0[0], w0[1], w0[2], w0[3]);
            *(uint4*)(orow1 + c) = make_uint4(w1[0], w1[1], w1[2], w1[3]);
        }
        TS(15, tid == 0);
    }
}

typedef CUresult (*PFN_encodeTiled)(CUtensorMap*, CUtensorMapDataType, cuuint32_t, void*, const cuuint64_t*,
                                    const cuuint64_t*, const cuuint32_t*, const cuuint32_t*, CUtensorMapInterleave,
                                    CUtensorMapSwizzle, CUtensorMapL2promotion, CUtensorMapFloatOOBfill);

static void make_map(PFN_encodeTiled enc, CUtensorMap* m, const void* ptr, uint64_t cols, uint64_t rows,
                     uint32_t box_cols, uint32_t box_rows)
{
    cuuint64_t dims[2] = {cols, rows};
    cuuint64_t strides[1] = {cols * 2};
    cuuint32_t box[2] = {box_cols, box_rows};
    cuuint32_t es[2] = {1, 1};
    enc(m, CU_TENSOR_MAP_DATA_TYPE_BFLOAT16, 2, const_cast<void*>(ptr), dims, strides, box, es,
        CU_TENSOR_MAP_INTERLEAVE_NONE, CU_TENSOR_MAP_SWIZZLE_128B, CU_TENSOR_MAP_L2_PROMOTION_L2_128B,
        CU_TENSOR_MAP_FLOAT_OOB_FILL_NONE);
}

extern "C" void kernel_launch(void* const* d_in, const int* in_sizes, int n_in, void* d_out, int out_size)
{
    const bf16* x    = (const bf16*)d_in[0];
    const bf16* wqkv = (const bf16*)d_in[1];
    const bf16* wo   = (const bf16*)d_in[2];
    const bf16* w1   = (const bf16*)d_in[4];
    const bf16* b1   = (const bf16*)d_in[5];
    const bf16* w2   = (const bf16*)d_in[6];
    const bf16* gw   = (const bf16*)d_in[7];

    static PFN_encodeTiled enc = nullptr;
    if (!enc) {
        void* fn = nullptr;
        cudaDriverEntryPointQueryResult qr;
        cudaGetDriverEntryPoint("cuTensorMapEncodeTiled", &fn, cudaEnableDefault, &qr);
        enc = (PFN_encodeTiled)fn;
        cudaFuncSetAttribute(k1_kernel, cudaFuncAttributeMaxDynamicSharedMemorySize, K1_SMEM);
        cudaFuncSetAttribute(k2_kernel, cudaFuncAttributeMaxDynamicSharedMemorySize, K2_SMEM);
        cudaFuncSetAttribute(k3_kernel, cudaFuncAttributeMaxDynamicSharedMemorySize, K3_SMEM);
    }
    void* a2p = nullptr;
    cudaGetSymbolAddress(&a2p, g_a2);
    void* qkvp = nullptr;
    cudaGetSymbolAddress(&qkvp, g_qkv);
    CUtensorMap tmX, tmWqkv, tmW1, tmA2, tmWo, tmW2, tmQKV;
    make_map(enc, &tmQKV, qkvp, 192, 8 * S_, 64, 128);
    make_map(enc, &tmX, x, D_, S_, 64, 128);
    make_map(enc, &tmWqkv, wqkv, 3 * D_, D_, 64, 64);
    make_map(enc, &tmW1, w1, F_, D_, 64, 64);
    make_map(enc, &tmA2, a2p, KA2, S_, 64, 128);
    make_map(enc, &tmWo, wo, D_, D_, 64, 64);
    make_map(enc, &tmW2, w2, D_, F_, 64, 64);

    cudaStream_t st = cudaStreamPerThread;
    k1_kernel<<<128, 384, K1_SMEM, st>>>(tmX, tmWqkv, tmW1, b1, gw, w1, wqkv, w2, wo);
    k2_kernel<<<128, 512, K2_SMEM, st>>>(tmQKV);
    k3_kernel<<<128, 384, K3_SMEM, st>>>(tmA2, tmWo, tmW2, (bf16*)d_out);
}
```

```cpp
#include <cuda_runtime.h>
#include <cuda_bf16.h>
#include <cuda.h>
#include <stdint.h>

typedef __nv_bfloat16 bf16;

constexpr int S_ = 2048, D_ = 512, F_ = 1376;
constexpr int KA2 = D_ + F_;
constexpr int FCH = 176;

__device__ bf16  g_qkv[8 * S_ * 192];
__device__ bf16  g_a2[S_ * KA2];
__device__ float g_gate[S_];

#define TS(k, cond) do { } while (0)

__device__ __forceinline__ uint32_t smem_u32(const void* p) { return (uint32_t)__cvta_generic_to_shared(p); }
__device__ __forceinline__ void mbar_init(uint32_t bar, uint32_t count) {
    asm volatile("mbarrier.init.shared::cta.b64 [%0], %1;" :: "r"(bar), "r"(count) : "memory");
}
__device__ __forceinline__ void mbar_expect_tx(uint32_t bar, uint32_t bytes) {
    asm volatile("mbarrier.arrive.expect_tx.shared::cta.b64 _, [%0], %1;" :: "r"(bar), "r"(bytes) : "memory");
}
__device__ __forceinline__ void mbar_arrive(uint32_t bar) {
    asm volatile("mbarrier.arrive.shared::cta.b64 _, [%0];" :: "r"(bar) : "memory");
}
__device__ __forceinline__ bool mbar_try_wait(uint32_t bar, uint32_t parity) {
    uint32_t ok;
    asm volatile("{\n.reg .pred p;\nmbarrier.try_wait.parity.shared::cta.b64 p, [%1], %2;\nselp.u32 %0, 1, 0, p;\n}"
                 : "=r"(ok) : "r"(bar), "r"(parity) : "memory");
    return ok != 0;
}
__device__ __forceinline__ void mbar_wait(uint32_t bar, uint32_t parity) {
    for (uint32_t it = 0; it < (1u << 22); ++it) { if (mbar_try_wait(bar, parity)) break; }
}
__device__ __forceinline__ void tma_load_2d(uint32_t dst, const CUtensorMap* map, int c0, int c1, uint32_t bar) {
    asm volatile("cp.async.bulk.tensor.2d.shared::cluster.global.mbarrier::complete_tx::bytes [%0], [%1, {%3, %4}], [%2];"
                 :: "r"(dst), "l"(map), "r"(bar), "r"(c0), "r"(c1) : "memory");
}
__device__ __forceinline__ void l2_prefetch(const void* p, uint32_t bytes) {
    asm volatile("cp.async.bulk.prefetch.L2.global [%0], %1;" :: "l"(p), "r"(bytes) : "memory");
}
__device__ __forceinline__ void fence_barrier_init() { asm volatile("fence.mbarrier_init.release.cluster;" ::: "memory"); }
__device__ __forceinline__ void wgmma_fence()  { asm volatile("wgmma.fence.sync.aligned;" ::: "memory"); }
__device__ __forceinline__ void wgmma_commit() { asm volatile("wgmma.commit_group.sync.aligned;" ::: "memory"); }
template <int N> __device__ __forceinline__ void wgmma_wait() { asm volatile("wgmma.wait_group.sync.aligned %0;" :: "n"(N) : "memory"); }
template <int R> __device__ __forceinline__ void reg_alloc()   { asm volatile("setmaxnreg.inc.sync.aligned.u32 %0;" :: "n"(R)); }
template <int R> __device__ __forceinline__ void reg_dealloc() { asm volatile("setmaxnreg.dec.sync.aligned.u32 %0;" :: "n"(R)); }
__device__ __forceinline__ void bar_sync(int id, int n)   { asm volatile("bar.sync %0, %1;" :: "r"(id), "r"(n) : "memory"); }
__device__ __forceinline__ void bar_arrive(int id, int n) { asm volatile("bar.arrive %0, %1;" :: "r"(id), "r"(n) : "memory"); }

__device__ __forceinline__ uint64_t make_desc(uint32_t addr, uint32_t lbo, uint32_t sbo) {
    uint64_t d = (uint64_t)((addr & 0x3FFFF) >> 4);
    d |= (uint64_t)((lbo & 0x3FFFF) >> 4) << 16;
    d |= (uint64_t)((sbo & 0x3FFFF) >> 4) << 32;
    d |= (uint64_t)1 << 62;
    return d;
}

template <int TB>
__device__ __forceinline__ void wgmma_n64(float (&d)[32], uint64_t da, uint64_t db, int scale_d) {
    asm volatile("{\n.reg .pred p;\nsetp.ne.b32 p, %34, 0;\n"
        "wgmma.mma_async.sync.aligned.m64n64k16.f32.bf16.bf16 {%0, %1, %2, %3, %4, %5, %6, %7, %8, %9, %10, %11, %12, %13, %14, %15, %16, %17, %18, %19, %20, %21, %22, %23, %24, %25, %26, %27, %28, %29, %30, %31}, %32, %33, p, 1, 1, 0, %35;\n}\n"
        : "+f"(d[0]), "+f"(d[1]), "+f"(d[2]), "+f"(d[3]), "+f"(d[4]), "+f"(d[5]), "+f"(d[6]), "+f"(d[7]), "+f"(d[8]), "+f"(d[9]), "+f"(d[10]), "+f"(d[11]), "+f"(d[12]), "+f"(d[13]), "+f"(d[14]), "+f"(d[15]), "+f"(d[16]), "+f"(d[17]), "+f"(d[18]), "+f"(d[19]), "+f"(d[20]), "+f"(d[21]), "+f"(d[22]), "+f"(d[23]), "+f"(d[24]), "+f"(d[25]), "+f"(d[26]), "+f"(d[27]), "+f"(d[28]), "+f"(d[29]), "+f"(d[30]), "+f"(d[31])
        : "l"(da), "l"(db), "r"(scale_d), "n"(TB));
}

template <int TB>
__device__ __forceinline__ void wgmma_n128(float (&d)[64], uint64_t da, uint64_t db, int scale_d) {
    asm volatile("{\n.reg .pred p;\nsetp.ne.b32 p, %66, 0;\n"
        "wgmma.mma_async.sync.aligned.m64n128k16.f32.bf16.bf16 {%0, %1, %2, %3, %4, %5, %6, %7, %8, %9, %10, %11, %12, %13, %14, %15, %16, %17, %18, %19, %20, %21, %22, %23, %24, %25, %26, %27, %28, %29, %30, %31, %32, %33, %34, %35, %36, %37, %38, %39, %40, %41, %42, %43, %44, %45, %46, %47, %48, %49, %50, %51, %52, %53, %54, %55, %56, %57, %58, %59, %60, %61, %62, %63}, %64, %65, p, 1, 1, 0, %67;\n}\n"
        : "+f"(d[0]), "+f"(d[1]), "+f"(d[2]), "+f"(d[3]), "+f"(d[4]), "+f"(d[5]), "+f"(d[6]), "+f"(d[7]), "+f"(d[8]), "+f"(d[9]), "+f"(d[10]), "+f"(d[11]), "+f"(d[12]), "+f"(d[13]), "+f"(d[14]), "+f"(d[15]), "+f"(d[16]), "+f"(d[17]), "+f"(d[18]), "+f"(d[19]), "+f"(d[20]), "+f"(d[21]), "+f"(d[22]), "+f"(d[23]), "+f"(d[24]), "+f"(d[25]), "+f"(d[26]), "+f"(d[27]), "+f"(d[28]), "+f"(d[29]), "+f"(d[30]), "+f"(d[31]), "+f"(d[32]), "+f"(d[33]), "+f"(d[34]), "+f"(d[35]), "+f"(d[36]), "+f"(d[37]), "+f"(d[38]), "+f"(d[39]), "+f"(d[40]), "+f"(d[41]), "+f"(d[42]), "+f"(d[43]), "+f"(d[44]), "+f"(d[45]), "+f"(d[46]), "+f"(d[47]), "+f"(d[48]), "+f"(d[49]), "+f"(d[50]), "+f"(d[51]), "+f"(d[52]), "+f"(d[53]), "+f"(d[54]), "+f"(d[55]), "+f"(d[56]), "+f"(d[57]), "+f"(d[58]), "+f"(d[59]), "+f"(d[60]), "+f"(d[61]), "+f"(d[62]), "+f"(d[63])
        : "l"(da), "l"(db), "r"(scale_d), "n"(TB));
}

template <int TB>
__device__ __forceinline__ void wgmma_n176(float (&d)[88], uint64_t da, uint64_t db, int scale_d) {
    asm volatile("{\n.reg .pred p;\nsetp.ne.b32 p, %90, 0;\n"
        "wgmma.mma_async.sync.aligned.m64n176k16.f32.bf16.bf16 {%0, %1, %2, %3, %4, %5, %6, %7, %8, %9, %10, %11, %12, %13, %14, %15, %16, %17, %18, %19, %20, %21, %22, %23, %24, %25, %26, %27, %28, %29, %30, %31, %32, %33, %34, %35, %36, %37, %38, %39, %40, %41, %42, %43, %44, %45, %46, %47, %48, %49, %50, %51, %52, %53, %54, %55, %56, %57, %58, %59, %60, %61, %62, %63, %64, %65, %66, %67, %68, %69, %70, %71, %72, %73, %74, %75, %76, %77, %78, %79, %80, %81, %82, %83, %84, %85, %86, %87}, %88, %89, p, 1, 1, 0, %91;\n}\n"
        : "+f"(d[0]), "+f"(d[1]), "+f"(d[2]), "+f"(d[3]), "+f"(d[4]), "+f"(d[5]), "+f"(d[6]), "+f"(d[7]), "+f"(d[8]), "+f"(d[9]), "+f"(d[10]), "+f"(d[11]), "+f"(d[12]), "+f"(d[13]), "+f"(d[14]), "+f"(d[15]), "+f"(d[16]), "+f"(d[17]), "+f"(d[18]), "+f"(d[19]), "+f"(d[20]), "+f"(d[21]), "+f"(d[22]), "+f"(d[23]), "+f"(d[24]), "+f"(d[25]), "+f"(d[26]), "+f"(d[27]), "+f"(d[28]), "+f"(d[29]), "+f"(d[30]), "+f"(d[31]), "+f"(d[32]), "+f"(d[33]), "+f"(d[34]), "+f"(d[35]), "+f"(d[36]), "+f"(d[37]), "+f"(d[38]), "+f"(d[39]), "+f"(d[40]), "+f"(d[41]), "+f"(d[42]), "+f"(d[43]), "+f"(d[44]), "+f"(d[45]), "+f"(d[46]), "+f"(d[47]), "+f"(d[48]), "+f"(d[49]), "+f"(d[50]), "+f"(d[51]), "+f"(d[52]), "+f"(d[53]), "+f"(d[54]), "+f"(d[55]), "+f"(d[56]), "+f"(d[57]), "+f"(d[58]), "+f"(d[59]), "+f"(d[60]), "+f"(d[61]), "+f"(d[62]), "+f"(d[63]), "+f"(d[64]), "+f"(d[65]), "+f"(d[66]), "+f"(d[67]), "+f"(d[68]), "+f"(d[69]), "+f"(d[70]), "+f"(d[71]), "+f"(d[72]), "+f"(d[73]), "+f"(d[74]), "+f"(d[75]), "+f"(d[76]), "+f"(d[77]), "+f"(d[78]), "+f"(d[79]), "+f"(d[80]), "+f"(d[81]), "+f"(d[82]), "+f"(d[83]), "+f"(d[84]), "+f"(d[85]), "+f"(d[86]), "+f"(d[87])
        : "l"(da), "l"(db), "r"(scale_d), "n"(TB));
}

template <int TB>
__device__ __forceinline__ void wgmma_n192(float (&d)[96], uint64_t da, uint64_t db, int scale_d) {
    asm volatile("{\n.reg .pred p;\nsetp.ne.b32 p, %98, 0;\n"
        "wgmma.mma_async.sync.aligned.m64n192k16.f32.bf16.bf16 {%0, %1, %2, %3, %4, %5, %6, %7, %8, %9, %10, %11, %12, %13, %14, %15, %16, %17, %18, %19, %20, %21, %22, %23, %24, %25, %26, %27, %28, %29, %30, %31, %32, %33, %34, %35, %36, %37, %38, %39, %40, %41, %42, %43, %44, %45, %46, %47, %48, %49, %50, %51, %52, %53, %54, %55, %56, %57, %58, %59, %60, %61, %62, %63, %64, %65, %66, %67, %68, %69, %70, %71, %72, %73, %74, %75, %76, %77, %78, %79, %80, %81, %82, %83, %84, %85, %86, %87, %88, %89, %90, %91, %92, %93, %94, %95}, %96, %97, p, 1, 1, 0, %99;\n}\n"
        : "+f"(d[0]), "+f"(d[1]), "+f"(d[2]), "+f"(d[3]), "+f"(d[4]), "+f"(d[5]), "+f"(d[6]), "+f"(d[7]), "+f"(d[8]), "+f"(d[9]), "+f"(d[10]), "+f"(d[11]), "+f"(d[12]), "+f"(d[13]), "+f"(d[14]), "+f"(d[15]), "+f"(d[16]), "+f"(d[17]), "+f"(d[18]), "+f"(d[19]), "+f"(d[20]), "+f"(d[21]), "+f"(d[22]), "+f"(d[23]), "+f"(d[24]), "+f"(d[25]), "+f"(d[26]), "+f"(d[27]), "+f"(d[28]), "+f"(d[29]), "+f"(d[30]), "+f"(d[31]), "+f"(d[32]), "+f"(d[33]), "+f"(d[34]), "+f"(d[35]), "+f"(d[36]), "+f"(d[37]), "+f"(d[38]), "+f"(d[39]), "+f"(d[40]), "+f"(d[41]), "+f"(d[42]), "+f"(d[43]), "+f"(d[44]), "+f"(d[45]), "+f"(d[46]), "+f"(d[47]), "+f"(d[48]), "+f"(d[49]), "+f"(d[50]), "+f"(d[51]), "+f"(d[52]), "+f"(d[53]), "+f"(d[54]), "+f"(d[55]), "+f"(d[56]), "+f"(d[57]), "+f"(d[58]), "+f"(d[59]), "+f"(d[60]), "+f"(d[61]), "+f"(d[62]), "+f"(d[63]), "+f"(d[64]), "+f"(d[65]), "+f"(d[66]), "+f"(d[67]), "+f"(d[68]), "+f"(d[69]), "+f"(d[70]), "+f"(d[71]), "+f"(d[72]), "+f"(d[73]), "+f"(d[74]), "+f"(d[75]), "+f"(d[76]), "+f"(d[77]), "+f"(d[78]), "+f"(d[79]), "+f"(d[80]), "+f"(d[81]), "+f"(d[82]), "+f"(d[83]), "+f"(d[84]), "+f"(d[85]), "+f"(d[86]), "+f"(d[87]), "+f"(d[88]), "+f"(d[89]), "+f"(d[90]), "+f"(d[91]), "+f"(d[92]), "+f"(d[93]), "+f"(d[94]), "+f"(d[95])
        : "l"(da), "l"(db), "r"(scale_d), "n"(TB));
}

__device__ __forceinline__ uint32_t pack_bf16(float lo, float hi) {
    uint32_t r;
    asm("cvt.rn.bf16x2.f32 %0, %1, %2;" : "=r"(r) : "f"(hi), "f"(lo));
    return r;
}
__device__ __forceinline__ float bf_lo(uint32_t v) { return __uint_as_float(v << 16); }
__device__ __forceinline__ float bf_hi(uint32_t v) { return __uint_as_float(v & 0xffff0000u); }

__device__ __forceinline__ void quad_transpose(uint32_t (&w)[4], int q) {
    const bool o1 = q & 1, o2 = q & 2;
    {
        uint32_t s0 = o1 ? w[0] : w[1], s1 = o1 ? w[2] : w[3];
        s0 = __shfl_xor_sync(0xffffffffu, s0, 1); s1 = __shfl_xor_sync(0xffffffffu, s1, 1);
        if (o1) { w[0] = s0; w[2] = s1; } else { w[1] = s0; w[3] = s1; }
    }
    {
        uint32_t s0 = o2 ? w[0] : w[2], s1 = o2 ? w[1] : w[3];
        s0 = __shfl_xor_sync(0xffffffffu, s0, 2); s1 = __shfl_xor_sync(0xffffffffu, s1, 2);
        if (o2) { w[0] = s0; w[1] = s1; } else { w[2] = s0; w[3] = s1; }
    }
}

__device__ __forceinline__ float ex2(float x) { float y; asm("ex2.approx.ftz.f32 %0, %1;" : "=f"(y) : "f"(x)); return y; }
__device__ __forceinline__ float rcp(float x) { float y; asm("rcp.approx.ftz.f32 %0, %1;" : "=f"(y) : "f"(x)); return y; }

__device__ __forceinline__ float ex2v(float x) { float y; asm volatile("ex2.approx.ftz.f32 %0, %1;" : "=f"(y) : "f"(x)); return y; }
__device__ __forceinline__ float rcpv(float x) { float y; asm volatile("rcp.approx.ftz.f32 %0, %1;" : "=f"(y) : "f"(x)); return y; }
__device__ __forceinline__ float mish_f(float h) {
    const float w = ex2v(-1.4426950408889634f * fabsf(h));
    const float t = w * w;
    const bool pos = h > 0.f;
    const float num = fmaf(2.f, w, pos ? 1.f : t);
    const float den = num + (pos ? t + t : 2.f);
    return h * num * rcpv(den);
}

constexpr int K1_STAGES = 4;
constexpr int K1_XBYTES = 128 * 512 * 2;
constexpr int K1_BSTAGE = 3 * 8192;
constexpr int K1_SMEM   = K1_XBYTES + K1_STAGES * K1_BSTAGE + 2048   + 1024  ;

__global__ void __launch_bounds__(384, 1)
k1_kernel(const __grid_constant__ CUtensorMap tmX, const __grid_constant__ CUtensorMap tmWqkv,
          const __grid_constant__ CUtensorMap tmW1, const bf16* __restrict__ b1,
          const bf16* __restrict__ gate_w, const bf16* __restrict__ w1p, const bf16* __restrict__ wqkvp,
          const bf16* __restrict__ w2p, const bf16* __restrict__ wop)
{

    extern __shared__ uint8_t smem_raw[];
    const uint32_t sbase = (smem_u32(smem_raw) + 1023u) & ~1023u;
    uint8_t* sgen = smem_raw + (sbase - smem_u32(smem_raw));
    const uint32_t sX = sbase;
    const uint32_t sB = sbase + K1_XBYTES;
    const uint32_t sBar = sB + K1_STAGES * K1_BSTAGE;
    const uint32_t x_full = sBar;
    const uint32_t b_full = sBar + 64;
    const uint32_t b_empty = sBar + 96;
    float* sGate = (float*)(sgen + K1_XBYTES + K1_STAGES * K1_BSTAGE + 128);
    uint8_t* sGw = sgen + K1_XBYTES + K1_STAGES * K1_BSTAGE + 640;
    uint32_t* sBias = (uint32_t*)(sgen + K1_XBYTES + K1_STAGES * K1_BSTAGE + 1664);

    const int rb = blockIdx.x >> 3, j = blockIdx.x & 7;
    const int tid = threadIdx.x, wg = tid >> 7, warp = tid >> 5, lane = tid & 31;
    TS(0, tid == 0);

    if (tid == 0) {
        for (int i = 0; i < 8; i++) mbar_init(x_full + 8 * i, 1);
        for (int i = 0; i < K1_STAGES; i++) { mbar_init(b_full + 8 * i, 1); mbar_init(b_empty + 8 * i, 8); }
        fence_barrier_init();
    }
    __syncthreads();

    if (wg == 2) {
        reg_dealloc<40>();
        if (tid == 288) {
            const int b = blockIdx.x;
            mbar_wait(b_full + 8, 0);
            l2_prefetch((const uint8_t*)wqkvp + b * 12288, 12288);
            l2_prefetch((const uint8_t*)w2p + b * 11008, 11008);
            l2_prefetch((const uint8_t*)wop + b * 4096, 4096);
        }
        if (tid == 256) {
            for (int it = 0; it < 16; it++) {
                if (it < 8) {
                    mbar_expect_tx(x_full + 8 * it, 16384);
                    tma_load_2d(sX + it * 16384, &tmX, it * 64, rb * 128, x_full + 8 * it);
                }
                const int st = it & 3;
                if (it >= K1_STAGES) mbar_wait(b_empty + 8 * st, ((it >> 2) - 1) & 1);
                mbar_expect_tx(b_full + 8 * st, K1_BSTAGE);
                const uint32_t dst = sB + st * K1_BSTAGE;
                if (it < 8) {
                    for (int b = 0; b < 3; b++) tma_load_2d(dst + b * 8192, &tmW1, j * FCH + b * 64, it * 64, b_full + 8 * st);
                } else {
                    for (int b = 0; b < 3; b++) tma_load_2d(dst + b * 8192, &tmWqkv, b * 512 + j * 64, (it - 8) * 64, b_full + 8 * st);
                }
            }
        }
    } else {
        reg_alloc<232>();
        if (tid < 64) ((uint4*)sGw)[tid] = __ldg((const uint4*)gate_w + tid);
        else if (tid < 64 + 88) {
            const int c = j * FCH + (tid - 64) * 2;
            sBias[tid - 64] = c < F_ ? __ldg((const uint32_t*)(b1 + c)) : 0u;
        }
        bar_sync(3, 256);
        const int t128 = tid & 127, w4 = warp & 3, q = lane & 3;
        float accF[88], accQ[96];
        float gs = 0.f;
        const int grow = wg * 64 + (t128 >> 1), ghalf = t128 & 1;
#pragma unroll
        for (int kc = 0; kc < 8; kc++) {
            const int st = kc & 3;
            mbar_wait(x_full + 8 * kc, 0);
            mbar_wait(b_full + 8 * st, (kc >> 2) & 1);
            TS(1, tid == 0 && kc == 0); TS(2, tid == 0 && kc == 4);
            wgmma_fence();
#pragma unroll
            for (int k16 = 0; k16 < 4; k16++) {
                const uint64_t db = make_desc(sB + st * K1_BSTAGE + k16 * 2048, 8192, 1024);
                const uint64_t da = make_desc(sX + kc * 16384 + wg * 8192 + k16 * 32, 16, 1024);
                wgmma_n176<1>(accF, da, db, (kc | k16) != 0);
            }
            wgmma_commit();
#pragma unroll
            for (int c = 0; c < 4; c++) {
                const int cc = ghalf * 4 + c;
                const uint4 xv = *(const uint4*)(sgen + kc * 16384 + grow * 128 + ((cc ^ (grow & 7)) << 4));
                const uint4 gv = *(const uint4*)(sGw + kc * 128 + cc * 16);
                gs = fmaf(bf_lo(xv.x), bf_lo(gv.x), gs); gs = fmaf(bf_hi(xv.x), bf_hi(gv.x), gs);
                gs = fmaf(bf_lo(xv.y), bf_lo(gv.y), gs); gs = fmaf(bf_hi(xv.y), bf_hi(gv.y), gs);
                gs = fmaf(bf_lo(xv.z), bf_lo(gv.z), gs); gs = fmaf(bf_hi(xv.z), bf_hi(gv.z), gs);
                gs = fmaf(bf_lo(xv.w), bf_lo(gv.w), gs); gs = fmaf(bf_hi(xv.w), bf_hi(gv.w), gs);
            }
            if (kc > 0) { wgmma_wait<1>(); if (lane == 0) mbar_arrive(b_empty + 8 * ((kc - 1) & 3)); }
        }
        gs += __shfl_xor_sync(0xffffffffu, gs, 1);
        {
            const float g = 1.f / (1.f + __expf(-gs));
            if (ghalf == 0) {
                sGate[grow] = g;
                if (j == 0) g_gate[rb * 128 + grow] = g;
            }
        }
        wgmma_wait<0>();
        if (lane == 0) mbar_arrive(b_empty + 8 * 3);
        bar_sync(1 + wg, 128);
        TS(3, tid == 0);
        const int n0 = j * FCH;
        const int rl = wg * 64 + w4 * 16 + (lane >> 2);
        const float om0 = 1.f - sGate[rl], om1 = 1.f - sGate[rl + 8];
        bf16* frow0 = g_a2 + (size_t)(rb * 128 + rl) * KA2 + D_ + n0;
        bf16* frow1 = frow0 + 8 * KA2;
#pragma unroll
        for (int kc = 0; kc < 8; kc++) {
            const int st = kc & 3;
            mbar_wait(b_full + 8 * st, ((kc + 8) >> 2) & 1);
            wgmma_fence();
#pragma unroll
            for (int k16 = 0; k16 < 4; k16++) {
                const uint64_t db = make_desc(sB + st * K1_BSTAGE + k16 * 2048, 8192, 1024);
                const uint64_t da = make_desc(sX + kc * 16384 + wg * 8192 + k16 * 32, 16, 1024);
                wgmma_n192<1>(accQ, da, db, (kc | k16) != 0);
            }
            wgmma_commit();
            if (kc < 6) {
                const int u = kc;
                uint32_t w0[4], w1[4];
#pragma unroll
                for (int i = 0; i < 4; i++) {
                    const int t = u * 4 + i;
                    if (t < 22) {
                        const uint32_t bv = sBias[t * 4 + q];
                        const float bb0 = bf_lo(bv), bb1 = bf_hi(bv);
                        w0[i] = pack_bf16(mish_f(accF[t * 4 + 0] + bb0) * om0, mish_f(accF[t * 4 + 1] + bb1) * om0);
                        w1[i] = pack_bf16(mish_f(accF[t * 4 + 2] + bb0) * om1, mish_f(accF[t * 4 + 3] + bb1) * om1);
                    } else { w0[i] = 0; w1[i] = 0; }
                }
                quad_transpose(w0, q);
                quad_transpose(w1, q);
                const int c = (u * 4 + q) * 8;
                if (c < FCH && n0 + c < F_) {
                    *(uint4*)(frow0 + c) = make_uint4(w0[0], w0[1], w0[2], w0[3]);
                    *(uint4*)(frow1 + c) = make_uint4(w1[0], w1[1], w1[2], w1[3]);
                }
            }
            if (kc > 0) { wgmma_wait<1>(); if (lane == 0) mbar_arrive(b_empty + 8 * ((kc - 1) & 3)); }
        }
        wgmma_wait<0>();
        TS(4, tid == 0);
        {
            bf16* orow0 = g_qkv + ((size_t)j * S_ + rb * 128 + rl) * 192;
            bf16* orow1 = orow0 + 8 * 192;
#pragma unroll
            for (int u = 0; u < 6; u++) {
                uint32_t w0[4], w1[4];
#pragma unroll
                for (int i = 0; i < 4; i++) {
                    const int t = u * 4 + i;
                    w0[i] = pack_bf16(accQ[t * 4 + 0], accQ[t * 4 + 1]);
                    w1[i] = pack_bf16(accQ[t * 4 + 2], accQ[t * 4 + 3]);
                }
                quad_transpose(w0, q);
                quad_transpose(w1, q);
                const int c = (u * 4 + q) * 8;
                *(uint4*)(orow0 + c) = make_uint4(w0[0], w0[1], w0[2], w0[3]);
                *(uint4*)(orow1 + c) = make_uint4(w1[0], w1[1], w1[2], w1[3]);
            }
        }
        TS(5, tid == 0);
    }
}

__device__ __forceinline__ void ldsm_x4(uint32_t (&r)[4], uint32_t addr) {
    asm("ldmatrix.sync.aligned.m8n8.x4.shared.b16 {%0,%1,%2,%3}, [%4];"
                 : "=r"(r[0]), "=r"(r[1]), "=r"(r[2]), "=r"(r[3]) : "r"(addr));
}
__device__ __forceinline__ void ldsm_x4_t(uint32_t (&r)[4], uint32_t addr) {
    asm("ldmatrix.sync.aligned.m8n8.x4.trans.shared.b16 {%0,%1,%2,%3}, [%4];"
                 : "=r"(r[0]), "=r"(r[1]), "=r"(r[2]), "=r"(r[3]) : "r"(addr));
}
__device__ __forceinline__ void mma16816(float (&d)[4], const uint32_t (&a)[4], uint32_t b0, uint32_t b1) {
    asm("mma.sync.aligned.m16n8k16.row.col.f32.bf16.bf16.f32 {%0,%1,%2,%3}, {%4,%5,%6,%7}, {%8,%9}, {%0,%1,%2,%3};"
                 : "+f"(d[0]), "+f"(d[1]), "+f"(d[2]), "+f"(d[3])
                 : "r"(a[0]), "r"(a[1]), "r"(a[2]), "r"(a[3]), "r"(b0), "r"(b1));
}
__device__ __forceinline__ void mma16816_z(float (&d)[4], const uint32_t (&a)[4], uint32_t b0, uint32_t b1) {
    asm("mma.sync.aligned.m16n8k16.row.col.f32.bf16.bf16.f32 {%0,%1,%2,%3}, {%4,%5,%6,%7}, {%8,%9}, {%10,%10,%10,%10};"
                 : "=f"(d[0]), "=f"(d[1]), "=f"(d[2]), "=f"(d[3])
                 : "r"(a[0]), "r"(a[1]), "r"(a[2]), "r"(a[3]), "r"(b0), "r"(b1), "f"(0.f));
}

constexpr int KV_PITCH = 128;

template <int EDGE, bool HEAD>
__device__ __forceinline__ void blk_scores(float (&s)[2][4], const uint32_t (&qa)[4], uint32_t kaddr, bool dead, int r0, int c0)
{
    uint32_t kf[4];
    ldsm_x4(kf, kaddr);
    mma16816_z(s[0], qa, kf[0], kf[1]);
    mma16816_z(s[1], qa, kf[2], kf[3]);
#pragma unroll
    for (int t = 0; t < 2; t++)
#pragma unroll
        for (int e = 0; e < 4; e++) {
            const int r = r0 + (e >> 1) * 8, c = t * 8 + c0 + (e & 1);
            if (EDGE == 1 && c <= r) s[t][e] = -1e30f;
            if (EDGE == 2 && c > r) s[t][e] = -1e30f;
            if (HEAD && dead) s[t][e] = -1e30f;
        }
}
__device__ __forceinline__ void blk_max(const float (&s)[2][4], float& n0, float& n1) {
    n0 = fmaxf(n0, fmaxf(fmaxf(s[0][0], s[0][1]), fmaxf(s[1][0], s[1][1])));
    n1 = fmaxf(n1, fmaxf(fmaxf(s[0][2], s[0][3]), fmaxf(s[1][2], s[1][3])));
}
__device__ __forceinline__ void blk_pv(const float (&s)[2][4], float mc0, float mc1, float& l0, float& l1,
                                       float (&o)[2][4], uint32_t vaddr) {
    const float C = 0.25f * 1.4426950408889634f;
    uint32_t pa[4];
#pragma unroll
    for (int t = 0; t < 2; t++) {
        const float p0 = ex2(fmaf(s[t][0], C, -mc0)), p1 = ex2(fmaf(s[t][1], C, -mc0));
        const float p2 = ex2(fmaf(s[t][2], C, -mc1)), p3 = ex2(fmaf(s[t][3], C, -mc1));
        l0 += p0 + p1; l1 += p2 + p3;
        pa[2 * t] = pack_bf16(p0, p1); pa[2 * t + 1] = pack_bf16(p2, p3);
    }
    uint32_t vf[4];
    ldsm_x4_t(vf, vaddr);
    mma16816(o[0], pa, vf[0], vf[1]);
    mma16816(o[1], pa, vf[2], vf[3]);
}
__device__ __forceinline__ void quad_max(float& n0, float& n1) {
    n0 = fmaxf(n0, __shfl_xor_sync(0xffffffffu, n0, 1)); n1 = fmaxf(n1, __shfl_xor_sync(0xffffffffu, n1, 1));
    n0 = fmaxf(n0, __shfl_xor_sync(0xffffffffu, n0, 2)); n1 = fmaxf(n1, __shfl_xor_sync(0xffffffffu, n1, 2));
}
template <int NC, int NN, bool FIRST, bool NEXT_IS_EDGE, bool HEAD>
__device__ __forceinline__ void pipe_step(const float (&sc)[5][2][4], float (&sn)[5][2][4], const uint32_t (&qa)[4],
                                          uint32_t ka, uint32_t va, int kc, int kn, int kb0, int r0, int c0,
                                          float& m0, float& m1, float& n0, float& n1, float& l0, float& l1, float (&o)[2][4])
{
    const float C = 0.25f * 1.4426950408889634f;
    const float mc0 = n0 * C, mc1 = n1 * C;
    if (!FIRST) {
        const float a0 = ex2(fmaf(m0, C, -mc0)), a1 = ex2(fmaf(m1, C, -mc1));
        l0 *= a0; l1 *= a1;
        o[0][0] *= a0; o[0][1] *= a0; o[1][0] *= a0; o[1][1] *= a0;
        o[0][2] *= a1; o[0][3] *= a1; o[1][2] *= a1; o[1][3] *= a1;
    }
    m0 = n0; m1 = n1;
#pragma unroll
    for (int b = 0; b < NC; b++) {
        if (b < NN) {
            if (NEXT_IS_EDGE && b == 0) blk_scores<1, HEAD>(sn[b], qa, ka + (kn + b) * 16 * KV_PITCH, kn + b < kb0, r0, c0);
            else                        blk_scores<0, HEAD>(sn[b], qa, ka + (kn + b) * 16 * KV_PITCH, kn + b < kb0, r0, c0);
        }
        blk_pv(sc[b], mc0, mc1, l0, l1, o, va + (kc + b) * 16 * KV_PITCH);
        if (b < NN) blk_max(sn[b], n0, n1);
    }
    if (NN > 0) quad_max(n0, n1);
}

template <bool HEAD>
__device__ __forceinline__ void attn_task(const uint32_t (&qa)[4], uint32_t ka, uint32_t va, int kb0, int lane,
                                          bf16* __restrict__ out  , float g0, float g1)
{
    const int r0 = lane >> 2, c0 = (lane & 3) * 2;
    float m0 = -1e30f, m1 = -1e30f, n0 = -1e30f, n1 = -1e30f, l0 = 0.f, l1 = 0.f;
    float o[2][4] = {{0.f, 0.f, 0.f, 0.f}, {0.f, 0.f, 0.f, 0.f}};
    float sa[5][2][4], sb[5][2][4];
#pragma unroll
    for (int b = 0; b < 5; b++) {
        if (b == 4) blk_scores<2, HEAD>(sa[b], qa, ka + (12 + b) * 16 * KV_PITCH, false, r0, c0);
        else        blk_scores<0, HEAD>(sa[b], qa, ka + (12 + b) * 16 * KV_PITCH, 12 + b < kb0, r0, c0);
        blk_max(sa[b], n0, n1);
    }
    quad_max(n0, n1);
    pipe_step<5, 4, true,  false, HEAD>(sa, sb, qa, ka, va, 12, 8, kb0, r0, c0, m0, m1, n0, n1, l0, l1, o);
    pipe_step<4, 4, false, false, HEAD>(sb, sa, qa, ka, va, 8, 4, kb0, r0, c0, m0, m1, n0, n1, l0, l1, o);
    pipe_step<4, 4, false, true,  HEAD>(sa, sb, qa, ka, va, 4, 0, kb0, r0, c0, m0, m1, n0, n1, l0, l1, o);
    pipe_step<4, 0, false, false, HEAD>(sb, sa, qa, ka, va, 0, 0, kb0, r0, c0, m0, m1, n0, n1, l0, l1, o);
    l0 += __shfl_xor_sync(0xffffffffu, l0, 1); l0 += __shfl_xor_sync(0xffffffffu, l0, 2);
    l1 += __shfl_xor_sync(0xffffffffu, l1, 1); l1 += __shfl_xor_sync(0xffffffffu, l1, 2);
    const float f0 = g0 / l0, f1 = g1 / l1;
#pragma unroll
    for (int t = 0; t < 2; t++) {
        *(uint32_t*)(out + (size_t)r0 * KA2 + t * 8 + c0) = pack_bf16(o[t][0] * f0, o[t][1] * f0);
        *(uint32_t*)(out + (size_t)(r0 + 8) * KA2 + t * 8 + c0) = pack_bf16(o[t][2] * f1, o[t][3] * f1);
    }
}

constexpr int K2_SMEM = 2 * 384 * KV_PITCH + 1024 + 64;

__global__ void __launch_bounds__(512, 1) k2_kernel(const __grid_constant__ CUtensorMap tmQKV)
{
    extern __shared__ uint8_t smem_raw[];
    const uint32_t sbase = (smem_u32(smem_raw) + 1023u) & ~1023u;
    uint8_t* sgen = smem_raw + (sbase - smem_u32(smem_raw));
    const uint32_t sK = sbase, sV = sK + 384 * KV_PITCH, kv_full = sbase + 2 * 384 * KV_PITCH;
    const int rb = blockIdx.x >> 3, j = blockIdx.x & 7;
    const int tid = threadIdx.x, warp = tid >> 5, lane = tid & 31;
    TS(6, tid == 0);
    if (tid == 0) {
        mbar_init(kv_full, 1);
        fence_barrier_init();
        const int nblk = rb >= 2 ? 3 : rb + 1;
        mbar_expect_tx(kv_full, nblk * 2 * 16384);
        for (int i = 0; i < nblk; i++) {
            const int row = j * S_ + (rb - i) * 128;
            tma_load_2d(sK + (2 - i) * 16384, &tmQKV, 64, row, kv_full);
            tma_load_2d(sV + (2 - i) * 16384, &tmQKV, 128, row, kv_full);
        }
    }
    if (rb < 2) {
        for (int i = tid; i < (2 - rb) * 1024; i += 512) {
            *(uint4*)(sgen + i * 16) = make_uint4(0, 0, 0, 0);
            *(uint4*)(sgen + 384 * KV_PITCH + i * 16) = make_uint4(0, 0, 0, 0);
        }
    }
    const int qt = warp & 7, h0 = (warp >> 3) * 2;
    const int q0g = rb * 128 + qt * 16;
    const int r0 = lane >> 2, c0 = (lane & 3) * 2;
    const bf16* qsrc = g_qkv + ((size_t)j * S_ + q0g) * 192 + h0 * 16;
    uint32_t qa[4], qn[4];
    qa[0] = *(const uint32_t*)(qsrc + (size_t)r0 * 192 + c0);
    qa[1] = *(const uint32_t*)(qsrc + (size_t)(r0 + 8) * 192 + c0);
    qa[2] = *(const uint32_t*)(qsrc + (size_t)r0 * 192 + c0 + 8);
    qa[3] = *(const uint32_t*)(qsrc + (size_t)(r0 + 8) * 192 + c0 + 8);
    qn[0] = *(const uint32_t*)(qsrc + (size_t)r0 * 192 + 16 + c0);
    qn[1] = *(const uint32_t*)(qsrc + (size_t)(r0 + 8) * 192 + 16 + c0);
    qn[2] = *(const uint32_t*)(qsrc + (size_t)r0 * 192 + 16 + c0 + 8);
    qn[3] = *(const uint32_t*)(qsrc + (size_t)(r0 + 8) * 192 + 16 + c0 + 8);
    const float g0 = g_gate[q0g + r0], g1 = g_gate[q0g + r0 + 8];
    const int kb0 = q0g < 256 ? (256 - q0g) >> 4 : 0;
    __syncthreads();
    mbar_wait(kv_full, 0);
    uint32_t sKd = sK, sVd = sV;
    asm volatile("" : "+r"(sKd), "+r"(sVd) :: "memory");
    TS(7, tid == 0);
    const int krow = qt * 16 + (lane & 7) + ((lane >> 4) << 3);
    const int vrow = qt * 16 + (lane & 15);
#pragma unroll 1
    for (int hh = 0; hh < 2; hh++) {
        const int hl = h0 + hh;
        const uint32_t ka = sKd + krow * KV_PITCH + (((2 * hl + ((lane >> 3) & 1)) ^ (lane & 7)) << 4);
        const uint32_t va = sVd + vrow * KV_PITCH + (((2 * hl + (lane >> 4)) ^ (lane & 7)) << 4);
        if (rb < 2) attn_task<true>(qa, ka, va, kb0, lane, g_a2 + (size_t)q0g * KA2 + (j * 4 + hl) * 16, g0, g1);
        else        attn_task<false>(qa, ka, va, kb0, lane, g_a2 + (size_t)q0g * KA2 + (j * 4 + hl) * 16, g0, g1);
        TS(8 + hh, tid == 0);
        qa[0] = qn[0]; qa[1] = qn[1]; qa[2] = qn[2]; qa[3] = qn[3];
    }
}

constexpr int K3_STAGES = 8;
constexpr int K3_STAGE = 16384 + 8192;
constexpr int K3_SMEM = K3_STAGES * K3_STAGE + 1024 + 1024;
constexpr int K3_KSTEPS = 30;

__global__ void __launch_bounds__(384, 1)
k3_kernel(const __grid_constant__ CUtensorMap tmA2, const __grid_constant__ CUtensorMap tmWo,
          const __grid_constant__ CUtensorMap tmW2, bf16* __restrict__ out)
{
    extern __shared__ uint8_t smem_raw[];
    const uint32_t sbase = (smem_u32(smem_raw) + 1023u) & ~1023u;
    const uint32_t sBar = sbase + K3_STAGES * K3_STAGE;
    const uint32_t full = sBar, empty = sBar + 64;
    const int rb = blockIdx.x >> 3, nb = blockIdx.x & 7;
    const int tid = threadIdx.x, wg = tid >> 7, warp = tid >> 5, lane = tid & 31;
    TS(10, tid == 0);
    if (tid == 0) {
        for (int i = 0; i < K3_STAGES; i++) { mbar_init(full + 8 * i, 1); mbar_init(empty + 8 * i, 8); }
        fence_barrier_init();
    }
    __syncthreads();
    if (wg == 2) {
        reg_dealloc<40>();
        if (tid == 256) {
            for (int ks = 0; ks < K3_KSTEPS; ks++) {
                const int st = ks % K3_STAGES;
                if (ks >= K3_STAGES) mbar_wait(empty + 8 * st, ((ks / K3_STAGES) - 1) & 1);
                mbar_expect_tx(full + 8 * st, K3_STAGE);
                const uint32_t dst = sbase + st * K3_STAGE;
                tma_load_2d(dst, &tmA2, ks * 64, rb * 128, full + 8 * st);
                if (ks < 8) tma_load_2d(dst + 16384, &tmWo, nb * 64, ks * 64, full + 8 * st);
                else        tma_load_2d(dst + 16384, &tmW2, nb * 64, (ks - 8) * 64, full + 8 * st);
            }
        }
    } else {
        reg_alloc<232>();
        float acc[32];
        for (int ks = 0; ks < K3_KSTEPS; ks++) {
            const int st = ks % K3_STAGES;
            mbar_wait(full + 8 * st, (ks / K3_STAGES) & 1);
            TS(11, tid == 0 && ks == 0); TS(12, tid == 0 && ks == 8); TS(13, tid == 0 && ks == 16);
            wgmma_fence();
#pragma unroll
            for (int k16 = 0; k16 < 4; k16++) {
                const uint64_t da = make_desc(sbase + st * K3_STAGE + wg * 8192 + k16 * 32, 16, 1024);
                const uint64_t db = make_desc(sbase + st * K3_STAGE + 16384 + k16 * 2048, 8192, 1024);
                wgmma_n64<1>(acc, da, db, (ks | k16) != 0);
            }
            wgmma_commit();
            if (ks > 0) { wgmma_wait<1>(); if (lane == 0) mbar_arrive(empty + 8 * ((ks - 1) % K3_STAGES)); }
        }
        wgmma_wait<0>();
        TS(14, tid == 0);
        const int q = lane & 3;
        const int r = rb * 128 + wg * 64 + (warp & 3) * 16 + (lane >> 2);
        bf16* orow0 = out + (size_t)r * D_ + nb * 64;
        bf16* orow1 = orow0 + 8 * D_;
#pragma unroll
        for (int u = 0; u < 2; u++) {
            uint32_t w0[4], w1[4];
#pragma unroll
            for (int i = 0; i < 4; i++) {
                const int t = u * 4 + i;
                w0[i] = pack_bf16(acc[t * 4 + 0], acc[t * 4 + 1]);
                w1[i] = pack_bf16(acc[t * 4 + 2], acc[t * 4 + 3]);
            }
            quad_transpose(w0, q);
            quad_transpose(w1, q);
            const int c = (u * 4 + q) * 8;
            *(uint4*)(orow0 + c) = make_uint4(w0[0], w0[1], w0[2], w0[3]);
            *(uint4*)(orow1 + c) = make_uint4(w1[0], w1[1], w1[2], w1[3]);
        }
        TS(15, tid == 0);
    }
}

typedef CUresult (*PFN_encodeTiled)(CUtensorMap*, CUtensorMapDataType, cuuint32_t, void*, const cuuint64_t*,
                                    const cuuint64_t*, const cuuint32_t*, const cuuint32_t*, CUtensorMapInterleave,
                                    CUtensorMapSwizzle, CUtensorMapL2promotion, CUtensorMapFloatOOBfill);

static void make_map(PFN_encodeTiled enc, CUtensorMap* m, const void* ptr, uint64_t cols, uint64_t rows,
                     uint32_t box_cols, uint32_t box_rows)
{
    cuuint64_t dims[2] = {cols, rows};
    cuuint64_t strides[1] = {cols * 2};
    cuuint32_t box[2] = {box_cols, box_rows};
    cuuint32_t es[2] = {1, 1};
    enc(m, CU_TENSOR_MAP_DATA_TYPE_BFLOAT16, 2, const_cast<void*>(ptr), dims, strides, box, es,
        CU_TENSOR_MAP_INTERLEAVE_NONE, CU_TENSOR_MAP_SWIZZLE_128B, CU_TENSOR_MAP_L2_PROMOTION_L2_128B,
        CU_TENSOR_MAP_FLOAT_OOB_FILL_NONE);
}

extern "C" void kernel_launch(void* const* d_in, const int* in_sizes, int n_in, void* d_out, int out_size)
{
    const bf16* x    = (const bf16*)d_in[0];
    const bf16* wqkv = (const bf16*)d_in[1];
    const bf16* wo   = (const bf16*)d_in[2];
    const bf16* w1   = (const bf16*)d_in[4];
    const bf16* b1   = (const bf16*)d_in[5];
    const bf16* w2   = (const bf16*)d_in[6];
    const bf16* gw   = (const bf16*)d_in[7];

    static PFN_encodeTiled enc = nullptr;
    if (!enc) {
        void* fn = nullptr;
        cudaDriverEntryPointQueryResult qr;
        cudaGetDriverEntryPoint("cuTensorMapEncodeTiled", &fn, cudaEnableDefault, &qr);
        enc = (PFN_encodeTiled)fn;
        cudaFuncSetAttribute(k1_kernel, cudaFuncAttributeMaxDynamicSharedMemorySize, K1_SMEM);
        cudaFuncSetAttribute(k2_kernel, cudaFuncAttributeMaxDynamicSharedMemorySize, K2_SMEM);
        cudaFuncSetAttribute(k3_kernel, cudaFuncAttributeMaxDynamicSharedMemorySize, K3_SMEM);
    }
    void* a2p = nullptr;
    cudaGetSymbolAddress(&a2p, g_a2);
    void* qkvp = nullptr;
    cudaGetSymbolAddress(&qkvp, g_qkv);
    CUtensorMap tmX, tmWqkv, tmW1, tmA2, tmWo, tmW2, tmQKV;
    make_map(enc, &tmQKV, qkvp, 192, 8 * S_, 64, 128);
    make_map(enc, &tmX, x, D_, S_, 64, 128);
    make_map(enc, &tmWqkv, wqkv, 3 * D_, D_, 64, 64);
    make_map(enc, &tmW1, w1, F_, D_, 64, 64);
    make_map(enc, &tmA2, a2p, KA2, S_, 64, 128);
    make_map(enc, &tmWo, wo, D_, D_, 64, 64);
    make_map(enc, &tmW2, w2, D_, F_, 64, 64);

    cudaStream_t st = cudaStreamPerThread;
    k1_kernel<<<128, 384, K1_SMEM, st>>>(tmX, tmWqkv, tmW1, b1, gw, w1, wqkv, w2, wo);
    k2_kernel<<<128, 512, K2_SMEM, st>>>(tmQKV);
    k3_kernel<<<128, 384, K3_SMEM, st>>>(tmA2, tmWo, tmW2, (bf16*)d_out);
}
```

```cpp
#include <cuda_runtime.h>
#include <cuda_bf16.h>
#include <cuda.h>
#include <stdint.h>

typedef __nv_bfloat16 bf16;

constexpr int S_ = 2048, D_ = 512, F_ = 1376;
constexpr int KA2 = D_ + F_;
constexpr int FCH = 176;

__device__ bf16  g_qkv[8 * S_ * 192];
__device__ bf16  g_a2[S_ * KA2];
__device__ float g_gate[S_];

#define TS(k, cond) do { } while (0)

__device__ __forceinline__ uint32_t smem_u32(const void* p) { return (uint32_t)__cvta_generic_to_shared(p); }
__device__ __forceinline__ void mbar_init(uint32_t bar, uint32_t count) {
    asm volatile("mbarrier.init.shared::cta.b64 [%0], %1;" :: "r"(bar), "r"(count) : "memory");
}
__device__ __forceinline__ void mbar_expect_tx(uint32_t bar, uint32_t bytes) {
    asm volatile("mbarrier.arrive.expect_tx.shared::cta.b64 _, [%0], %1;" :: "r"(bar), "r"(bytes) : "memory");
}
__device__ __forceinline__ void mbar_arrive(uint32_t bar) {
    asm volatile("mbarrier.arrive.shared::cta.b64 _, [%0];" :: "r"(bar) : "memory");
}
__device__ __forceinline__ bool mbar_try_wait(uint32_t bar, uint32_t parity) {
    uint32_t ok;
    asm volatile("{\n.reg .pred p;\nmbarrier.try_wait.parity.shared::cta.b64 p, [%1], %2;\nselp.u32 %0, 1, 0, p;\n}"
                 : "=r"(ok) : "r"(bar), "r"(parity) : "memory");
    return ok != 0;
}
__device__ __forceinline__ void mbar_wait(uint32_t bar, uint32_t parity) {
    for (uint32_t it = 0; it < (1u << 22); ++it) { if (mbar_try_wait(bar, parity)) break; }
}
__device__ __forceinline__ void tma_load_2d(uint32_t dst, const CUtensorMap* map, int c0, int c1, uint32_t bar) {
    asm volatile("cp.async.bulk.tensor.2d.shared::cluster.global.mbarrier::complete_tx::bytes [%0], [%1, {%3, %4}], [%2];"
                 :: "r"(dst), "l"(map), "r"(bar), "r"(c0), "r"(c1) : "memory");
}
__device__ __forceinline__ void l2_prefetch(const void* p, uint32_t bytes) {
    asm volatile("cp.async.bulk.prefetch.L2.global [%0], %1;" :: "l"(p), "r"(bytes) : "memory");
}
__device__ __forceinline__ void fence_barrier_init() { asm volatile("fence.mbarrier_init.release.cluster;" ::: "memory"); }
__device__ __forceinline__ void wgmma_fence()  { asm volatile("wgmma.fence.sync.aligned;" ::: "memory"); }
__device__ __forceinline__ void wgmma_commit() { asm volatile("wgmma.commit_group.sync.aligned;" ::: "memory"); }
template <int N> __device__ __forceinline__ void wgmma_wait() { asm volatile("wgmma.wait_group.sync.aligned %0;" :: "n"(N) : "memory"); }
template <int R> __device__ __forceinline__ void reg_alloc()   { asm volatile("setmaxnreg.inc.sync.aligned.u32 %0;" :: "n"(R)); }
template <int R> __device__ __forceinline__ void reg_dealloc() { asm volatile("setmaxnreg.dec.sync.aligned.u32 %0;" :: "n"(R)); }
__device__ __forceinline__ void bar_sync(int id, int n)   { asm volatile("bar.sync %0, %1;" :: "r"(id), "r"(n) : "memory"); }
__device__ __forceinline__ void bar_arrive(int id, int n) { asm volatile("bar.arrive %0, %1;" :: "r"(id), "r"(n) : "memory"); }

__device__ __forceinline__ uint64_t make_desc(uint32_t addr, uint32_t lbo, uint32_t sbo) {
    uint64_t d = (uint64_t)((addr & 0x3FFFF) >> 4);
    d |= (uint64_t)((lbo & 0x3FFFF) >> 4) << 16;
    d |= (uint64_t)((sbo & 0x3FFFF) >> 4) << 32;
    d |= (uint64_t)1 << 62;
    return d;
}

template <int TB>
__device__ __forceinline__ void wgmma_n64(float (&d)[32], uint64_t da, uint64_t db, int scale_d) {
    asm volatile("{\n.reg .pred p;\nsetp.ne.b32 p, %34, 0;\n"
        "wgmma.mma_async.sync.aligned.m64n64k16.f32.bf16.bf16 {%0, %1, %2, %3, %4, %5, %6, %7, %8, %9, %10, %11, %12, %13, %14, %15, %16, %17, %18, %19, %20, %21, %22, %23, %24, %25, %26, %27, %28, %29, %30, %31}, %32, %33, p, 1, 1, 0, %35;\n}\n"
        : "+f"(d[0]), "+f"(d[1]), "+f"(d[2]), "+f"(d[3]), "+f"(d[4]), "+f"(d[5]), "+f"(d[6]), "+f"(d[7]), "+f"(d[8]), "+f"(d[9]), "+f"(d[10]), "+f"(d[11]), "+f"(d[12]), "+f"(d[13]), "+f"(d[14]), "+f"(d[15]), "+f"(d[16]), "+f"(d[17]), "+f"(d[18]), "+f"(d[19]), "+f"(d[20]), "+f"(d[21]), "+f"(d[22]), "+f"(d[23]), "+f"(d[24]), "+f"(d[25]), "+f"(d[26]), "+f"(d[27]), "+f"(d[28]), "+f"(d[29]), "+f"(d[30]), "+f"(d[31])
        : "l"(da), "l"(db), "r"(scale_d), "n"(TB));
}

template <int TB>
__device__ __forceinline__ void wgmma_n128(float (&d)[64], uint64_t da, uint64_t db, int scale_d) {
    asm volatile("{\n.reg .pred p;\nsetp.ne.b32 p, %66, 0;\n"
        "wgmma.mma_async.sync.aligned.m64n128k16.f32.bf16.bf16 {%0, %1, %2, %3, %4, %5, %6, %7, %8, %9, %10, %11, %12, %13, %14, %15, %16, %17, %18, %19, %20, %21, %22, %23, %24, %25, %26, %27, %28, %29, %30, %31, %32, %33, %34, %35, %36, %37, %38, %39, %40, %41, %42, %43, %44, %45, %46, %47, %48, %49, %50, %51, %52, %53, %54, %55, %56, %57, %58, %59, %60, %61, %62, %63}, %64, %65, p, 1, 1, 0, %67;\n}\n"
        : "+f"(d[0]), "+f"(d[1]), "+f"(d[2]), "+f"(d[3]), "+f"(d[4]), "+f"(d[5]), "+f"(d[6]), "+f"(d[7]), "+f"(d[8]), "+f"(d[9]), "+f"(d[10]), "+f"(d[11]), "+f"(d[12]), "+f"(d[13]), "+f"(d[14]), "+f"(d[15]), "+f"(d[16]), "+f"(d[17]), "+f"(d[18]), "+f"(d[19]), "+f"(d[20]), "+f"(d[21]), "+f"(d[22]), "+f"(d[23]), "+f"(d[24]), "+f"(d[25]), "+f"(d[26]), "+f"(d[27]), "+f"(d[28]), "+f"(d[29]), "+f"(d[30]), "+f"(d[31]), "+f"(d[32]), "+f"(d[33]), "+f"(d[34]), "+f"(d[35]), "+f"(d[36]), "+f"(d[37]), "+f"(d[38]), "+f"(d[39]), "+f"(d[40]), "+f"(d[41]), "+f"(d[42]), "+f"(d[43]), "+f"(d[44]), "+f"(d[45]), "+f"(d[46]), "+f"(d[47]), "+f"(d[48]), "+f"(d[49]), "+f"(d[50]), "+f"(d[51]), "+f"(d[52]), "+f"(d[53]), "+f"(d[54]), "+f"(d[55]), "+f"(d[56]), "+f"(d[57]), "+f"(d[58]), "+f"(d[59]), "+f"(d[60]), "+f"(d[61]), "+f"(d[62]), "+f"(d[63])
        : "l"(da), "l"(db), "r"(scale_d), "n"(TB));
}

template <int TB>
__device__ __forceinline__ void wgmma_n176(float (&d)[88], uint64_t da, uint64_t db, int scale_d) {
    asm volatile("{\n.reg .pred p;\nsetp.ne.b32 p, %90, 0;\n"
        "wgmma.mma_async.sync.aligned.m64n176k16.f32.bf16.bf16 {%0, %1, %2, %3, %4, %5, %6, %7, %8, %9, %10, %11, %12, %13, %14, %15, %16, %17, %18, %19, %20, %21, %22, %23, %24, %25, %26, %27, %28, %29, %30, %31, %32, %33, %34, %35, %36, %37, %38, %39, %40, %41, %42, %43, %44, %45, %46, %47, %48, %49, %50, %51, %52, %53, %54, %55, %56, %57, %58, %59, %60, %61, %62, %63, %64, %65, %66, %67, %68, %69, %70, %71, %72, %73, %74, %75, %76, %77, %78, %79, %80, %81, %82, %83, %84, %85, %86, %87}, %88, %89, p, 1, 1, 0, %91;\n}\n"
        : "+f"(d[0]), "+f"(d[1]), "+f"(d[2]), "+f"(d[3]), "+f"(d[4]), "+f"(d[5]), "+f"(d[6]), "+f"(d[7]), "+f"(d[8]), "+f"(d[9]), "+f"(d[10]), "+f"(d[11]), "+f"(d[12]), "+f"(d[13]), "+f"(d[14]), "+f"(d[15]), "+f"(d[16]), "+f"(d[17]), "+f"(d[18]), "+f"(d[19]), "+f"(d[20]), "+f"(d[21]), "+f"(d[22]), "+f"(d[23]), "+f"(d[24]), "+f"(d[25]), "+f"(d[26]), "+f"(d[27]), "+f"(d[28]), "+f"(d[29]), "+f"(d[30]), "+f"(d[31]), "+f"(d[32]), "+f"(d[33]), "+f"(d[34]), "+f"(d[35]), "+f"(d[36]), "+f"(d[37]), "+f"(d[38]), "+f"(d[39]), "+f"(d[40]), "+f"(d[41]), "+f"(d[42]), "+f"(d[43]), "+f"(d[44]), "+f"(d[45]), "+f"(d[46]), "+f"(d[47]), "+f"(d[48]), "+f"(d[49]), "+f"(d[50]), "+f"(d[51]), "+f"(d[52]), "+f"(d[53]), "+f"(d[54]), "+f"(d[55]), "+f"(d[56]), "+f"(d[57]), "+f"(d[58]), "+f"(d[59]), "+f"(d[60]), "+f"(d[61]), "+f"(d[62]), "+f"(d[63]), "+f"(d[64]), "+f"(d[65]), "+f"(d[66]), "+f"(d[67]), "+f"(d[68]), "+f"(d[69]), "+f"(d[70]), "+f"(d[71]), "+f"(d[72]), "+f"(d[73]), "+f"(d[74]), "+f"(d[75]), "+f"(d[76]), "+f"(d[77]), "+f"(d[78]), "+f"(d[79]), "+f"(d[80]), "+f"(d[81]), "+f"(d[82]), "+f"(d[83]), "+f"(d[84]), "+f"(d[85]), "+f"(d[86]), "+f"(d[87])
        : "l"(da), "l"(db), "r"(scale_d), "n"(TB));
}

template <int TB>
__device__ __forceinline__ void wgmma_n192(float (&d)[96], uint64_t da, uint64_t db, int scale_d) {
    asm volatile("{\n.reg .pred p;\nsetp.ne.b32 p, %98, 0;\n"
        "wgmma.mma_async.sync.aligned.m64n192k16.f32.bf16.bf16 {%0, %1, %2, %3, %4, %5, %6, %7, %8, %9, %10, %11, %12, %13, %14, %15, %16, %17, %18, %19, %20, %21, %22, %23, %24, %25, %26, %27, %28, %29, %30, %31, %32, %33, %34, %35, %36, %37, %38, %39, %40, %41, %42, %43, %44, %45, %46, %47, %48, %49, %50, %51, %52, %53, %54, %55, %56, %57, %58, %59, %60, %61, %62, %63, %64, %65, %66, %67, %68, %69, %70, %71, %72, %73, %74, %75, %76, %77, %78, %79, %80, %81, %82, %83, %84, %85, %86, %87, %88, %89, %90, %91, %92, %93, %94, %95}, %96, %97, p, 1, 1, 0, %99;\n}\n"
        : "+f"(d[0]), "+f"(d[1]), "+f"(d[2]), "+f"(d[3]), "+f"(d[4]), "+f"(d[5]), "+f"(d[6]), "+f"(d[7]), "+f"(d[8]), "+f"(d[9]), "+f"(d[10]), "+f"(d[11]), "+f"(d[12]), "+f"(d[13]), "+f"(d[14]), "+f"(d[15]), "+f"(d[16]), "+f"(d[17]), "+f"(d[18]), "+f"(d[19]), "+f"(d[20]), "+f"(d[21]), "+f"(d[22]), "+f"(d[23]), "+f"(d[24]), "+f"(d[25]), "+f"(d[26]), "+f"(d[27]), "+f"(d[28]), "+f"(d[29]), "+f"(d[30]), "+f"(d[31]), "+f"(d[32]), "+f"(d[33]), "+f"(d[34]), "+f"(d[35]), "+f"(d[36]), "+f"(d[37]), "+f"(d[38]), "+f"(d[39]), "+f"(d[40]), "+f"(d[41]), "+f"(d[42]), "+f"(d[43]), "+f"(d[44]), "+f"(d[45]), "+f"(d[46]), "+f"(d[47]), "+f"(d[48]), "+f"(d[49]), "+f"(d[50]), "+f"(d[51]), "+f"(d[52]), "+f"(d[53]), "+f"(d[54]), "+f"(d[55]), "+f"(d[56]), "+f"(d[57]), "+f"(d[58]), "+f"(d[59]), "+f"(d[60]), "+f"(d[61]), "+f"(d[62]), "+f"(d[63]), "+f"(d[64]), "+f"(d[65]), "+f"(d[66]), "+f"(d[67]), "+f"(d[68]), "+f"(d[69]), "+f"(d[70]), "+f"(d[71]), "+f"(d[72]), "+f"(d[73]), "+f"(d[74]), "+f"(d[75]), "+f"(d[76]), "+f"(d[77]), "+f"(d[78]), "+f"(d[79]), "+f"(d[80]), "+f"(d[81]), "+f"(d[82]), "+f"(d[83]), "+f"(d[84]), "+f"(d[85]), "+f"(d[86]), "+f"(d[87]), "+f"(d[88]), "+f"(d[89]), "+f"(d[90]), "+f"(d[91]), "+f"(d[92]), "+f"(d[93]), "+f"(d[94]), "+f"(d[95])
        : "l"(da), "l"(db), "r"(scale_d), "n"(TB));
}

__device__ __forceinline__ uint32_t pack_bf16(float lo, float hi) {
    uint32_t r;
    asm("cvt.rn.bf16x2.f32 %0, %1, %2;" : "=r"(r) : "f"(hi), "f"(lo));
    return r;
}
__device__ __forceinline__ float bf_lo(uint32_t v) { return __uint_as_float(v << 16); }
__device__ __forceinline__ float bf_hi(uint32_t v) { return __uint_as_float(v & 0xffff0000u); }

__device__ __forceinline__ void quad_transpose(uint32_t (&w)[4], int q) {
    const bool o1 = q & 1, o2 = q & 2;
    {
        uint32_t s0 = o1 ? w[0] : w[1], s1 = o1 ? w[2] : w[3];
        s0 = __shfl_xor_sync(0xffffffffu, s0, 1); s1 = __shfl_xor_sync(0xffffffffu, s1, 1);
        if (o1) { w[0] = s0; w[2] = s1; } else { w[1] = s0; w[3] = s1; }
    }
    {
        uint32_t s0 = o2 ? w[0] : w[2], s1 = o2 ? w[1] : w[3];
        s0 = __shfl_xor_sync(0xffffffffu, s0, 2); s1 = __shfl_xor_sync(0xffffffffu, s1, 2);
        if (o2) { w[0] = s0; w[1] = s1; } else { w[2] = s0; w[3] = s1; }
    }
}

__device__ __forceinline__ float ex2(float x) { float y; asm("ex2.approx.ftz.f32 %0, %1;" : "=f"(y) : "f"(x)); return y; }
__device__ __forceinline__ float rcp(float x) { float y; asm("rcp.approx.ftz.f32 %0, %1;" : "=f"(y) : "f"(x)); return y; }

__device__ __forceinline__ float ex2v(float x) { float y; asm volatile("ex2.approx.ftz.f32 %0, %1;" : "=f"(y) : "f"(x)); return y; }
__device__ __forceinline__ float rcpv(float x) { float y; asm volatile("rcp.approx.ftz.f32 %0, %1;" : "=f"(y) : "f"(x)); return y; }
__device__ __forceinline__ float mish_f(float h) {
    const float e = ex2v(1.4426950408889634f * fminf(h, 20.f));
    const float n = fmaf(e, e, e + e);
    return h * n * rcpv(n + 2.f);
}

__device__ __forceinline__ void pdl_wait()   { asm volatile("griddepcontrol.wait;" ::: "memory"); }
__device__ __forceinline__ void pdl_launch() { asm volatile("griddepcontrol.launch_dependents;" ::: "memory"); }

constexpr int K1_STAGES = 4;
constexpr int K1_XBYTES = 128 * 512 * 2;
constexpr int K1_BSTAGE = 3 * 8192;
constexpr int K1_SMEM   = K1_XBYTES + K1_STAGES * K1_BSTAGE + 2048   + 1024  ;

__global__ void __launch_bounds__(384, 1)
k1_kernel(const __grid_constant__ CUtensorMap tmX, const __grid_constant__ CUtensorMap tmWqkv,
          const __grid_constant__ CUtensorMap tmW1, const bf16* __restrict__ b1,
          const bf16* __restrict__ gate_w, const bf16* __restrict__ w1p, const bf16* __restrict__ wqkvp,
          const bf16* __restrict__ w2p, const bf16* __restrict__ wop)
{

    extern __shared__ uint8_t smem_raw[];
    const uint32_t sbase = (smem_u32(smem_raw) + 1023u) & ~1023u;
    uint8_t* sgen = smem_raw + (sbase - smem_u32(smem_raw));
    const uint32_t sX = sbase;
    const uint32_t sB = sbase + K1_XBYTES;
    const uint32_t sBar = sB + K1_STAGES * K1_BSTAGE;
    const uint32_t x_full = sBar;
    const uint32_t b_full = sBar + 64;
    const uint32_t b_empty = sBar + 96;
    float* sGate = (float*)(sgen + K1_XBYTES + K1_STAGES * K1_BSTAGE + 128);
    uint8_t* sGw = sgen + K1_XBYTES + K1_STAGES * K1_BSTAGE + 640;
    uint32_t* sBias = (uint32_t*)(sgen + K1_XBYTES + K1_STAGES * K1_BSTAGE + 1664);

    const int rb = blockIdx.x >> 3, j = blockIdx.x & 7;
    const int tid = threadIdx.x, wg = tid >> 7, warp = tid >> 5, lane = tid & 31;
    TS(0, tid == 0);
    pdl_launch();

    if (tid == 0) {
        for (int i = 0; i < 8; i++) mbar_init(x_full + 8 * i, 1);
        for (int i = 0; i < K1_STAGES; i++) { mbar_init(b_full + 8 * i, 1); mbar_init(b_empty + 8 * i, 8); }
        fence_barrier_init();
    }
    __syncthreads();

    if (wg == 2) {
        reg_dealloc<40>();
        if (tid == 288) {
            const int b = blockIdx.x;
            mbar_wait(b_full + 8, 0);
            l2_prefetch((const uint8_t*)wqkvp + b * 12288, 12288);
            l2_prefetch((const uint8_t*)w2p + b * 11008, 11008);
            l2_prefetch((const uint8_t*)wop + b * 4096, 4096);
        }
        if (tid == 256) {
            for (int it = 0; it < 16; it++) {
                if (it < 8) {
                    mbar_expect_tx(x_full + 8 * it, 16384);
                    tma_load_2d(sX + it * 16384, &tmX, it * 64, rb * 128, x_full + 8 * it);
                }
                const int st = it & 3;
                if (it >= K1_STAGES) mbar_wait(b_empty + 8 * st, ((it >> 2) - 1) & 1);
                mbar_expect_tx(b_full + 8 * st, K1_BSTAGE);
                const uint32_t dst = sB + st * K1_BSTAGE;
                if (it < 8) {
                    for (int b = 0; b < 3; b++) tma_load_2d(dst + b * 8192, &tmW1, j * FCH + b * 64, it * 64, b_full + 8 * st);
                } else {
                    for (int b = 0; b < 3; b++) tma_load_2d(dst + b * 8192, &tmWqkv, b * 512 + j * 64, (it - 8) * 64, b_full + 8 * st);
                }
            }
        }
    } else {
        reg_alloc<232>();
        if (tid < 64) ((uint4*)sGw)[tid] = __ldg((const uint4*)gate_w + tid);
        else if (tid < 64 + 88) {
            const int c = j * FCH + (tid - 64) * 2;
            sBias[tid - 64] = c < F_ ? __ldg((const uint32_t*)(b1 + c)) : 0u;
        }
        bar_sync(3, 256);
        const int t128 = tid & 127, w4 = warp & 3, q = lane & 3;
        float accF[88], accQ[96];
        float gs = 0.f;
        const int grow = wg * 64 + (t128 >> 1), ghalf = t128 & 1;
#pragma unroll
        for (int kc = 0; kc < 8; kc++) {
            const int st = kc & 3;
            mbar_wait(x_full + 8 * kc, 0);
            mbar_wait(b_full + 8 * st, (kc >> 2) & 1);
            TS(1, tid == 0 && kc == 0); TS(2, tid == 0 && kc == 4);
            wgmma_fence();
#pragma unroll
            for (int k16 = 0; k16 < 4; k16++) {
                const uint64_t db = make_desc(sB + st * K1_BSTAGE + k16 * 2048, 8192, 1024);
                const uint64_t da = make_desc(sX + kc * 16384 + wg * 8192 + k16 * 32, 16, 1024);
                wgmma_n176<1>(accF, da, db, (kc | k16) != 0);
            }
            wgmma_commit();
#pragma unroll
            for (int c = 0; c < 4; c++) {
                const int cc = ghalf * 4 + c;
                const uint4 xv = *(const uint4*)(sgen + kc * 16384 + grow * 128 + ((cc ^ (grow & 7)) << 4));
                const uint4 gv = *(const uint4*)(sGw + kc * 128 + cc * 16);
                gs = fmaf(bf_lo(xv.x), bf_lo(gv.x), gs); gs = fmaf(bf_hi(xv.x), bf_hi(gv.x), gs);
                gs = fmaf(bf_lo(xv.y), bf_lo(gv.y), gs); gs = fmaf(bf_hi(xv.y), bf_hi(gv.y), gs);
                gs = fmaf(bf_lo(xv.z), bf_lo(gv.z), gs); gs = fmaf(bf_hi(xv.z), bf_hi(gv.z), gs);
                gs = fmaf(bf_lo(xv.w), bf_lo(gv.w), gs); gs = fmaf(bf_hi(xv.w), bf_hi(gv.w), gs);
            }
            if (kc > 0) { wgmma_wait<1>(); if (lane == 0) mbar_arrive(b_empty + 8 * ((kc - 1) & 3)); }
        }
        gs += __shfl_xor_sync(0xffffffffu, gs, 1);
        {
            const float g = 1.f / (1.f + __expf(-gs));
            if (ghalf == 0) {
                sGate[grow] = g;
                if (j == 0) g_gate[rb * 128 + grow] = g;
            }
        }
        wgmma_wait<0>();
        if (lane == 0) mbar_arrive(b_empty + 8 * 3);
        bar_sync(1 + wg, 128);
        TS(3, tid == 0);
        const int n0 = j * FCH;
        const int rl = wg * 64 + w4 * 16 + (lane >> 2);
        const float om0 = 1.f - sGate[rl], om1 = 1.f - sGate[rl + 8];
        bf16* frow0 = g_a2 + (size_t)(rb * 128 + rl) * KA2 + D_ + n0;
        bf16* frow1 = frow0 + 8 * KA2;
#pragma unroll
        for (int kc = 0; kc < 8; kc++) {
            const int st = kc & 3;
            mbar_wait(b_full + 8 * st, ((kc + 8) >> 2) & 1);
            wgmma_fence();
#pragma unroll
            for (int k16 = 0; k16 < 4; k16++) {
                const uint64_t db = make_desc(sB + st * K1_BSTAGE + k16 * 2048, 8192, 1024);
                const uint64_t da = make_desc(sX + kc * 16384 + wg * 8192 + k16 * 32, 16, 1024);
                wgmma_n192<1>(accQ, da, db, (kc | k16) != 0);
            }
            wgmma_commit();
            if (kc < 6) {
                const int u = kc;
                uint32_t w0[4], w1[4];
#pragma unroll
                for (int i = 0; i < 4; i++) {
                    const int t = u * 4 + i;
                    if (t < 22) {
                        const uint32_t bv = sBias[t * 4 + q];
                        const float bb0 = bf_lo(bv), bb1 = bf_hi(bv);
                        w0[i] = pack_bf16(mish_f(accF[t * 4 + 0] + bb0) * om0, mish_f(accF[t * 4 + 1] + bb1) * om0);
                        w1[i] = pack_bf16(mish_f(accF[t * 4 + 2] + bb0) * om1, mish_f(accF[t * 4 + 3] + bb1) * om1);
                    } else { w0[i] = 0; w1[i] = 0; }
                }
                quad_transpose(w0, q);
                quad_transpose(w1, q);
                const int c = (u * 4 + q) * 8;
                if (c < FCH && n0 + c < F_) {
                    *(uint4*)(frow0 + c) = make_uint4(w0[0], w0[1], w0[2], w0[3]);
                    *(uint4*)(frow1 + c) = make_uint4(w1[0], w1[1], w1[2], w1[3]);
                }
            }
            if (kc > 0) { wgmma_wait<1>(); if (lane == 0) mbar_arrive(b_empty + 8 * ((kc - 1) & 3)); }
        }
        wgmma_wait<0>();
        TS(4, tid == 0);
        {
            bf16* orow0 = g_qkv + ((size_t)j * S_ + rb * 128 + rl) * 192;
            bf16* orow1 = orow0 + 8 * 192;
#pragma unroll
            for (int u = 0; u < 6; u++) {
                uint32_t w0[4], w1[4];
#pragma unroll
                for (int i = 0; i < 4; i++) {
                    const int t = u * 4 + i;
                    w0[i] = pack_bf16(accQ[t * 4 + 0], accQ[t * 4 + 1]);
                    w1[i] = pack_bf16(accQ[t * 4 + 2], accQ[t * 4 + 3]);
                }
                quad_transpose(w0, q);
                quad_transpose(w1, q);
                const int c = (u * 4 + q) * 8;
                *(uint4*)(orow0 + c) = make_uint4(w0[0], w0[1], w0[2], w0[3]);
                *(uint4*)(orow1 + c) = make_uint4(w1[0], w1[1], w1[2], w1[3]);
            }
        }
        TS(5, tid == 0);
    }
}

__device__ __forceinline__ void ldsm_x4(uint32_t (&r)[4], uint32_t addr) {
    asm("ldmatrix.sync.aligned.m8n8.x4.shared.b16 {%0,%1,%2,%3}, [%4];"
                 : "=r"(r[0]), "=r"(r[1]), "=r"(r[2]), "=r"(r[3]) : "r"(addr));
}
__device__ __forceinline__ void ldsm_x4_t(uint32_t (&r)[4], uint32_t addr) {
    asm("ldmatrix.sync.aligned.m8n8.x4.trans.shared.b16 {%0,%1,%2,%3}, [%4];"
                 : "=r"(r[0]), "=r"(r[1]), "=r"(r[2]), "=r"(r[3]) : "r"(addr));
}
__device__ __forceinline__ void mma16816(float (&d)[4], const uint32_t (&a)[4], uint32_t b0, uint32_t b1) {
    asm("mma.sync.aligned.m16n8k16.row.col.f32.bf16.bf16.f32 {%0,%1,%2,%3}, {%4,%5,%6,%7}, {%8,%9}, {%0,%1,%2,%3};"
                 : "+f"(d[0]), "+f"(d[1]), "+f"(d[2]), "+f"(d[3])
                 : "r"(a[0]), "r"(a[1]), "r"(a[2]), "r"(a[3]), "r"(b0), "r"(b1));
}
__device__ __forceinline__ void mma16816_z(float (&d)[4], const uint32_t (&a)[4], uint32_t b0, uint32_t b1) {
    asm("mma.sync.aligned.m16n8k16.row.col.f32.bf16.bf16.f32 {%0,%1,%2,%3}, {%4,%5,%6,%7}, {%8,%9}, {%10,%10,%10,%10};"
                 : "=f"(d[0]), "=f"(d[1]), "=f"(d[2]), "=f"(d[3])
                 : "r"(a[0]), "r"(a[1]), "r"(a[2]), "r"(a[3]), "r"(b0), "r"(b1), "f"(0.f));
}

constexpr int KV_PITCH = 128;

template <int EDGE, bool HEAD>
__device__ __forceinline__ void blk_scores(float (&s)[2][4], const uint32_t (&qa)[4], uint32_t kaddr, bool dead, int r0, int c0)
{
    uint32_t kf[4];
    ldsm_x4(kf, kaddr);
    mma16816_z(s[0], qa, kf[0], kf[1]);
    mma16816_z(s[1], qa, kf[2], kf[3]);
#pragma unroll
    for (int t = 0; t < 2; t++)
#pragma unroll
        for (int e = 0; e < 4; e++) {
            const int r = r0 + (e >> 1) * 8, c = t * 8 + c0 + (e & 1);
            if (EDGE == 1 && c <= r) s[t][e] = -1e30f;
            if (EDGE == 2 && c > r) s[t][e] = -1e30f;
            if (HEAD && dead) s[t][e] = -1e30f;
        }
}
__device__ __forceinline__ void blk_max(const float (&s)[2][4], float& n0, float& n1) {
    n0 = fmaxf(n0, fmaxf(fmaxf(s[0][0], s[0][1]), fmaxf(s[1][0], s[1][1])));
    n1 = fmaxf(n1, fmaxf(fmaxf(s[0][2], s[0][3]), fmaxf(s[1][2], s[1][3])));
}
__device__ __forceinline__ void blk_pv(const float (&s)[2][4], float mc0, float mc1, float& l0, float& l1,
                                       float (&o)[2][4], uint32_t vaddr) {
    const float C = 0.25f * 1.4426950408889634f;
    uint32_t pa[4];
#pragma unroll
    for (int t = 0; t < 2; t++) {
        const float p0 = ex2(fmaf(s[t][0], C, -mc0)), p1 = ex2(fmaf(s[t][1], C, -mc0));
        const float p2 = ex2(fmaf(s[t][2], C, -mc1)), p3 = ex2(fmaf(s[t][3], C, -mc1));
        l0 += p0 + p1; l1 += p2 + p3;
        pa[2 * t] = pack_bf16(p0, p1); pa[2 * t + 1] = pack_bf16(p2, p3);
    }
    uint32_t vf[4];
    ldsm_x4_t(vf, vaddr);
    mma16816(o[0], pa, vf[0], vf[1]);
    mma16816(o[1], pa, vf[2], vf[3]);
}
__device__ __forceinline__ void quad_max(float& n0, float& n1) {
    n0 = fmaxf(n0, __shfl_xor_sync(0xffffffffu, n0, 1)); n1 = fmaxf(n1, __shfl_xor_sync(0xffffffffu, n1, 1));
    n0 = fmaxf(n0, __shfl_xor_sync(0xffffffffu, n0, 2)); n1 = fmaxf(n1, __shfl_xor_sync(0xffffffffu, n1, 2));
}
template <int NC, int NN, bool FIRST, bool NEXT_IS_EDGE, bool HEAD>
__device__ __forceinline__ void pipe_step(const float (&sc)[5][2][4], float (&sn)[5][2][4], const uint32_t (&qa)[4],
                                          uint32_t ka, uint32_t va, int kc, int kn, int kb0, int r0, int c0,
                                          float& m0, float& m1, float& n0, float& n1, float& l0, float& l1, float (&o)[2][4])
{
    const float C = 0.25f * 1.4426950408889634f;
    const float mc0 = n0 * C, mc1 = n1 * C;
    if (!FIRST) {
        const float a0 = ex2(fmaf(m0, C, -mc0)), a1 = ex2(fmaf(m1, C, -mc1));
        l0 *= a0; l1 *= a1;
        o[0][0] *= a0; o[0][1] *= a0; o[1][0] *= a0; o[1][1] *= a0;
        o[0][2] *= a1; o[0][3] *= a1; o[1][2] *= a1; o[1][3] *= a1;
    }
    m0 = n0; m1 = n1;
#pragma unroll
    for (int b = 0; b < NC; b++) {
        if (b < NN) {
            if (NEXT_IS_EDGE && b == 0) blk_scores<1, HEAD>(sn[b], qa, ka + (kn + b) * 16 * KV_PITCH, kn + b < kb0, r0, c0);
            else                        blk_scores<0, HEAD>(sn[b], qa, ka + (kn + b) * 16 * KV_PITCH, kn + b < kb0, r0, c0);
        }
        blk_pv(sc[b], mc0, mc1, l0, l1, o, va + (kc + b) * 16 * KV_PITCH);
        if (b < NN) blk_max(sn[b], n0, n1);
    }
    if (NN > 0) quad_max(n0, n1);
}

template <bool HEAD>
__device__ __forceinline__ void attn_task(const uint32_t (&qa)[4], uint32_t ka, uint32_t va, int kb0, int lane,
                                          bf16* __restrict__ out  , float g0, float g1)
{
    const int r0 = lane >> 2, c0 = (lane & 3) * 2;
    float m0 = -1e30f, m1 = -1e30f, n0 = -1e30f, n1 = -1e30f, l0 = 0.f, l1 = 0.f;
    float o[2][4] = {{0.f, 0.f, 0.f, 0.f}, {0.f, 0.f, 0.f, 0.f}};
    float sa[5][2][4], sb[5][2][4];
#pragma unroll
    for (int b = 0; b < 5; b++) {
        if (b == 4) blk_scores<2, HEAD>(sa[b], qa, ka + (12 + b) * 16 * KV_PITCH, false, r0, c0);
        else        blk_scores<0, HEAD>(sa[b], qa, ka + (12 + b) * 16 * KV_PITCH, 12 + b < kb0, r0, c0);
        blk_max(sa[b], n0, n1);
    }
    quad_max(n0, n1);
    pipe_step<5, 4, true,  false, HEAD>(sa, sb, qa, ka, va, 12, 8, kb0, r0, c0, m0, m1, n0, n1, l0, l1, o);
    pipe_step<4, 4, false, false, HEAD>(sb, sa, qa, ka, va, 8, 4, kb0, r0, c0, m0, m1, n0, n1, l0, l1, o);
    pipe_step<4, 4, false, true,  HEAD>(sa, sb, qa, ka, va, 4, 0, kb0, r0, c0, m0, m1, n0, n1, l0, l1, o);
    pipe_step<4, 0, false, false, HEAD>(sb, sa, qa, ka, va, 0, 0, kb0, r0, c0, m0, m1, n0, n1, l0, l1, o);
    l0 += __shfl_xor_sync(0xffffffffu, l0, 1); l0 += __shfl_xor_sync(0xffffffffu, l0, 2);
    l1 += __shfl_xor_sync(0xffffffffu, l1, 1); l1 += __shfl_xor_sync(0xffffffffu, l1, 2);
    const float f0 = g0 / l0, f1 = g1 / l1;
#pragma unroll
    for (int t = 0; t < 2; t++) {
        *(uint32_t*)(out + (size_t)r0 * KA2 + t * 8 + c0) = pack_bf16(o[t][0] * f0, o[t][1] * f0);
        *(uint32_t*)(out + (size_t)(r0 + 8) * KA2 + t * 8 + c0) = pack_bf16(o[t][2] * f1, o[t][3] * f1);
    }
}

constexpr int K2_SMEM = 2 * 384 * KV_PITCH + 1024 + 64;

__global__ void __launch_bounds__(512, 1) k2_kernel(const __grid_constant__ CUtensorMap tmQKV)
{
    extern __shared__ uint8_t smem_raw[];
    const uint32_t sbase = (smem_u32(smem_raw) + 1023u) & ~1023u;
    uint8_t* sgen = smem_raw + (sbase - smem_u32(smem_raw));
    const uint32_t sK = sbase, sV = sK + 384 * KV_PITCH, kv_full = sbase + 2 * 384 * KV_PITCH;
    const int rb = blockIdx.x >> 3, j = blockIdx.x & 7;
    const int tid = threadIdx.x, warp = tid >> 5, lane = tid & 31;
    pdl_launch();
    if (tid == 0) {
        mbar_init(kv_full, 1);
        fence_barrier_init();
    }
    pdl_wait();
    TS(6, tid == 0);
    if (tid == 0) {
        const int nblk = rb >= 2 ? 3 : rb + 1;
        mbar_expect_tx(kv_full, nblk * 2 * 16384);
        for (int i = 0; i < nblk; i++) {
            const int row = j * S_ + (rb - i) * 128;
            tma_load_2d(sK + (2 - i) * 16384, &tmQKV, 64, row, kv_full);
            tma_load_2d(sV + (2 - i) * 16384, &tmQKV, 128, row, kv_full);
        }
    }
    if (rb < 2) {
        for (int i = tid; i < (2 - rb) * 1024; i += 512) {
            *(uint4*)(sgen + i * 16) = make_uint4(0, 0, 0, 0);
            *(uint4*)(sgen + 384 * KV_PITCH + i * 16) = make_uint4(0, 0, 0, 0);
        }
    }
    const int qt = warp & 7, h0 = (warp >> 3) * 2;
    const int q0g = rb * 128 + qt * 16;
    const int r0 = lane >> 2, c0 = (lane & 3) * 2;
    const bf16* qsrc = g_qkv + ((size_t)j * S_ + q0g) * 192 + h0 * 16;
    uint32_t qa[4], qn[4];
    qa[0] = *(const uint32_t*)(qsrc + (size_t)r0 * 192 + c0);
    qa[1] = *(const uint32_t*)(qsrc + (size_t)(r0 + 8) * 192 + c0);
    qa[2] = *(const uint32_t*)(qsrc + (size_t)r0 * 192 + c0 + 8);
    qa[3] = *(const uint32_t*)(qsrc + (size_t)(r0 + 8) * 192 + c0 + 8);
    qn[0] = *(const uint32_t*)(qsrc + (size_t)r0 * 192 + 16 + c0);
    qn[1] = *(const uint32_t*)(qsrc + (size_t)(r0 + 8) * 192 + 16 + c0);
    qn[2] = *(const uint32_t*)(qsrc + (size_t)r0 * 192 + 16 + c0 + 8);
    qn[3] = *(const uint32_t*)(qsrc + (size_t)(r0 + 8) * 192 + 16 + c0 + 8);
    const float g0 = g_gate[q0g + r0], g1 = g_gate[q0g + r0 + 8];
    const int kb0 = q0g < 256 ? (256 - q0g) >> 4 : 0;
    __syncthreads();
    mbar_wait(kv_full, 0);
    uint32_t sKd = sK, sVd = sV;
    asm volatile("" : "+r"(sKd), "+r"(sVd) :: "memory");
    TS(7, tid == 0);
    const int krow = qt * 16 + (lane & 7) + ((lane >> 4) << 3);
    const int vrow = qt * 16 + (lane & 15);
#pragma unroll 1
    for (int hh = 0; hh < 2; hh++) {
        const int hl = h0 + hh;
        const uint32_t ka = sKd + krow * KV_PITCH + (((2 * hl + ((lane >> 3) & 1)) ^ (lane & 7)) << 4);
        const uint32_t va = sVd + vrow * KV_PITCH + (((2 * hl + (lane >> 4)) ^ (lane & 7)) << 4);
        if (rb < 2) attn_task<true>(qa, ka, va, kb0, lane, g_a2 + (size_t)q0g * KA2 + (j * 4 + hl) * 16, g0, g1);
        else        attn_task<false>(qa, ka, va, kb0, lane, g_a2 + (size_t)q0g * KA2 + (j * 4 + hl) * 16, g0, g1);
        TS(8 + hh, tid == 0);
        qa[0] = qn[0]; qa[1] = qn[1]; qa[2] = qn[2]; qa[3] = qn[3];
    }
}

constexpr int K3_STAGES = 8;
constexpr int K3_STAGE = 16384 + 8192;
constexpr int K3_SMEM = K3_STAGES * K3_STAGE + 1024 + 1024;
constexpr int K3_KSTEPS = 30;

__global__ void __launch_bounds__(384, 1)
k3_kernel(const __grid_constant__ CUtensorMap tmA2, const __grid_constant__ CUtensorMap tmWo,
          const __grid_constant__ CUtensorMap tmW2, bf16* __restrict__ out)
{
    extern __shared__ uint8_t smem_raw[];
    const uint32_t sbase = (smem_u32(smem_raw) + 1023u) & ~1023u;
    const uint32_t sBar = sbase + K3_STAGES * K3_STAGE;
    const uint32_t full = sBar, empty = sBar + 64;
    const int rb = blockIdx.x >> 3, nb = blockIdx.x & 7;
    const int tid = threadIdx.x, wg = tid >> 7, warp = tid >> 5, lane = tid & 31;
    if (tid == 0) {
        for (int i = 0; i < K3_STAGES; i++) { mbar_init(full + 8 * i, 1); mbar_init(empty + 8 * i, 8); }
        fence_barrier_init();
    }
    __syncthreads();
    pdl_wait();
    TS(10, tid == 0);
    if (wg == 2) {
        reg_dealloc<40>();
        if (tid == 256) {
            for (int ks = 0; ks < K3_KSTEPS; ks++) {
                const int st = ks % K3_STAGES;
                if (ks >= K3_STAGES) mbar_wait(empty + 8 * st, ((ks / K3_STAGES) - 1) & 1);
                mbar_expect_tx(full + 8 * st, K3_STAGE);
                const uint32_t dst = sbase + st * K3_STAGE;
                tma_load_2d(dst, &tmA2, ks * 64, rb * 128, full + 8 * st);
                if (ks < 8) tma_load_2d(dst + 16384, &tmWo, nb * 64, ks * 64, full + 8 * st);
                else        tma_load_2d(dst + 16384, &tmW2, nb * 64, (ks - 8) * 64, full + 8 * st);
            }
        }
    } else {
        reg_alloc<232>();
        float acc[32];
        for (int ks = 0; ks < K3_KSTEPS; ks++) {
            const int st = ks % K3_STAGES;
            mbar_wait(full + 8 * st, (ks / K3_STAGES) & 1);
            TS(11, tid == 0 && ks == 0); TS(12, tid == 0 && ks == 8); TS(13, tid == 0 && ks == 16);
            wgmma_fence();
#pragma unroll
            for (int k16 = 0; k16 < 4; k16++) {
                const uint64_t da = make_desc(sbase + st * K3_STAGE + wg * 8192 + k16 * 32, 16, 1024);
                const uint64_t db = make_desc(sbase + st * K3_STAGE + 16384 + k16 * 2048, 8192, 1024);
                wgmma_n64<1>(acc, da, db, (ks | k16) != 0);
            }
            wgmma_commit();
            if (ks > 0) { wgmma_wait<1>(); if (lane == 0) mbar_arrive(empty + 8 * ((ks - 1) % K3_STAGES)); }
        }
        wgmma_wait<0>();
        TS(14, tid == 0);
        const int q = lane & 3;
        const int r = rb * 128 + wg * 64 + (warp & 3) * 16 + (lane >> 2);
        bf16* orow0 = out + (size_t)r * D_ + nb * 64;
        bf16* orow1 = orow0 + 8 * D_;
#pragma unroll
        for (int u = 0; u < 2; u++) {
            uint32_t w0[4], w1[4];
#pragma unroll
            for (int i = 0; i < 4; i++) {
                const int t = u * 4 + i;
                w0[i] = pack_bf16(acc[t * 4 + 0], acc[t * 4 + 1]);
                w1[i] = pack_bf16(acc[t * 4 + 2], acc[t * 4 + 3]);
            }
            quad_transpose(w0, q);
            quad_transpose(w1, q);
            const int c = (u * 4 + q) * 8;
            *(uint4*)(orow0 + c) = make_uint4(w0[0], w0[1], w0[2], w0[3]);
            *(uint4*)(orow1 + c) = make_uint4(w1[0], w1[1], w1[2], w1[3]);
        }
        TS(15, tid == 0);
    }
}

typedef CUresult (*PFN_encodeTiled)(CUtensorMap*, CUtensorMapDataType, cuuint32_t, void*, const cuuint64_t*,
                                    const cuuint64_t*, const cuuint32_t*, const cuuint32_t*, CUtensorMapInterleave,
                                    CUtensorMapSwizzle, CUtensorMapL2promotion, CUtensorMapFloatOOBfill);

static void make_map(PFN_encodeTiled enc, CUtensorMap* m, const void* ptr, uint64_t cols, uint64_t rows,
                     uint32_t box_cols, uint32_t box_rows)
{
    cuuint64_t dims[2] = {cols, rows};
    cuuint64_t strides[1] = {cols * 2};
    cuuint32_t box[2] = {box_cols, box_rows};
    cuuint32_t es[2] = {1, 1};
    enc(m, CU_TENSOR_MAP_DATA_TYPE_BFLOAT16, 2, const_cast<void*>(ptr), dims, strides, box, es,
        CU_TENSOR_MAP_INTERLEAVE_NONE, CU_TENSOR_MAP_SWIZZLE_128B, CU_TENSOR_MAP_L2_PROMOTION_L2_128B,
        CU_TENSOR_MAP_FLOAT_OOB_FILL_NONE);
}

extern "C" void kernel_launch(void* const* d_in, const int* in_sizes, int n_in, void* d_out, int out_size)
{
    const bf16* x    = (const bf16*)d_in[0];
    const bf16* wqkv = (const bf16*)d_in[1];
    const bf16* wo   = (const bf16*)d_in[2];
    const bf16* w1   = (const bf16*)d_in[4];
    const bf16* b1   = (const bf16*)d_in[5];
    const bf16* w2   = (const bf16*)d_in[6];
    const bf16* gw   = (const bf16*)d_in[7];

    static PFN_encodeTiled enc = nullptr;
    if (!enc) {
        void* fn = nullptr;
        cudaDriverEntryPointQueryResult qr;
        cudaGetDriverEntryPoint("cuTensorMapEncodeTiled", &fn, cudaEnableDefault, &qr);
        enc = (PFN_encodeTiled)fn;
        cudaFuncSetAttribute(k1_kernel, cudaFuncAttributeMaxDynamicSharedMemorySize, K1_SMEM);
        cudaFuncSetAttribute(k2_kernel, cudaFuncAttributeMaxDynamicSharedMemorySize, K2_SMEM);
        cudaFuncSetAttribute(k3_kernel, cudaFuncAttributeMaxDynamicSharedMemorySize, K3_SMEM);
    }
    void* a2p = nullptr;
    cudaGetSymbolAddress(&a2p, g_a2);
    void* qkvp = nullptr;
    cudaGetSymbolAddress(&qkvp, g_qkv);
    CUtensorMap tmX, tmWqkv, tmW1, tmA2, tmWo, tmW2, tmQKV;
    make_map(enc, &tmQKV, qkvp, 192, 8 * S_, 64, 128);
    make_map(enc, &tmX, x, D_, S_, 64, 128);
    make_map(enc, &tmWqkv, wqkv, 3 * D_, D_, 64, 64);
    make_map(enc, &tmW1, w1, F_, D_, 64, 64);
    make_map(enc, &tmA2, a2p, KA2, S_, 64, 128);
    make_map(enc, &tmWo, wo, D_, D_, 64, 64);
    make_map(enc, &tmW2, w2, D_, F_, 64, 64);

    cudaStream_t st = cudaStreamPerThread;
    k1_kernel<<<128, 384, K1_SMEM, st>>>(tmX, tmWqkv, tmW1, b1, gw, w1, wqkv, w2, wo);
    cudaLaunchAttribute at[1];
    at[0].id = cudaLaunchAttributeProgrammaticStreamSerialization;
    at[0].val.programmaticStreamSerializationAllowed = 1;
    cudaLaunchConfig_t cfg = {};
    cfg.gridDim = dim3(128); cfg.stream = st; cfg.attrs = at; cfg.numAttrs = 1;
    cfg.blockDim = dim3(512); cfg.dynamicSmemBytes = K2_SMEM;
    cudaLaunchKernelEx(&cfg, k2_kernel, tmQKV);
    cfg.blockDim = dim3(384); cfg.dynamicSmemBytes = K3_SMEM;
    cudaLaunchKernelEx(&cfg, k3_kernel, tmA2, tmWo, tmW2, (bf16*)d_out);
}
```

```cpp
#include <cuda_runtime.h>
#include <cuda_bf16.h>
#include <cuda.h>
#include <stdint.h>

typedef __nv_bfloat16 bf16;

constexpr int S_ = 2048, D_ = 512, F_ = 1376;
constexpr int KA2 = D_ + F_;
constexpr int FCH = 176;

__device__ bf16  g_qkv[8 * S_ * 192];
__device__ bf16  g_a2[S_ * KA2];
__device__ float g_gate[S_];

#define TS(k, cond) do { } while (0)

__device__ __forceinline__ uint32_t smem_u32(const void* p) { return (uint32_t)__cvta_generic_to_shared(p); }
__device__ __forceinline__ void mbar_init(uint32_t bar, uint32_t count) {
    asm volatile("mbarrier.init.shared::cta.b64 [%0], %1;" :: "r"(bar), "r"(count) : "memory");
}
__device__ __forceinline__ void mbar_expect_tx(uint32_t bar, uint32_t bytes) {
    asm volatile("mbarrier.arrive.expect_tx.shared::cta.b64 _, [%0], %1;" :: "r"(bar), "r"(bytes) : "memory");
}
__device__ __forceinline__ void mbar_arrive(uint32_t bar) {
    asm volatile("mbarrier.arrive.shared::cta.b64 _, [%0];" :: "r"(bar) : "memory");
}
__device__ __forceinline__ bool mbar_try_wait(uint32_t bar, uint32_t parity) {
    uint32_t ok;
    asm volatile("{\n.reg .pred p;\nmbarrier.try_wait.parity.shared::cta.b64 p, [%1], %2;\nselp.u32 %0, 1, 0, p;\n}"
                 : "=r"(ok) : "r"(bar), "r"(parity) : "memory");
    return ok != 0;
}
__device__ __forceinline__ void mbar_wait(uint32_t bar, uint32_t parity) {
    for (uint32_t it = 0; it < (1u << 22); ++it) { if (mbar_try_wait(bar, parity)) break; }
}
__device__ __forceinline__ void tma_load_2d(uint32_t dst, const CUtensorMap* map, int c0, int c1, uint32_t bar) {
    asm volatile("cp.async.bulk.tensor.2d.shared::cluster.global.mbarrier::complete_tx::bytes [%0], [%1, {%3, %4}], [%2];"
                 :: "r"(dst), "l"(map), "r"(bar), "r"(c0), "r"(c1) : "memory");
}
__device__ __forceinline__ void l2_prefetch(const void* p, uint32_t bytes) {
    asm volatile("cp.async.bulk.prefetch.L2.global [%0], %1;" :: "l"(p), "r"(bytes) : "memory");
}
__device__ __forceinline__ void fence_barrier_init() { asm volatile("fence.mbarrier_init.release.cluster;" ::: "memory"); }
__device__ __forceinline__ void wgmma_fence()  { asm volatile("wgmma.fence.sync.aligned;" ::: "memory"); }
__device__ __forceinline__ void wgmma_commit() { asm volatile("wgmma.commit_group.sync.aligned;" ::: "memory"); }
template <int N> __device__ __forceinline__ void wgmma_wait() { asm volatile("wgmma.wait_group.sync.aligned %0;" :: "n"(N) : "memory"); }
template <int R> __device__ __forceinline__ void reg_alloc()   { asm volatile("setmaxnreg.inc.sync.aligned.u32 %0;" :: "n"(R)); }
template <int R> __device__ __forceinline__ void reg_dealloc() { asm volatile("setmaxnreg.dec.sync.aligned.u32 %0;" :: "n"(R)); }
__device__ __forceinline__ void bar_sync(int id, int n)   { asm volatile("bar.sync %0, %1;" :: "r"(id), "r"(n) : "memory"); }
__device__ __forceinline__ void bar_arrive(int id, int n) { asm volatile("bar.arrive %0, %1;" :: "r"(id), "r"(n) : "memory"); }

__device__ __forceinline__ uint64_t make_desc(uint32_t addr, uint32_t lbo, uint32_t sbo) {
    uint64_t d = (uint64_t)((addr & 0x3FFFF) >> 4);
    d |= (uint64_t)((lbo & 0x3FFFF) >> 4) << 16;
    d |= (uint64_t)((sbo & 0x3FFFF) >> 4) << 32;
    d |= (uint64_t)1 << 62;
    return d;
}

template <int TB>
__device__ __forceinline__ void wgmma_n64(float (&d)[32], uint64_t da, uint64_t db, int scale_d) {
    asm volatile("{\n.reg .pred p;\nsetp.ne.b32 p, %34, 0;\n"
        "wgmma.mma_async.sync.aligned.m64n64k16.f32.bf16.bf16 {%0, %1, %2, %3, %4, %5, %6, %7, %8, %9, %10, %11, %12, %13, %14, %15, %16, %17, %18, %19, %20, %21, %22, %23, %24, %25, %26, %27, %28, %29, %30, %31}, %32, %33, p, 1, 1, 0, %35;\n}\n"
        : "+f"(d[0]), "+f"(d[1]), "+f"(d[2]), "+f"(d[3]), "+f"(d[4]), "+f"(d[5]), "+f"(d[6]), "+f"(d[7]), "+f"(d[8]), "+f"(d[9]), "+f"(d[10]), "+f"(d[11]), "+f"(d[12]), "+f"(d[13]), "+f"(d[14]), "+f"(d[15]), "+f"(d[16]), "+f"(d[17]), "+f"(d[18]), "+f"(d[19]), "+f"(d[20]), "+f"(d[21]), "+f"(d[22]), "+f"(d[23]), "+f"(d[24]), "+f"(d[25]), "+f"(d[26]), "+f"(d[27]), "+f"(d[28]), "+f"(d[29]), "+f"(d[30]), "+f"(d[31])
        : "l"(da), "l"(db), "r"(scale_d), "n"(TB));
}

template <int TB>
__device__ __forceinline__ void wgmma_n128(float (&d)[64], uint64_t da, uint64_t db, int scale_d) {
    asm volatile("{\n.reg .pred p;\nsetp.ne.b32 p, %66, 0;\n"
        "wgmma.mma_async.sync.aligned.m64n128k16.f32.bf16.bf16 {%0, %1, %2, %3, %4, %5, %6, %7, %8, %9, %10, %11, %12, %13, %14, %15, %16, %17, %18, %19, %20, %21, %22, %23, %24, %25, %26, %27, %28, %29, %30, %31, %32, %33, %34, %35, %36, %37, %38, %39, %40, %41, %42, %43, %44, %45, %46, %47, %48, %49, %50, %51, %52, %53, %54, %55, %56, %57, %58, %59, %60, %61, %62, %63}, %64, %65, p, 1, 1, 0, %67;\n}\n"
        : "+f"(d[0]), "+f"(d[1]), "+f"(d[2]), "+f"(d[3]), "+f"(d[4]), "+f"(d[5]), "+f"(d[6]), "+f"(d[7]), "+f"(d[8]), "+f"(d[9]), "+f"(d[10]), "+f"(d[11]), "+f"(d[12]), "+f"(d[13]), "+f"(d[14]), "+f"(d[15]), "+f"(d[16]), "+f"(d[17]), "+f"(d[18]), "+f"(d[19]), "+f"(d[20]), "+f"(d[21]), "+f"(d[22]), "+f"(d[23]), "+f"(d[24]), "+f"(d[25]), "+f"(d[26]), "+f"(d[27]), "+f"(d[28]), "+f"(d[29]), "+f"(d[30]), "+f"(d[31]), "+f"(d[32]), "+f"(d[33]), "+f"(d[34]), "+f"(d[35]), "+f"(d[36]), "+f"(d[37]), "+f"(d[38]), "+f"(d[39]), "+f"(d[40]), "+f"(d[41]), "+f"(d[42]), "+f"(d[43]), "+f"(d[44]), "+f"(d[45]), "+f"(d[46]), "+f"(d[47]), "+f"(d[48]), "+f"(d[49]), "+f"(d[50]), "+f"(d[51]), "+f"(d[52]), "+f"(d[53]), "+f"(d[54]), "+f"(d[55]), "+f"(d[56]), "+f"(d[57]), "+f"(d[58]), "+f"(d[59]), "+f"(d[60]), "+f"(d[61]), "+f"(d[62]), "+f"(d[63])
        : "l"(da), "l"(db), "r"(scale_d), "n"(TB));
}

template <int TB>
__device__ __forceinline__ void wgmma_n176(float (&d)[88], uint64_t da, uint64_t db, int scale_d) {
    asm volatile("{\n.reg .pred p;\nsetp.ne.b32 p, %90, 0;\n"
        "wgmma.mma_async.sync.aligned.m64n176k16.f32.bf16.bf16 {%0, %1, %2, %3, %4, %5, %6, %7, %8, %9, %10, %11, %12, %13, %14, %15, %16, %17, %18, %19, %20, %21, %22, %23, %24, %25, %26, %27, %28, %29, %30, %31, %32, %33, %34, %35, %36, %37, %38, %39, %40, %41, %42, %43, %44, %45, %46, %47, %48, %49, %50, %51, %52, %53, %54, %55, %56, %57, %58, %59, %60, %61, %62, %63, %64, %65, %66, %67, %68, %69, %70, %71, %72, %73, %74, %75, %76, %77, %78, %79, %80, %81, %82, %83, %84, %85, %86, %87}, %88, %89, p, 1, 1, 0, %91;\n}\n"
        : "+f"(d[0]), "+f"(d[1]), "+f"(d[2]), "+f"(d[3]), "+f"(d[4]), "+f"(d[5]), "+f"(d[6]), "+f"(d[7]), "+f"(d[8]), "+f"(d[9]), "+f"(d[10]), "+f"(d[11]), "+f"(d[12]), "+f"(d[13]), "+f"(d[14]), "+f"(d[15]), "+f"(d[16]), "+f"(d[17]), "+f"(d[18]), "+f"(d[19]), "+f"(d[20]), "+f"(d[21]), "+f"(d[22]), "+f"(d[23]), "+f"(d[24]), "+f"(d[25]), "+f"(d[26]), "+f"(d[27]), "+f"(d[28]), "+f"(d[29]), "+f"(d[30]), "+f"(d[31]), "+f"(d[32]), "+f"(d[33]), "+f"(d[34]), "+f"(d[35]), "+f"(d[36]), "+f"(d[37]), "+f"(d[38]), "+f"(d[39]), "+f"(d[40]), "+f"(d[41]), "+f"(d[42]), "+f"(d[43]), "+f"(d[44]), "+f"(d[45]), "+f"(d[46]), "+f"(d[47]), "+f"(d[48]), "+f"(d[49]), "+f"(d[50]), "+f"(d[51]), "+f"(d[52]), "+f"(d[53]), "+f"(d[54]), "+f"(d[55]), "+f"(d[56]), "+f"(d[57]), "+f"(d[58]), "+f"(d[59]), "+f"(d[60]), "+f"(d[61]), "+f"(d[62]), "+f"(d[63]), "+f"(d[64]), "+f"(d[65]), "+f"(d[66]), "+f"(d[67]), "+f"(d[68]), "+f"(d[69]), "+f"(d[70]), "+f"(d[71]), "+f"(d[72]), "+f"(d[73]), "+f"(d[74]), "+f"(d[75]), "+f"(d[76]), "+f"(d[77]), "+f"(d[78]), "+f"(d[79]), "+f"(d[80]), "+f"(d[81]), "+f"(d[82]), "+f"(d[83]), "+f"(d[84]), "+f"(d[85]), "+f"(d[86]), "+f"(d[87])
        : "l"(da), "l"(db), "r"(scale_d), "n"(TB));
}

template <int TB>
__device__ __forceinline__ void wgmma_n192(float (&d)[96], uint64_t da, uint64_t db, int scale_d) {
    asm volatile("{\n.reg .pred p;\nsetp.ne.b32 p, %98, 0;\n"
        "wgmma.mma_async.sync.aligned.m64n192k16.f32.bf16.bf16 {%0, %1, %2, %3, %4, %5, %6, %7, %8, %9, %10, %11, %12, %13, %14, %15, %16, %17, %18, %19, %20, %21, %22, %23, %24, %25, %26, %27, %28, %29, %30, %31, %32, %33, %34, %35, %36, %37, %38, %39, %40, %41, %42, %43, %44, %45, %46, %47, %48, %49, %50, %51, %52, %53, %54, %55, %56, %57, %58, %59, %60, %61, %62, %63, %64, %65, %66, %67, %68, %69, %70, %71, %72, %73, %74, %75, %76, %77, %78, %79, %80, %81, %82, %83, %84, %85, %86, %87, %88, %89, %90, %91, %92, %93, %94, %95}, %96, %97, p, 1, 1, 0, %99;\n}\n"
        : "+f"(d[0]), "+f"(d[1]), "+f"(d[2]), "+f"(d[3]), "+f"(d[4]), "+f"(d[5]), "+f"(d[6]), "+f"(d[7]), "+f"(d[8]), "+f"(d[9]), "+f"(d[10]), "+f"(d[11]), "+f"(d[12]), "+f"(d[13]), "+f"(d[14]), "+f"(d[15]), "+f"(d[16]), "+f"(d[17]), "+f"(d[18]), "+f"(d[19]), "+f"(d[20]), "+f"(d[21]), "+f"(d[22]), "+f"(d[23]), "+f"(d[24]), "+f"(d[25]), "+f"(d[26]), "+f"(d[27]), "+f"(d[28]), "+f"(d[29]), "+f"(d[30]), "+f"(d[31]), "+f"(d[32]), "+f"(d[33]), "+f"(d[34]), "+f"(d[35]), "+f"(d[36]), "+f"(d[37]), "+f"(d[38]), "+f"(d[39]), "+f"(d[40]), "+f"(d[41]), "+f"(d[42]), "+f"(d[43]), "+f"(d[44]), "+f"(d[45]), "+f"(d[46]), "+f"(d[47]), "+f"(d[48]), "+f"(d[49]), "+f"(d[50]), "+f"(d[51]), "+f"(d[52]), "+f"(d[53]), "+f"(d[54]), "+f"(d[55]), "+f"(d[56]), "+f"(d[57]), "+f"(d[58]), "+f"(d[59]), "+f"(d[60]), "+f"(d[61]), "+f"(d[62]), "+f"(d[63]), "+f"(d[64]), "+f"(d[65]), "+f"(d[66]), "+f"(d[67]), "+f"(d[68]), "+f"(d[69]), "+f"(d[70]), "+f"(d[71]), "+f"(d[72]), "+f"(d[73]), "+f"(d[74]), "+f"(d[75]), "+f"(d[76]), "+f"(d[77]), "+f"(d[78]), "+f"(d[79]), "+f"(d[80]), "+f"(d[81]), "+f"(d[82]), "+f"(d[83]), "+f"(d[84]), "+f"(d[85]), "+f"(d[86]), "+f"(d[87]), "+f"(d[88]), "+f"(d[89]), "+f"(d[90]), "+f"(d[91]), "+f"(d[92]), "+f"(d[93]), "+f"(d[94]), "+f"(d[95])
        : "l"(da), "l"(db), "r"(scale_d), "n"(TB));
}

__device__ __forceinline__ uint32_t pack_bf16(float lo, float hi) {
    uint32_t r;
    asm("cvt.rn.bf16x2.f32 %0, %1, %2;" : "=r"(r) : "f"(hi), "f"(lo));
    return r;
}
__device__ __forceinline__ float bf_lo(uint32_t v) { return __uint_as_float(v << 16); }
__device__ __forceinline__ float bf_hi(uint32_t v) { return __uint_as_float(v & 0xffff0000u); }

__device__ __forceinline__ void quad_transpose(uint32_t (&w)[4], int q) {
    const bool o1 = q & 1, o2 = q & 2;
    {
        uint32_t s0 = o1 ? w[0] : w[1], s1 = o1 ? w[2] : w[3];
        s0 = __shfl_xor_sync(0xffffffffu, s0, 1); s1 = __shfl_xor_sync(0xffffffffu, s1, 1);
        if (o1) { w[0] = s0; w[2] = s1; } else { w[1] = s0; w[3] = s1; }
    }
    {
        uint32_t s0 = o2 ? w[0] : w[2], s1 = o2 ? w[1] : w[3];
        s0 = __shfl_xor_sync(0xffffffffu, s0, 2); s1 = __shfl_xor_sync(0xffffffffu, s1, 2);
        if (o2) { w[0] = s0; w[1] = s1; } else { w[2] = s0; w[3] = s1; }
    }
}

__device__ __forceinline__ float ex2(float x) { float y; asm("ex2.approx.ftz.f32 %0, %1;" : "=f"(y) : "f"(x)); return y; }
__device__ __forceinline__ float rcp(float x) { float y; asm("rcp.approx.ftz.f32 %0, %1;" : "=f"(y) : "f"(x)); return y; }

__device__ __forceinline__ float ex2v(float x) { float y; asm volatile("ex2.approx.ftz.f32 %0, %1;" : "=f"(y) : "f"(x)); return y; }
__device__ __forceinline__ float rcpv(float x) { float y; asm volatile("rcp.approx.ftz.f32 %0, %1;" : "=f"(y) : "f"(x)); return y; }
__device__ __forceinline__ float mish_f(float h) {
    const float e = ex2v(1.4426950408889634f * fminf(h, 20.f));
    const float n = fmaf(e, e, e + e);
    return h * n * rcpv(n + 2.f);
}

__device__ __forceinline__ void pdl_wait()   { asm volatile("griddepcontrol.wait;" ::: "memory"); }
__device__ __forceinline__ void pdl_launch() { asm volatile("griddepcontrol.launch_dependents;" ::: "memory"); }

constexpr int K1_STAGES = 4;
constexpr int K1_XBYTES = 128 * 512 * 2;
constexpr int K1_BSTAGE = 3 * 8192;
constexpr int K1_SMEM   = K1_XBYTES + K1_STAGES * K1_BSTAGE + 2048   + 1024  ;

__global__ void __launch_bounds__(384, 1)
k1_kernel(const __grid_constant__ CUtensorMap tmX, const __grid_constant__ CUtensorMap tmWqkv,
          const __grid_constant__ CUtensorMap tmW1, const bf16* __restrict__ b1,
          const bf16* __restrict__ gate_w, const bf16* __restrict__ w1p, const bf16* __restrict__ wqkvp,
          const bf16* __restrict__ w2p, const bf16* __restrict__ wop)
{

    extern __shared__ uint8_t smem_raw[];
    const uint32_t sbase = (smem_u32(smem_raw) + 1023u) & ~1023u;
    uint8_t* sgen = smem_raw + (sbase - smem_u32(smem_raw));
    const uint32_t sX = sbase;
    const uint32_t sB = sbase + K1_XBYTES;
    const uint32_t sBar = sB + K1_STAGES * K1_BSTAGE;
    const uint32_t x_full = sBar;
    const uint32_t b_full = sBar + 64;
    const uint32_t b_empty = sBar + 96;
    float* sGate = (float*)(sgen + K1_XBYTES + K1_STAGES * K1_BSTAGE + 128);
    uint8_t* sGw = sgen + K1_XBYTES + K1_STAGES * K1_BSTAGE + 640;
    uint32_t* sBias = (uint32_t*)(sgen + K1_XBYTES + K1_STAGES * K1_BSTAGE + 1664);

    const int rb = blockIdx.x >> 3, j = blockIdx.x & 7;
    const int tid = threadIdx.x, wg = tid >> 7, warp = tid >> 5, lane = tid & 31;
    TS(0, tid == 0);
    pdl_launch();

    if (tid == 0) {
        for (int i = 0; i < 8; i++) mbar_init(x_full + 8 * i, 1);
        for (int i = 0; i < K1_STAGES; i++) { mbar_init(b_full + 8 * i, 1); mbar_init(b_empty + 8 * i, 8); }
        fence_barrier_init();
    }
    __syncthreads();

    if (wg == 2) {
        reg_dealloc<40>();
        if (tid == 288) {
            const int b = blockIdx.x;
            mbar_wait(b_full + 8, 0);
            l2_prefetch((const uint8_t*)wqkvp + b * 12288, 12288);
            l2_prefetch((const uint8_t*)w2p + b * 11008, 11008);
            l2_prefetch((const uint8_t*)wop + b * 4096, 4096);
        }
        if (tid == 256) {
            for (int it = 0; it < 16; it++) {
                if (it < 8) {
                    mbar_expect_tx(x_full + 8 * it, 16384);
                    tma_load_2d(sX + it * 16384, &tmX, it * 64, rb * 128, x_full + 8 * it);
                }
                const int st = it & 3;
                if (it >= K1_STAGES) mbar_wait(b_empty + 8 * st, ((it >> 2) - 1) & 1);
                mbar_expect_tx(b_full + 8 * st, K1_BSTAGE);
                const uint32_t dst = sB + st * K1_BSTAGE;
                if (it < 8) {
                    for (int b = 0; b < 3; b++) tma_load_2d(dst + b * 8192, &tmW1, j * FCH + b * 64, it * 64, b_full + 8 * st);
                } else {
                    for (int b = 0; b < 3; b++) tma_load_2d(dst + b * 8192, &tmWqkv, b * 512 + j * 64, (it - 8) * 64, b_full + 8 * st);
                }
            }
        }
    } else {
        reg_alloc<232>();
        if (tid < 64) ((uint4*)sGw)[tid] = __ldg((const uint4*)gate_w + tid);
        else if (tid < 64 + 88) {
            const int c = j * FCH + (tid - 64) * 2;
            sBias[tid - 64] = c < F_ ? __ldg((const uint32_t*)(b1 + c)) : 0u;
        }
        bar_sync(3, 256);
        const int t128 = tid & 127, w4 = warp & 3, q = lane & 3;
        float accF[88], accQ[96];
        float gs = 0.f;
        const int grow = wg * 64 + (t128 >> 1), ghalf = t128 & 1;
#pragma unroll
        for (int kc = 0; kc < 8; kc++) {
            const int st = kc & 3;
            mbar_wait(x_full + 8 * kc, 0);
            mbar_wait(b_full + 8 * st, (kc >> 2) & 1);
            TS(1, tid == 0 && kc == 0); TS(2, tid == 0 && kc == 4);
            wgmma_fence();
#pragma unroll
            for (int k16 = 0; k16 < 4; k16++) {
                const uint64_t db = make_desc(sB + st * K1_BSTAGE + k16 * 2048, 8192, 1024);
                const uint64_t da = make_desc(sX + kc * 16384 + wg * 8192 + k16 * 32, 16, 1024);
                wgmma_n176<1>(accF, da, db, (kc | k16) != 0);
            }
            wgmma_commit();
#pragma unroll
            for (int c = 0; c < 4; c++) {
                const int cc = ghalf * 4 + c;
                const uint4 xv = *(const uint4*)(sgen + kc * 16384 + grow * 128 + ((cc ^ (grow & 7)) << 4));
                const uint4 gv = *(const uint4*)(sGw + kc * 128 + cc * 16);
                gs = fmaf(bf_lo(xv.x), bf_lo(gv.x), gs); gs = fmaf(bf_hi(xv.x), bf_hi(gv.x), gs);
                gs = fmaf(bf_lo(xv.y), bf_lo(gv.y), gs); gs = fmaf(bf_hi(xv.y), bf_hi(gv.y), gs);
                gs = fmaf(bf_lo(xv.z), bf_lo(gv.z), gs); gs = fmaf(bf_hi(xv.z), bf_hi(gv.z), gs);
                gs = fmaf(bf_lo(xv.w), bf_lo(gv.w), gs); gs = fmaf(bf_hi(xv.w), bf_hi(gv.w), gs);
            }
            if (kc > 0) { wgmma_wait<1>(); if (lane == 0) mbar_arrive(b_empty + 8 * ((kc - 1) & 3)); }
        }
        gs += __shfl_xor_sync(0xffffffffu, gs, 1);
        {
            const float g = 1.f / (1.f + __expf(-gs));
            if (ghalf == 0) {
                sGate[grow] = g;
                if (j == 0) g_gate[rb * 128 + grow] = g;
            }
        }
        wgmma_wait<0>();
        if (lane == 0) mbar_arrive(b_empty + 8 * 3);
        bar_sync(1 + wg, 128);
        TS(3, tid == 0);
        const int n0 = j * FCH;
        const int rl = wg * 64 + w4 * 16 + (lane >> 2);
        const float om0 = 1.f - sGate[rl], om1 = 1.f - sGate[rl + 8];
        bf16* frow0 = g_a2 + (size_t)(rb * 128 + rl) * KA2 + D_ + n0;
        bf16* frow1 = frow0 + 8 * KA2;
        auto ffn_chunk = [&](int u) {
            uint32_t w0[4], w1[4];
#pragma unroll
            for (int i = 0; i < 4; i++) {
                const int t = u * 4 + i;
                if (t < 22) {
                    const uint32_t bv = sBias[t * 4 + q];
                    const float bb0 = bf_lo(bv), bb1 = bf_hi(bv);
                    w0[i] = pack_bf16(mish_f(accF[t * 4 + 0] + bb0) * om0, mish_f(accF[t * 4 + 1] + bb1) * om0);
                    w1[i] = pack_bf16(mish_f(accF[t * 4 + 2] + bb0) * om1, mish_f(accF[t * 4 + 3] + bb1) * om1);
                } else { w0[i] = 0; w1[i] = 0; }
            }
            quad_transpose(w0, q);
            quad_transpose(w1, q);
            const int c = (u * 4 + q) * 8;
            if (c < FCH && n0 + c < F_) {
                *(uint4*)(frow0 + c) = make_uint4(w0[0], w0[1], w0[2], w0[3]);
                *(uint4*)(frow1 + c) = make_uint4(w1[0], w1[1], w1[2], w1[3]);
            }
        };
#pragma unroll
        for (int kc = 0; kc < 8; kc++) {
            const int st = kc & 3;
            if (kc < 6 && wg == 1) ffn_chunk(kc);
            mbar_wait(b_full + 8 * st, ((kc + 8) >> 2) & 1);
            wgmma_fence();
#pragma unroll
            for (int k16 = 0; k16 < 4; k16++) {
                const uint64_t db = make_desc(sB + st * K1_BSTAGE + k16 * 2048, 8192, 1024);
                const uint64_t da = make_desc(sX + kc * 16384 + wg * 8192 + k16 * 32, 16, 1024);
                wgmma_n192<1>(accQ, da, db, (kc | k16) != 0);
            }
            wgmma_commit();
            if (kc < 6 && wg == 0) ffn_chunk(kc);
            if (kc > 0) { wgmma_wait<1>(); if (lane == 0) mbar_arrive(b_empty + 8 * ((kc - 1) & 3)); }
        }
        wgmma_wait<0>();
        TS(4, tid == 0);
        {
            bf16* orow0 = g_qkv + ((size_t)j * S_ + rb * 128 + rl) * 192;
            bf16* orow1 = orow0 + 8 * 192;
#pragma unroll
            for (int u = 0; u < 6; u++) {
                uint32_t w0[4], w1[4];
#pragma unroll
                for (int i = 0; i < 4; i++) {
                    const int t = u * 4 + i;
                    w0[i] = pack_bf16(accQ[t * 4 + 0], accQ[t * 4 + 1]);
                    w1[i] = pack_bf16(accQ[t * 4 + 2], accQ[t * 4 + 3]);
                }
                quad_transpose(w0, q);
                quad_transpose(w1, q);
                const int c = (u * 4 + q) * 8;
                *(uint4*)(orow0 + c) = make_uint4(w0[0], w0[1], w0[2], w0[3]);
                *(uint4*)(orow1 + c) = make_uint4(w1[0], w1[1], w1[2], w1[3]);
            }
        }
        TS(5, tid == 0);
    }
}

__device__ __forceinline__ void ldsm_x4(uint32_t (&r)[4], uint32_t addr) {
    asm("ldmatrix.sync.aligned.m8n8.x4.shared.b16 {%0,%1,%2,%3}, [%4];"
                 : "=r"(r[0]), "=r"(r[1]), "=r"(r[2]), "=r"(r[3]) : "r"(addr));
}
__device__ __forceinline__ void ldsm_x4_t(uint32_t (&r)[4], uint32_t addr) {
    asm("ldmatrix.sync.aligned.m8n8.x4.trans.shared.b16 {%0,%1,%2,%3}, [%4];"
                 : "=r"(r[0]), "=r"(r[1]), "=r"(r[2]), "=r"(r[3]) : "r"(addr));
}
__device__ __forceinline__ void mma16816(float (&d)[4], const uint32_t (&a)[4], uint32_t b0, uint32_t b1) {
    asm("mma.sync.aligned.m16n8k16.row.col.f32.bf16.bf16.f32 {%0,%1,%2,%3}, {%4,%5,%6,%7}, {%8,%9}, {%0,%1,%2,%3};"
                 : "+f"(d[0]), "+f"(d[1]), "+f"(d[2]), "+f"(d[3])
                 : "r"(a[0]), "r"(a[1]), "r"(a[2]), "r"(a[3]), "r"(b0), "r"(b1));
}
__device__ __forceinline__ void mma16816_z(float (&d)[4], const uint32_t (&a)[4], uint32_t b0, uint32_t b1) {
    asm("mma.sync.aligned.m16n8k16.row.col.f32.bf16.bf16.f32 {%0,%1,%2,%3}, {%4,%5,%6,%7}, {%8,%9}, {%10,%10,%10,%10};"
                 : "=f"(d[0]), "=f"(d[1]), "=f"(d[2]), "=f"(d[3])
                 : "r"(a[0]), "r"(a[1]), "r"(a[2]), "r"(a[3]), "r"(b0), "r"(b1), "f"(0.f));
}

constexpr int KV_PITCH = 128;

template <int EDGE, bool HEAD>
__device__ __forceinline__ void blk_scores(float (&s)[2][4], const uint32_t (&qa)[4], uint32_t kaddr, bool dead, int r0, int c0)
{
    uint32_t kf[4];
    ldsm_x4(kf, kaddr);
    mma16816_z(s[0], qa, kf[0], kf[1]);
    mma16816_z(s[1], qa, kf[2], kf[3]);
#pragma unroll
    for (int t = 0; t < 2; t++)
#pragma unroll
        for (int e = 0; e < 4; e++) {
            const int r = r0 + (e >> 1) * 8, c = t * 8 + c0 + (e & 1);
            if (EDGE == 1 && c <= r) s[t][e] = -1e30f;
            if (EDGE == 2 && c > r) s[t][e] = -1e30f;
            if (HEAD && dead) s[t][e] = -1e30f;
        }
}
__device__ __forceinline__ void blk_max(const float (&s)[2][4], float& n0, float& n1) {
    n0 = fmaxf(n0, fmaxf(fmaxf(s[0][0], s[0][1]), fmaxf(s[1][0], s[1][1])));
    n1 = fmaxf(n1, fmaxf(fmaxf(s[0][2], s[0][3]), fmaxf(s[1][2], s[1][3])));
}
__device__ __forceinline__ void blk_pv(const float (&s)[2][4], float mc0, float mc1, float& l0, float& l1,
                                       float (&o)[2][4], uint32_t vaddr) {
    const float C = 0.25f * 1.4426950408889634f;
    uint32_t pa[4];
#pragma unroll
    for (int t = 0; t < 2; t++) {
        const float p0 = ex2(fmaf(s[t][0], C, -mc0)), p1 = ex2(fmaf(s[t][1], C, -mc0));
        const float p2 = ex2(fmaf(s[t][2], C, -mc1)), p3 = ex2(fmaf(s[t][3], C, -mc1));
        l0 += p0 + p1; l1 += p2 + p3;
        pa[2 * t] = pack_bf16(p0, p1); pa[2 * t + 1] = pack_bf16(p2, p3);
    }
    uint32_t vf[4];
    ldsm_x4_t(vf, vaddr);
    mma16816(o[0], pa, vf[0], vf[1]);
    mma16816(o[1], pa, vf[2], vf[3]);
}
__device__ __forceinline__ void quad_max(float& n0, float& n1) {
    n0 = fmaxf(n0, __shfl_xor_sync(0xffffffffu, n0, 1)); n1 = fmaxf(n1, __shfl_xor_sync(0xffffffffu, n1, 1));
    n0 = fmaxf(n0, __shfl_xor_sync(0xffffffffu, n0, 2)); n1 = fmaxf(n1, __shfl_xor_sync(0xffffffffu, n1, 2));
}
template <int NC, int NN, bool FIRST, bool NEXT_IS_EDGE, bool HEAD>
__device__ __forceinline__ void pipe_step(const float (&sc)[5][2][4], float (&sn)[5][2][4], const uint32_t (&qa)[4],
                                          uint32_t ka, uint32_t va, int kc, int kn, int kb0, int r0, int c0,
                                          float& m0, float& m1, float& n0, float& n1, float& l0, float& l1, float (&o)[2][4])
{
    const float C = 0.25f * 1.4426950408889634f;
    const float mc0 = n0 * C, mc1 = n1 * C;
    if (!FIRST) {
        const float a0 = ex2(fmaf(m0, C, -mc0)), a1 = ex2(fmaf(m1, C, -mc1));
        l0 *= a0; l1 *= a1;
        o[0][0] *= a0; o[0][1] *= a0; o[1][0] *= a0; o[1][1] *= a0;
        o[0][2] *= a1; o[0][3] *= a1; o[1][2] *= a1; o[1][3] *= a1;
    }
    m0 = n0; m1 = n1;
#pragma unroll
    for (int b = 0; b < NC; b++) {
        if (b < NN) {
            if (NEXT_IS_EDGE && b == 0) blk_scores<1, HEAD>(sn[b], qa, ka + (kn + b) * 16 * KV_PITCH, kn + b < kb0, r0, c0);
            else                        blk_scores<0, HEAD>(sn[b], qa, ka + (kn + b) * 16 * KV_PITCH, kn + b < kb0, r0, c0);
        }
        blk_pv(sc[b], mc0, mc1, l0, l1, o, va + (kc + b) * 16 * KV_PITCH);
        if (b < NN) blk_max(sn[b], n0, n1);
    }
    if (NN > 0) quad_max(n0, n1);
}

template <bool HEAD>
__device__ __forceinline__ void attn_task(const uint32_t (&qa)[4], uint32_t ka, uint32_t va, int kb0, int lane,
                                          bf16* __restrict__ out  , float g0, float g1)
{
    const int r0 = lane >> 2, c0 = (lane & 3) * 2;
    float m0 = -1e30f, m1 = -1e30f, n0 = -1e30f, n1 = -1e30f, l0 = 0.f, l1 = 0.f;
    float o[2][4] = {{0.f, 0.f, 0.f, 0.f}, {0.f, 0.f, 0.f, 0.f}};
    float sa[5][2][4], sb[5][2][4];
#pragma unroll
    for (int b = 0; b < 5; b++) {
        if (b == 4) blk_scores<2, HEAD>(sa[b], qa, ka + (12 + b) * 16 * KV_PITCH, false, r0, c0);
        else        blk_scores<0, HEAD>(sa[b], qa, ka + (12 + b) * 16 * KV_PITCH, 12 + b < kb0, r0, c0);
        blk_max(sa[b], n0, n1);
    }
    quad_max(n0, n1);
    pipe_step<5, 4, true,  false, HEAD>(sa, sb, qa, ka, va, 12, 8, kb0, r0, c0, m0, m1, n0, n1, l0, l1, o);
    pipe_step<4, 4, false, false, HEAD>(sb, sa, qa, ka, va, 8, 4, kb0, r0, c0, m0, m1, n0, n1, l0, l1, o);
    pipe_step<4, 4, false, true,  HEAD>(sa, sb, qa, ka, va, 4, 0, kb0, r0, c0, m0, m1, n0, n1, l0, l1, o);
    pipe_step<4, 0, false, false, HEAD>(sb, sa, qa, ka, va, 0, 0, kb0, r0, c0, m0, m1, n0, n1, l0, l1, o);
    l0 += __shfl_xor_sync(0xffffffffu, l0, 1); l0 += __shfl_xor_sync(0xffffffffu, l0, 2);
    l1 += __shfl_xor_sync(0xffffffffu, l1, 1); l1 += __shfl_xor_sync(0xffffffffu, l1, 2);
    const float f0 = g0 / l0, f1 = g1 / l1;
#pragma unroll
    for (int t = 0; t < 2; t++) {
        *(uint32_t*)(out + (size_t)r0 * KA2 + t * 8 + c0) = pack_bf16(o[t][0] * f0, o[t][1] * f0);
        *(uint32_t*)(out + (size_t)(r0 + 8) * KA2 + t * 8 + c0) = pack_bf16(o[t][2] * f1, o[t][3] * f1);
    }
}

constexpr int K2_SMEM = 2 * 384 * KV_PITCH + 1024 + 64;

__global__ void __launch_bounds__(512, 1) k2_kernel(const __grid_constant__ CUtensorMap tmQKV)
{
    extern __shared__ uint8_t smem_raw[];
    const uint32_t sbase = (smem_u32(smem_raw) + 1023u) & ~1023u;
    uint8_t* sgen = smem_raw + (sbase - smem_u32(smem_raw));
    const uint32_t sK = sbase, sV = sK + 384 * KV_PITCH, kv_full = sbase + 2 * 384 * KV_PITCH;
    const int rb = blockIdx.x >> 3, j = blockIdx.x & 7;
    const int tid = threadIdx.x, warp = tid >> 5, lane = tid & 31;
    pdl_launch();
    if (tid == 0) {
        mbar_init(kv_full, 1);
        fence_barrier_init();
    }
    pdl_wait();
    TS(6, tid == 0);
    if (tid == 0) {
        const int nblk = rb >= 2 ? 3 : rb + 1;
        mbar_expect_tx(kv_full, nblk * 2 * 16384);
        for (int i = 0; i < nblk; i++) {
            const int row = j * S_ + (rb - i) * 128;
            tma_load_2d(sK + (2 - i) * 16384, &tmQKV, 64, row, kv_full);
            tma_load_2d(sV + (2 - i) * 16384, &tmQKV, 128, row, kv_full);
        }
    }
    if (rb < 2) {
        for (int i = tid; i < (2 - rb) * 1024; i += 512) {
            *(uint4*)(sgen + i * 16) = make_uint4(0, 0, 0, 0);
            *(uint4*)(sgen + 384 * KV_PITCH + i * 16) = make_uint4(0, 0, 0, 0);
        }
    }
    const int qt = warp & 7, h0 = (warp >> 3) * 2;
    const int q0g = rb * 128 + qt * 16;
    const int r0 = lane >> 2, c0 = (lane & 3) * 2;
    const bf16* qsrc = g_qkv + ((size_t)j * S_ + q0g) * 192 + h0 * 16;
    uint32_t qa[4], qn[4];
    qa[0] = *(const uint32_t*)(qsrc + (size_t)r0 * 192 + c0);
    qa[1] = *(const uint32_t*)(qsrc + (size_t)(r0 + 8) * 192 + c0);
    qa[2] = *(const uint32_t*)(qsrc + (size_t)r0 * 192 + c0 + 8);
    qa[3] = *(const uint32_t*)(qsrc + (size_t)(r0 + 8) * 192 + c0 + 8);
    qn[0] = *(const uint32_t*)(qsrc + (size_t)r0 * 192 + 16 + c0);
    qn[1] = *(const uint32_t*)(qsrc + (size_t)(r0 + 8) * 192 + 16 + c0);
    qn[2] = *(const uint32_t*)(qsrc + (size_t)r0 * 192 + 16 + c0 + 8);
    qn[3] = *(const uint32_t*)(qsrc + (size_t)(r0 + 8) * 192 + 16 + c0 + 8);
    const float g0 = g_gate[q0g + r0], g1 = g_gate[q0g + r0 + 8];
    const int kb0 = q0g < 256 ? (256 - q0g) >> 4 : 0;
    __syncthreads();
    mbar_wait(kv_full, 0);
    uint32_t sKd = sK, sVd = sV;
    asm volatile("" : "+r"(sKd), "+r"(sVd) :: "memory");
    TS(7, tid == 0);
    const int krow = qt * 16 + (lane & 7) + ((lane >> 4) << 3);
    const int vrow = qt * 16 + (lane & 15);
#pragma unroll 1
    for (int hh = 0; hh < 2; hh++) {
        const int hl = h0 + hh;
        const uint32_t ka = sKd + krow * KV_PITCH + (((2 * hl + ((lane >> 3) & 1)) ^ (lane & 7)) << 4);
        const uint32_t va = sVd + vrow * KV_PITCH + (((2 * hl + (lane >> 4)) ^ (lane & 7)) << 4);
        if (rb < 2) attn_task<true>(qa, ka, va, kb0, lane, g_a2 + (size_t)q0g * KA2 + (j * 4 + hl) * 16, g0, g1);
        else        attn_task<false>(qa, ka, va, kb0, lane, g_a2 + (size_t)q0g * KA2 + (j * 4 + hl) * 16, g0, g1);
        TS(8 + hh, tid == 0);
        qa[0] = qn[0]; qa[1] = qn[1]; qa[2] = qn[2]; qa[3] = qn[3];
    }
}

constexpr int K3_STAGES = 8;
constexpr int K3_STAGE = 16384 + 8192;
constexpr int K3_SMEM = K3_STAGES * K3_STAGE + 1024 + 1024;
constexpr int K3_KSTEPS = 30;

__global__ void __launch_bounds__(384, 1)
k3_kernel(const __grid_constant__ CUtensorMap tmA2, const __grid_constant__ CUtensorMap tmWo,
          const __grid_constant__ CUtensorMap tmW2, bf16* __restrict__ out)
{
    extern __shared__ uint8_t smem_raw[];
    const uint32_t sbase = (smem_u32(smem_raw) + 1023u) & ~1023u;
    const uint32_t sBar = sbase + K3_STAGES * K3_STAGE;
    const uint32_t full = sBar, empty = sBar + 64;
    const int rb = blockIdx.x >> 3, nb = blockIdx.x & 7;
    const int tid = threadIdx.x, wg = tid >> 7, warp = tid >> 5, lane = tid & 31;
    if (tid == 0) {
        for (int i = 0; i < K3_STAGES; i++) { mbar_init(full + 8 * i, 1); mbar_init(empty + 8 * i, 8); }
        fence_barrier_init();
    }
    __syncthreads();
    pdl_wait();
    TS(10, tid == 0);
    if (wg == 2) {
        reg_dealloc<40>();
        if (tid == 256) {
            for (int ks = 0; ks < K3_KSTEPS; ks++) {
                const int st = ks % K3_STAGES;
                if (ks >= K3_STAGES) mbar_wait(empty + 8 * st, ((ks / K3_STAGES) - 1) & 1);
                mbar_expect_tx(full + 8 * st, K3_STAGE);
                const uint32_t dst = sbase + st * K3_STAGE;
                tma_load_2d(dst, &tmA2, ks * 64, rb * 128, full + 8 * st);
                if (ks < 8) tma_load_2d(dst + 16384, &tmWo, nb * 64, ks * 64, full + 8 * st);
                else        tma_load_2d(dst + 16384, &tmW2, nb * 64, (ks - 8) * 64, full + 8 * st);
            }
        }
    } else {
        reg_alloc<232>();
        float acc[32];
        for (int ks = 0; ks < K3_KSTEPS; ks++) {
            const int st = ks % K3_STAGES;
            mbar_wait(full + 8 * st, (ks / K3_STAGES) & 1);
            TS(11, tid == 0 && ks == 0); TS(12, tid == 0 && ks == 8); TS(13, tid == 0 && ks == 16);
            wgmma_fence();
#pragma unroll
            for (int k16 = 0; k16 < 4; k16++) {
                const uint64_t da = make_desc(sbase + st * K3_STAGE + wg * 8192 + k16 * 32, 16, 1024);
                const uint64_t db = make_desc(sbase + st * K3_STAGE + 16384 + k16 * 2048, 8192, 1024);
                wgmma_n64<1>(acc, da, db, (ks | k16) != 0);
            }
            wgmma_commit();
            if (ks > 0) { wgmma_wait<1>(); if (lane == 0) mbar_arrive(empty + 8 * ((ks - 1) % K3_STAGES)); }
        }
        wgmma_wait<0>();
        TS(14, tid == 0);
        const int q = lane & 3;
        const int r = rb * 128 + wg * 64 + (warp & 3) * 16 + (lane >> 2);
        bf16* orow0 = out + (size_t)r * D_ + nb * 64;
        bf16* orow1 = orow0 + 8 * D_;
#pragma unroll
        for (int u = 0; u < 2; u++) {
            uint32_t w0[4], w1[4];
#pragma unroll
            for (int i = 0; i < 4; i++) {
                const int t = u * 4 + i;
                w0[i] = pack_bf16(acc[t * 4 + 0], acc[t * 4 + 1]);
                w1[i] = pack_bf16(acc[t * 4 + 2], acc[t * 4 + 3]);
            }
            quad_transpose(w0, q);
            quad_transpose(w1, q);
            const int c = (u * 4 + q) * 8;
            *(uint4*)(orow0 + c) = make_uint4(w0[0], w0[1], w0[2], w0[3]);
            *(uint4*)(orow1 + c) = make_uint4(w1[0], w1[1], w1[2], w1[3]);
        }
        TS(15, tid == 0);
    }
}

typedef CUresult (*PFN_encodeTiled)(CUtensorMap*, CUtensorMapDataType, cuuint32_t, void*, const cuuint64_t*,
                                    const cuuint64_t*, const cuuint32_t*, const cuuint32_t*, CUtensorMapInterleave,
                                    CUtensorMapSwizzle, CUtensorMapL2promotion, CUtensorMapFloatOOBfill);

static void make_map(PFN_encodeTiled enc, CUtensorMap* m, const void* ptr, uint64_t cols, uint64_t rows,
                     uint32_t box_cols, uint32_t box_rows)
{
    cuuint64_t dims[2] = {cols, rows};
    cuuint64_t strides[1] = {cols * 2};
    cuuint32_t box[2] = {box_cols, box_rows};
    cuuint32_t es[2] = {1, 1};
    enc(m, CU_TENSOR_MAP_DATA_TYPE_BFLOAT16, 2, const_cast<void*>(ptr), dims, strides, box, es,
        CU_TENSOR_MAP_INTERLEAVE_NONE, CU_TENSOR_MAP_SWIZZLE_128B, CU_TENSOR_MAP_L2_PROMOTION_L2_128B,
        CU_TENSOR_MAP_FLOAT_OOB_FILL_NONE);
}

extern "C" void kernel_launch(void* const* d_in, const int* in_sizes, int n_in, void* d_out, int out_size)
{
    const bf16* x    = (const bf16*)d_in[0];
    const bf16* wqkv = (const bf16*)d_in[1];
    const bf16* wo   = (const bf16*)d_in[2];
    const bf16* w1   = (const bf16*)d_in[4];
    const bf16* b1   = (const bf16*)d_in[5];
    const bf16* w2   = (const bf16*)d_in[6];
    const bf16* gw   = (const bf16*)d_in[7];

    static PFN_encodeTiled enc = nullptr;
    if (!enc) {
        void* fn = nullptr;
        cudaDriverEntryPointQueryResult qr;
        cudaGetDriverEntryPoint("cuTensorMapEncodeTiled", &fn, cudaEnableDefault, &qr);
        enc = (PFN_encodeTiled)fn;
        cudaFuncSetAttribute(k1_kernel, cudaFuncAttributeMaxDynamicSharedMemorySize, K1_SMEM);
        cudaFuncSetAttribute(k2_kernel, cudaFuncAttributeMaxDynamicSharedMemorySize, K2_SMEM);
        cudaFuncSetAttribute(k3_kernel, cudaFuncAttributeMaxDynamicSharedMemorySize, K3_SMEM);
    }
    void* a2p = nullptr;
    cudaGetSymbolAddress(&a2p, g_a2);
    void* qkvp = nullptr;
    cudaGetSymbolAddress(&qkvp, g_qkv);
    CUtensorMap tmX, tmWqkv, tmW1, tmA2, tmWo, tmW2, tmQKV;
    make_map(enc, &tmQKV, qkvp, 192, 8 * S_, 64, 128);
    make_map(enc, &tmX, x, D_, S_, 64, 128);
    make_map(enc, &tmWqkv, wqkv, 3 * D_, D_, 64, 64);
    make_map(enc, &tmW1, w1, F_, D_, 64, 64);
    make_map(enc, &tmA2, a2p, KA2, S_, 64, 128);
    make_map(enc, &tmWo, wo, D_, D_, 64, 64);
    make_map(enc, &tmW2, w2, D_, F_, 64, 64);

    cudaStream_t st = cudaStreamPerThread;
    k1_kernel<<<128, 384, K1_SMEM, st>>>(tmX, tmWqkv, tmW1, b1, gw, w1, wqkv, w2, wo);
    cudaLaunchAttribute at[1];
    at[0].id = cudaLaunchAttributeProgrammaticStreamSerialization;
    at[0].val.programmaticStreamSerializationAllowed = 1;
    cudaLaunchConfig_t cfg = {};
    cfg.gridDim = dim3(128); cfg.stream = st; cfg.attrs = at; cfg.numAttrs = 1;
    cfg.blockDim = dim3(512); cfg.dynamicSmemBytes = K2_SMEM;
    cudaLaunchKernelEx(&cfg, k2_kernel, tmQKV);
    k3_kernel<<<128, 384, K3_SMEM, st>>>(tmA2, tmWo, tmW2, (bf16*)d_out);
}
```

```cpp
#include <cuda_runtime.h>
#include <cuda_bf16.h>
#include <cuda.h>
#include <stdint.h>

typedef __nv_bfloat16 bf16;

constexpr int S_ = 2048, D_ = 512, F_ = 1376;
constexpr int KA2 = D_ + F_;
constexpr int FCH = 176;

__device__ bf16  g_qkv[8 * S_ * 192];
__device__ bf16  g_a2[S_ * KA2];
__device__ float g_gate[S_];

#define TS(k, cond) do { } while (0)

__device__ __forceinline__ uint32_t smem_u32(const void* p) { return (uint32_t)__cvta_generic_to_shared(p); }
__device__ __forceinline__ void mbar_init(uint32_t bar, uint32_t count) {
    asm volatile("mbarrier.init.shared::cta.b64 [%0], %1;" :: "r"(bar), "r"(count) : "memory");
}
__device__ __forceinline__ void mbar_expect_tx(uint32_t bar, uint32_t bytes) {
    asm volatile("mbarrier.arrive.expect_tx.shared::cta.b64 _, [%0], %1;" :: "r"(bar), "r"(bytes) : "memory");
}
__device__ __forceinline__ void mbar_arrive(uint32_t bar) {
    asm volatile("mbarrier.arrive.shared::cta.b64 _, [%0];" :: "r"(bar) : "memory");
}
__device__ __forceinline__ bool mbar_try_wait(uint32_t bar, uint32_t parity) {
    uint32_t ok;
    asm volatile("{\n.reg .pred p;\nmbarrier.try_wait.parity.shared::cta.b64 p, [%1], %2;\nselp.u32 %0, 1, 0, p;\n}"
                 : "=r"(ok) : "r"(bar), "r"(parity) : "memory");
    return ok != 0;
}
__device__ __forceinline__ void mbar_wait(uint32_t bar, uint32_t parity) {
    for (uint32_t it = 0; it < (1u << 22); ++it) { if (mbar_try_wait(bar, parity)) break; }
}
__device__ __forceinline__ void tma_load_2d(uint32_t dst, const CUtensorMap* map, int c0, int c1, uint32_t bar) {
    asm volatile("cp.async.bulk.tensor.2d.shared::cluster.global.mbarrier::complete_tx::bytes [%0], [%1, {%3, %4}], [%2];"
                 :: "r"(dst), "l"(map), "r"(bar), "r"(c0), "r"(c1) : "memory");
}
__device__ __forceinline__ void l2_prefetch(const void* p, uint32_t bytes) {
    asm volatile("cp.async.bulk.prefetch.L2.global [%0], %1;" :: "l"(p), "r"(bytes) : "memory");
}
__device__ __forceinline__ void fence_barrier_init() { asm volatile("fence.mbarrier_init.release.cluster;" ::: "memory"); }
__device__ __forceinline__ void wgmma_fence()  { asm volatile("wgmma.fence.sync.aligned;" ::: "memory"); }
__device__ __forceinline__ void wgmma_commit() { asm volatile("wgmma.commit_group.sync.aligned;" ::: "memory"); }
template <int N> __device__ __forceinline__ void wgmma_wait() { asm volatile("wgmma.wait_group.sync.aligned %0;" :: "n"(N) : "memory"); }
template <int R> __device__ __forceinline__ void reg_alloc()   { asm volatile("setmaxnreg.inc.sync.aligned.u32 %0;" :: "n"(R)); }
template <int R> __device__ __forceinline__ void reg_dealloc() { asm volatile("setmaxnreg.dec.sync.aligned.u32 %0;" :: "n"(R)); }
__device__ __forceinline__ void bar_sync(int id, int n)   { asm volatile("bar.sync %0, %1;" :: "r"(id), "r"(n) : "memory"); }
__device__ __forceinline__ void bar_arrive(int id, int n) { asm volatile("bar.arrive %0, %1;" :: "r"(id), "r"(n) : "memory"); }

__device__ __forceinline__ uint64_t make_desc(uint32_t addr, uint32_t lbo, uint32_t sbo) {
    uint64_t d = (uint64_t)((addr & 0x3FFFF) >> 4);
    d |= (uint64_t)((lbo & 0x3FFFF) >> 4) << 16;
    d |= (uint64_t)((sbo & 0x3FFFF) >> 4) << 32;
    d |= (uint64_t)1 << 62;
    return d;
}

template <int TB>
__device__ __forceinline__ void wgmma_n64(float (&d)[32], uint64_t da, uint64_t db, int scale_d) {
    asm volatile("{\n.reg .pred p;\nsetp.ne.b32 p, %34, 0;\n"
        "wgmma.mma_async.sync.aligned.m64n64k16.f32.bf16.bf16 {%0, %1, %2, %3, %4, %5, %6, %7, %8, %9, %10, %11, %12, %13, %14, %15, %16, %17, %18, %19, %20, %21, %22, %23, %24, %25, %26, %27, %28, %29, %30, %31}, %32, %33, p, 1, 1, 0, %35;\n}\n"
        : "+f"(d[0]), "+f"(d[1]), "+f"(d[2]), "+f"(d[3]), "+f"(d[4]), "+f"(d[5]), "+f"(d[6]), "+f"(d[7]), "+f"(d[8]), "+f"(d[9]), "+f"(d[10]), "+f"(d[11]), "+f"(d[12]), "+f"(d[13]), "+f"(d[14]), "+f"(d[15]), "+f"(d[16]), "+f"(d[17]), "+f"(d[18]), "+f"(d[19]), "+f"(d[20]), "+f"(d[21]), "+f"(d[22]), "+f"(d[23]), "+f"(d[24]), "+f"(d[25]), "+f"(d[26]), "+f"(d[27]), "+f"(d[28]), "+f"(d[29]), "+f"(d[30]), "+f"(d[31])
        : "l"(da), "l"(db), "r"(scale_d), "n"(TB));
}

template <int TB>
__device__ __forceinline__ void wgmma_n128(float (&d)[64], uint64_t da, uint64_t db, int scale_d) {
    asm volatile("{\n.reg .pred p;\nsetp.ne.b32 p, %66, 0;\n"
        "wgmma.mma_async.sync.aligned.m64n128k16.f32.bf16.bf16 {%0, %1, %2, %3, %4, %5, %6, %7, %8, %9, %10, %11, %12, %13, %14, %15, %16, %17, %18, %19, %20, %21, %22, %23, %24, %25, %26, %27, %28, %29, %30, %31, %32, %33, %34, %35, %36, %37, %38, %39, %40, %41, %42, %43, %44, %45, %46, %47, %48, %49, %50, %51, %52, %53, %54, %55, %56, %57, %58, %59, %60, %61, %62, %63}, %64, %65, p, 1, 1, 0, %67;\n}\n"
        : "+f"(d[0]), "+f"(d[1]), "+f"(d[2]), "+f"(d[3]), "+f"(d[4]), "+f"(d[5]), "+f"(d[6]), "+f"(d[7]), "+f"(d[8]), "+f"(d[9]), "+f"(d[10]), "+f"(d[11]), "+f"(d[12]), "+f"(d[13]), "+f"(d[14]), "+f"(d[15]), "+f"(d[16]), "+f"(d[17]), "+f"(d[18]), "+f"(d[19]), "+f"(d[20]), "+f"(d[21]), "+f"(d[22]), "+f"(d[23]), "+f"(d[24]), "+f"(d[25]), "+f"(d[26]), "+f"(d[27]), "+f"(d[28]), "+f"(d[29]), "+f"(d[30]), "+f"(d[31]), "+f"(d[32]), "+f"(d[33]), "+f"(d[34]), "+f"(d[35]), "+f"(d[36]), "+f"(d[37]), "+f"(d[38]), "+f"(d[39]), "+f"(d[40]), "+f"(d[41]), "+f"(d[42]), "+f"(d[43]), "+f"(d[44]), "+f"(d[45]), "+f"(d[46]), "+f"(d[47]), "+f"(d[48]), "+f"(d[49]), "+f"(d[50]), "+f"(d[51]), "+f"(d[52]), "+f"(d[53]), "+f"(d[54]), "+f"(d[55]), "+f"(d[56]), "+f"(d[57]), "+f"(d[58]), "+f"(d[59]), "+f"(d[60]), "+f"(d[61]), "+f"(d[62]), "+f"(d[63])
        : "l"(da), "l"(db), "r"(scale_d), "n"(TB));
}

template <int TB>
__device__ __forceinline__ void wgmma_n176(float (&d)[88], uint64_t da, uint64_t db, int scale_d) {
    asm volatile("{\n.reg .pred p;\nsetp.ne.b32 p, %90, 0;\n"
        "wgmma.mma_async.sync.aligned.m64n176k16.f32.bf16.bf16 {%0, %1, %2, %3, %4, %5, %6, %7, %8, %9, %10, %11, %12, %13, %14, %15, %16, %17, %18, %19, %20, %21, %22, %23, %24, %25, %26, %27, %28, %29, %30, %31, %32, %33, %34, %35, %36, %37, %38, %39, %40, %41, %42, %43, %44, %45, %46, %47, %48, %49, %50, %51, %52, %53, %54, %55, %56, %57, %58, %59, %60, %61, %62, %63, %64, %65, %66, %67, %68, %69, %70, %71, %72, %73, %74, %75, %76, %77, %78, %79, %80, %81, %82, %83, %84, %85, %86, %87}, %88, %89, p, 1, 1, 0, %91;\n}\n"
        : "+f"(d[0]), "+f"(d[1]), "+f"(d[2]), "+f"(d[3]), "+f"(d[4]), "+f"(d[5]), "+f"(d[6]), "+f"(d[7]), "+f"(d[8]), "+f"(d[9]), "+f"(d[10]), "+f"(d[11]), "+f"(d[12]), "+f"(d[13]), "+f"(d[14]), "+f"(d[15]), "+f"(d[16]), "+f"(d[17]), "+f"(d[18]), "+f"(d[19]), "+f"(d[20]), "+f"(d[21]), "+f"(d[22]), "+f"(d[23]), "+f"(d[24]), "+f"(d[25]), "+f"(d[26]), "+f"(d[27]), "+f"(d[28]), "+f"(d[29]), "+f"(d[30]), "+f"(d[31]), "+f"(d[32]), "+f"(d[33]), "+f"(d[34]), "+f"(d[35]), "+f"(d[36]), "+f"(d[37]), "+f"(d[38]), "+f"(d[39]), "+f"(d[40]), "+f"(d[41]), "+f"(d[42]), "+f"(d[43]), "+f"(d[44]), "+f"(d[45]), "+f"(d[46]), "+f"(d[47]), "+f"(d[48]), "+f"(d[49]), "+f"(d[50]), "+f"(d[51]), "+f"(d[52]), "+f"(d[53]), "+f"(d[54]), "+f"(d[55]), "+f"(d[56]), "+f"(d[57]), "+f"(d[58]), "+f"(d[59]), "+f"(d[60]), "+f"(d[61]), "+f"(d[62]), "+f"(d[63]), "+f"(d[64]), "+f"(d[65]), "+f"(d[66]), "+f"(d[67]), "+f"(d[68]), "+f"(d[69]), "+f"(d[70]), "+f"(d[71]), "+f"(d[72]), "+f"(d[73]), "+f"(d[74]), "+f"(d[75]), "+f"(d[76]), "+f"(d[77]), "+f"(d[78]), "+f"(d[79]), "+f"(d[80]), "+f"(d[81]), "+f"(d[82]), "+f"(d[83]), "+f"(d[84]), "+f"(d[85]), "+f"(d[86]), "+f"(d[87])
        : "l"(da), "l"(db), "r"(scale_d), "n"(TB));
}

template <int TB>
__device__ __forceinline__ void wgmma_n192(float (&d)[96], uint64_t da, uint64_t db, int scale_d) {
    asm volatile("{\n.reg .pred p;\nsetp.ne.b32 p, %98, 0;\n"
        "wgmma.mma_async.sync.aligned.m64n192k16.f32.bf16.bf16 {%0, %1, %2, %3, %4, %5, %6, %7, %8, %9, %10, %11, %12, %13, %14, %15, %16, %17, %18, %19, %20, %21, %22, %23, %24, %25, %26, %27, %28, %29, %30, %31, %32, %33, %34, %35, %36, %37, %38, %39, %40, %41, %42, %43, %44, %45, %46, %47, %48, %49, %50, %51, %52, %53, %54, %55, %56, %57, %58, %59, %60, %61, %62, %63, %64, %65, %66, %67, %68, %69, %70, %71, %72, %73, %74, %75, %76, %77, %78, %79, %80, %81, %82, %83, %84, %85, %86, %87, %88, %89, %90, %91, %92, %93, %94, %95}, %96, %97, p, 1, 1, 0, %99;\n}\n"
        : "+f"(d[0]), "+f"(d[1]), "+f"(d[2]), "+f"(d[3]), "+f"(d[4]), "+f"(d[5]), "+f"(d[6]), "+f"(d[7]), "+f"(d[8]), "+f"(d[9]), "+f"(d[10]), "+f"(d[11]), "+f"(d[12]), "+f"(d[13]), "+f"(d[14]), "+f"(d[15]), "+f"(d[16]), "+f"(d[17]), "+f"(d[18]), "+f"(d[19]), "+f"(d[20]), "+f"(d[21]), "+f"(d[22]), "+f"(d[23]), "+f"(d[24]), "+f"(d[25]), "+f"(d[26]), "+f"(d[27]), "+f"(d[28]), "+f"(d[29]), "+f"(d[30]), "+f"(d[31]), "+f"(d[32]), "+f"(d[33]), "+f"(d[34]), "+f"(d[35]), "+f"(d[36]), "+f"(d[37]), "+f"(d[38]), "+f"(d[39]), "+f"(d[40]), "+f"(d[41]), "+f"(d[42]), "+f"(d[43]), "+f"(d[44]), "+f"(d[45]), "+f"(d[46]), "+f"(d[47]), "+f"(d[48]), "+f"(d[49]), "+f"(d[50]), "+f"(d[51]), "+f"(d[52]), "+f"(d[53]), "+f"(d[54]), "+f"(d[55]), "+f"(d[56]), "+f"(d[57]), "+f"(d[58]), "+f"(d[59]), "+f"(d[60]), "+f"(d[61]), "+f"(d[62]), "+f"(d[63]), "+f"(d[64]), "+f"(d[65]), "+f"(d[66]), "+f"(d[67]), "+f"(d[68]), "+f"(d[69]), "+f"(d[70]), "+f"(d[71]), "+f"(d[72]), "+f"(d[73]), "+f"(d[74]), "+f"(d[75]), "+f"(d[76]), "+f"(d[77]), "+f"(d[78]), "+f"(d[79]), "+f"(d[80]), "+f"(d[81]), "+f"(d[82]), "+f"(d[83]), "+f"(d[84]), "+f"(d[85]), "+f"(d[86]), "+f"(d[87]), "+f"(d[88]), "+f"(d[89]), "+f"(d[90]), "+f"(d[91]), "+f"(d[92]), "+f"(d[93]), "+f"(d[94]), "+f"(d[95])
        : "l"(da), "l"(db), "r"(scale_d), "n"(TB));
}

__device__ __forceinline__ uint32_t pack_bf16(float lo, float hi) {
    uint32_t r;
    asm("cvt.rn.bf16x2.f32 %0, %1, %2;" : "=r"(r) : "f"(hi), "f"(lo));
    return r;
}
__device__ __forceinline__ float bf_lo(uint32_t v) { return __uint_as_float(v << 16); }
__device__ __forceinline__ float bf_hi(uint32_t v) { return __uint_as_float(v & 0xffff0000u); }

__device__ __forceinline__ void quad_transpose(uint32_t (&w)[4], int q) {
    const bool o1 = q & 1, o2 = q & 2;
    {
        uint32_t s0 = o1 ? w[0] : w[1], s1 = o1 ? w[2] : w[3];
        s0 = __shfl_xor_sync(0xffffffffu, s0, 1); s1 = __shfl_xor_sync(0xffffffffu, s1, 1);
        if (o1) { w[0] = s0; w[2] = s1; } else { w[1] = s0; w[3] = s1; }
    }
    {
        uint32_t s0 = o2 ? w[0] : w[2], s1 = o2 ? w[1] : w[3];
        s0 = __shfl_xor_sync(0xffffffffu, s0, 2); s1 = __shfl_xor_sync(0xffffffffu, s1, 2);
        if (o2) { w[0] = s0; w[1] = s1; } else { w[2] = s0; w[3] = s1; }
    }
}

__device__ __forceinline__ float ex2(float x) { float y; asm("ex2.approx.ftz.f32 %0, %1;" : "=f"(y) : "f"(x)); return y; }
__device__ __forceinline__ float rcp(float x) { float y; asm("rcp.approx.ftz.f32 %0, %1;" : "=f"(y) : "f"(x)); return y; }

__device__ __forceinline__ float ex2v(float x) { float y; asm volatile("ex2.approx.ftz.f32 %0, %1;" : "=f"(y) : "f"(x)); return y; }
__device__ __forceinline__ float rcpv(float x) { float y; asm volatile("rcp.approx.ftz.f32 %0, %1;" : "=f"(y) : "f"(x)); return y; }
__device__ __forceinline__ float mish_f(float h) {
    const float e = ex2v(1.4426950408889634f * fminf(h, 20.f));
    const float n = fmaf(e, e, e + e);
    return h * n * rcpv(n + 2.f);
}

__device__ __forceinline__ void pdl_wait()   { asm volatile("griddepcontrol.wait;" ::: "memory"); }
__device__ __forceinline__ void pdl_launch() { asm volatile("griddepcontrol.launch_dependents;" ::: "memory"); }

constexpr int K1_STAGES = 4;
constexpr int K1_XBYTES = 128 * 512 * 2;
constexpr int K1_BSTAGE = 3 * 8192;
constexpr int K1_SMEM   = K1_XBYTES + K1_STAGES * K1_BSTAGE + 2048   + 1024  ;
constexpr int HPITCH = 368;

__global__ void __launch_bounds__(512, 1)
k1_kernel(const __grid_constant__ CUtensorMap tmX, const __grid_constant__ CUtensorMap tmWqkv,
          const __grid_constant__ CUtensorMap tmW1, const bf16* __restrict__ b1,
          const bf16* __restrict__ gate_w, const bf16* __restrict__ w1p, const bf16* __restrict__ wqkvp,
          const bf16* __restrict__ w2p, const bf16* __restrict__ wop)
{
    extern __shared__ uint8_t smem_raw[];
    const uint32_t sbase = (smem_u32(smem_raw) + 1023u) & ~1023u;
    uint8_t* sgen = smem_raw + (sbase - smem_u32(smem_raw));
    const uint32_t sX = sbase;
    const uint32_t sB = sbase + K1_XBYTES;
    const uint32_t sBar = sB + K1_STAGES * K1_BSTAGE;
    const uint32_t x_full = sBar;
    const uint32_t b_full = sBar + 64;
    const uint32_t b_empty = sBar + 96;
    float* sGate = (float*)(sgen + K1_XBYTES + K1_STAGES * K1_BSTAGE + 128);
    uint32_t* sBias = (uint32_t*)(sgen + K1_XBYTES + K1_STAGES * K1_BSTAGE + 1664);

    const int rb = blockIdx.x >> 3, j = blockIdx.x & 7;
    const int tid = threadIdx.x, wg = tid >> 7, warp = tid >> 5, lane = tid & 31;
    TS(0, tid == 0);
    pdl_launch();

    if (tid == 0) {
        for (int i = 0; i < 8; i++) mbar_init(x_full + 8 * i, 1);
        for (int i = 0; i < K1_STAGES; i++) { mbar_init(b_full + 8 * i, 1); mbar_init(b_empty + 8 * i, 8); }
        fence_barrier_init();
    }
    __syncthreads();

    if (wg >= 2) {
        reg_dealloc<40>();
        if (warp == 8) {
            if (lane == 0) {
                for (int it = 0; it < 16; it++) {
                    if (it < 8) {
                        mbar_expect_tx(x_full + 8 * it, 16384);
                        tma_load_2d(sX + it * 16384, &tmX, it * 64, rb * 128, x_full + 8 * it);
                    }
                    const int st = it & 3;
                    if (it >= K1_STAGES) mbar_wait(b_empty + 8 * st, ((it >> 2) - 1) & 1);
                    mbar_expect_tx(b_full + 8 * st, K1_BSTAGE);
                    const uint32_t dst = sB + st * K1_BSTAGE;
                    if (it < 8) {
                        for (int b = 0; b < 3; b++) tma_load_2d(dst + b * 8192, &tmW1, j * FCH + b * 64, it * 64, b_full + 8 * st);
                    } else {
                        for (int b = 0; b < 3; b++) tma_load_2d(dst + b * 8192, &tmWqkv, b * 512 + j * 64, (it - 8) * 64, b_full + 8 * st);
                    }
                }
            }
        } else {
            if (wg == 3) {
                const int r = tid - 384;
                float gs = 0.f;
#pragma unroll 1
                for (int kc = 0; kc < 8; kc++) {
                    mbar_wait(x_full + 8 * kc, 0);
#pragma unroll 2
                    for (int c = 0; c < 8; c++) {
                        const uint4 xv = *(const uint4*)(sgen + kc * 16384 + r * 128 + ((c ^ (r & 7)) << 4));
                        const uint4 gv = __ldg((const uint4*)(gate_w + kc * 64 + c * 8));
                        gs = fmaf(bf_lo(xv.x), bf_lo(gv.x), gs); gs = fmaf(bf_hi(xv.x), bf_hi(gv.x), gs);
                        gs = fmaf(bf_lo(xv.y), bf_lo(gv.y), gs); gs = fmaf(bf_hi(xv.y), bf_hi(gv.y), gs);
                        gs = fmaf(bf_lo(xv.z), bf_lo(gv.z), gs); gs = fmaf(bf_hi(xv.z), bf_hi(gv.z), gs);
                        gs = fmaf(bf_lo(xv.w), bf_lo(gv.w), gs); gs = fmaf(bf_hi(xv.w), bf_hi(gv.w), gs);
                    }
                }
                const float g = 1.f / (1.f + __expf(-gs));
                sGate[r] = g;
                if (j == 0) g_gate[rb * 128 + r] = g;
                bar_arrive(3, 256 + 128);
            } else if (tid == 288) {
                const int b = blockIdx.x;
                mbar_wait(b_full + 8, 0);
                l2_prefetch((const uint8_t*)wqkvp + b * 12288, 12288);
                l2_prefetch((const uint8_t*)w2p + b * 11008, 11008);
                l2_prefetch((const uint8_t*)wop + b * 4096, 4096);
            }
            __syncwarp();
            const int ht = tid - 288;
            const int n0 = j * FCH;
#pragma unroll 1
            for (int w = 0; w < 2; w++) {
                bar_sync(4 + w, 128 + 224);
#pragma unroll 1
                for (int it = ht; it < 64 * 22; it += 224) {
                    const int r = it / 22, c = it - r * 22;
                    const int p = r / 22, rr = r - p * 22;
                    const uint4 hv = *(const uint4*)(sgen + p * 16384 + w * 8192 + rr * HPITCH + c * 16);
                    const float om = 1.f - sGate[w * 64 + r];
                    uint4 o;
                    o.x = pack_bf16(mish_f(bf_lo(hv.x)) * om, mish_f(bf_hi(hv.x)) * om);
                    o.y = pack_bf16(mish_f(bf_lo(hv.y)) * om, mish_f(bf_hi(hv.y)) * om);
                    o.z = pack_bf16(mish_f(bf_lo(hv.z)) * om, mish_f(bf_hi(hv.z)) * om);
                    o.w = pack_bf16(mish_f(bf_lo(hv.w)) * om, mish_f(bf_hi(hv.w)) * om);
                    if (n0 + c * 8 < F_)
                        *(uint4*)(g_a2 + (size_t)(rb * 128 + w * 64 + r) * KA2 + D_ + n0 + c * 8) = o;
                }
            }
            TS(16, tid == 288);
        }
    } else {
        reg_alloc<216>();
        if (tid < 88) {
            const int c = j * FCH + tid * 2;
            sBias[tid] = c < F_ ? __ldg((const uint32_t*)(b1 + c)) : 0u;
        }
        const int w4 = warp & 3, q = lane & 3;
        float accF[88], accQ[96];
#pragma unroll 1
        for (int kc = 0; kc < 8; kc++) {
            const int st = kc & 3;
            mbar_wait(x_full + 8 * kc, 0);
            mbar_wait(b_full + 8 * st, (kc >> 2) & 1);
            TS(1, tid == 0 && kc == 0); TS(2, tid == 0 && kc == 4);
            wgmma_fence();
#pragma unroll
            for (int k16 = 0; k16 < 4; k16++) {
                const uint64_t db = make_desc(sB + st * K1_BSTAGE + k16 * 2048, 8192, 1024);
                const uint64_t da = make_desc(sX + kc * 16384 + wg * 8192 + k16 * 32, 16, 1024);
                wgmma_n176<1>(accF, da, db, (kc | k16) != 0);
            }
            wgmma_commit();
            if (kc > 0) { wgmma_wait<1>(); if (lane == 0) mbar_arrive(b_empty + 8 * ((kc - 1) & 3)); }
        }
        TS(3, tid == 0);
        const int rl = wg * 64 + w4 * 16 + (lane >> 2);
#pragma unroll 1
        for (int kc = 0; kc < 8; kc++) {
            const int st = kc & 3;
            mbar_wait(b_full + 8 * st, ((kc + 8) >> 2) & 1);
            wgmma_fence();
#pragma unroll
            for (int k16 = 0; k16 < 4; k16++) {
                const uint64_t db = make_desc(sB + st * K1_BSTAGE + k16 * 2048, 8192, 1024);
                const uint64_t da = make_desc(sX + kc * 16384 + wg * 8192 + k16 * 32, 16, 1024);
                wgmma_n192<1>(accQ, da, db, (kc | k16) != 0);
            }
            wgmma_commit();
            wgmma_wait<1>();
            if (lane == 0) mbar_arrive(b_empty + 8 * ((kc + 3) & 3));
            if (kc == 3) {
                bar_sync(3, 256 + 128);
                const int r0 = w4 * 16 + (lane >> 2), r1 = r0 + 8;
                uint8_t* d0 = sgen + (r0 / 22) * 16384 + wg * 8192 + (r0 % 22) * HPITCH + q * 4;
                uint8_t* d1 = sgen + (r1 / 22) * 16384 + wg * 8192 + (r1 % 22) * HPITCH + q * 4;
#pragma unroll
                for (int t = 0; t < 22; t++) {
                    const uint32_t bv = sBias[t * 4 + q];
                    const float bb0 = bf_lo(bv), bb1 = bf_hi(bv);
                    *(uint32_t*)(d0 + t * 16) = pack_bf16(accF[t * 4 + 0] + bb0, accF[t * 4 + 1] + bb1);
                    *(uint32_t*)(d1 + t * 16) = pack_bf16(accF[t * 4 + 2] + bb0, accF[t * 4 + 3] + bb1);
                }
                bar_arrive(4 + wg, 128 + 224);
            }
        }
        wgmma_wait<0>();
        TS(4, tid == 0);
        {
            bf16* orow0 = g_qkv + ((size_t)j * S_ + rb * 128 + rl) * 192;
            bf16* orow1 = orow0 + 8 * 192;
#pragma unroll
            for (int u = 0; u < 6; u++) {
                uint32_t w0[4], w1[4];
#pragma unroll
                for (int i = 0; i < 4; i++) {
                    const int t = u * 4 + i;
                    w0[i] = pack_bf16(accQ[t * 4 + 0], accQ[t * 4 + 1]);
                    w1[i] = pack_bf16(accQ[t * 4 + 2], accQ[t * 4 + 3]);
                }
                quad_transpose(w0, q);
                quad_transpose(w1, q);
                const int c = (u * 4 + q) * 8;
                *(uint4*)(orow0 + c) = make_uint4(w0[0], w0[1], w0[2], w0[3]);
                *(uint4*)(orow1 + c) = make_uint4(w1[0], w1[1], w1[2], w1[3]);
            }
        }
        TS(5, tid == 0);
    }
}

__device__ __forceinline__ void ldsm_x4(uint32_t (&r)[4], uint32_t addr) {
    asm("ldmatrix.sync.aligned.m8n8.x4.shared.b16 {%0,%1,%2,%3}, [%4];"
                 : "=r"(r[0]), "=r"(r[1]), "=r"(r[2]), "=r"(r[3]) : "r"(addr));
}
__device__ __forceinline__ void ldsm_x4_t(uint32_t (&r)[4], uint32_t addr) {
    asm("ldmatrix.sync.aligned.m8n8.x4.trans.shared.b16 {%0,%1,%2,%3}, [%4];"
                 : "=r"(r[0]), "=r"(r[1]), "=r"(r[2]), "=r"(r[3]) : "r"(addr));
}
__device__ __forceinline__ void mma16816(float (&d)[4], const uint32_t (&a)[4], uint32_t b0, uint32_t b1) {
    asm("mma.sync.aligned.m16n8k16.row.col.f32.bf16.bf16.f32 {%0,%1,%2,%3}, {%4,%5,%6,%7}, {%8,%9}, {%0,%1,%2,%3};"
                 : "+f"(d[0]), "+f"(d[1]), "+f"(d[2]), "+f"(d[3])
                 : "r"(a[0]), "r"(a[1]), "r"(a[2]), "r"(a[3]), "r"(b0), "r"(b1));
}
__device__ __forceinline__ void mma16816_z(float (&d)[4], const uint32_t (&a)[4], uint32_t b0, uint32_t b1) {
    asm("mma.sync.aligned.m16n8k16.row.col.f32.bf16.bf16.f32 {%0,%1,%2,%3}, {%4,%5,%6,%7}, {%8,%9}, {%10,%10,%10,%10};"
                 : "=f"(d[0]), "=f"(d[1]), "=f"(d[2]), "=f"(d[3])
                 : "r"(a[0]), "r"(a[1]), "r"(a[2]), "r"(a[3]), "r"(b0), "r"(b1), "f"(0.f));
}

constexpr int KV_PITCH = 128;

template <int EDGE, bool HEAD>
__device__ __forceinline__ void blk_scores(float (&s)[2][4], const uint32_t (&qa)[4], uint32_t kaddr, bool dead, int r0, int c0)
{
    uint32_t kf[4];
    ldsm_x4(kf, kaddr);
    mma16816_z(s[0], qa, kf[0], kf[1]);
    mma16816_z(s[1], qa, kf[2], kf[3]);
#pragma unroll
    for (int t = 0; t < 2; t++)
#pragma unroll
        for (int e = 0; e < 4; e++) {
            const int r = r0 + (e >> 1) * 8, c = t * 8 + c0 + (e & 1);
            if (EDGE == 1 && c <= r) s[t][e] = -1e30f;
            if (EDGE == 2 && c > r) s[t][e] = -1e30f;
            if (HEAD && dead) s[t][e] = -1e30f;
        }
}
__device__ __forceinline__ void blk_max(const float (&s)[2][4], float& n0, float& n1) {
    n0 = fmaxf(n0, fmaxf(fmaxf(s[0][0], s[0][1]), fmaxf(s[1][0], s[1][1])));
    n1 = fmaxf(n1, fmaxf(fmaxf(s[0][2], s[0][3]), fmaxf(s[1][2], s[1][3])));
}
__device__ __forceinline__ void blk_pv(const float (&s)[2][4], float mc0, float mc1, float& l0, float& l1,
                                       float (&o)[2][4], uint32_t vaddr) {
    const float C = 0.25f * 1.4426950408889634f;
    uint32_t pa[4];
#pragma unroll
    for (int t = 0; t < 2; t++) {
        const float p0 = ex2(fmaf(s[t][0], C, -mc0)), p1 = ex2(fmaf(s[t][1], C, -mc0));
        const float p2 = ex2(fmaf(s[t][2], C, -mc1)), p3 = ex2(fmaf(s[t][3], C, -mc1));
        l0 += p0 + p1; l1 += p2 + p3;
        pa[2 * t] = pack_bf16(p0, p1); pa[2 * t + 1] = pack_bf16(p2, p3);
    }
    uint32_t vf[4];
    ldsm_x4_t(vf, vaddr);
    mma16816(o[0], pa, vf[0], vf[1]);
    mma16816(o[1], pa, vf[2], vf[3]);
}
__device__ __forceinline__ void quad_max(float& n0, float& n1) {
    n0 = fmaxf(n0, __shfl_xor_sync(0xffffffffu, n0, 1)); n1 = fmaxf(n1, __shfl_xor_sync(0xffffffffu, n1, 1));
    n0 = fmaxf(n0, __shfl_xor_sync(0xffffffffu, n0, 2)); n1 = fmaxf(n1, __shfl_xor_sync(0xffffffffu, n1, 2));
}
template <int NC, int NN, bool FIRST, bool NEXT_IS_EDGE, bool HEAD>
__device__ __forceinline__ void pipe_step(const float (&sc)[5][2][4], float (&sn)[5][2][4], const uint32_t (&qa)[4],
                                          uint32_t ka, uint32_t va, int kc, int kn, int kb0, int r0, int c0,
                                          float& m0, float& m1, float& n0, float& n1, float& l0, float& l1, float (&o)[2][4])
{
    const float C = 0.25f * 1.4426950408889634f;
    const float mc0 = n0 * C, mc1 = n1 * C;
    if (!FIRST) {
        const float a0 = ex2(fmaf(m0, C, -mc0)), a1 = ex2(fmaf(m1, C, -mc1));
        l0 *= a0; l1 *= a1;
        o[0][0] *= a0; o[0][1] *= a0; o[1][0] *= a0; o[1][1] *= a0;
        o[0][2] *= a1; o[0][3] *= a1; o[1][2] *= a1; o[1][3] *= a1;
    }
    m0 = n0; m1 = n1;
#pragma unroll
    for (int b = 0; b < NC; b++) {
        if (b < NN) {
            if (NEXT_IS_EDGE && b == 0) blk_scores<1, HEAD>(sn[b], qa, ka + (kn + b) * 16 * KV_PITCH, kn + b < kb0, r0, c0);
            else                        blk_scores<0, HEAD>(sn[b], qa, ka + (kn + b) * 16 * KV_PITCH, kn + b < kb0, r0, c0);
        }
        blk_pv(sc[b], mc0, mc1, l0, l1, o, va + (kc + b) * 16 * KV_PITCH);
        if (b < NN) blk_max(sn[b], n0, n1);
    }
    if (NN > 0) quad_max(n0, n1);
}

template <bool HEAD>
__device__ __forceinline__ void attn_task(const uint32_t (&qa)[4], uint32_t ka, uint32_t va, int kb0, int lane,
                                          bf16* __restrict__ out  , float g0, float g1)
{
    const int r0 = lane >> 2, c0 = (lane & 3) * 2;
    float m0 = -1e30f, m1 = -1e30f, n0 = -1e30f, n1 = -1e30f, l0 = 0.f, l1 = 0.f;
    float o[2][4] = {{0.f, 0.f, 0.f, 0.f}, {0.f, 0.f, 0.f, 0.f}};
    float sa[5][2][4], sb[5][2][4];
#pragma unroll
    for (int b = 0; b < 5; b++) {
        if (b == 4) blk_scores<2, HEAD>(sa[b], qa, ka + (12 + b) * 16 * KV_PITCH, false, r0, c0);
        else        blk_scores<0, HEAD>(sa[b], qa, ka + (12 + b) * 16 * KV_PITCH, 12 + b < kb0, r0, c0);
        blk_max(sa[b], n0, n1);
    }
    quad_max(n0, n1);
    pipe_step<5, 4, true,  false, HEAD>(sa, sb, qa, ka, va, 12, 8, kb0, r0, c0, m0, m1, n0, n1, l0, l1, o);
    pipe_step<4, 4, false, false, HEAD>(sb, sa, qa, ka, va, 8, 4, kb0, r0, c0, m0, m1, n0, n1, l0, l1, o);
    pipe_step<4, 4, false, true,  HEAD>(sa, sb, qa, ka, va, 4, 0, kb0, r0, c0, m0, m1, n0, n1, l0, l1, o);
    pipe_step<4, 0, false, false, HEAD>(sb, sa, qa, ka, va, 0, 0, kb0, r0, c0, m0, m1, n0, n1, l0, l1, o);
    l0 += __shfl_xor_sync(0xffffffffu, l0, 1); l0 += __shfl_xor_sync(0xffffffffu, l0, 2);
    l1 += __shfl_xor_sync(0xffffffffu, l1, 1); l1 += __shfl_xor_sync(0xffffffffu, l1, 2);
    const float f0 = g0 / l0, f1 = g1 / l1;
#pragma unroll
    for (int t = 0; t < 2; t++) {
        *(uint32_t*)(out + (size_t)r0 * KA2 + t * 8 + c0) = pack_bf16(o[t][0] * f0, o[t][1] * f0);
        *(uint32_t*)(out + (size_t)(r0 + 8) * KA2 + t * 8 + c0) = pack_bf16(o[t][2] * f1, o[t][3] * f1);
    }
}

constexpr int K2_SMEM = 2 * 384 * KV_PITCH + 1024 + 64;

__global__ void __launch_bounds__(512, 1) k2_kernel(const __grid_constant__ CUtensorMap tmQKV)
{
    extern __shared__ uint8_t smem_raw[];
    const uint32_t sbase = (smem_u32(smem_raw) + 1023u) & ~1023u;
    uint8_t* sgen = smem_raw + (sbase - smem_u32(smem_raw));
    const uint32_t sK = sbase, sV = sK + 384 * KV_PITCH, kv_full = sbase + 2 * 384 * KV_PITCH;
    const int rb = blockIdx.x >> 3, j = blockIdx.x & 7;
    const int tid = threadIdx.x, warp = tid >> 5, lane = tid & 31;
    pdl_launch();
    if (tid == 0) {
        mbar_init(kv_full, 1);
        fence_barrier_init();
    }
    pdl_wait();
    TS(6, tid == 0);
    if (tid == 0) {
        const int nblk = rb >= 2 ? 3 : rb + 1;
        mbar_expect_tx(kv_full, nblk * 2 * 16384);
        for (int i = 0; i < nblk; i++) {
            const int row = j * S_ + (rb - i) * 128;
            tma_load_2d(sK + (2 - i) * 16384, &tmQKV, 64, row, kv_full);
            tma_load_2d(sV + (2 - i) * 16384, &tmQKV, 128, row, kv_full);
        }
    }
    if (rb < 2) {
        for (int i = tid; i < (2 - rb) * 1024; i += 512) {
            *(uint4*)(sgen + i * 16) = make_uint4(0, 0, 0, 0);
            *(uint4*)(sgen + 384 * KV_PITCH + i * 16) = make_uint4(0, 0, 0, 0);
        }
    }
    const int qt = warp & 7, h0 = (warp >> 3) * 2;
    const int q0g = rb * 128 + qt * 16;
    const int r0 = lane >> 2, c0 = (lane & 3) * 2;
    const bf16* qsrc = g_qkv + ((size_t)j * S_ + q0g) * 192 + h0 * 16;
    uint32_t qa[4], qn[4];
    qa[0] = *(const uint32_t*)(qsrc + (size_t)r0 * 192 + c0);
    qa[1] = *(const uint32_t*)(qsrc + (size_t)(r0 + 8) * 192 + c0);
    qa[2] = *(const uint32_t*)(qsrc + (size_t)r0 * 192 + c0 + 8);
    qa[3] = *(const uint32_t*)(qsrc + (size_t)(r0 + 8) * 192 + c0 + 8);
    qn[0] = *(const uint32_t*)(qsrc + (size_t)r0 * 192 + 16 + c0);
    qn[1] = *(const uint32_t*)(qsrc + (size_t)(r0 + 8) * 192 + 16 + c0);
    qn[2] = *(const uint32_t*)(qsrc + (size_t)r0 * 192 + 16 + c0 + 8);
    qn[3] = *(const uint32_t*)(qsrc + (size_t)(r0 + 8) * 192 + 16 + c0 + 8);
    const float g0 = g_gate[q0g + r0], g1 = g_gate[q0g + r0 + 8];
    const int kb0 = q0g < 256 ? (256 - q0g) >> 4 : 0;
    __syncthreads();
    mbar_wait(kv_full, 0);
    uint32_t sKd = sK, sVd = sV;
    asm volatile("" : "+r"(sKd), "+r"(sVd) :: "memory");
    TS(7, tid == 0);
    const int krow = qt * 16 + (lane & 7) + ((lane >> 4) << 3);
    const int vrow = qt * 16 + (lane & 15);
#pragma unroll 1
    for (int hh = 0; hh < 2; hh++) {
        const int hl = h0 + hh;
        const uint32_t ka = sKd + krow * KV_PITCH + (((2 * hl + ((lane >> 3) & 1)) ^ (lane & 7)) << 4);
        const uint32_t va = sVd + vrow * KV_PITCH + (((2 * hl + (lane >> 4)) ^ (lane & 7)) << 4);
        if (rb < 2) attn_task<true>(qa, ka, va, kb0, lane, g_a2 + (size_t)q0g * KA2 + (j * 4 + hl) * 16, g0, g1);
        else        attn_task<false>(qa, ka, va, kb0, lane, g_a2 + (size_t)q0g * KA2 + (j * 4 + hl) * 16, g0, g1);
        TS(8 + hh, tid == 0);
        qa[0] = qn[0]; qa[1] = qn[1]; qa[2] = qn[2]; qa[3] = qn[3];
    }
}

constexpr int K3_STAGES = 8;
constexpr int K3_STAGE = 16384 + 8192;
constexpr int K3_SMEM = K3_STAGES * K3_STAGE + 1024 + 1024;
constexpr int K3_KSTEPS = 30;

__global__ void __launch_bounds__(384, 1)
k3_kernel(const __grid_constant__ CUtensorMap tmA2, const __grid_constant__ CUtensorMap tmWo,
          const __grid_constant__ CUtensorMap tmW2, bf16* __restrict__ out)
{
    extern __shared__ uint8_t smem_raw[];
    const uint32_t sbase = (smem_u32(smem_raw) + 1023u) & ~1023u;
    const uint32_t sBar = sbase + K3_STAGES * K3_STAGE;
    const uint32_t full = sBar, empty = sBar + 64;
    const int rb = blockIdx.x >> 3, nb = blockIdx.x & 7;
    const int tid = threadIdx.x, wg = tid >> 7, warp = tid >> 5, lane = tid & 31;
    if (tid == 0) {
        for (int i = 0; i < K3_STAGES; i++) { mbar_init(full + 8 * i, 1); mbar_init(empty + 8 * i, 8); }
        fence_barrier_init();
    }
    __syncthreads();
    pdl_wait();
    TS(10, tid == 0);
    if (wg == 2) {
        reg_dealloc<40>();
        if (tid == 256) {
            for (int ks = 0; ks < K3_KSTEPS; ks++) {
                const int st = ks % K3_STAGES;
                if (ks >= K3_STAGES) mbar_wait(empty + 8 * st, ((ks / K3_STAGES) - 1) & 1);
                mbar_expect_tx(full + 8 * st, K3_STAGE);
                const uint32_t dst = sbase + st * K3_STAGE;
                tma_load_2d(dst, &tmA2, ks * 64, rb * 128, full + 8 * st);
                if (ks < 8) tma_load_2d(dst + 16384, &tmWo, nb * 64, ks * 64, full + 8 * st);
                else        tma_load_2d(dst + 16384, &tmW2, nb * 64, (ks - 8) * 64, full + 8 * st);
            }
        }
    } else {
        reg_alloc<232>();
        float acc[32];
        for (int ks = 0; ks < K3_KSTEPS; ks++) {
            const int st = ks % K3_STAGES;
            mbar_wait(full + 8 * st, (ks / K3_STAGES) & 1);
            TS(11, tid == 0 && ks == 0); TS(12, tid == 0 && ks == 8); TS(13, tid == 0 && ks == 16);
            wgmma_fence();
#pragma unroll
            for (int k16 = 0; k16 < 4; k16++) {
                const uint64_t da = make_desc(sbase + st * K3_STAGE + wg * 8192 + k16 * 32, 16, 1024);
                const uint64_t db = make_desc(sbase + st * K3_STAGE + 16384 + k16 * 2048, 8192, 1024);
                wgmma_n64<1>(acc, da, db, (ks | k16) != 0);
            }
            wgmma_commit();
            if (ks > 0) { wgmma_wait<1>(); if (lane == 0) mbar_arrive(empty + 8 * ((ks - 1) % K3_STAGES)); }
        }
        wgmma_wait<0>();
        TS(14, tid == 0);
        const int q = lane & 3;
        const int r = rb * 128 + wg * 64 + (warp & 3) * 16 + (lane >> 2);
        bf16* orow0 = out + (size_t)r * D_ + nb * 64;
        bf16* orow1 = orow0 + 8 * D_;
#pragma unroll
        for (int u = 0; u < 2; u++) {
            uint32_t w0[4], w1[4];
#pragma unroll
            for (int i = 0; i < 4; i++) {
                const int t = u * 4 + i;
                w0[i] = pack_bf16(acc[t * 4 + 0], acc[t * 4 + 1]);
                w1[i] = pack_bf16(acc[t * 4 + 2], acc[t * 4 + 3]);
            }
            quad_transpose(w0, q);
            quad_transpose(w1, q);
            const int c = (u * 4 + q) * 8;
            *(uint4*)(orow0 + c) = make_uint4(w0[0], w0[1], w0[2], w0[3]);
            *(uint4*)(orow1 + c) = make_uint4(w1[0], w1[1], w1[2], w1[3]);
        }
        TS(15, tid == 0);
    }
}

typedef CUresult (*PFN_encodeTiled)(CUtensorMap*, CUtensorMapDataType, cuuint32_t, void*, const cuuint64_t*,
                                    const cuuint64_t*, const cuuint32_t*, const cuuint32_t*, CUtensorMapInterleave,
                                    CUtensorMapSwizzle, CUtensorMapL2promotion, CUtensorMapFloatOOBfill);

static void make_map(PFN_encodeTiled enc, CUtensorMap* m, const void* ptr, uint64_t cols, uint64_t rows,
                     uint32_t box_cols, uint32_t box_rows)
{
    cuuint64_t dims[2] = {cols, rows};
    cuuint64_t strides[1] = {cols * 2};
    cuuint32_t box[2] = {box_cols, box_rows};
    cuuint32_t es[2] = {1, 1};
    enc(m, CU_TENSOR_MAP_DATA_TYPE_BFLOAT16, 2, const_cast<void*>(ptr), dims, strides, box, es,
        CU_TENSOR_MAP_INTERLEAVE_NONE, CU_TENSOR_MAP_SWIZZLE_128B, CU_TENSOR_MAP_L2_PROMOTION_L2_128B,
        CU_TENSOR_MAP_FLOAT_OOB_FILL_NONE);
}

extern "C" void kernel_launch(void* const* d_in, const int* in_sizes, int n_in, void* d_out, int out_size)
{
    const bf16* x    = (const bf16*)d_in[0];
    const bf16* wqkv = (const bf16*)d_in[1];
    const bf16* wo   = (const bf16*)d_in[2];
    const bf16* w1   = (const bf16*)d_in[4];
    const bf16* b1   = (const bf16*)d_in[5];
    const bf16* w2   = (const bf16*)d_in[6];
    const bf16* gw   = (const bf16*)d_in[7];

    static PFN_encodeTiled enc = nullptr;
    if (!enc) {
        void* fn = nullptr;
        cudaDriverEntryPointQueryResult qr;
        cudaGetDriverEntryPoint("cuTensorMapEncodeTiled", &fn, cudaEnableDefault, &qr);
        enc = (PFN_encodeTiled)fn;
        cudaFuncSetAttribute(k1_kernel, cudaFuncAttributeMaxDynamicSharedMemorySize, K1_SMEM);
        cudaFuncSetAttribute(k2_kernel, cudaFuncAttributeMaxDynamicSharedMemorySize, K2_SMEM);
        cudaFuncSetAttribute(k3_kernel, cudaFuncAttributeMaxDynamicSharedMemorySize, K3_SMEM);
    }
    void* a2p = nullptr;
    cudaGetSymbolAddress(&a2p, g_a2);
    void* qkvp = nullptr;
    cudaGetSymbolAddress(&qkvp, g_qkv);
    CUtensorMap tmX, tmWqkv, tmW1, tmA2, tmWo, tmW2, tmQKV;
    make_map(enc, &tmQKV, qkvp, 192, 8 * S_, 64, 128);
    make_map(enc, &tmX, x, D_, S_, 64, 128);
    make_map(enc, &tmWqkv, wqkv, 3 * D_, D_, 64, 64);
    make_map(enc, &tmW1, w1, F_, D_, 64, 64);
    make_map(enc, &tmA2, a2p, KA2, S_, 64, 128);
    make_map(enc, &tmWo, wo, D_, D_, 64, 64);
    make_map(enc, &tmW2, w2, D_, F_, 64, 64);

    cudaStream_t st = cudaStreamPerThread;
    k1_kernel<<<128, 512, K1_SMEM, st>>>(tmX, tmWqkv, tmW1, b1, gw, w1, wqkv, w2, wo);
    cudaLaunchAttribute at[1];
    at[0].id = cudaLaunchAttributeProgrammaticStreamSerialization;
    at[0].val.programmaticStreamSerializationAllowed = 1;
    cudaLaunchConfig_t cfg = {};
    cfg.gridDim = dim3(128); cfg.stream = st; cfg.attrs = at; cfg.numAttrs = 1;
    cfg.blockDim = dim3(512); cfg.dynamicSmemBytes = K2_SMEM;
    cudaLaunchKernelEx(&cfg, k2_kernel, tmQKV);
    k3_kernel<<<128, 384, K3_SMEM, st>>>(tmA2, tmWo, tmW2, (bf16*)d_out);
}
```

```cpp
#include <cuda_runtime.h>
#include <cuda_bf16.h>
#include <cuda.h>
#include <stdint.h>

typedef __nv_bfloat16 bf16;

constexpr int S_ = 2048, D_ = 512, F_ = 1376;
constexpr int KA2 = D_ + F_;
constexpr int FCH = 176;

__device__ bf16  g_qkv[8 * S_ * 192];
__device__ bf16  g_a2[S_ * KA2];
__device__ float g_gate[S_];

#define TS(k, cond) do { } while (0)

__device__ __forceinline__ uint32_t smem_u32(const void* p) { return (uint32_t)__cvta_generic_to_shared(p); }
__device__ __forceinline__ void mbar_init(uint32_t bar, uint32_t count) {
    asm volatile("mbarrier.init.shared::cta.b64 [%0], %1;" :: "r"(bar), "r"(count) : "memory");
}
__device__ __forceinline__ void mbar_expect_tx(uint32_t bar, uint32_t bytes) {
    asm volatile("mbarrier.arrive.expect_tx.shared::cta.b64 _, [%0], %1;" :: "r"(bar), "r"(bytes) : "memory");
}
__device__ __forceinline__ void mbar_arrive(uint32_t bar) {
    asm volatile("mbarrier.arrive.shared::cta.b64 _, [%0];" :: "r"(bar) : "memory");
}
__device__ __forceinline__ bool mbar_try_wait(uint32_t bar, uint32_t parity) {
    uint32_t ok;
    asm volatile("{\n.reg .pred p;\nmbarrier.try_wait.parity.shared::cta.b64 p, [%1], %2;\nselp.u32 %0, 1, 0, p;\n}"
                 : "=r"(ok) : "r"(bar), "r"(parity) : "memory");
    return ok != 0;
}
__device__ __forceinline__ void mbar_wait(uint32_t bar, uint32_t parity) {
    for (uint32_t it = 0; it < (1u << 22); ++it) { if (mbar_try_wait(bar, parity)) break; }
}
__device__ __forceinline__ void tma_load_2d(uint32_t dst, const CUtensorMap* map, int c0, int c1, uint32_t bar) {
    asm volatile("cp.async.bulk.tensor.2d.shared::cluster.global.mbarrier::complete_tx::bytes [%0], [%1, {%3, %4}], [%2];"
                 :: "r"(dst), "l"(map), "r"(bar), "r"(c0), "r"(c1) : "memory");
}
__device__ __forceinline__ void l2_prefetch(const void* p, uint32_t bytes) {
    asm volatile("cp.async.bulk.prefetch.L2.global [%0], %1;" :: "l"(p), "r"(bytes) : "memory");
}
__device__ __forceinline__ void fence_barrier_init() { asm volatile("fence.mbarrier_init.release.cluster;" ::: "memory"); }
__device__ __forceinline__ void wgmma_fence()  { asm volatile("wgmma.fence.sync.aligned;" ::: "memory"); }
__device__ __forceinline__ void wgmma_commit() { asm volatile("wgmma.commit_group.sync.aligned;" ::: "memory"); }
template <int N> __device__ __forceinline__ void wgmma_wait() { asm volatile("wgmma.wait_group.sync.aligned %0;" :: "n"(N) : "memory"); }
template <int R> __device__ __forceinline__ void reg_alloc()   { asm volatile("setmaxnreg.inc.sync.aligned.u32 %0;" :: "n"(R)); }
template <int R> __device__ __forceinline__ void reg_dealloc() { asm volatile("setmaxnreg.dec.sync.aligned.u32 %0;" :: "n"(R)); }
__device__ __forceinline__ void bar_sync(int id, int n)   { asm volatile("bar.sync %0, %1;" :: "r"(id), "r"(n) : "memory"); }
__device__ __forceinline__ void bar_arrive(int id, int n) { asm volatile("bar.arrive %0, %1;" :: "r"(id), "r"(n) : "memory"); }

__device__ __forceinline__ uint64_t make_desc(uint32_t addr, uint32_t lbo, uint32_t sbo) {
    uint64_t d = (uint64_t)((addr & 0x3FFFF) >> 4);
    d |= (uint64_t)((lbo & 0x3FFFF) >> 4) << 16;
    d |= (uint64_t)((sbo & 0x3FFFF) >> 4) << 32;
    d |= (uint64_t)1 << 62;
    return d;
}

template <int TB>
__device__ __forceinline__ void wgmma_n64(float (&d)[32], uint64_t da, uint64_t db, int scale_d) {
    asm volatile("{\n.reg .pred p;\nsetp.ne.b32 p, %34, 0;\n"
        "wgmma.mma_async.sync.aligned.m64n64k16.f32.bf16.bf16 {%0, %1, %2, %3, %4, %5, %6, %7, %8, %9, %10, %11, %12, %13, %14, %15, %16, %17, %18, %19, %20, %21, %22, %23, %24, %25, %26, %27, %28, %29, %30, %31}, %32, %33, p, 1, 1, 0, %35;\n}\n"
        : "+f"(d[0]), "+f"(d[1]), "+f"(d[2]), "+f"(d[3]), "+f"(d[4]), "+f"(d[5]), "+f"(d[6]), "+f"(d[7]), "+f"(d[8]), "+f"(d[9]), "+f"(d[10]), "+f"(d[11]), "+f"(d[12]), "+f"(d[13]), "+f"(d[14]), "+f"(d[15]), "+f"(d[16]), "+f"(d[17]), "+f"(d[18]), "+f"(d[19]), "+f"(d[20]), "+f"(d[21]), "+f"(d[22]), "+f"(d[23]), "+f"(d[24]), "+f"(d[25]), "+f"(d[26]), "+f"(d[27]), "+f"(d[28]), "+f"(d[29]), "+f"(d[30]), "+f"(d[31])
        : "l"(da), "l"(db), "r"(scale_d), "n"(TB));
}

template <int TB>
__device__ __forceinline__ void wgmma_n128(float (&d)[64], uint64_t da, uint64_t db, int scale_d) {
    asm volatile("{\n.reg .pred p;\nsetp.ne.b32 p, %66, 0;\n"
        "wgmma.mma_async.sync.aligned.m64n128k16.f32.bf16.bf16 {%0, %1, %2, %3, %4, %5, %6, %7, %8, %9, %10, %11, %12, %13, %14, %15, %16, %17, %18, %19, %20, %21, %22, %23, %24, %25, %26, %27, %28, %29, %30, %31, %32, %33, %34, %35, %36, %37, %38, %39, %40, %41, %42, %43, %44, %45, %46, %47, %48, %49, %50, %51, %52, %53, %54, %55, %56, %57, %58, %59, %60, %61, %62, %63}, %64, %65, p, 1, 1, 0, %67;\n}\n"
        : "+f"(d[0]), "+f"(d[1]), "+f"(d[2]), "+f"(d[3]), "+f"(d[4]), "+f"(d[5]), "+f"(d[6]), "+f"(d[7]), "+f"(d[8]), "+f"(d[9]), "+f"(d[10]), "+f"(d[11]), "+f"(d[12]), "+f"(d[13]), "+f"(d[14]), "+f"(d[15]), "+f"(d[16]), "+f"(d[17]), "+f"(d[18]), "+f"(d[19]), "+f"(d[20]), "+f"(d[21]), "+f"(d[22]), "+f"(d[23]), "+f"(d[24]), "+f"(d[25]), "+f"(d[26]), "+f"(d[27]), "+f"(d[28]), "+f"(d[29]), "+f"(d[30]), "+f"(d[31]), "+f"(d[32]), "+f"(d[33]), "+f"(d[34]), "+f"(d[35]), "+f"(d[36]), "+f"(d[37]), "+f"(d[38]), "+f"(d[39]), "+f"(d[40]), "+f"(d[41]), "+f"(d[42]), "+f"(d[43]), "+f"(d[44]), "+f"(d[45]), "+f"(d[46]), "+f"(d[47]), "+f"(d[48]), "+f"(d[49]), "+f"(d[50]), "+f"(d[51]), "+f"(d[52]), "+f"(d[53]), "+f"(d[54]), "+f"(d[55]), "+f"(d[56]), "+f"(d[57]), "+f"(d[58]), "+f"(d[59]), "+f"(d[60]), "+f"(d[61]), "+f"(d[62]), "+f"(d[63])
        : "l"(da), "l"(db), "r"(scale_d), "n"(TB));
}

template <int TB>
__device__ __forceinline__ void wgmma_n176(float (&d)[88], uint64_t da, uint64_t db, int scale_d) {
    asm volatile("{\n.reg .pred p;\nsetp.ne.b32 p, %90, 0;\n"
        "wgmma.mma_async.sync.aligned.m64n176k16.f32.bf16.bf16 {%0, %1, %2, %3, %4, %5, %6, %7, %8, %9, %10, %11, %12, %13, %14, %15, %16, %17, %18, %19, %20, %21, %22, %23, %24, %25, %26, %27, %28, %29, %30, %31, %32, %33, %34, %35, %36, %37, %38, %39, %40, %41, %42, %43, %44, %45, %46, %47, %48, %49, %50, %51, %52, %53, %54, %55, %56, %57, %58, %59, %60, %61, %62, %63, %64, %65, %66, %67, %68, %69, %70, %71, %72, %73, %74, %75, %76, %77, %78, %79, %80, %81, %82, %83, %84, %85, %86, %87}, %88, %89, p, 1, 1, 0, %91;\n}\n"
        : "+f"(d[0]), "+f"(d[1]), "+f"(d[2]), "+f"(d[3]), "+f"(d[4]), "+f"(d[5]), "+f"(d[6]), "+f"(d[7]), "+f"(d[8]), "+f"(d[9]), "+f"(d[10]), "+f"(d[11]), "+f"(d[12]), "+f"(d[13]), "+f"(d[14]), "+f"(d[15]), "+f"(d[16]), "+f"(d[17]), "+f"(d[18]), "+f"(d[19]), "+f"(d[20]), "+f"(d[21]), "+f"(d[22]), "+f"(d[23]), "+f"(d[24]), "+f"(d[25]), "+f"(d[26]), "+f"(d[27]), "+f"(d[28]), "+f"(d[29]), "+f"(d[30]), "+f"(d[31]), "+f"(d[32]), "+f"(d[33]), "+f"(d[34]), "+f"(d[35]), "+f"(d[36]), "+f"(d[37]), "+f"(d[38]), "+f"(d[39]), "+f"(d[40]), "+f"(d[41]), "+f"(d[42]), "+f"(d[43]), "+f"(d[44]), "+f"(d[45]), "+f"(d[46]), "+f"(d[47]), "+f"(d[48]), "+f"(d[49]), "+f"(d[50]), "+f"(d[51]), "+f"(d[52]), "+f"(d[53]), "+f"(d[54]), "+f"(d[55]), "+f"(d[56]), "+f"(d[57]), "+f"(d[58]), "+f"(d[59]), "+f"(d[60]), "+f"(d[61]), "+f"(d[62]), "+f"(d[63]), "+f"(d[64]), "+f"(d[65]), "+f"(d[66]), "+f"(d[67]), "+f"(d[68]), "+f"(d[69]), "+f"(d[70]), "+f"(d[71]), "+f"(d[72]), "+f"(d[73]), "+f"(d[74]), "+f"(d[75]), "+f"(d[76]), "+f"(d[77]), "+f"(d[78]), "+f"(d[79]), "+f"(d[80]), "+f"(d[81]), "+f"(d[82]), "+f"(d[83]), "+f"(d[84]), "+f"(d[85]), "+f"(d[86]), "+f"(d[87])
        : "l"(da), "l"(db), "r"(scale_d), "n"(TB));
}

template <int TB>
__device__ __forceinline__ void wgmma_n192(float (&d)[96], uint64_t da, uint64_t db, int scale_d) {
    asm volatile("{\n.reg .pred p;\nsetp.ne.b32 p, %98, 0;\n"
        "wgmma.mma_async.sync.aligned.m64n192k16.f32.bf16.bf16 {%0, %1, %2, %3, %4, %5, %6, %7, %8, %9, %10, %11, %12, %13, %14, %15, %16, %17, %18, %19, %20, %21, %22, %23, %24, %25, %26, %27, %28, %29, %30, %31, %32, %33, %34, %35, %36, %37, %38, %39, %40, %41, %42, %43, %44, %45, %46, %47, %48, %49, %50, %51, %52, %53, %54, %55, %56, %57, %58, %59, %60, %61, %62, %63, %64, %65, %66, %67, %68, %69, %70, %71, %72, %73, %74, %75, %76, %77, %78, %79, %80, %81, %82, %83, %84, %85, %86, %87, %88, %89, %90, %91, %92, %93, %94, %95}, %96, %97, p, 1, 1, 0, %99;\n}\n"
        : "+f"(d[0]), "+f"(d[1]), "+f"(d[2]), "+f"(d[3]), "+f"(d[4]), "+f"(d[5]), "+f"(d[6]), "+f"(d[7]), "+f"(d[8]), "+f"(d[9]), "+f"(d[10]), "+f"(d[11]), "+f"(d[12]), "+f"(d[13]), "+f"(d[14]), "+f"(d[15]), "+f"(d[16]), "+f"(d[17]), "+f"(d[18]), "+f"(d[19]), "+f"(d[20]), "+f"(d[21]), "+f"(d[22]), "+f"(d[23]), "+f"(d[24]), "+f"(d[25]), "+f"(d[26]), "+f"(d[27]), "+f"(d[28]), "+f"(d[29]), "+f"(d[30]), "+f"(d[31]), "+f"(d[32]), "+f"(d[33]), "+f"(d[34]), "+f"(d[35]), "+f"(d[36]), "+f"(d[37]), "+f"(d[38]), "+f"(d[39]), "+f"(d[40]), "+f"(d[41]), "+f"(d[42]), "+f"(d[43]), "+f"(d[44]), "+f"(d[45]), "+f"(d[46]), "+f"(d[47]), "+f"(d[48]), "+f"(d[49]), "+f"(d[50]), "+f"(d[51]), "+f"(d[52]), "+f"(d[53]), "+f"(d[54]), "+f"(d[55]), "+f"(d[56]), "+f"(d[57]), "+f"(d[58]), "+f"(d[59]), "+f"(d[60]), "+f"(d[61]), "+f"(d[62]), "+f"(d[63]), "+f"(d[64]), "+f"(d[65]), "+f"(d[66]), "+f"(d[67]), "+f"(d[68]), "+f"(d[69]), "+f"(d[70]), "+f"(d[71]), "+f"(d[72]), "+f"(d[73]), "+f"(d[74]), "+f"(d[75]), "+f"(d[76]), "+f"(d[77]), "+f"(d[78]), "+f"(d[79]), "+f"(d[80]), "+f"(d[81]), "+f"(d[82]), "+f"(d[83]), "+f"(d[84]), "+f"(d[85]), "+f"(d[86]), "+f"(d[87]), "+f"(d[88]), "+f"(d[89]), "+f"(d[90]), "+f"(d[91]), "+f"(d[92]), "+f"(d[93]), "+f"(d[94]), "+f"(d[95])
        : "l"(da), "l"(db), "r"(scale_d), "n"(TB));
}

__device__ __forceinline__ uint32_t pack_bf16(float lo, float hi) {
    uint32_t r;
    asm("cvt.rn.bf16x2.f32 %0, %1, %2;" : "=r"(r) : "f"(hi), "f"(lo));
    return r;
}
__device__ __forceinline__ float bf_lo(uint32_t v) { return __uint_as_float(v << 16); }
__device__ __forceinline__ float bf_hi(uint32_t v) { return __uint_as_float(v & 0xffff0000u); }

__device__ __forceinline__ void quad_transpose(uint32_t (&w)[4], int q) {
    const bool o1 = q & 1, o2 = q & 2;
    {
        uint32_t s0 = o1 ? w[0] : w[1], s1 = o1 ? w[2] : w[3];
        s0 = __shfl_xor_sync(0xffffffffu, s0, 1); s1 = __shfl_xor_sync(0xffffffffu, s1, 1);
        if (o1) { w[0] = s0; w[2] = s1; } else { w[1] = s0; w[3] = s1; }
    }
    {
        uint32_t s0 = o2 ? w[0] : w[2], s1 = o2 ? w[1] : w[3];
        s0 = __shfl_xor_sync(0xffffffffu, s0, 2); s1 = __shfl_xor_sync(0xffffffffu, s1, 2);
        if (o2) { w[0] = s0; w[1] = s1; } else { w[2] = s0; w[3] = s1; }
    }
}

__device__ __forceinline__ float ex2(float x) { float y; asm("ex2.approx.ftz.f32 %0, %1;" : "=f"(y) : "f"(x)); return y; }
__device__ __forceinline__ float rcp(float x) { float y; asm("rcp.approx.ftz.f32 %0, %1;" : "=f"(y) : "f"(x)); return y; }

__device__ __forceinline__ float ex2v(float x) { float y; asm volatile("ex2.approx.ftz.f32 %0, %1;" : "=f"(y) : "f"(x)); return y; }
__device__ __forceinline__ float rcpv(float x) { float y; asm volatile("rcp.approx.ftz.f32 %0, %1;" : "=f"(y) : "f"(x)); return y; }
__device__ __forceinline__ float mish_f(float h) {
    const float e = ex2v(1.4426950408889634f * fminf(h, 20.f));
    const float n = fmaf(e, e, e + e);
    return h * n * rcpv(n + 2.f);
}

__device__ __forceinline__ void pdl_wait()   { asm volatile("griddepcontrol.wait;" ::: "memory"); }
__device__ __forceinline__ void pdl_launch() { asm volatile("griddepcontrol.launch_dependents;" ::: "memory"); }

constexpr int K1_STAGES = 4;
constexpr int K1_XBYTES = 128 * 512 * 2;
constexpr int K1_BSTAGE = 3 * 8192;
constexpr int K1_SMEM   = K1_XBYTES + K1_STAGES * K1_BSTAGE + 2048   + 1024  ;
constexpr int HPITCH = 368;

__global__ void __launch_bounds__(512, 1)
k1_kernel(const __grid_constant__ CUtensorMap tmX, const __grid_constant__ CUtensorMap tmWqkv,
          const __grid_constant__ CUtensorMap tmW1, const bf16* __restrict__ b1,
          const bf16* __restrict__ gate_w, const bf16* __restrict__ w1p, const bf16* __restrict__ wqkvp,
          const bf16* __restrict__ w2p, const bf16* __restrict__ wop)
{
    extern __shared__ uint8_t smem_raw[];
    const uint32_t sbase = (smem_u32(smem_raw) + 1023u) & ~1023u;
    uint8_t* sgen = smem_raw + (sbase - smem_u32(smem_raw));
    const uint32_t sX = sbase;
    const uint32_t sB = sbase + K1_XBYTES;
    const uint32_t sBar = sB + K1_STAGES * K1_BSTAGE;
    const uint32_t x_full = sBar;
    const uint32_t b_full = sBar + 64;
    const uint32_t b_empty = sBar + 96;
    float* sGate = (float*)(sgen + K1_XBYTES + K1_STAGES * K1_BSTAGE + 128);
    uint8_t* sGw = sgen + K1_XBYTES + K1_STAGES * K1_BSTAGE + 640;
    uint32_t* sBias = (uint32_t*)(sgen + K1_XBYTES + K1_STAGES * K1_BSTAGE + 1664);

    const int rb = blockIdx.x >> 3, j = blockIdx.x & 7;
    const int tid = threadIdx.x, wg = tid >> 7, warp = tid >> 5, lane = tid & 31;
    TS(0, tid == 0);
    pdl_launch();

    if (tid == 0) {
        for (int i = 0; i < 8; i++) mbar_init(x_full + 8 * i, 1);
        for (int i = 0; i < K1_STAGES; i++) { mbar_init(b_full + 8 * i, 1); mbar_init(b_empty + 8 * i, 8); }
        fence_barrier_init();
    }
    __syncthreads();

    if (wg >= 2) {
        reg_dealloc<40>();
        if (warp == 8) {
            if (lane == 0) {
                for (int it = 0; it < 16; it++) {
                    if (it < 8) {
                        mbar_expect_tx(x_full + 8 * it, 16384);
                        tma_load_2d(sX + it * 16384, &tmX, it * 64, rb * 128, x_full + 8 * it);
                    }
                    const int st = it & 3;
                    if (it >= K1_STAGES) mbar_wait(b_empty + 8 * st, ((it >> 2) - 1) & 1);
                    mbar_expect_tx(b_full + 8 * st, K1_BSTAGE);
                    const uint32_t dst = sB + st * K1_BSTAGE;
                    if (it < 8) {
                        for (int b = 0; b < 3; b++) tma_load_2d(dst + b * 8192, &tmW1, j * FCH + b * 64, it * 64, b_full + 8 * st);
                    } else {
                        for (int b = 0; b < 3; b++) tma_load_2d(dst + b * 8192, &tmWqkv, b * 512 + j * 64, (it - 8) * 64, b_full + 8 * st);
                    }
                }
            }
        } else {
            if (wg == 3) {
                const int r = tid - 384;
                if (r < 64) ((uint4*)sGw)[r] = __ldg((const uint4*)gate_w + r);
                bar_sync(6, 128);
                float gs = 0.f;
#pragma unroll 1
                for (int kc = 0; kc < 8; kc++) {
                    mbar_wait(x_full + 8 * kc, 0);
#pragma unroll 4
                    for (int c = 0; c < 8; c++) {
                        const uint4 xv = *(const uint4*)(sgen + kc * 16384 + r * 128 + ((c ^ (r & 7)) << 4));
                        const uint4 gv = *(const uint4*)(sGw + kc * 128 + c * 16);
                        gs = fmaf(bf_lo(xv.x), bf_lo(gv.x), gs); gs = fmaf(bf_hi(xv.x), bf_hi(gv.x), gs);
                        gs = fmaf(bf_lo(xv.y), bf_lo(gv.y), gs); gs = fmaf(bf_hi(xv.y), bf_hi(gv.y), gs);
                        gs = fmaf(bf_lo(xv.z), bf_lo(gv.z), gs); gs = fmaf(bf_hi(xv.z), bf_hi(gv.z), gs);
                        gs = fmaf(bf_lo(xv.w), bf_lo(gv.w), gs); gs = fmaf(bf_hi(xv.w), bf_hi(gv.w), gs);
                    }
                }
                const float g = 1.f / (1.f + __expf(-gs));
                sGate[r] = g;
                if (j == 0) g_gate[rb * 128 + r] = g;
                bar_arrive(3, 256 + 128);
            } else if (tid == 288) {
                const int b = blockIdx.x;
                mbar_wait(b_full + 8, 0);
                l2_prefetch((const uint8_t*)wqkvp + b * 12288, 12288);
                l2_prefetch((const uint8_t*)w2p + b * 11008, 11008);
                l2_prefetch((const uint8_t*)wop + b * 4096, 4096);
            }
            __syncwarp();
            const int ht = tid - 288;
            const int n0 = j * FCH;
#pragma unroll 1
            for (int w = 0; w < 2; w++) {
                bar_sync(4 + w, 128 + 224);
#pragma unroll 1
                for (int it = ht; it < 64 * 22; it += 224) {
                    const int r = it / 22, c = it - r * 22;
                    const int p = r / 22, rr = r - p * 22;
                    const uint4 hv = *(const uint4*)(sgen + p * 16384 + w * 8192 + rr * HPITCH + c * 16);
                    const float om = 1.f - sGate[w * 64 + r];
                    uint4 o;
                    o.x = pack_bf16(mish_f(bf_lo(hv.x)) * om, mish_f(bf_hi(hv.x)) * om);
                    o.y = pack_bf16(mish_f(bf_lo(hv.y)) * om, mish_f(bf_hi(hv.y)) * om);
                    o.z = pack_bf16(mish_f(bf_lo(hv.z)) * om, mish_f(bf_hi(hv.z)) * om);
                    o.w = pack_bf16(mish_f(bf_lo(hv.w)) * om, mish_f(bf_hi(hv.w)) * om);
                    if (n0 + c * 8 < F_)
                        *(uint4*)(g_a2 + (size_t)(rb * 128 + w * 64 + r) * KA2 + D_ + n0 + c * 8) = o;
                }
            }
            TS(16, tid == 288);
        }
    } else {
        reg_alloc<216>();
        if (tid < 88) {
            const int c = j * FCH + tid * 2;
            sBias[tid] = c < F_ ? __ldg((const uint32_t*)(b1 + c)) : 0u;
        }
        const int w4 = warp & 3, q = lane & 3;
        float accF[88], accQ[96];
#pragma unroll 1
        for (int kc = 0; kc < 8; kc++) {
            const int st = kc & 3;
            mbar_wait(x_full + 8 * kc, 0);
            mbar_wait(b_full + 8 * st, (kc >> 2) & 1);
            TS(1, tid == 0 && kc == 0); TS(2, tid == 0 && kc == 4);
            wgmma_fence();
#pragma unroll
            for (int k16 = 0; k16 < 4; k16++) {
                const uint64_t db = make_desc(sB + st * K1_BSTAGE + k16 * 2048, 8192, 1024);
                const uint64_t da = make_desc(sX + kc * 16384 + wg * 8192 + k16 * 32, 16, 1024);
                wgmma_n176<1>(accF, da, db, (kc | k16) != 0);
            }
            wgmma_commit();
            if (kc > 0) { wgmma_wait<1>(); if (lane == 0) mbar_arrive(b_empty + 8 * ((kc - 1) & 3)); }
        }
        TS(3, tid == 0);
        const int rl = wg * 64 + w4 * 16 + (lane >> 2);
#pragma unroll 1
        for (int kc = 0; kc < 8; kc++) {
            const int st = kc & 3;
            mbar_wait(b_full + 8 * st, ((kc + 8) >> 2) & 1);
            wgmma_fence();
#pragma unroll
            for (int k16 = 0; k16 < 4; k16++) {
                const uint64_t db = make_desc(sB + st * K1_BSTAGE + k16 * 2048, 8192, 1024);
                const uint64_t da = make_desc(sX + kc * 16384 + wg * 8192 + k16 * 32, 16, 1024);
                wgmma_n192<1>(accQ, da, db, (kc | k16) != 0);
            }
            wgmma_commit();
            wgmma_wait<1>();
            if (lane == 0) mbar_arrive(b_empty + 8 * ((kc + 3) & 3));
            if (kc == 3) {
                bar_sync(3, 256 + 128);
                const int r0 = w4 * 16 + (lane >> 2), r1 = r0 + 8;
                uint8_t* d0 = sgen + (r0 / 22) * 16384 + wg * 8192 + (r0 % 22) * HPITCH + q * 4;
                uint8_t* d1 = sgen + (r1 / 22) * 16384 + wg * 8192 + (r1 % 22) * HPITCH + q * 4;
#pragma unroll
                for (int t = 0; t < 22; t++) {
                    const uint32_t bv = sBias[t * 4 + q];
                    const float bb0 = bf_lo(bv), bb1 = bf_hi(bv);
                    *(uint32_t*)(d0 + t * 16) = pack_bf16(accF[t * 4 + 0] + bb0, accF[t * 4 + 1] + bb1);
                    *(uint32_t*)(d1 + t * 16) = pack_bf16(accF[t * 4 + 2] + bb0, accF[t * 4 + 3] + bb1);
                }
                bar_arrive(4 + wg, 128 + 224);
            }
        }
        wgmma_wait<0>();
        TS(4, tid == 0);
        {
            bf16* orow0 = g_qkv + ((size_t)j * S_ + rb * 128 + rl) * 192;
            bf16* orow1 = orow0 + 8 * 192;
#pragma unroll
            for (int u = 0; u < 6; u++) {
                uint32_t w0[4], w1[4];
#pragma unroll
                for (int i = 0; i < 4; i++) {
                    const int t = u * 4 + i;
                    w0[i] = pack_bf16(accQ[t * 4 + 0], accQ[t * 4 + 1]);
                    w1[i] = pack_bf16(accQ[t * 4 + 2], accQ[t * 4 + 3]);
                }
                quad_transpose(w0, q);
                quad_transpose(w1, q);
                const int c = (u * 4 + q) * 8;
                *(uint4*)(orow0 + c) = make_uint4(w0[0], w0[1], w0[2], w0[3]);
                *(uint4*)(orow1 + c) = make_uint4(w1[0], w1[1], w1[2], w1[3]);
            }
        }
        TS(5, tid == 0);
    }
}

__device__ __forceinline__ void ldsm_x4(uint32_t (&r)[4], uint32_t addr) {
    asm("ldmatrix.sync.aligned.m8n8.x4.shared.b16 {%0,%1,%2,%3}, [%4];"
                 : "=r"(r[0]), "=r"(r[1]), "=r"(r[2]), "=r"(r[3]) : "r"(addr));
}
__device__ __forceinline__ void ldsm_x4_t(uint32_t (&r)[4], uint32_t addr) {
    asm("ldmatrix.sync.aligned.m8n8.x4.trans.shared.b16 {%0,%1,%2,%3}, [%4];"
                 : "=r"(r[0]), "=r"(r[1]), "=r"(r[2]), "=r"(r[3]) : "r"(addr));
}
__device__ __forceinline__ void mma16816(float (&d)[4], const uint32_t (&a)[4], uint32_t b0, uint32_t b1) {
    asm("mma.sync.aligned.m16n8k16.row.col.f32.bf16.bf16.f32 {%0,%1,%2,%3}, {%4,%5,%6,%7}, {%8,%9}, {%0,%1,%2,%3};"
                 : "+f"(d[0]), "+f"(d[1]), "+f"(d[2]), "+f"(d[3])
                 : "r"(a[0]), "r"(a[1]), "r"(a[2]), "r"(a[3]), "r"(b0), "r"(b1));
}
__device__ __forceinline__ void mma16816_z(float (&d)[4], const uint32_t (&a)[4], uint32_t b0, uint32_t b1) {
    asm("mma.sync.aligned.m16n8k16.row.col.f32.bf16.bf16.f32 {%0,%1,%2,%3}, {%4,%5,%6,%7}, {%8,%9}, {%10,%10,%10,%10};"
                 : "=f"(d[0]), "=f"(d[1]), "=f"(d[2]), "=f"(d[3])
                 : "r"(a[0]), "r"(a[1]), "r"(a[2]), "r"(a[3]), "r"(b0), "r"(b1), "f"(0.f));
}

constexpr int KV_PITCH = 128;

template <int EDGE, bool HEAD>
__device__ __forceinline__ void blk_scores(float (&s)[2][4], const uint32_t (&qa)[4], uint32_t kaddr, bool dead, int r0, int c0)
{
    uint32_t kf[4];
    ldsm_x4(kf, kaddr);
    mma16816_z(s[0], qa, kf[0], kf[1]);
    mma16816_z(s[1], qa, kf[2], kf[3]);
#pragma unroll
    for (int t = 0; t < 2; t++)
#pragma unroll
        for (int e = 0; e < 4; e++) {
            const int r = r0 + (e >> 1) * 8, c = t * 8 + c0 + (e & 1);
            if (EDGE == 1 && c <= r) s[t][e] = -1e30f;
            if (EDGE == 2 && c > r) s[t][e] = -1e30f;
            if (HEAD && dead) s[t][e] = -1e30f;
        }
}
__device__ __forceinline__ void blk_max(const float (&s)[2][4], float& n0, float& n1) {
    n0 = fmaxf(n0, fmaxf(fmaxf(s[0][0], s[0][1]), fmaxf(s[1][0], s[1][1])));
    n1 = fmaxf(n1, fmaxf(fmaxf(s[0][2], s[0][3]), fmaxf(s[1][2], s[1][3])));
}
__device__ __forceinline__ void blk_pv(const float (&s)[2][4], float mc0, float mc1, float& l0, float& l1,
                                       float (&o)[2][4], uint32_t vaddr) {
    const float C = 0.25f * 1.4426950408889634f;
    uint32_t pa[4];
#pragma unroll
    for (int t = 0; t < 2; t++) {
        const float p0 = ex2(fmaf(s[t][0], C, -mc0)), p1 = ex2(fmaf(s[t][1], C, -mc0));
        const float p2 = ex2(fmaf(s[t][2], C, -mc1)), p3 = ex2(fmaf(s[t][3], C, -mc1));
        l0 += p0 + p1; l1 += p2 + p3;
        pa[2 * t] = pack_bf16(p0, p1); pa[2 * t + 1] = pack_bf16(p2, p3);
    }
    uint32_t vf[4];
    ldsm_x4_t(vf, vaddr);
    mma16816(o[0], pa, vf[0], vf[1]);
    mma16816(o[1], pa, vf[2], vf[3]);
}
__device__ __forceinline__ void quad_max(float& n0, float& n1) {
    n0 = fmaxf(n0, __shfl_xor_sync(0xffffffffu, n0, 1)); n1 = fmaxf(n1, __shfl_xor_sync(0xffffffffu, n1, 1));
    n0 = fmaxf(n0, __shfl_xor_sync(0xffffffffu, n0, 2)); n1 = fmaxf(n1, __shfl_xor_sync(0xffffffffu, n1, 2));
}
template <int NC, int NN, bool FIRST, bool NEXT_IS_EDGE, bool HEAD>
__device__ __forceinline__ void pipe_step(const float (&sc)[5][2][4], float (&sn)[5][2][4], const uint32_t (&qa)[4],
                                          uint32_t ka, uint32_t va, int kc, int kn, int kb0, int r0, int c0,
                                          float& m0, float& m1, float& n0, float& n1, float& l0, float& l1, float (&o)[2][4])
{
    const float C = 0.25f * 1.4426950408889634f;
    const float mc0 = n0 * C, mc1 = n1 * C;
    if (!FIRST) {
        const float a0 = ex2(fmaf(m0, C, -mc0)), a1 = ex2(fmaf(m1, C, -mc1));
        l0 *= a0; l1 *= a1;
        o[0][0] *= a0; o[0][1] *= a0; o[1][0] *= a0; o[1][1] *= a0;
        o[0][2] *= a1; o[0][3] *= a1; o[1][2] *= a1; o[1][3] *= a1;
    }
    m0 = n0; m1 = n1;
#pragma unroll
    for (int b = 0; b < NC; b++) {
        if (b < NN) {
            if (NEXT_IS_EDGE && b == 0) blk_scores<1, HEAD>(sn[b], qa, ka + (kn + b) * 16 * KV_PITCH, kn + b < kb0, r0, c0);
            else                        blk_scores<0, HEAD>(sn[b], qa, ka + (kn + b) * 16 * KV_PITCH, kn + b < kb0, r0, c0);
        }
        blk_pv(sc[b], mc0, mc1, l0, l1, o, va + (kc + b) * 16 * KV_PITCH);
        if (b < NN) blk_max(sn[b], n0, n1);
    }
    if (NN > 0) quad_max(n0, n1);
}

template <bool HEAD>
__device__ __forceinline__ void attn_task(const uint32_t (&qa)[4], uint32_t ka, uint32_t va, int kb0, int lane,
                                          bf16* __restrict__ out  , float g0, float g1)
{
    const int r0 = lane >> 2, c0 = (lane & 3) * 2;
    float m0 = -1e30f, m1 = -1e30f, n0 = -1e30f, n1 = -1e30f, l0 = 0.f, l1 = 0.f;
    float o[2][4] = {{0.f, 0.f, 0.f, 0.f}, {0.f, 0.f, 0.f, 0.f}};
    float sa[5][2][4], sb[5][2][4];
#pragma unroll
    for (int b = 0; b < 5; b++) {
        if (b == 4) blk_scores<2, HEAD>(sa[b], qa, ka + (12 + b) * 16 * KV_PITCH, false, r0, c0);
        else        blk_scores<0, HEAD>(sa[b], qa, ka + (12 + b) * 16 * KV_PITCH, 12 + b < kb0, r0, c0);
        blk_max(sa[b], n0, n1);
    }
    quad_max(n0, n1);
    pipe_step<5, 4, true,  false, HEAD>(sa, sb, qa, ka, va, 12, 8, kb0, r0, c0, m0, m1, n0, n1, l0, l1, o);
    pipe_step<4, 4, false, false, HEAD>(sb, sa, qa, ka, va, 8, 4, kb0, r0, c0, m0, m1, n0, n1, l0, l1, o);
    pipe_step<4, 4, false, true,  HEAD>(sa, sb, qa, ka, va, 4, 0, kb0, r0, c0, m0, m1, n0, n1, l0, l1, o);
    pipe_step<4, 0, false, false, HEAD>(sb, sa, qa, ka, va, 0, 0, kb0, r0, c0, m0, m1, n0, n1, l0, l1, o);
    l0 += __shfl_xor_sync(0xffffffffu, l0, 1); l0 += __shfl_xor_sync(0xffffffffu, l0, 2);
    l1 += __shfl_xor_sync(0xffffffffu, l1, 1); l1 += __shfl_xor_sync(0xffffffffu, l1, 2);
    const float f0 = g0 / l0, f1 = g1 / l1;
#pragma unroll
    for (int t = 0; t < 2; t++) {
        *(uint32_t*)(out + (size_t)r0 * KA2 + t * 8 + c0) = pack_bf16(o[t][0] * f0, o[t][1] * f0);
        *(uint32_t*)(out + (size_t)(r0 + 8) * KA2 + t * 8 + c0) = pack_bf16(o[t][2] * f1, o[t][3] * f1);
    }
}

constexpr int K2_SMEM = 2 * 384 * KV_PITCH + 1024 + 64;

__global__ void __launch_bounds__(512, 1) k2_kernel(const __grid_constant__ CUtensorMap tmQKV)
{
    extern __shared__ uint8_t smem_raw[];
    const uint32_t sbase = (smem_u32(smem_raw) + 1023u) & ~1023u;
    uint8_t* sgen = smem_raw + (sbase - smem_u32(smem_raw));
    const uint32_t sK = sbase, sV = sK + 384 * KV_PITCH, kv_full = sbase + 2 * 384 * KV_PITCH;
    const int rb = blockIdx.x >> 3, j = blockIdx.x & 7;
    const int tid = threadIdx.x, warp = tid >> 5, lane = tid & 31;
    pdl_launch();
    if (tid == 0) {
        mbar_init(kv_full, 1);
        fence_barrier_init();
    }
    pdl_wait();
    TS(6, tid == 0);
    if (tid == 0) {
        const int nblk = rb >= 2 ? 3 : rb + 1;
        mbar_expect_tx(kv_full, nblk * 2 * 16384);
        for (int i = 0; i < nblk; i++) {
            const int row = j * S_ + (rb - i) * 128;
            tma_load_2d(sK + (2 - i) * 16384, &tmQKV, 64, row, kv_full);
            tma_load_2d(sV + (2 - i) * 16384, &tmQKV, 128, row, kv_full);
        }
    }
    if (rb < 2) {
        for (int i = tid; i < (2 - rb) * 1024; i += 512) {
            *(uint4*)(sgen + i * 16) = make_uint4(0, 0, 0, 0);
            *(uint4*)(sgen + 384 * KV_PITCH + i * 16) = make_uint4(0, 0, 0, 0);
        }
    }
    const int qt = warp & 7, h0 = (warp >> 3) * 2;
    const int q0g = rb * 128 + qt * 16;
    const int r0 = lane >> 2, c0 = (lane & 3) * 2;
    const bf16* qsrc = g_qkv + ((size_t)j * S_ + q0g) * 192 + h0 * 16;
    uint32_t qa[4], qn[4];
    qa[0] = *(const uint32_t*)(qsrc + (size_t)r0 * 192 + c0);
    qa[1] = *(const uint32_t*)(qsrc + (size_t)(r0 + 8) * 192 + c0);
    qa[2] = *(const uint32_t*)(qsrc + (size_t)r0 * 192 + c0 + 8);
    qa[3] = *(const uint32_t*)(qsrc + (size_t)(r0 + 8) * 192 + c0 + 8);
    qn[0] = *(const uint32_t*)(qsrc + (size_t)r0 * 192 + 16 + c0);
    qn[1] = *(const uint32_t*)(qsrc + (size_t)(r0 + 8) * 192 + 16 + c0);
    qn[2] = *(const uint32_t*)(qsrc + (size_t)r0 * 192 + 16 + c0 + 8);
    qn[3] = *(const uint32_t*)(qsrc + (size_t)(r0 + 8) * 192 + 16 + c0 + 8);
    const float g0 = g_gate[q0g + r0], g1 = g_gate[q0g + r0 + 8];
    const int kb0 = q0g < 256 ? (256 - q0g) >> 4 : 0;
    __syncthreads();
    mbar_wait(kv_full, 0);
    uint32_t sKd = sK, sVd = sV;
    asm volatile("" : "+r"(sKd), "+r"(sVd) :: "memory");
    TS(7, tid == 0);
    const int krow = qt * 16 + (lane & 7) + ((lane >> 4) << 3);
    const int vrow = qt * 16 + (lane & 15);
#pragma unroll 1
    for (int hh = 0; hh < 2; hh++) {
        const int hl = h0 + hh;
        const uint32_t ka = sKd + krow * KV_PITCH + (((2 * hl + ((lane >> 3) & 1)) ^ (lane & 7)) << 4);
        const uint32_t va = sVd + vrow * KV_PITCH + (((2 * hl + (lane >> 4)) ^ (lane & 7)) << 4);
        if (rb < 2) attn_task<true>(qa, ka, va, kb0, lane, g_a2 + (size_t)q0g * KA2 + (j * 4 + hl) * 16, g0, g1);
        else        attn_task<false>(qa, ka, va, kb0, lane, g_a2 + (size_t)q0g * KA2 + (j * 4 + hl) * 16, g0, g1);
        TS(8 + hh, tid == 0);
        qa[0] = qn[0]; qa[1] = qn[1]; qa[2] = qn[2]; qa[3] = qn[3];
    }
}

constexpr int K3_STAGES = 8;
constexpr int K3_STAGE = 16384 + 8192;
constexpr int K3_SMEM = K3_STAGES * K3_STAGE + 1024 + 1024;
constexpr int K3_KSTEPS = 30;

__global__ void __launch_bounds__(384, 1)
k3_kernel(const __grid_constant__ CUtensorMap tmA2, const __grid_constant__ CUtensorMap tmWo,
          const __grid_constant__ CUtensorMap tmW2, bf16* __restrict__ out)
{
    extern __shared__ uint8_t smem_raw[];
    const uint32_t sbase = (smem_u32(smem_raw) + 1023u) & ~1023u;
    const uint32_t sBar = sbase + K3_STAGES * K3_STAGE;
    const uint32_t full = sBar, empty = sBar + 64;
    const int rb = blockIdx.x >> 3, nb = blockIdx.x & 7;
    const int tid = threadIdx.x, wg = tid >> 7, warp = tid >> 5, lane = tid & 31;
    if (tid == 0) {
        for (int i = 0; i < K3_STAGES; i++) { mbar_init(full + 8 * i, 1); mbar_init(empty + 8 * i, 8); }
        fence_barrier_init();
    }
    __syncthreads();
    pdl_wait();
    TS(10, tid == 0);
    if (wg == 2) {
        reg_dealloc<40>();
        if (tid == 256) {
            for (int ks = 0; ks < K3_KSTEPS; ks++) {
                const int st = ks % K3_STAGES;
                if (ks >= K3_STAGES) mbar_wait(empty + 8 * st, ((ks / K3_STAGES) - 1) & 1);
                mbar_expect_tx(full + 8 * st, K3_STAGE);
                const uint32_t dst = sbase + st * K3_STAGE;
                tma_load_2d(dst, &tmA2, ks * 64, rb * 128, full + 8 * st);
                if (ks < 8) tma_load_2d(dst + 16384, &tmWo, nb * 64, ks * 64, full + 8 * st);
                else        tma_load_2d(dst + 16384, &tmW2, nb * 64, (ks - 8) * 64, full + 8 * st);
            }
        }
    } else {
        reg_alloc<232>();
        float acc[32];
        for (int ks = 0; ks < K3_KSTEPS; ks++) {
            const int st = ks % K3_STAGES;
            mbar_wait(full + 8 * st, (ks / K3_STAGES) & 1);
            TS(11, tid == 0 && ks == 0); TS(12, tid == 0 && ks == 8); TS(13, tid == 0 && ks == 16);
            wgmma_fence();
#pragma unroll
            for (int k16 = 0; k16 < 4; k16++) {
                const uint64_t da = make_desc(sbase + st * K3_STAGE + wg * 8192 + k16 * 32, 16, 1024);
                const uint64_t db = make_desc(sbase + st * K3_STAGE + 16384 + k16 * 2048, 8192, 1024);
                wgmma_n64<1>(acc, da, db, (ks | k16) != 0);
            }
            wgmma_commit();
            if (ks > 0) { wgmma_wait<1>(); if (lane == 0) mbar_arrive(empty + 8 * ((ks - 1) % K3_STAGES)); }
        }
        wgmma_wait<0>();
        TS(14, tid == 0);
        const int q = lane & 3;
        const int r = rb * 128 + wg * 64 + (warp & 3) * 16 + (lane >> 2);
        bf16* orow0 = out + (size_t)r * D_ + nb * 64;
        bf16* orow1 = orow0 + 8 * D_;
#pragma unroll
        for (int u = 0; u < 2; u++) {
            uint32_t w0[4], w1[4];
#pragma unroll
            for (int i = 0; i < 4; i++) {
                const int t = u * 4 + i;
                w0[i] = pack_bf16(acc[t * 4 + 0], acc[t * 4 + 1]);
                w1[i] = pack_bf16(acc[t * 4 + 2], acc[t * 4 + 3]);
            }
            quad_transpose(w0, q);
            quad_transpose(w1, q);
            const int c = (u * 4 + q) * 8;
            *(uint4*)(orow0 + c) = make_uint4(w0[0], w0[1], w0[2], w0[3]);
            *(uint4*)(orow1 + c) = make_uint4(w1[0], w1[1], w1[2], w1[3]);
        }
        TS(15, tid == 0);
    }
}

typedef CUresult (*PFN_encodeTiled)(CUtensorMap*, CUtensorMapDataType, cuuint32_t, void*, const cuuint64_t*,
                                    const cuuint64_t*, const cuuint32_t*, const cuuint32_t*, CUtensorMapInterleave,
                                    CUtensorMapSwizzle, CUtensorMapL2promotion, CUtensorMapFloatOOBfill);

static void make_map(PFN_encodeTiled enc, CUtensorMap* m, const void* ptr, uint64_t cols, uint64_t rows,
                     uint32_t box_cols, uint32_t box_rows)
{
    cuuint64_t dims[2] = {cols, rows};
    cuuint64_t strides[1] = {cols * 2};
    cuuint32_t box[2] = {box_cols, box_rows};
    cuuint32_t es[2] = {1, 1};
    enc(m, CU_TENSOR_MAP_DATA_TYPE_BFLOAT16, 2, const_cast<void*>(ptr), dims, strides, box, es,
        CU_TENSOR_MAP_INTERLEAVE_NONE, CU_TENSOR_MAP_SWIZZLE_128B, CU_TENSOR_MAP_L2_PROMOTION_L2_128B,
        CU_TENSOR_MAP_FLOAT_OOB_FILL_NONE);
}

extern "C" void kernel_launch(void* const* d_in, const int* in_sizes, int n_in, void* d_out, int out_size)
{
    const bf16* x    = (const bf16*)d_in[0];
    const bf16* wqkv = (const bf16*)d_in[1];
    const bf16* wo   = (const bf16*)d_in[2];
    const bf16* w1   = (const bf16*)d_in[4];
    const bf16* b1   = (const bf16*)d_in[5];
    const bf16* w2   = (const bf16*)d_in[6];
    const bf16* gw   = (const bf16*)d_in[7];

    static PFN_encodeTiled enc = nullptr;
    if (!enc) {
        void* fn = nullptr;
        cudaDriverEntryPointQueryResult qr;
        cudaGetDriverEntryPoint("cuTensorMapEncodeTiled", &fn, cudaEnableDefault, &qr);
        enc = (PFN_encodeTiled)fn;
        cudaFuncSetAttribute(k1_kernel, cudaFuncAttributeMaxDynamicSharedMemorySize, K1_SMEM);
        cudaFuncSetAttribute(k2_kernel, cudaFuncAttributeMaxDynamicSharedMemorySize, K2_SMEM);
        cudaFuncSetAttribute(k3_kernel, cudaFuncAttributeMaxDynamicSharedMemorySize, K3_SMEM);
    }
    void* a2p = nullptr;
    cudaGetSymbolAddress(&a2p, g_a2);
    void* qkvp = nullptr;
    cudaGetSymbolAddress(&qkvp, g_qkv);
    CUtensorMap tmX, tmWqkv, tmW1, tmA2, tmWo, tmW2, tmQKV;
    make_map(enc, &tmQKV, qkvp, 192, 8 * S_, 64, 128);
    make_map(enc, &tmX, x, D_, S_, 64, 128);
    make_map(enc, &tmWqkv, wqkv, 3 * D_, D_, 64, 64);
    make_map(enc, &tmW1, w1, F_, D_, 64, 64);
    make_map(enc, &tmA2, a2p, KA2, S_, 64, 128);
    make_map(enc, &tmWo, wo, D_, D_, 64, 64);
    make_map(enc, &tmW2, w2, D_, F_, 64, 64);

    cudaStream_t st = cudaStreamPerThread;
    k1_kernel<<<128, 512, K1_SMEM, st>>>(tmX, tmWqkv, tmW1, b1, gw, w1, wqkv, w2, wo);
    cudaLaunchAttribute at[1];
    at[0].id = cudaLaunchAttributeProgrammaticStreamSerialization;
    at[0].val.programmaticStreamSerializationAllowed = 1;
    cudaLaunchConfig_t cfg = {};
    cfg.gridDim = dim3(128); cfg.stream = st; cfg.attrs = at; cfg.numAttrs = 1;
    cfg.blockDim = dim3(512); cfg.dynamicSmemBytes = K2_SMEM;
    cudaLaunchKernelEx(&cfg, k2_kernel, tmQKV);
    k3_kernel<<<128, 384, K3_SMEM, st>>>(tmA2, tmWo, tmW2, (bf16*)d_out);
}
```

```cpp
#include <cuda_runtime.h>
#include <cuda_bf16.h>
#include <cuda.h>
#include <stdint.h>

typedef __nv_bfloat16 bf16;

constexpr int S_ = 2048, D_ = 512, F_ = 1376;
constexpr int KA2 = D_ + F_;
constexpr int FCH = 176;

__device__ bf16  g_qkv[8 * S_ * 192];
__device__ bf16  g_a2[S_ * KA2];
__device__ float g_gate[S_];

#define TS(k, cond) do { } while (0)

__device__ __forceinline__ uint32_t smem_u32(const void* p) { return (uint32_t)__cvta_generic_to_shared(p); }
__device__ __forceinline__ void mbar_init(uint32_t bar, uint32_t count) {
    asm volatile("mbarrier.init.shared::cta.b64 [%0], %1;" :: "r"(bar), "r"(count) : "memory");
}
__device__ __forceinline__ void mbar_expect_tx(uint32_t bar, uint32_t bytes) {
    asm volatile("mbarrier.arrive.expect_tx.shared::cta.b64 _, [%0], %1;" :: "r"(bar), "r"(bytes) : "memory");
}
__device__ __forceinline__ void mbar_arrive(uint32_t bar) {
    asm volatile("mbarrier.arrive.shared::cta.b64 _, [%0];" :: "r"(bar) : "memory");
}
__device__ __forceinline__ bool mbar_try_wait(uint32_t bar, uint32_t parity) {
    uint32_t ok;
    asm volatile("{\n.reg .pred p;\nmbarrier.try_wait.parity.shared::cta.b64 p, [%1], %2;\nselp.u32 %0, 1, 0, p;\n}"
                 : "=r"(ok) : "r"(bar), "r"(parity) : "memory");
    return ok != 0;
}
__device__ __forceinline__ void mbar_wait(uint32_t bar, uint32_t parity) {
    for (uint32_t it = 0; it < (1u << 22); ++it) { if (mbar_try_wait(bar, parity)) break; }
}
__device__ __forceinline__ void tma_load_2d(uint32_t dst, const CUtensorMap* map, int c0, int c1, uint32_t bar) {
    asm volatile("cp.async.bulk.tensor.2d.shared::cluster.global.mbarrier::complete_tx::bytes [%0], [%1, {%3, %4}], [%2];"
                 :: "r"(dst), "l"(map), "r"(bar), "r"(c0), "r"(c1) : "memory");
}
__device__ __forceinline__ void l2_prefetch(const void* p, uint32_t bytes) {
    asm volatile("cp.async.bulk.prefetch.L2.global [%0], %1;" :: "l"(p), "r"(bytes) : "memory");
}
__device__ __forceinline__ void fence_barrier_init() { asm volatile("fence.mbarrier_init.release.cluster;" ::: "memory"); }
__device__ __forceinline__ void wgmma_fence()  { asm volatile("wgmma.fence.sync.aligned;" ::: "memory"); }
__device__ __forceinline__ void wgmma_commit() { asm volatile("wgmma.commit_group.sync.aligned;" ::: "memory"); }
template <int N> __device__ __forceinline__ void wgmma_wait() { asm volatile("wgmma.wait_group.sync.aligned %0;" :: "n"(N) : "memory"); }
template <int R> __device__ __forceinline__ void reg_alloc()   { asm volatile("setmaxnreg.inc.sync.aligned.u32 %0;" :: "n"(R)); }
template <int R> __device__ __forceinline__ void reg_dealloc() { asm volatile("setmaxnreg.dec.sync.aligned.u32 %0;" :: "n"(R)); }
__device__ __forceinline__ void bar_sync(int id, int n)   { asm volatile("bar.sync %0, %1;" :: "r"(id), "r"(n) : "memory"); }
__device__ __forceinline__ void bar_arrive(int id, int n) { asm volatile("bar.arrive %0, %1;" :: "r"(id), "r"(n) : "memory"); }

__device__ __forceinline__ uint64_t make_desc(uint32_t addr, uint32_t lbo, uint32_t sbo) {
    uint64_t d = (uint64_t)((addr & 0x3FFFF) >> 4);
    d |= (uint64_t)((lbo & 0x3FFFF) >> 4) << 16;
    d |= (uint64_t)((sbo & 0x3FFFF) >> 4) << 32;
    d |= (uint64_t)1 << 62;
    return d;
}

template <int TB>
__device__ __forceinline__ void wgmma_n64(float (&d)[32], uint64_t da, uint64_t db, int scale_d) {
    asm volatile("{\n.reg .pred p;\nsetp.ne.b32 p, %34, 0;\n"
        "wgmma.mma_async.sync.aligned.m64n64k16.f32.bf16.bf16 {%0, %1, %2, %3, %4, %5, %6, %7, %8, %9, %10, %11, %12, %13, %14, %15, %16, %17, %18, %19, %20, %21, %22, %23, %24, %25, %26, %27, %28, %29, %30, %31}, %32, %33, p, 1, 1, 0, %35;\n}\n"
        : "+f"(d[0]), "+f"(d[1]), "+f"(d[2]), "+f"(d[3]), "+f"(d[4]), "+f"(d[5]), "+f"(d[6]), "+f"(d[7]), "+f"(d[8]), "+f"(d[9]), "+f"(d[10]), "+f"(d[11]), "+f"(d[12]), "+f"(d[13]), "+f"(d[14]), "+f"(d[15]), "+f"(d[16]), "+f"(d[17]), "+f"(d[18]), "+f"(d[19]), "+f"(d[20]), "+f"(d[21]), "+f"(d[22]), "+f"(d[23]), "+f"(d[24]), "+f"(d[25]), "+f"(d[26]), "+f"(d[27]), "+f"(d[28]), "+f"(d[29]), "+f"(d[30]), "+f"(d[31])
        : "l"(da), "l"(db), "r"(scale_d), "n"(TB));
}

template <int TB>
__device__ __forceinline__ void wgmma_n128(float (&d)[64], uint64_t da, uint64_t db, int scale_d) {
    asm volatile("{\n.reg .pred p;\nsetp.ne.b32 p, %66, 0;\n"
        "wgmma.mma_async.sync.aligned.m64n128k16.f32.bf16.bf16 {%0, %1, %2, %3, %4, %5, %6, %7, %8, %9, %10, %11, %12, %13, %14, %15, %16, %17, %18, %19, %20, %21, %22, %23, %24, %25, %26, %27, %28, %29, %30, %31, %32, %33, %34, %35, %36, %37, %38, %39, %40, %41, %42, %43, %44, %45, %46, %47, %48, %49, %50, %51, %52, %53, %54, %55, %56, %57, %58, %59, %60, %61, %62, %63}, %64, %65, p, 1, 1, 0, %67;\n}\n"
        : "+f"(d[0]), "+f"(d[1]), "+f"(d[2]), "+f"(d[3]), "+f"(d[4]), "+f"(d[5]), "+f"(d[6]), "+f"(d[7]), "+f"(d[8]), "+f"(d[9]), "+f"(d[10]), "+f"(d[11]), "+f"(d[12]), "+f"(d[13]), "+f"(d[14]), "+f"(d[15]), "+f"(d[16]), "+f"(d[17]), "+f"(d[18]), "+f"(d[19]), "+f"(d[20]), "+f"(d[21]), "+f"(d[22]), "+f"(d[23]), "+f"(d[24]), "+f"(d[25]), "+f"(d[26]), "+f"(d[27]), "+f"(d[28]), "+f"(d[29]), "+f"(d[30]), "+f"(d[31]), "+f"(d[32]), "+f"(d[33]), "+f"(d[34]), "+f"(d[35]), "+f"(d[36]), "+f"(d[37]), "+f"(d[38]), "+f"(d[39]), "+f"(d[40]), "+f"(d[41]), "+f"(d[42]), "+f"(d[43]), "+f"(d[44]), "+f"(d[45]), "+f"(d[46]), "+f"(d[47]), "+f"(d[48]), "+f"(d[49]), "+f"(d[50]), "+f"(d[51]), "+f"(d[52]), "+f"(d[53]), "+f"(d[54]), "+f"(d[55]), "+f"(d[56]), "+f"(d[57]), "+f"(d[58]), "+f"(d[59]), "+f"(d[60]), "+f"(d[61]), "+f"(d[62]), "+f"(d[63])
        : "l"(da), "l"(db), "r"(scale_d), "n"(TB));
}

template <int TB>
__device__ __forceinline__ void wgmma_n176(float (&d)[88], uint64_t da, uint64_t db, int scale_d) {
    asm volatile("{\n.reg .pred p;\nsetp.ne.b32 p, %90, 0;\n"
        "wgmma.mma_async.sync.aligned.m64n176k16.f32.bf16.bf16 {%0, %1, %2, %3, %4, %5, %6, %7, %8, %9, %10, %11, %12, %13, %14, %15, %16, %17, %18, %19, %20, %21, %22, %23, %24, %25, %26, %27, %28, %29, %30, %31, %32, %33, %34, %35, %36, %37, %38, %39, %40, %41, %42, %43, %44, %45, %46, %47, %48, %49, %50, %51, %52, %53, %54, %55, %56, %57, %58, %59, %60, %61, %62, %63, %64, %65, %66, %67, %68, %69, %70, %71, %72, %73, %74, %75, %76, %77, %78, %79, %80, %81, %82, %83, %84, %85, %86, %87}, %88, %89, p, 1, 1, 0, %91;\n}\n"
        : "+f"(d[0]), "+f"(d[1]), "+f"(d[2]), "+f"(d[3]), "+f"(d[4]), "+f"(d[5]), "+f"(d[6]), "+f"(d[7]), "+f"(d[8]), "+f"(d[9]), "+f"(d[10]), "+f"(d[11]), "+f"(d[12]), "+f"(d[13]), "+f"(d[14]), "+f"(d[15]), "+f"(d[16]), "+f"(d[17]), "+f"(d[18]), "+f"(d[19]), "+f"(d[20]), "+f"(d[21]), "+f"(d[22]), "+f"(d[23]), "+f"(d[24]), "+f"(d[25]), "+f"(d[26]), "+f"(d[27]), "+f"(d[28]), "+f"(d[29]), "+f"(d[30]), "+f"(d[31]), "+f"(d[32]), "+f"(d[33]), "+f"(d[34]), "+f"(d[35]), "+f"(d[36]), "+f"(d[37]), "+f"(d[38]), "+f"(d[39]), "+f"(d[40]), "+f"(d[41]), "+f"(d[42]), "+f"(d[43]), "+f"(d[44]), "+f"(d[45]), "+f"(d[46]), "+f"(d[47]), "+f"(d[48]), "+f"(d[49]), "+f"(d[50]), "+f"(d[51]), "+f"(d[52]), "+f"(d[53]), "+f"(d[54]), "+f"(d[55]), "+f"(d[56]), "+f"(d[57]), "+f"(d[58]), "+f"(d[59]), "+f"(d[60]), "+f"(d[61]), "+f"(d[62]), "+f"(d[63]), "+f"(d[64]), "+f"(d[65]), "+f"(d[66]), "+f"(d[67]), "+f"(d[68]), "+f"(d[69]), "+f"(d[70]), "+f"(d[71]), "+f"(d[72]), "+f"(d[73]), "+f"(d[74]), "+f"(d[75]), "+f"(d[76]), "+f"(d[77]), "+f"(d[78]), "+f"(d[79]), "+f"(d[80]), "+f"(d[81]), "+f"(d[82]), "+f"(d[83]), "+f"(d[84]), "+f"(d[85]), "+f"(d[86]), "+f"(d[87])
        : "l"(da), "l"(db), "r"(scale_d), "n"(TB));
}

template <int TB>
__device__ __forceinline__ void wgmma_n192(float (&d)[96], uint64_t da, uint64_t db, int scale_d) {
    asm volatile("{\n.reg .pred p;\nsetp.ne.b32 p, %98, 0;\n"
        "wgmma.mma_async.sync.aligned.m64n192k16.f32.bf16.bf16 {%0, %1, %2, %3, %4, %5, %6, %7, %8, %9, %10, %11, %12, %13, %14, %15, %16, %17, %18, %19, %20, %21, %22, %23, %24, %25, %26, %27, %28, %29, %30, %31, %32, %33, %34, %35, %36, %37, %38, %39, %40, %41, %42, %43, %44, %45, %46, %47, %48, %49, %50, %51, %52, %53, %54, %55, %56, %57, %58, %59, %60, %61, %62, %63, %64, %65, %66, %67, %68, %69, %70, %71, %72, %73, %74, %75, %76, %77, %78, %79, %80, %81, %82, %83, %84, %85, %86, %87, %88, %89, %90, %91, %92, %93, %94, %95}, %96, %97, p, 1, 1, 0, %99;\n}\n"
        : "+f"(d[0]), "+f"(d[1]), "+f"(d[2]), "+f"(d[3]), "+f"(d[4]), "+f"(d[5]), "+f"(d[6]), "+f"(d[7]), "+f"(d[8]), "+f"(d[9]), "+f"(d[10]), "+f"(d[11]), "+f"(d[12]), "+f"(d[13]), "+f"(d[14]), "+f"(d[15]), "+f"(d[16]), "+f"(d[17]), "+f"(d[18]), "+f"(d[19]), "+f"(d[20]), "+f"(d[21]), "+f"(d[22]), "+f"(d[23]), "+f"(d[24]), "+f"(d[25]), "+f"(d[26]), "+f"(d[27]), "+f"(d[28]), "+f"(d[29]), "+f"(d[30]), "+f"(d[31]), "+f"(d[32]), "+f"(d[33]), "+f"(d[34]), "+f"(d[35]), "+f"(d[36]), "+f"(d[37]), "+f"(d[38]), "+f"(d[39]), "+f"(d[40]), "+f"(d[41]), "+f"(d[42]), "+f"(d[43]), "+f"(d[44]), "+f"(d[45]), "+f"(d[46]), "+f"(d[47]), "+f"(d[48]), "+f"(d[49]), "+f"(d[50]), "+f"(d[51]), "+f"(d[52]), "+f"(d[53]), "+f"(d[54]), "+f"(d[55]), "+f"(d[56]), "+f"(d[57]), "+f"(d[58]), "+f"(d[59]), "+f"(d[60]), "+f"(d[61]), "+f"(d[62]), "+f"(d[63]), "+f"(d[64]), "+f"(d[65]), "+f"(d[66]), "+f"(d[67]), "+f"(d[68]), "+f"(d[69]), "+f"(d[70]), "+f"(d[71]), "+f"(d[72]), "+f"(d[73]), "+f"(d[74]), "+f"(d[75]), "+f"(d[76]), "+f"(d[77]), "+f"(d[78]), "+f"(d[79]), "+f"(d[80]), "+f"(d[81]), "+f"(d[82]), "+f"(d[83]), "+f"(d[84]), "+f"(d[85]), "+f"(d[86]), "+f"(d[87]), "+f"(d[88]), "+f"(d[89]), "+f"(d[90]), "+f"(d[91]), "+f"(d[92]), "+f"(d[93]), "+f"(d[94]), "+f"(d[95])
        : "l"(da), "l"(db), "r"(scale_d), "n"(TB));
}

__device__ __forceinline__ uint32_t pack_bf16(float lo, float hi) {
    uint32_t r;
    asm("cvt.rn.bf16x2.f32 %0, %1, %2;" : "=r"(r) : "f"(hi), "f"(lo));
    return r;
}
__device__ __forceinline__ float bf_lo(uint32_t v) { return __uint_as_float(v << 16); }
__device__ __forceinline__ float bf_hi(uint32_t v) { return __uint_as_float(v & 0xffff0000u); }

__device__ __forceinline__ void quad_transpose(uint32_t (&w)[4], int q) {
    const bool o1 = q & 1, o2 = q & 2;
    {
        uint32_t s0 = o1 ? w[0] : w[1], s1 = o1 ? w[2] : w[3];
        s0 = __shfl_xor_sync(0xffffffffu, s0, 1); s1 = __shfl_xor_sync(0xffffffffu, s1, 1);
        if (o1) { w[0] = s0; w[2] = s1; } else { w[1] = s0; w[3] = s1; }
    }
    {
        uint32_t s0 = o2 ? w[0] : w[2], s1 = o2 ? w[1] : w[3];
        s0 = __shfl_xor_sync(0xffffffffu, s0, 2); s1 = __shfl_xor_sync(0xffffffffu, s1, 2);
        if (o2) { w[0] = s0; w[1] = s1; } else { w[2] = s0; w[3] = s1; }
    }
}

__device__ __forceinline__ float ex2(float x) { float y; asm("ex2.approx.ftz.f32 %0, %1;" : "=f"(y) : "f"(x)); return y; }
__device__ __forceinline__ float rcp(float x) { float y; asm("rcp.approx.ftz.f32 %0, %1;" : "=f"(y) : "f"(x)); return y; }

__device__ __forceinline__ float ex2v(float x) { float y; asm volatile("ex2.approx.ftz.f32 %0, %1;" : "=f"(y) : "f"(x)); return y; }
__device__ __forceinline__ float rcpv(float x) { float y; asm volatile("rcp.approx.ftz.f32 %0, %1;" : "=f"(y) : "f"(x)); return y; }
__device__ __forceinline__ float mish_f(float h) {
    const float e = ex2(1.4426950408889634f * fminf(h, 20.f));
    const float n = fmaf(e, e, e + e);
    return h * n * rcp(n + 2.f);
}

__device__ __forceinline__ void pdl_wait()   { asm volatile("griddepcontrol.wait;" ::: "memory"); }
__device__ __forceinline__ void pdl_launch() { asm volatile("griddepcontrol.launch_dependents;" ::: "memory"); }

constexpr int K1_STAGES = 4;
constexpr int K1_XBYTES = 128 * 512 * 2;
constexpr int K1_BSTAGE = 3 * 8192;
constexpr int K1_SMEM   = K1_XBYTES + K1_STAGES * K1_BSTAGE + 2048   + 1024  ;
constexpr int HPITCH = 368;

__global__ void __launch_bounds__(512, 1)
k1_kernel(const __grid_constant__ CUtensorMap tmX, const __grid_constant__ CUtensorMap tmWqkv,
          const __grid_constant__ CUtensorMap tmW1, const bf16* __restrict__ b1,
          const bf16* __restrict__ gate_w, const bf16* __restrict__ w1p, const bf16* __restrict__ wqkvp,
          const bf16* __restrict__ w2p, const bf16* __restrict__ wop)
{
    extern __shared__ uint8_t smem_raw[];
    const uint32_t sbase = (smem_u32(smem_raw) + 1023u) & ~1023u;
    uint8_t* sgen = smem_raw + (sbase - smem_u32(smem_raw));
    const uint32_t sX = sbase;
    const uint32_t sB = sbase + K1_XBYTES;
    const uint32_t sBar = sB + K1_STAGES * K1_BSTAGE;
    const uint32_t x_full = sBar;
    const uint32_t b_full = sBar + 64;
    const uint32_t b_empty = sBar + 96;
    float* sGate = (float*)(sgen + K1_XBYTES + K1_STAGES * K1_BSTAGE + 128);
    uint8_t* sGw = sgen + K1_XBYTES + K1_STAGES * K1_BSTAGE + 640;
    uint32_t* sBias = (uint32_t*)(sgen + K1_XBYTES + K1_STAGES * K1_BSTAGE + 1664);

    const int rb = blockIdx.x >> 3, j = blockIdx.x & 7;
    const int tid = threadIdx.x, wg = tid >> 7, warp = tid >> 5, lane = tid & 31;
    TS(0, tid == 0);
    pdl_launch();

    if (tid == 0) {
        for (int i = 0; i < 8; i++) mbar_init(x_full + 8 * i, 1);
        for (int i = 0; i < K1_STAGES; i++) { mbar_init(b_full + 8 * i, 1); mbar_init(b_empty + 8 * i, 8); }
        fence_barrier_init();
    }
    __syncthreads();

    if (wg >= 2) {
        reg_dealloc<40>();
        if (warp == 8) {
            if (lane == 0) {
                for (int it = 0; it < 16; it++) {
                    if (it < 8) {
                        mbar_expect_tx(x_full + 8 * it, 16384);
                        tma_load_2d(sX + it * 16384, &tmX, it * 64, rb * 128, x_full + 8 * it);
                    }
                    const int st = it & 3;
                    if (it >= K1_STAGES) mbar_wait(b_empty + 8 * st, ((it >> 2) - 1) & 1);
                    mbar_expect_tx(b_full + 8 * st, K1_BSTAGE);
                    const uint32_t dst = sB + st * K1_BSTAGE;
                    if (it < 8) {
                        for (int b = 0; b < 3; b++) tma_load_2d(dst + b * 8192, &tmW1, j * FCH + b * 64, it * 64, b_full + 8 * st);
                    } else {
                        for (int b = 0; b < 3; b++) tma_load_2d(dst + b * 8192, &tmWqkv, b * 512 + j * 64, (it - 8) * 64, b_full + 8 * st);
                    }
                }
            }
        } else {
            if (tid == 288) {
                const int b = blockIdx.x;
                mbar_wait(b_full + 8, 0);
                l2_prefetch((const uint8_t*)wqkvp + b * 12288, 12288);
                l2_prefetch((const uint8_t*)w2p + b * 11008, 11008);
                l2_prefetch((const uint8_t*)wop + b * 4096, 4096);
            }
            __syncwarp();
            const int ht = tid - 288;
            const int n0 = j * FCH;
#pragma unroll 1
            for (int w = 0; w < 2; w++) {
                bar_sync(4 + w, 128 + 224);
#pragma unroll 2
                for (int it = ht; it < 64 * 22; it += 224) {
                    const int r = it / 22, c = it - r * 22;
                    const int p = r / 22, rr = r - p * 22;
                    const uint4 hv = *(const uint4*)(sgen + p * 16384 + w * 8192 + rr * HPITCH + c * 16);
                    uint4 o;
                    o.x = pack_bf16(mish_f(bf_lo(hv.x)), mish_f(bf_hi(hv.x)));
                    o.y = pack_bf16(mish_f(bf_lo(hv.y)), mish_f(bf_hi(hv.y)));
                    o.z = pack_bf16(mish_f(bf_lo(hv.z)), mish_f(bf_hi(hv.z)));
                    o.w = pack_bf16(mish_f(bf_lo(hv.w)), mish_f(bf_hi(hv.w)));
                    if (n0 + c * 8 < F_)
                        *(uint4*)(g_a2 + (size_t)(rb * 128 + w * 64 + r) * KA2 + D_ + n0 + c * 8) = o;
                }
            }
            TS(16, tid == 288);
        }
    } else {
        reg_alloc<216>();
        if (tid < 88) {
            const int c = j * FCH + tid * 2;
            sBias[tid] = c < F_ ? __ldg((const uint32_t*)(b1 + c)) : 0u;
        }
        const int w4 = warp & 3, q = lane & 3;
        float accF[88], accQ[96];
#pragma unroll 1
        for (int kc = 0; kc < 8; kc++) {
            const int st = kc & 3;
            mbar_wait(x_full + 8 * kc, 0);
            mbar_wait(b_full + 8 * st, (kc >> 2) & 1);
            TS(1, tid == 0 && kc == 0); TS(2, tid == 0 && kc == 4);
            wgmma_fence();
#pragma unroll
            for (int k16 = 0; k16 < 4; k16++) {
                const uint64_t db = make_desc(sB + st * K1_BSTAGE + k16 * 2048, 8192, 1024);
                const uint64_t da = make_desc(sX + kc * 16384 + wg * 8192 + k16 * 32, 16, 1024);
                wgmma_n176<1>(accF, da, db, (kc | k16) != 0);
            }
            wgmma_commit();
            if (kc > 0) { wgmma_wait<1>(); if (lane == 0) mbar_arrive(b_empty + 8 * ((kc - 1) & 3)); }
        }
        TS(3, tid == 0);
        const int rl = wg * 64 + w4 * 16 + (lane >> 2);
#pragma unroll 1
        for (int kc = 0; kc < 8; kc++) {
            const int st = kc & 3;
            mbar_wait(b_full + 8 * st, ((kc + 8) >> 2) & 1);
            wgmma_fence();
#pragma unroll
            for (int k16 = 0; k16 < 4; k16++) {
                const uint64_t db = make_desc(sB + st * K1_BSTAGE + k16 * 2048, 8192, 1024);
                const uint64_t da = make_desc(sX + kc * 16384 + wg * 8192 + k16 * 32, 16, 1024);
                wgmma_n192<1>(accQ, da, db, (kc | k16) != 0);
            }
            wgmma_commit();
            wgmma_wait<1>();
            if (lane == 0) mbar_arrive(b_empty + 8 * ((kc + 3) & 3));
            if (kc == 3) {
                bar_sync(3, 256);
                const int r0 = w4 * 16 + (lane >> 2), r1 = r0 + 8;
                uint8_t* d0 = sgen + (r0 / 22) * 16384 + wg * 8192 + (r0 % 22) * HPITCH + q * 4;
                uint8_t* d1 = sgen + (r1 / 22) * 16384 + wg * 8192 + (r1 % 22) * HPITCH + q * 4;
#pragma unroll
                for (int t = 0; t < 22; t++) {
                    const uint32_t bv = sBias[t * 4 + q];
                    const float bb0 = bf_lo(bv), bb1 = bf_hi(bv);
                    *(uint32_t*)(d0 + t * 16) = pack_bf16(accF[t * 4 + 0] + bb0, accF[t * 4 + 1] + bb1);
                    *(uint32_t*)(d1 + t * 16) = pack_bf16(accF[t * 4 + 2] + bb0, accF[t * 4 + 3] + bb1);
                }
                bar_arrive(4 + wg, 128 + 224);
            }
        }
        wgmma_wait<0>();
        TS(4, tid == 0);
        {
            bf16* orow0 = g_qkv + ((size_t)j * S_ + rb * 128 + rl) * 192;
            bf16* orow1 = orow0 + 8 * 192;
#pragma unroll
            for (int u = 0; u < 6; u++) {
                uint32_t w0[4], w1[4];
#pragma unroll
                for (int i = 0; i < 4; i++) {
                    const int t = u * 4 + i;
                    w0[i] = pack_bf16(accQ[t * 4 + 0], accQ[t * 4 + 1]);
                    w1[i] = pack_bf16(accQ[t * 4 + 2], accQ[t * 4 + 3]);
                }
                quad_transpose(w0, q);
                quad_transpose(w1, q);
                const int c = (u * 4 + q) * 8;
                *(uint4*)(orow0 + c) = make_uint4(w0[0], w0[1], w0[2], w0[3]);
                *(uint4*)(orow1 + c) = make_uint4(w1[0], w1[1], w1[2], w1[3]);
            }
        }
        TS(5, tid == 0);
    }
}

__device__ __forceinline__ void ldsm_x4(uint32_t (&r)[4], uint32_t addr) {
    asm("ldmatrix.sync.aligned.m8n8.x4.shared.b16 {%0,%1,%2,%3}, [%4];"
                 : "=r"(r[0]), "=r"(r[1]), "=r"(r[2]), "=r"(r[3]) : "r"(addr));
}
__device__ __forceinline__ void ldsm_x4_t(uint32_t (&r)[4], uint32_t addr) {
    asm("ldmatrix.sync.aligned.m8n8.x4.trans.shared.b16 {%0,%1,%2,%3}, [%4];"
                 : "=r"(r[0]), "=r"(r[1]), "=r"(r[2]), "=r"(r[3]) : "r"(addr));
}
__device__ __forceinline__ void mma16816(float (&d)[4], const uint32_t (&a)[4], uint32_t b0, uint32_t b1) {
    asm("mma.sync.aligned.m16n8k16.row.col.f32.bf16.bf16.f32 {%0,%1,%2,%3}, {%4,%5,%6,%7}, {%8,%9}, {%0,%1,%2,%3};"
                 : "+f"(d[0]), "+f"(d[1]), "+f"(d[2]), "+f"(d[3])
                 : "r"(a[0]), "r"(a[1]), "r"(a[2]), "r"(a[3]), "r"(b0), "r"(b1));
}
__device__ __forceinline__ void mma16816_z(float (&d)[4], const uint32_t (&a)[4], uint32_t b0, uint32_t b1) {
    asm("mma.sync.aligned.m16n8k16.row.col.f32.bf16.bf16.f32 {%0,%1,%2,%3}, {%4,%5,%6,%7}, {%8,%9}, {%10,%10,%10,%10};"
                 : "=f"(d[0]), "=f"(d[1]), "=f"(d[2]), "=f"(d[3])
                 : "r"(a[0]), "r"(a[1]), "r"(a[2]), "r"(a[3]), "r"(b0), "r"(b1), "f"(0.f));
}

constexpr int KV_PITCH = 128;

template <int EDGE, bool HEAD>
__device__ __forceinline__ void blk_scores(float (&s)[2][4], const uint32_t (&qa)[4], uint32_t kaddr, bool dead, int r0, int c0)
{
    uint32_t kf[4];
    ldsm_x4(kf, kaddr);
    mma16816_z(s[0], qa, kf[0], kf[1]);
    mma16816_z(s[1], qa, kf[2], kf[3]);
#pragma unroll
    for (int t = 0; t < 2; t++)
#pragma unroll
        for (int e = 0; e < 4; e++) {
            const int r = r0 + (e >> 1) * 8, c = t * 8 + c0 + (e & 1);
            if (EDGE == 1 && c <= r) s[t][e] = -1e30f;
            if (EDGE == 2 && c > r) s[t][e] = -1e30f;
            if (HEAD && dead) s[t][e] = -1e30f;
        }
}
__device__ __forceinline__ void blk_max(const float (&s)[2][4], float& n0, float& n1) {
    n0 = fmaxf(n0, fmaxf(fmaxf(s[0][0], s[0][1]), fmaxf(s[1][0], s[1][1])));
    n1 = fmaxf(n1, fmaxf(fmaxf(s[0][2], s[0][3]), fmaxf(s[1][2], s[1][3])));
}
__device__ __forceinline__ void blk_pv(const float (&s)[2][4], float mc0, float mc1, float& l0, float& l1,
                                       float (&o)[2][4], uint32_t vaddr) {
    const float C = 0.25f * 1.4426950408889634f;
    uint32_t pa[4];
#pragma unroll
    for (int t = 0; t < 2; t++) {
        const float p0 = ex2(fmaf(s[t][0], C, -mc0)), p1 = ex2(fmaf(s[t][1], C, -mc0));
        const float p2 = ex2(fmaf(s[t][2], C, -mc1)), p3 = ex2(fmaf(s[t][3], C, -mc1));
        l0 += p0 + p1; l1 += p2 + p3;
        pa[2 * t] = pack_bf16(p0, p1); pa[2 * t + 1] = pack_bf16(p2, p3);
    }
    uint32_t vf[4];
    ldsm_x4_t(vf, vaddr);
    mma16816(o[0], pa, vf[0], vf[1]);
    mma16816(o[1], pa, vf[2], vf[3]);
}
__device__ __forceinline__ void quad_max(float& n0, float& n1) {
    n0 = fmaxf(n0, __shfl_xor_sync(0xffffffffu, n0, 1)); n1 = fmaxf(n1, __shfl_xor_sync(0xffffffffu, n1, 1));
    n0 = fmaxf(n0, __shfl_xor_sync(0xffffffffu, n0, 2)); n1 = fmaxf(n1, __shfl_xor_sync(0xffffffffu, n1, 2));
}
template <int NC, int NN, bool FIRST, bool NEXT_IS_EDGE, bool HEAD>
__device__ __forceinline__ void pipe_step(const float (&sc)[5][2][4], float (&sn)[5][2][4], const uint32_t (&qa)[4],
                                          uint32_t ka, uint32_t va, int kc, int kn, int kb0, int r0, int c0,
                                          float& m0, float& m1, float& n0, float& n1, float& l0, float& l1, float (&o)[2][4])
{
    const float C = 0.25f * 1.4426950408889634f;
    const float mc0 = n0 * C, mc1 = n1 * C;
    if (!FIRST) {
        const float a0 = ex2(fmaf(m0, C, -mc0)), a1 = ex2(fmaf(m1, C, -mc1));
        l0 *= a0; l1 *= a1;
        o[0][0] *= a0; o[0][1] *= a0; o[1][0] *= a0; o[1][1] *= a0;
        o[0][2] *= a1; o[0][3] *= a1; o[1][2] *= a1; o[1][3] *= a1;
    }
    m0 = n0; m1 = n1;
#pragma unroll
    for (int b = 0; b < NC; b++) {
        if (b < NN) {
            if (NEXT_IS_EDGE && b == 0) blk_scores<1, HEAD>(sn[b], qa, ka + (kn + b) * 16 * KV_PITCH, kn + b < kb0, r0, c0);
            else                        blk_scores<0, HEAD>(sn[b], qa, ka + (kn + b) * 16 * KV_PITCH, kn + b < kb0, r0, c0);
        }
        blk_pv(sc[b], mc0, mc1, l0, l1, o, va + (kc + b) * 16 * KV_PITCH);
        if (b < NN) blk_max(sn[b], n0, n1);
    }
    if (NN > 0) quad_max(n0, n1);
}

template <bool HEAD>
__device__ __forceinline__ void attn_task(const uint32_t (&qa)[4], uint32_t ka, uint32_t va, int kb0, int lane,
                                          bf16* __restrict__ out  , float g0, float g1)
{
    const int r0 = lane >> 2, c0 = (lane & 3) * 2;
    float m0 = -1e30f, m1 = -1e30f, n0 = -1e30f, n1 = -1e30f, l0 = 0.f, l1 = 0.f;
    float o[2][4] = {{0.f, 0.f, 0.f, 0.f}, {0.f, 0.f, 0.f, 0.f}};
    float sa[5][2][4], sb[5][2][4];
#pragma unroll
    for (int b = 0; b < 5; b++) {
        if (b == 4) blk_scores<2, HEAD>(sa[b], qa, ka + (12 + b) * 16 * KV_PITCH, false, r0, c0);
        else        blk_scores<0, HEAD>(sa[b], qa, ka + (12 + b) * 16 * KV_PITCH, 12 + b < kb0, r0, c0);
        blk_max(sa[b], n0, n1);
    }
    quad_max(n0, n1);
    pipe_step<5, 4, true,  false, HEAD>(sa, sb, qa, ka, va, 12, 8, kb0, r0, c0, m0, m1, n0, n1, l0, l1, o);
    pipe_step<4, 4, false, false, HEAD>(sb, sa, qa, ka, va, 8, 4, kb0, r0, c0, m0, m1, n0, n1, l0, l1, o);
    pipe_step<4, 4, false, true,  HEAD>(sa, sb, qa, ka, va, 4, 0, kb0, r0, c0, m0, m1, n0, n1, l0, l1, o);
    pipe_step<4, 0, false, false, HEAD>(sb, sa, qa, ka, va, 0, 0, kb0, r0, c0, m0, m1, n0, n1, l0, l1, o);
    l0 += __shfl_xor_sync(0xffffffffu, l0, 1); l0 += __shfl_xor_sync(0xffffffffu, l0, 2);
    l1 += __shfl_xor_sync(0xffffffffu, l1, 1); l1 += __shfl_xor_sync(0xffffffffu, l1, 2);
    const float f0 = g0 / l0, f1 = g1 / l1;
#pragma unroll
    for (int t = 0; t < 2; t++) {
        *(uint32_t*)(out + (size_t)r0 * KA2 + t * 8 + c0) = pack_bf16(o[t][0] * f0, o[t][1] * f0);
        *(uint32_t*)(out + (size_t)(r0 + 8) * KA2 + t * 8 + c0) = pack_bf16(o[t][2] * f1, o[t][3] * f1);
    }
}

constexpr int K2_SMEM = 2 * 384 * KV_PITCH + 1024 + 64;

__global__ void __launch_bounds__(512, 1) k2_kernel(const __grid_constant__ CUtensorMap tmQKV)
{
    extern __shared__ uint8_t smem_raw[];
    const uint32_t sbase = (smem_u32(smem_raw) + 1023u) & ~1023u;
    uint8_t* sgen = smem_raw + (sbase - smem_u32(smem_raw));
    const uint32_t sK = sbase, sV = sK + 384 * KV_PITCH, kv_full = sbase + 2 * 384 * KV_PITCH;
    const int rb = blockIdx.x >> 3, j = blockIdx.x & 7;
    const int tid = threadIdx.x, warp = tid >> 5, lane = tid & 31;
    pdl_launch();
    if (tid == 0) {
        mbar_init(kv_full, 1);
        fence_barrier_init();
    }
    pdl_wait();
    TS(6, tid == 0);
    if (tid == 0) {
        const int nblk = rb >= 2 ? 3 : rb + 1;
        mbar_expect_tx(kv_full, nblk * 2 * 16384);
        for (int i = 0; i < nblk; i++) {
            const int row = j * S_ + (rb - i) * 128;
            tma_load_2d(sK + (2 - i) * 16384, &tmQKV, 64, row, kv_full);
            tma_load_2d(sV + (2 - i) * 16384, &tmQKV, 128, row, kv_full);
        }
    }
    if (rb < 2) {
        for (int i = tid; i < (2 - rb) * 1024; i += 512) {
            *(uint4*)(sgen + i * 16) = make_uint4(0, 0, 0, 0);
            *(uint4*)(sgen + 384 * KV_PITCH + i * 16) = make_uint4(0, 0, 0, 0);
        }
    }
    const int qt = warp & 7, h0 = (warp >> 3) * 2;
    const int q0g = rb * 128 + qt * 16;
    const int r0 = lane >> 2, c0 = (lane & 3) * 2;
    const bf16* qsrc = g_qkv + ((size_t)j * S_ + q0g) * 192 + h0 * 16;
    uint32_t qa[4], qn[4];
    qa[0] = *(const uint32_t*)(qsrc + (size_t)r0 * 192 + c0);
    qa[1] = *(const uint32_t*)(qsrc + (size_t)(r0 + 8) * 192 + c0);
    qa[2] = *(const uint32_t*)(qsrc + (size_t)r0 * 192 + c0 + 8);
    qa[3] = *(const uint32_t*)(qsrc + (size_t)(r0 + 8) * 192 + c0 + 8);
    qn[0] = *(const uint32_t*)(qsrc + (size_t)r0 * 192 + 16 + c0);
    qn[1] = *(const uint32_t*)(qsrc + (size_t)(r0 + 8) * 192 + 16 + c0);
    qn[2] = *(const uint32_t*)(qsrc + (size_t)r0 * 192 + 16 + c0 + 8);
    qn[3] = *(const uint32_t*)(qsrc + (size_t)(r0 + 8) * 192 + 16 + c0 + 8);
    const float g0 = 1.f, g1 = 1.f;
    const int kb0 = q0g < 256 ? (256 - q0g) >> 4 : 0;
    __syncthreads();
    mbar_wait(kv_full, 0);
    uint32_t sKd = sK, sVd = sV;
    asm volatile("" : "+r"(sKd), "+r"(sVd) :: "memory");
    TS(7, tid == 0);
    const int krow = qt * 16 + (lane & 7) + ((lane >> 4) << 3);
    const int vrow = qt * 16 + (lane & 15);
#pragma unroll 1
    for (int hh = 0; hh < 2; hh++) {
        const int hl = h0 + hh;
        const uint32_t ka = sKd + krow * KV_PITCH + (((2 * hl + ((lane >> 3) & 1)) ^ (lane & 7)) << 4);
        const uint32_t va = sVd + vrow * KV_PITCH + (((2 * hl + (lane >> 4)) ^ (lane & 7)) << 4);
        if (rb < 2) attn_task<true>(qa, ka, va, kb0, lane, g_a2 + (size_t)q0g * KA2 + (j * 4 + hl) * 16, g0, g1);
        else        attn_task<false>(qa, ka, va, kb0, lane, g_a2 + (size_t)q0g * KA2 + (j * 4 + hl) * 16, g0, g1);
        TS(8 + hh, tid == 0);
        qa[0] = qn[0]; qa[1] = qn[1]; qa[2] = qn[2]; qa[3] = qn[3];
    }
}

constexpr int K3_STAGES = 8;
constexpr int K3_STAGE = 16384 + 8192;
constexpr int K3_SMEM = K3_STAGES * K3_STAGE + 1024 + 1024;
constexpr int K3_KSTEPS = 30;

__global__ void __launch_bounds__(384, 1)
k3_kernel(const __grid_constant__ CUtensorMap tmA2, const __grid_constant__ CUtensorMap tmWo,
          const __grid_constant__ CUtensorMap tmW2, const bf16* __restrict__ x, const bf16* __restrict__ gate_w,
          bf16* __restrict__ out)
{
    extern __shared__ uint8_t smem_raw[];
    const uint32_t sbase = (smem_u32(smem_raw) + 1023u) & ~1023u;
    uint8_t* sgen = smem_raw + (sbase - smem_u32(smem_raw));
    const uint32_t sBar = sbase + K3_STAGES * K3_STAGE;
    const uint32_t full = sBar, empty = sBar + 64;
    float* sGate = (float*)(sgen + K3_STAGES * K3_STAGE + 256);
    const int rb = blockIdx.x >> 3, nb = blockIdx.x & 7;
    const int tid = threadIdx.x, wg = tid >> 7, warp = tid >> 5, lane = tid & 31;
    if (tid == 0) {
        for (int i = 0; i < K3_STAGES; i++) { mbar_init(full + 8 * i, 1); mbar_init(empty + 8 * i, 8); }
        fence_barrier_init();
    }
    __syncthreads();
    TS(10, tid == 0);
    if (wg == 2) {
        reg_dealloc<40>();
        if (warp == 8) {
            if (lane == 0) {
                for (int ks = 0; ks < K3_KSTEPS; ks++) {
                    const int st = ks % K3_STAGES;
                    if (ks >= K3_STAGES) mbar_wait(empty + 8 * st, ((ks / K3_STAGES) - 1) & 1);
                    mbar_expect_tx(full + 8 * st, K3_STAGE);
                    const uint32_t dst = sbase + st * K3_STAGE;
                    tma_load_2d(dst, &tmA2, ks * 64, rb * 128, full + 8 * st);
                    if (ks < 8) tma_load_2d(dst + 16384, &tmWo, nb * 64, ks * 64, full + 8 * st);
                    else        tma_load_2d(dst + 16384, &tmW2, nb * 64, (ks - 8) * 64, full + 8 * st);
                }
            }
        } else {
            const uint4 ga = __ldg((const uint4*)gate_w + lane * 2), gb = __ldg((const uint4*)gate_w + lane * 2 + 1);
#pragma unroll 4
            for (int r = warp - 9; r < 128; r += 3) {
                const uint4* xr = (const uint4*)(x + (size_t)(rb * 128 + r) * D_) + lane * 2;
                const uint4 xa = __ldg(xr), xb = __ldg(xr + 1);
                float gs = bf_lo(xa.x) * bf_lo(ga.x);
                gs = fmaf(bf_hi(xa.x), bf_hi(ga.x), gs);
                gs = fmaf(bf_lo(xa.y), bf_lo(ga.y), gs); gs = fmaf(bf_hi(xa.y), bf_hi(ga.y), gs);
                gs = fmaf(bf_lo(xa.z), bf_lo(ga.z), gs); gs = fmaf(bf_hi(xa.z), bf_hi(ga.z), gs);
                gs = fmaf(bf_lo(xa.w), bf_lo(ga.w), gs); gs = fmaf(bf_hi(xa.w), bf_hi(ga.w), gs);
                gs = fmaf(bf_lo(xb.x), bf_lo(gb.x), gs); gs = fmaf(bf_hi(xb.x), bf_hi(gb.x), gs);
                gs = fmaf(bf_lo(xb.y), bf_lo(gb.y), gs); gs = fmaf(bf_hi(xb.y), bf_hi(gb.y), gs);
                gs = fmaf(bf_lo(xb.z), bf_lo(gb.z), gs); gs = fmaf(bf_hi(xb.z), bf_hi(gb.z), gs);
                gs = fmaf(bf_lo(xb.w), bf_lo(gb.w), gs); gs = fmaf(bf_hi(xb.w), bf_hi(gb.w), gs);
#pragma unroll
                for (int o = 16; o > 0; o >>= 1) gs += __shfl_xor_sync(0xffffffffu, gs, o);
                if (lane == 0) sGate[r] = 1.f / (1.f + __expf(-gs));
            }
            bar_arrive(1, 256 + 96);
        }
    } else {
        reg_alloc<232>();
        float accA[32], accB[32];
        for (int ks = 0; ks < 8; ks++) {
            mbar_wait(full + 8 * ks, 0);
            TS(11, tid == 0 && ks == 0);
            wgmma_fence();
#pragma unroll
            for (int k16 = 0; k16 < 4; k16++) {
                const uint64_t da = make_desc(sbase + ks * K3_STAGE + wg * 8192 + k16 * 32, 16, 1024);
                const uint64_t db = make_desc(sbase + ks * K3_STAGE + 16384 + k16 * 2048, 8192, 1024);
                wgmma_n64<1>(accA, da, db, (ks | k16) != 0);
            }
            wgmma_commit();
            if (ks > 0) { wgmma_wait<1>(); if (lane == 0) mbar_arrive(empty + 8 * (ks - 1)); }
        }
        for (int ks = 8; ks < K3_KSTEPS; ks++) {
            const int st = ks % K3_STAGES;
            mbar_wait(full + 8 * st, (ks / K3_STAGES) & 1);
            TS(12, tid == 0 && ks == 8); TS(13, tid == 0 && ks == 16);
            wgmma_fence();
#pragma unroll
            for (int k16 = 0; k16 < 4; k16++) {
                const uint64_t da = make_desc(sbase + st * K3_STAGE + wg * 8192 + k16 * 32, 16, 1024);
                const uint64_t db = make_desc(sbase + st * K3_STAGE + 16384 + k16 * 2048, 8192, 1024);
                wgmma_n64<1>(accB, da, db, ((ks - 8) | k16) != 0);
            }
            wgmma_commit();
            wgmma_wait<1>();
            if (lane == 0) mbar_arrive(empty + 8 * ((ks - 1) % K3_STAGES));
        }
        wgmma_wait<0>();
        TS(14, tid == 0);
        bar_sync(1, 256 + 96);
        const int q = lane & 3;
        const int rl = wg * 64 + (warp & 3) * 16 + (lane >> 2);
        const float g0 = sGate[rl], g1 = sGate[rl + 8];
        bf16* orow0 = out + (size_t)(rb * 128 + rl) * D_ + nb * 64;
        bf16* orow1 = orow0 + 8 * D_;
#pragma unroll
        for (int u = 0; u < 2; u++) {
            uint32_t w0[4], w1[4];
#pragma unroll
            for (int i = 0; i < 4; i++) {
                const int t = u * 4 + i;
                w0[i] = pack_bf16(fmaf(g0, accA[t * 4 + 0] - accB[t * 4 + 0], accB[t * 4 + 0]), fmaf(g0, accA[t * 4 + 1] - accB[t * 4 + 1], accB[t * 4 + 1]));
                w1[i] = pack_bf16(fmaf(g1, accA[t * 4 + 2] - accB[t * 4 + 2], accB[t * 4 + 2]), fmaf(g1, accA[t * 4 + 3] - accB[t * 4 + 3], accB[t * 4 + 3]));
            }
            quad_transpose(w0, q);
            quad_transpose(w1, q);
            const int c = (u * 4 + q) * 8;
            *(uint4*)(orow0 + c) = make_uint4(w0[0], w0[1], w0[2], w0[3]);
            *(uint4*)(orow1 + c) = make_uint4(w1[0], w1[1], w1[2], w1[3]);
        }
        TS(15, tid == 0);
    }
}

typedef CUresult (*PFN_encodeTiled)(CUtensorMap*, CUtensorMapDataType, cuuint32_t, void*, const cuuint64_t*,
                                    const cuuint64_t*, const cuuint32_t*, const cuuint32_t*, CUtensorMapInterleave,
                                    CUtensorMapSwizzle, CUtensorMapL2promotion, CUtensorMapFloatOOBfill);

static void make_map(PFN_encodeTiled enc, CUtensorMap* m, const void* ptr, uint64_t cols, uint64_t rows,
                     uint32_t box_cols, uint32_t box_rows)
{
    cuuint64_t dims[2] = {cols, rows};
    cuuint64_t strides[1] = {cols * 2};
    cuuint32_t box[2] = {box_cols, box_rows};
    cuuint32_t es[2] = {1, 1};
    enc(m, CU_TENSOR_MAP_DATA_TYPE_BFLOAT16, 2, const_cast<void*>(ptr), dims, strides, box, es,
        CU_TENSOR_MAP_INTERLEAVE_NONE, CU_TENSOR_MAP_SWIZZLE_128B, CU_TENSOR_MAP_L2_PROMOTION_L2_128B,
        CU_TENSOR_MAP_FLOAT_OOB_FILL_NONE);
}

extern "C" void kernel_launch(void* const* d_in, const int* in_sizes, int n_in, void* d_out, int out_size)
{
    const bf16* x    = (const bf16*)d_in[0];
    const bf16* wqkv = (const bf16*)d_in[1];
    const bf16* wo   = (const bf16*)d_in[2];
    const bf16* w1   = (const bf16*)d_in[4];
    const bf16* b1   = (const bf16*)d_in[5];
    const bf16* w2   = (const bf16*)d_in[6];
    const bf16* gw   = (const bf16*)d_in[7];

    static PFN_encodeTiled enc = nullptr;
    if (!enc) {
        void* fn = nullptr;
        cudaDriverEntryPointQueryResult qr;
        cudaGetDriverEntryPoint("cuTensorMapEncodeTiled", &fn, cudaEnableDefault, &qr);
        enc = (PFN_encodeTiled)fn;
        cudaFuncSetAttribute(k1_kernel, cudaFuncAttributeMaxDynamicSharedMemorySize, K1_SMEM);
        cudaFuncSetAttribute(k2_kernel, cudaFuncAttributeMaxDynamicSharedMemorySize, K2_SMEM);
        cudaFuncSetAttribute(k3_kernel, cudaFuncAttributeMaxDynamicSharedMemorySize, K3_SMEM);
    }
    void* a2p = nullptr;
    cudaGetSymbolAddress(&a2p, g_a2);
    void* qkvp = nullptr;
    cudaGetSymbolAddress(&qkvp, g_qkv);
    CUtensorMap tmX, tmWqkv, tmW1, tmA2, tmWo, tmW2, tmQKV;
    make_map(enc, &tmQKV, qkvp, 192, 8 * S_, 64, 128);
    make_map(enc, &tmX, x, D_, S_, 64, 128);
    make_map(enc, &tmWqkv, wqkv, 3 * D_, D_, 64, 64);
    make_map(enc, &tmW1, w1, F_, D_, 64, 64);
    make_map(enc, &tmA2, a2p, KA2, S_, 64, 128);
    make_map(enc, &tmWo, wo, D_, D_, 64, 64);
    make_map(enc, &tmW2, w2, D_, F_, 64, 64);

    cudaStream_t st = cudaStreamPerThread;
    k1_kernel<<<128, 512, K1_SMEM, st>>>(tmX, tmWqkv, tmW1, b1, gw, w1, wqkv, w2, wo);
    cudaLaunchAttribute at[1];
    at[0].id = cudaLaunchAttributeProgrammaticStreamSerialization;
    at[0].val.programmaticStreamSerializationAllowed = 1;
    cudaLaunchConfig_t cfg = {};
    cfg.gridDim = dim3(128); cfg.stream = st; cfg.attrs = at; cfg.numAttrs = 1;
    cfg.blockDim = dim3(512); cfg.dynamicSmemBytes = K2_SMEM;
    cudaLaunchKernelEx(&cfg, k2_kernel, tmQKV);
    k3_kernel<<<128, 384, K3_SMEM, st>>>(tmA2, tmWo, tmW2, x, gw, (bf16*)d_out);
}
```

```cpp
#include <cuda_runtime.h>
#include <cuda_bf16.h>
#include <cuda.h>
#include <stdint.h>

typedef __nv_bfloat16 bf16;

constexpr int S_ = 2048, D_ = 512, F_ = 1376;
constexpr int KA2 = D_ + F_;
constexpr int FCH = 176;

__device__ bf16  g_qkv[8 * S_ * 192];
__device__ bf16  g_a2[S_ * KA2];
__device__ float g_gate[S_];

#define TS(k, cond) do { } while (0)

__device__ __forceinline__ uint32_t smem_u32(const void* p) { return (uint32_t)__cvta_generic_to_shared(p); }
__device__ __forceinline__ void mbar_init(uint32_t bar, uint32_t count) {
    asm volatile("mbarrier.init.shared::cta.b64 [%0], %1;" :: "r"(bar), "r"(count) : "memory");
}
__device__ __forceinline__ void mbar_expect_tx(uint32_t bar, uint32_t bytes) {
    asm volatile("mbarrier.arrive.expect_tx.shared::cta.b64 _, [%0], %1;" :: "r"(bar), "r"(bytes) : "memory");
}
__device__ __forceinline__ void mbar_arrive(uint32_t bar) {
    asm volatile("mbarrier.arrive.shared::cta.b64 _, [%0];" :: "r"(bar) : "memory");
}
__device__ __forceinline__ bool mbar_try_wait(uint32_t bar, uint32_t parity) {
    uint32_t ok;
    asm volatile("{\n.reg .pred p;\nmbarrier.try_wait.parity.shared::cta.b64 p, [%1], %2;\nselp.u32 %0, 1, 0, p;\n}"
                 : "=r"(ok) : "r"(bar), "r"(parity) : "memory");
    return ok != 0;
}
__device__ __forceinline__ void mbar_wait(uint32_t bar, uint32_t parity) {
    for (uint32_t it = 0; it < (1u << 22); ++it) { if (mbar_try_wait(bar, parity)) break; }
}
__device__ __forceinline__ void tma_load_2d(uint32_t dst, const CUtensorMap* map, int c0, int c1, uint32_t bar) {
    asm volatile("cp.async.bulk.tensor.2d.shared::cluster.global.mbarrier::complete_tx::bytes [%0], [%1, {%3, %4}], [%2];"
                 :: "r"(dst), "l"(map), "r"(bar), "r"(c0), "r"(c1) : "memory");
}
__device__ __forceinline__ void l2_prefetch(const void* p, uint32_t bytes) {
    asm volatile("cp.async.bulk.prefetch.L2.global [%0], %1;" :: "l"(p), "r"(bytes) : "memory");
}
__device__ __forceinline__ void fence_barrier_init() { asm volatile("fence.mbarrier_init.release.cluster;" ::: "memory"); }
__device__ __forceinline__ void wgmma_fence()  { asm volatile("wgmma.fence.sync.aligned;" ::: "memory"); }
__device__ __forceinline__ void wgmma_commit() { asm volatile("wgmma.commit_group.sync.aligned;" ::: "memory"); }
template <int N> __device__ __forceinline__ void wgmma_wait() { asm volatile("wgmma.wait_group.sync.aligned %0;" :: "n"(N) : "memory"); }
template <int R> __device__ __forceinline__ void reg_alloc()   { asm volatile("setmaxnreg.inc.sync.aligned.u32 %0;" :: "n"(R)); }
template <int R> __device__ __forceinline__ void reg_dealloc() { asm volatile("setmaxnreg.dec.sync.aligned.u32 %0;" :: "n"(R)); }
__device__ __forceinline__ void bar_sync(int id, int n)   { asm volatile("bar.sync %0, %1;" :: "r"(id), "r"(n) : "memory"); }
__device__ __forceinline__ void bar_arrive(int id, int n) { asm volatile("bar.arrive %0, %1;" :: "r"(id), "r"(n) : "memory"); }

__device__ __forceinline__ uint64_t make_desc(uint32_t addr, uint32_t lbo, uint32_t sbo) {
    uint64_t d = (uint64_t)((addr & 0x3FFFF) >> 4);
    d |= (uint64_t)((lbo & 0x3FFFF) >> 4) << 16;
    d |= (uint64_t)((sbo & 0x3FFFF) >> 4) << 32;
    d |= (uint64_t)1 << 62;
    return d;
}

template <int TB>
__device__ __forceinline__ void wgmma_n64(float (&d)[32], uint64_t da, uint64_t db, int scale_d) {
    asm volatile("{\n.reg .pred p;\nsetp.ne.b32 p, %34, 0;\n"
        "wgmma.mma_async.sync.aligned.m64n64k16.f32.bf16.bf16 {%0, %1, %2, %3, %4, %5, %6, %7, %8, %9, %10, %11, %12, %13, %14, %15, %16, %17, %18, %19, %20, %21, %22, %23, %24, %25, %26, %27, %28, %29, %30, %31}, %32, %33, p, 1, 1, 0, %35;\n}\n"
        : "+f"(d[0]), "+f"(d[1]), "+f"(d[2]), "+f"(d[3]), "+f"(d[4]), "+f"(d[5]), "+f"(d[6]), "+f"(d[7]), "+f"(d[8]), "+f"(d[9]), "+f"(d[10]), "+f"(d[11]), "+f"(d[12]), "+f"(d[13]), "+f"(d[14]), "+f"(d[15]), "+f"(d[16]), "+f"(d[17]), "+f"(d[18]), "+f"(d[19]), "+f"(d[20]), "+f"(d[21]), "+f"(d[22]), "+f"(d[23]), "+f"(d[24]), "+f"(d[25]), "+f"(d[26]), "+f"(d[27]), "+f"(d[28]), "+f"(d[29]), "+f"(d[30]), "+f"(d[31])
        : "l"(da), "l"(db), "r"(scale_d), "n"(TB));
}

template <int TB>
__device__ __forceinline__ void wgmma_n128(float (&d)[64], uint64_t da, uint64_t db, int scale_d) {
    asm volatile("{\n.reg .pred p;\nsetp.ne.b32 p, %66, 0;\n"
        "wgmma.mma_async.sync.aligned.m64n128k16.f32.bf16.bf16 {%0, %1, %2, %3, %4, %5, %6, %7, %8, %9, %10, %11, %12, %13, %14, %15, %16, %17, %18, %19, %20, %21, %22, %23, %24, %25, %26, %27, %28, %29, %30, %31, %32, %33, %34, %35, %36, %37, %38, %39, %40, %41, %42, %43, %44, %45, %46, %47, %48, %49, %50, %51, %52, %53, %54, %55, %56, %57, %58, %59, %60, %61, %62, %63}, %64, %65, p, 1, 1, 0, %67;\n}\n"
        : "+f"(d[0]), "+f"(d[1]), "+f"(d[2]), "+f"(d[3]), "+f"(d[4]), "+f"(d[5]), "+f"(d[6]), "+f"(d[7]), "+f"(d[8]), "+f"(d[9]), "+f"(d[10]), "+f"(d[11]), "+f"(d[12]), "+f"(d[13]), "+f"(d[14]), "+f"(d[15]), "+f"(d[16]), "+f"(d[17]), "+f"(d[18]), "+f"(d[19]), "+f"(d[20]), "+f"(d[21]), "+f"(d[22]), "+f"(d[23]), "+f"(d[24]), "+f"(d[25]), "+f"(d[26]), "+f"(d[27]), "+f"(d[28]), "+f"(d[29]), "+f"(d[30]), "+f"(d[31]), "+f"(d[32]), "+f"(d[33]), "+f"(d[34]), "+f"(d[35]), "+f"(d[36]), "+f"(d[37]), "+f"(d[38]), "+f"(d[39]), "+f"(d[40]), "+f"(d[41]), "+f"(d[42]), "+f"(d[43]), "+f"(d[44]), "+f"(d[45]), "+f"(d[46]), "+f"(d[47]), "+f"(d[48]), "+f"(d[49]), "+f"(d[50]), "+f"(d[51]), "+f"(d[52]), "+f"(d[53]), "+f"(d[54]), "+f"(d[55]), "+f"(d[56]), "+f"(d[57]), "+f"(d[58]), "+f"(d[59]), "+f"(d[60]), "+f"(d[61]), "+f"(d[62]), "+f"(d[63])
        : "l"(da), "l"(db), "r"(scale_d), "n"(TB));
}

template <int TB>
__device__ __forceinline__ void wgmma_n176(float (&d)[88], uint64_t da, uint64_t db, int scale_d) {
    asm volatile("{\n.reg .pred p;\nsetp.ne.b32 p, %90, 0;\n"
        "wgmma.mma_async.sync.aligned.m64n176k16.f32.bf16.bf16 {%0, %1, %2, %3, %4, %5, %6, %7, %8, %9, %10, %11, %12, %13, %14, %15, %16, %17, %18, %19, %20, %21, %22, %23, %24, %25, %26, %27, %28, %29, %30, %31, %32, %33, %34, %35, %36, %37, %38, %39, %40, %41, %42, %43, %44, %45, %46, %47, %48, %49, %50, %51, %52, %53, %54, %55, %56, %57, %58, %59, %60, %61, %62, %63, %64, %65, %66, %67, %68, %69, %70, %71, %72, %73, %74, %75, %76, %77, %78, %79, %80, %81, %82, %83, %84, %85, %86, %87}, %88, %89, p, 1, 1, 0, %91;\n}\n"
        : "+f"(d[0]), "+f"(d[1]), "+f"(d[2]), "+f"(d[3]), "+f"(d[4]), "+f"(d[5]), "+f"(d[6]), "+f"(d[7]), "+f"(d[8]), "+f"(d[9]), "+f"(d[10]), "+f"(d[11]), "+f"(d[12]), "+f"(d[13]), "+f"(d[14]), "+f"(d[15]), "+f"(d[16]), "+f"(d[17]), "+f"(d[18]), "+f"(d[19]), "+f"(d[20]), "+f"(d[21]), "+f"(d[22]), "+f"(d[23]), "+f"(d[24]), "+f"(d[25]), "+f"(d[26]), "+f"(d[27]), "+f"(d[28]), "+f"(d[29]), "+f"(d[30]), "+f"(d[31]), "+f"(d[32]), "+f"(d[33]), "+f"(d[34]), "+f"(d[35]), "+f"(d[36]), "+f"(d[37]), "+f"(d[38]), "+f"(d[39]), "+f"(d[40]), "+f"(d[41]), "+f"(d[42]), "+f"(d[43]), "+f"(d[44]), "+f"(d[45]), "+f"(d[46]), "+f"(d[47]), "+f"(d[48]), "+f"(d[49]), "+f"(d[50]), "+f"(d[51]), "+f"(d[52]), "+f"(d[53]), "+f"(d[54]), "+f"(d[55]), "+f"(d[56]), "+f"(d[57]), "+f"(d[58]), "+f"(d[59]), "+f"(d[60]), "+f"(d[61]), "+f"(d[62]), "+f"(d[63]), "+f"(d[64]), "+f"(d[65]), "+f"(d[66]), "+f"(d[67]), "+f"(d[68]), "+f"(d[69]), "+f"(d[70]), "+f"(d[71]), "+f"(d[72]), "+f"(d[73]), "+f"(d[74]), "+f"(d[75]), "+f"(d[76]), "+f"(d[77]), "+f"(d[78]), "+f"(d[79]), "+f"(d[80]), "+f"(d[81]), "+f"(d[82]), "+f"(d[83]), "+f"(d[84]), "+f"(d[85]), "+f"(d[86]), "+f"(d[87])
        : "l"(da), "l"(db), "r"(scale_d), "n"(TB));
}

template <int TB>
__device__ __forceinline__ void wgmma_n192(float (&d)[96], uint64_t da, uint64_t db, int scale_d) {
    asm volatile("{\n.reg .pred p;\nsetp.ne.b32 p, %98, 0;\n"
        "wgmma.mma_async.sync.aligned.m64n192k16.f32.bf16.bf16 {%0, %1, %2, %3, %4, %5, %6, %7, %8, %9, %10, %11, %12, %13, %14, %15, %16, %17, %18, %19, %20, %21, %22, %23, %24, %25, %26, %27, %28, %29, %30, %31, %32, %33, %34, %35, %36, %37, %38, %39, %40, %41, %42, %43, %44, %45, %46, %47, %48, %49, %50, %51, %52, %53, %54, %55, %56, %57, %58, %59, %60, %61, %62, %63, %64, %65, %66, %67, %68, %69, %70, %71, %72, %73, %74, %75, %76, %77, %78, %79, %80, %81, %82, %83, %84, %85, %86, %87, %88, %89, %90, %91, %92, %93, %94, %95}, %96, %97, p, 1, 1, 0, %99;\n}\n"
        : "+f"(d[0]), "+f"(d[1]), "+f"(d[2]), "+f"(d[3]), "+f"(d[4]), "+f"(d[5]), "+f"(d[6]), "+f"(d[7]), "+f"(d[8]), "+f"(d[9]), "+f"(d[10]), "+f"(d[11]), "+f"(d[12]), "+f"(d[13]), "+f"(d[14]), "+f"(d[15]), "+f"(d[16]), "+f"(d[17]), "+f"(d[18]), "+f"(d[19]), "+f"(d[20]), "+f"(d[21]), "+f"(d[22]), "+f"(d[23]), "+f"(d[24]), "+f"(d[25]), "+f"(d[26]), "+f"(d[27]), "+f"(d[28]), "+f"(d[29]), "+f"(d[30]), "+f"(d[31]), "+f"(d[32]), "+f"(d[33]), "+f"(d[34]), "+f"(d[35]), "+f"(d[36]), "+f"(d[37]), "+f"(d[38]), "+f"(d[39]), "+f"(d[40]), "+f"(d[41]), "+f"(d[42]), "+f"(d[43]), "+f"(d[44]), "+f"(d[45]), "+f"(d[46]), "+f"(d[47]), "+f"(d[48]), "+f"(d[49]), "+f"(d[50]), "+f"(d[51]), "+f"(d[52]), "+f"(d[53]), "+f"(d[54]), "+f"(d[55]), "+f"(d[56]), "+f"(d[57]), "+f"(d[58]), "+f"(d[59]), "+f"(d[60]), "+f"(d[61]), "+f"(d[62]), "+f"(d[63]), "+f"(d[64]), "+f"(d[65]), "+f"(d[66]), "+f"(d[67]), "+f"(d[68]), "+f"(d[69]), "+f"(d[70]), "+f"(d[71]), "+f"(d[72]), "+f"(d[73]), "+f"(d[74]), "+f"(d[75]), "+f"(d[76]), "+f"(d[77]), "+f"(d[78]), "+f"(d[79]), "+f"(d[80]), "+f"(d[81]), "+f"(d[82]), "+f"(d[83]), "+f"(d[84]), "+f"(d[85]), "+f"(d[86]), "+f"(d[87]), "+f"(d[88]), "+f"(d[89]), "+f"(d[90]), "+f"(d[91]), "+f"(d[92]), "+f"(d[93]), "+f"(d[94]), "+f"(d[95])
        : "l"(da), "l"(db), "r"(scale_d), "n"(TB));
}

__device__ __forceinline__ uint32_t pack_bf16(float lo, float hi) {
    uint32_t r;
    asm("cvt.rn.bf16x2.f32 %0, %1, %2;" : "=r"(r) : "f"(hi), "f"(lo));
    return r;
}
__device__ __forceinline__ float bf_lo(uint32_t v) { return __uint_as_float(v << 16); }
__device__ __forceinline__ float bf_hi(uint32_t v) { return __uint_as_float(v & 0xffff0000u); }

__device__ __forceinline__ void quad_transpose(uint32_t (&w)[4], int q) {
    const bool o1 = q & 1, o2 = q & 2;
    {
        uint32_t s0 = o1 ? w[0] : w[1], s1 = o1 ? w[2] : w[3];
        s0 = __shfl_xor_sync(0xffffffffu, s0, 1); s1 = __shfl_xor_sync(0xffffffffu, s1, 1);
        if (o1) { w[0] = s0; w[2] = s1; } else { w[1] = s0; w[3] = s1; }
    }
    {
        uint32_t s0 = o2 ? w[0] : w[2], s1 = o2 ? w[1] : w[3];
        s0 = __shfl_xor_sync(0xffffffffu, s0, 2); s1 = __shfl_xor_sync(0xffffffffu, s1, 2);
        if (o2) { w[0] = s0; w[1] = s1; } else { w[2] = s0; w[3] = s1; }
    }
}

__device__ __forceinline__ float ex2(float x) { float y; asm("ex2.approx.ftz.f32 %0, %1;" : "=f"(y) : "f"(x)); return y; }
__device__ __forceinline__ float rcp(float x) { float y; asm("rcp.approx.ftz.f32 %0, %1;" : "=f"(y) : "f"(x)); return y; }

__device__ __forceinline__ float ex2v(float x) { float y; asm volatile("ex2.approx.ftz.f32 %0, %1;" : "=f"(y) : "f"(x)); return y; }
__device__ __forceinline__ float rcpv(float x) { float y; asm volatile("rcp.approx.ftz.f32 %0, %1;" : "=f"(y) : "f"(x)); return y; }
__device__ __forceinline__ float mish_f(float h) {
    const float e = ex2v(1.4426950408889634f * fminf(h, 20.f));
    const float n = fmaf(e, e, e + e);
    return h * n * rcpv(n + 2.f);
}

__device__ __forceinline__ void pdl_wait()   { asm volatile("griddepcontrol.wait;" ::: "memory"); }
__device__ __forceinline__ void pdl_launch() { asm volatile("griddepcontrol.launch_dependents;" ::: "memory"); }

constexpr int K1_STAGES = 4;
constexpr int K1_XBYTES = 128 * 512 * 2;
constexpr int K1_BSTAGE = 3 * 8192;
constexpr int K1_SMEM   = K1_XBYTES + K1_STAGES * K1_BSTAGE + 2048   + 1024  ;

__global__ void __launch_bounds__(384, 1)
k1_kernel(const __grid_constant__ CUtensorMap tmX, const __grid_constant__ CUtensorMap tmWqkv,
          const __grid_constant__ CUtensorMap tmW1, const bf16* __restrict__ b1,
          const bf16* __restrict__ gate_w, const bf16* __restrict__ w1p, const bf16* __restrict__ wqkvp,
          const bf16* __restrict__ w2p, const bf16* __restrict__ wop)
{

    extern __shared__ uint8_t smem_raw[];
    const uint32_t sbase = (smem_u32(smem_raw) + 1023u) & ~1023u;
    uint8_t* sgen = smem_raw + (sbase - smem_u32(smem_raw));
    const uint32_t sX = sbase;
    const uint32_t sB = sbase + K1_XBYTES;
    const uint32_t sBar = sB + K1_STAGES * K1_BSTAGE;
    const uint32_t x_full = sBar;
    const uint32_t b_full = sBar + 64;
    const uint32_t b_empty = sBar + 96;
    float* sGate = (float*)(sgen + K1_XBYTES + K1_STAGES * K1_BSTAGE + 128);
    uint8_t* sGw = sgen + K1_XBYTES + K1_STAGES * K1_BSTAGE + 640;
    uint32_t* sBias = (uint32_t*)(sgen + K1_XBYTES + K1_STAGES * K1_BSTAGE + 1664);

    const int rb = blockIdx.x >> 3, j = blockIdx.x & 7;
    const int tid = threadIdx.x, wg = tid >> 7, warp = tid >> 5, lane = tid & 31;
    TS(0, tid == 0);
    pdl_launch();

    if (tid == 0) {
        for (int i = 0; i < 8; i++) mbar_init(x_full + 8 * i, 1);
        for (int i = 0; i < K1_STAGES; i++) { mbar_init(b_full + 8 * i, 1); mbar_init(b_empty + 8 * i, 8); }
        fence_barrier_init();
    }
    __syncthreads();

    if (wg == 2) {
        reg_dealloc<40>();
        if (tid == 288) {
            const int b = blockIdx.x;
            mbar_wait(b_full + 8, 0);
            l2_prefetch((const uint8_t*)wqkvp + b * 12288, 12288);
            l2_prefetch((const uint8_t*)w2p + b * 11008, 11008);
            l2_prefetch((const uint8_t*)wop + b * 4096, 4096);
        }
        if (tid == 256) {
            for (int it = 0; it < 16; it++) {
                if (it < 8) {
                    mbar_expect_tx(x_full + 8 * it, 16384);
                    tma_load_2d(sX + it * 16384, &tmX, it * 64, rb * 128, x_full + 8 * it);
                }
                const int st = it & 3;
                if (it >= K1_STAGES) mbar_wait(b_empty + 8 * st, ((it >> 2) - 1) & 1);
                mbar_expect_tx(b_full + 8 * st, K1_BSTAGE);
                const uint32_t dst = sB + st * K1_BSTAGE;
                if (it < 8) {
                    for (int b = 0; b < 3; b++) tma_load_2d(dst + b * 8192, &tmW1, j * FCH + b * 64, it * 64, b_full + 8 * st);
                } else {
                    for (int b = 0; b < 3; b++) tma_load_2d(dst + b * 8192, &tmWqkv, b * 512 + j * 64, (it - 8) * 64, b_full + 8 * st);
                }
            }
        }
    } else {
        reg_alloc<232>();
        if (tid < 64) ((uint4*)sGw)[tid] = __ldg((const uint4*)gate_w + tid);
        else if (tid < 64 + 88) {
            const int c = j * FCH + (tid - 64) * 2;
            sBias[tid - 64] = c < F_ ? __ldg((const uint32_t*)(b1 + c)) : 0u;
        }
        bar_sync(3, 256);
        const int t128 = tid & 127, w4 = warp & 3, q = lane & 3;
        float accF[88], accQ[96];
        float gs = 0.f;
        const int grow = wg * 64 + (t128 >> 1), ghalf = t128 & 1;
#pragma unroll
        for (int kc = 0; kc < 8; kc++) {
            const int st = kc & 3;
            mbar_wait(x_full + 8 * kc, 0);
            mbar_wait(b_full + 8 * st, (kc >> 2) & 1);
            TS(1, tid == 0 && kc == 0); TS(2, tid == 0 && kc == 4);
            wgmma_fence();
#pragma unroll
            for (int k16 = 0; k16 < 4; k16++) {
                const uint64_t db = make_desc(sB + st * K1_BSTAGE + k16 * 2048, 8192, 1024);
                const uint64_t da = make_desc(sX + kc * 16384 + wg * 8192 + k16 * 32, 16, 1024);
                wgmma_n176<1>(accF, da, db, (kc | k16) != 0);
            }
            wgmma_commit();
#pragma unroll
            for (int c = 0; c < 4; c++) {
                const int cc = ghalf * 4 + c;
                const uint4 xv = *(const uint4*)(sgen + kc * 16384 + grow * 128 + ((cc ^ (grow & 7)) << 4));
                const uint4 gv = *(const uint4*)(sGw + kc * 128 + cc * 16);
                gs = fmaf(bf_lo(xv.x), bf_lo(gv.x), gs); gs = fmaf(bf_hi(xv.x), bf_hi(gv.x), gs);
                gs = fmaf(bf_lo(xv.y), bf_lo(gv.y), gs); gs = fmaf(bf_hi(xv.y), bf_hi(gv.y), gs);
                gs = fmaf(bf_lo(xv.z), bf_lo(gv.z), gs); gs = fmaf(bf_hi(xv.z), bf_hi(gv.z), gs);
                gs = fmaf(bf_lo(xv.w), bf_lo(gv.w), gs); gs = fmaf(bf_hi(xv.w), bf_hi(gv.w), gs);
            }
            if (kc > 0) { wgmma_wait<1>(); if (lane == 0) mbar_arrive(b_empty + 8 * ((kc - 1) & 3)); }
        }
        gs += __shfl_xor_sync(0xffffffffu, gs, 1);
        {
            const float g = 1.f / (1.f + __expf(-gs));
            if (ghalf == 0) {
                sGate[grow] = g;
                if (j == 0) g_gate[rb * 128 + grow] = g;
            }
        }
        wgmma_wait<0>();
        if (lane == 0) mbar_arrive(b_empty + 8 * 3);
        bar_sync(1 + wg, 128);
        TS(3, tid == 0);
        const int n0 = j * FCH;
        const int rl = wg * 64 + w4 * 16 + (lane >> 2);
        const float om0 = 1.f - sGate[rl], om1 = 1.f - sGate[rl + 8];
        bf16* frow0 = g_a2 + (size_t)(rb * 128 + rl) * KA2 + D_ + n0;
        bf16* frow1 = frow0 + 8 * KA2;
        auto ffn_chunk = [&](int u) {
            uint32_t w0[4], w1[4];
#pragma unroll
            for (int i = 0; i < 4; i++) {
                const int t = u * 4 + i;
                if (t < 22) {
                    const uint32_t bv = sBias[t * 4 + q];
                    const float bb0 = bf_lo(bv), bb1 = bf_hi(bv);
                    w0[i] = pack_bf16(mish_f(accF[t * 4 + 0] + bb0) * om0, mish_f(accF[t * 4 + 1] + bb1) * om0);
                    w1[i] = pack_bf16(mish_f(accF[t * 4 + 2] + bb0) * om1, mish_f(accF[t * 4 + 3] + bb1) * om1);
                } else { w0[i] = 0; w1[i] = 0; }
            }
            quad_transpose(w0, q);
            quad_transpose(w1, q);
            const int c = (u * 4 + q) * 8;
            if (c < FCH && n0 + c < F_) {
                *(uint4*)(frow0 + c) = make_uint4(w0[0], w0[1], w0[2], w0[3]);
                *(uint4*)(frow1 + c) = make_uint4(w1[0], w1[1], w1[2], w1[3]);
            }
        };
#pragma unroll
        for (int kc = 0; kc < 8; kc++) {
            const int st = kc & 3;
            mbar_wait(b_full + 8 * st, ((kc + 8) >> 2) & 1);
            wgmma_fence();
#pragma unroll
            for (int k16 = 0; k16 < 4; k16++) {
                const uint64_t db = make_desc(sB + st * K1_BSTAGE + k16 * 2048, 8192, 1024);
                const uint64_t da = make_desc(sX + kc * 16384 + wg * 8192 + k16 * 32, 16, 1024);
                wgmma_n192<1>(accQ, da, db, (kc | k16) != 0);
            }
            wgmma_commit();
            if (kc < 6) ffn_chunk(kc);
            if (kc > 0) { wgmma_wait<1>(); if (lane == 0) mbar_arrive(b_empty + 8 * ((kc - 1) & 3)); }
        }
        wgmma_wait<0>();
        TS(4, tid == 0);
        {
            bf16* orow0 = g_qkv + ((size_t)j * S_ + rb * 128 + rl) * 192;
            bf16* orow1 = orow0 + 8 * 192;
#pragma unroll
            for (int u = 0; u < 6; u++) {
                uint32_t w0[4], w1[4];
#pragma unroll
                for (int i = 0; i < 4; i++) {
                    const int t = u * 4 + i;
                    w0[i] = pack_bf16(accQ[t * 4 + 0], accQ[t * 4 + 1]);
                    w1[i] = pack_bf16(accQ[t * 4 + 2], accQ[t * 4 + 3]);
                }
                quad_transpose(w0, q);
                quad_transpose(w1, q);
                const int c = (u * 4 + q) * 8;
                *(uint4*)(orow0 + c) = make_uint4(w0[0], w0[1], w0[2], w0[3]);
                *(uint4*)(orow1 + c) = make_uint4(w1[0], w1[1], w1[2], w1[3]);
            }
        }
        TS(5, tid == 0);
    }
}

__device__ __forceinline__ void ldsm_x4(uint32_t (&r)[4], uint32_t addr) {
    asm("ldmatrix.sync.aligned.m8n8.x4.shared.b16 {%0,%1,%2,%3}, [%4];"
                 : "=r"(r[0]), "=r"(r[1]), "=r"(r[2]), "=r"(r[3]) : "r"(addr));
}
__device__ __forceinline__ void ldsm_x4_t(uint32_t (&r)[4], uint32_t addr) {
    asm("ldmatrix.sync.aligned.m8n8.x4.trans.shared.b16 {%0,%1,%2,%3}, [%4];"
                 : "=r"(r[0]), "=r"(r[1]), "=r"(r[2]), "=r"(r[3]) : "r"(addr));
}
__device__ __forceinline__ void mma16816(float (&d)[4], const uint32_t (&a)[4], uint32_t b0, uint32_t b1) {
    asm("mma.sync.aligned.m16n8k16.row.col.f32.bf16.bf16.f32 {%0,%1,%2,%3}, {%4,%5,%6,%7}, {%8,%9}, {%0,%1,%2,%3};"
                 : "+f"(d[0]), "+f"(d[1]), "+f"(d[2]), "+f"(d[3])
                 : "r"(a[0]), "r"(a[1]), "r"(a[2]), "r"(a[3]), "r"(b0), "r"(b1));
}
__device__ __forceinline__ void mma16816_z(float (&d)[4], const uint32_t (&a)[4], uint32_t b0, uint32_t b1) {
    asm("mma.sync.aligned.m16n8k16.row.col.f32.bf16.bf16.f32 {%0,%1,%2,%3}, {%4,%5,%6,%7}, {%8,%9}, {%10,%10,%10,%10};"
                 : "=f"(d[0]), "=f"(d[1]), "=f"(d[2]), "=f"(d[3])
                 : "r"(a[0]), "r"(a[1]), "r"(a[2]), "r"(a[3]), "r"(b0), "r"(b1), "f"(0.f));
}

constexpr int KV_PITCH = 128;

template <int EDGE, bool HEAD>
__device__ __forceinline__ void blk_scores(float (&s)[2][4], const uint32_t (&qa)[4], uint32_t kaddr, bool dead, int r0, int c0)
{
    uint32_t kf[4];
    ldsm_x4(kf, kaddr);
    mma16816_z(s[0], qa, kf[0], kf[1]);
    mma16816_z(s[1], qa, kf[2], kf[3]);
#pragma unroll
    for (int t = 0; t < 2; t++)
#pragma unroll
        for (int e = 0; e < 4; e++) {
            const int r = r0 + (e >> 1) * 8, c = t * 8 + c0 + (e & 1);
            if (EDGE == 1 && c <= r) s[t][e] = -1e30f;
            if (EDGE == 2 && c > r) s[t][e] = -1e30f;
            if (HEAD && dead) s[t][e] = -1e30f;
        }
}
__device__ __forceinline__ void blk_max(const float (&s)[2][4], float& n0, float& n1) {
    n0 = fmaxf(n0, fmaxf(fmaxf(s[0][0], s[0][1]), fmaxf(s[1][0], s[1][1])));
    n1 = fmaxf(n1, fmaxf(fmaxf(s[0][2], s[0][3]), fmaxf(s[1][2], s[1][3])));
}
__device__ __forceinline__ void blk_pv(const float (&s)[2][4], float mc0, float mc1, float (&l)[4],
                                       float (&o)[2][4], uint32_t vaddr) {
    const float C = 0.25f * 1.4426950408889634f;
    uint32_t pa[4];
#pragma unroll
    for (int t = 0; t < 2; t++) {
        const float p0 = ex2(fmaf(s[t][0], C, -mc0)), p1 = ex2(fmaf(s[t][1], C, -mc0));
        const float p2 = ex2(fmaf(s[t][2], C, -mc1)), p3 = ex2(fmaf(s[t][3], C, -mc1));
        pa[2 * t] = pack_bf16(p0, p1); pa[2 * t + 1] = pack_bf16(p2, p3);
    }
    uint32_t vf[4];
    ldsm_x4_t(vf, vaddr);
    mma16816(o[0], pa, vf[0], vf[1]);
    mma16816(o[1], pa, vf[2], vf[3]);
    mma16816(l, pa, 0x3F803F80u, 0x3F803F80u);
}
__device__ __forceinline__ void quad_max(float& n0, float& n1) {
    n0 = fmaxf(n0, __shfl_xor_sync(0xffffffffu, n0, 1)); n1 = fmaxf(n1, __shfl_xor_sync(0xffffffffu, n1, 1));
    n0 = fmaxf(n0, __shfl_xor_sync(0xffffffffu, n0, 2)); n1 = fmaxf(n1, __shfl_xor_sync(0xffffffffu, n1, 2));
}
template <int NC, int NN, bool FIRST, bool NEXT_IS_EDGE, bool HEAD>
__device__ __forceinline__ void pipe_step(const float (&sc)[5][2][4], float (&sn)[5][2][4], const uint32_t (&qa)[4],
                                          uint32_t ka, uint32_t va, int kc, int kn, int kb0, int r0, int c0,
                                          float& m0, float& m1, float& n0, float& n1, float (&l)[4], float (&o)[2][4])
{
    const float C = 0.25f * 1.4426950408889634f;
    const float mc0 = n0 * C, mc1 = n1 * C;
    if (!FIRST) {
        const float a0 = ex2(fmaf(m0, C, -mc0)), a1 = ex2(fmaf(m1, C, -mc1));
        l[0] *= a0; l[2] *= a1;
        o[0][0] *= a0; o[0][1] *= a0; o[1][0] *= a0; o[1][1] *= a0;
        o[0][2] *= a1; o[0][3] *= a1; o[1][2] *= a1; o[1][3] *= a1;
    }
    m0 = n0; m1 = n1;
#pragma unroll
    for (int b = 0; b < NC; b++) {
        if (b < NN) {
            if (NEXT_IS_EDGE && b == 0) blk_scores<1, HEAD>(sn[b], qa, ka + (kn + b) * 16 * KV_PITCH, kn + b < kb0, r0, c0);
            else                        blk_scores<0, HEAD>(sn[b], qa, ka + (kn + b) * 16 * KV_PITCH, kn + b < kb0, r0, c0);
        }
        blk_pv(sc[b], mc0, mc1, l, o, va + (kc + b) * 16 * KV_PITCH);
        if (b < NN) blk_max(sn[b], n0, n1);
    }
    if (NN > 0) quad_max(n0, n1);
}

template <bool HEAD>
__device__ __forceinline__ void attn_task(const uint32_t (&qa)[4], uint32_t ka, uint32_t va, int kb0, int lane,
                                          bf16* __restrict__ out  , float g0, float g1)
{
    const int r0 = lane >> 2, c0 = (lane & 3) * 2;
    float m0 = -1e30f, m1 = -1e30f, n0 = -1e30f, n1 = -1e30f;
    float l[4] = {0.f, 0.f, 0.f, 0.f};
    float o[2][4] = {{0.f, 0.f, 0.f, 0.f}, {0.f, 0.f, 0.f, 0.f}};
    float sa[5][2][4], sb[5][2][4];
#pragma unroll
    for (int b = 0; b < 5; b++) {
        if (b == 4) blk_scores<2, HEAD>(sa[b], qa, ka + (12 + b) * 16 * KV_PITCH, false, r0, c0);
        else        blk_scores<0, HEAD>(sa[b], qa, ka + (12 + b) * 16 * KV_PITCH, 12 + b < kb0, r0, c0);
        blk_max(sa[b], n0, n1);
    }
    quad_max(n0, n1);
    pipe_step<5, 4, true,  false, HEAD>(sa, sb, qa, ka, va, 12, 8, kb0, r0, c0, m0, m1, n0, n1, l, o);
    pipe_step<4, 4, false, false, HEAD>(sb, sa, qa, ka, va, 8, 4, kb0, r0, c0, m0, m1, n0, n1, l, o);
    pipe_step<4, 4, false, true,  HEAD>(sa, sb, qa, ka, va, 4, 0, kb0, r0, c0, m0, m1, n0, n1, l, o);
    pipe_step<4, 0, false, false, HEAD>(sb, sa, qa, ka, va, 0, 0, kb0, r0, c0, m0, m1, n0, n1, l, o);
    const float f0 = __fdividef(g0, l[0]), f1 = __fdividef(g1, l[2]);
#pragma unroll
    for (int t = 0; t < 2; t++) {
        *(uint32_t*)(out + (size_t)r0 * KA2 + t * 8 + c0) = pack_bf16(o[t][0] * f0, o[t][1] * f0);
        *(uint32_t*)(out + (size_t)(r0 + 8) * KA2 + t * 8 + c0) = pack_bf16(o[t][2] * f1, o[t][3] * f1);
    }
}

constexpr int K2_SMEM = 2 * 384 * KV_PITCH + 1024 + 64;

__global__ void __launch_bounds__(512, 1) k2_kernel(const __grid_constant__ CUtensorMap tmQKV)
{
    extern __shared__ uint8_t smem_raw[];
    const uint32_t sbase = (smem_u32(smem_raw) + 1023u) & ~1023u;
    uint8_t* sgen = smem_raw + (sbase - smem_u32(smem_raw));
    const uint32_t sK = sbase, sV = sK + 384 * KV_PITCH, kv_full = sbase + 2 * 384 * KV_PITCH;
    const int rb = blockIdx.x >> 3, j = blockIdx.x & 7;
    const int tid = threadIdx.x, warp = tid >> 5, lane = tid & 31;
    pdl_launch();
    if (tid == 0) {
        mbar_init(kv_full, 1);
        fence_barrier_init();
    }
    pdl_wait();
    TS(6, tid == 0);
    if (tid == 0) {
        const int nblk = rb >= 2 ? 3 : rb + 1;
        mbar_expect_tx(kv_full, nblk * 2 * 16384);
        for (int i = 0; i < nblk; i++) {
            const int row = j * S_ + (rb - i) * 128;
            tma_load_2d(sK + (2 - i) * 16384, &tmQKV, 64, row, kv_full);
            tma_load_2d(sV + (2 - i) * 16384, &tmQKV, 128, row, kv_full);
        }
    }
    if (rb < 2) {
        for (int i = tid; i < (2 - rb) * 1024; i += 512) {
            *(uint4*)(sgen + i * 16) = make_uint4(0, 0, 0, 0);
            *(uint4*)(sgen + 384 * KV_PITCH + i * 16) = make_uint4(0, 0, 0, 0);
        }
    }
    const int qt = warp & 7, h0 = (warp >> 3) * 2;
    const int q0g = rb * 128 + qt * 16;
    const int r0 = lane >> 2, c0 = (lane & 3) * 2;
    const bf16* qsrc = g_qkv + ((size_t)j * S_ + q0g) * 192 + h0 * 16;
    uint32_t qa[4], qn[4];
    qa[0] = *(const uint32_t*)(qsrc + (size_t)r0 * 192 + c0);
    qa[1] = *(const uint32_t*)(qsrc + (size_t)(r0 + 8) * 192 + c0);
    qa[2] = *(const uint32_t*)(qsrc + (size_t)r0 * 192 + c0 + 8);
    qa[3] = *(const uint32_t*)(qsrc + (size_t)(r0 + 8) * 192 + c0 + 8);
    qn[0] = *(const uint32_t*)(qsrc + (size_t)r0 * 192 + 16 + c0);
    qn[1] = *(const uint32_t*)(qsrc + (size_t)(r0 + 8) * 192 + 16 + c0);
    qn[2] = *(const uint32_t*)(qsrc + (size_t)r0 * 192 + 16 + c0 + 8);
    qn[3] = *(const uint32_t*)(qsrc + (size_t)(r0 + 8) * 192 + 16 + c0 + 8);
    const float g0 = g_gate[q0g + r0], g1 = g_gate[q0g + r0 + 8];
    const int kb0 = q0g < 256 ? (256 - q0g) >> 4 : 0;
    __syncthreads();
    mbar_wait(kv_full, 0);
    uint32_t sKd = sK, sVd = sV;
    asm volatile("" : "+r"(sKd), "+r"(sVd) :: "memory");
    TS(7, tid == 0);
    const int krow = qt * 16 + (lane & 7) + ((lane >> 4) << 3);
    const int vrow = qt * 16 + (lane & 15);
#pragma unroll 1
    for (int hh = 0; hh < 2; hh++) {
        const int hl = h0 + hh;
        const uint32_t ka = sKd + krow * KV_PITCH + (((2 * hl + ((lane >> 3) & 1)) ^ (lane & 7)) << 4);
        const uint32_t va = sVd + vrow * KV_PITCH + (((2 * hl + (lane >> 4)) ^ (lane & 7)) << 4);
        if (rb < 2) attn_task<true>(qa, ka, va, kb0, lane, g_a2 + (size_t)q0g * KA2 + (j * 4 + hl) * 16, g0, g1);
        else        attn_task<false>(qa, ka, va, kb0, lane, g_a2 + (size_t)q0g * KA2 + (j * 4 + hl) * 16, g0, g1);
        TS(8 + hh, tid == 0);
        qa[0] = qn[0]; qa[1] = qn[1]; qa[2] = qn[2]; qa[3] = qn[3];
    }
}

constexpr int K3_STAGES = 8;
constexpr int K3_STAGE = 16384 + 8192;
constexpr int K3_SMEM = K3_STAGES * K3_STAGE + 1024 + 1024;
constexpr int K3_KSTEPS = 30;

__global__ void __launch_bounds__(384, 1)
k3_kernel(const __grid_constant__ CUtensorMap tmA2, const __grid_constant__ CUtensorMap tmWo,
          const __grid_constant__ CUtensorMap tmW2, bf16* __restrict__ out)
{
    extern __shared__ uint8_t smem_raw[];
    const uint32_t sbase = (smem_u32(smem_raw) + 1023u) & ~1023u;
    const uint32_t sBar = sbase + K3_STAGES * K3_STAGE;
    const uint32_t full = sBar, empty = sBar + 64;
    const int rb = blockIdx.x >> 3, nb = blockIdx.x & 7;
    const int tid = threadIdx.x, wg = tid >> 7, warp = tid >> 5, lane = tid & 31;
    if (tid == 0) {
        for (int i = 0; i < K3_STAGES; i++) { mbar_init(full + 8 * i, 1); mbar_init(empty + 8 * i, 8); }
        fence_barrier_init();
    }
    __syncthreads();
    pdl_wait();
    TS(10, tid == 0);
    if (wg == 2) {
        reg_dealloc<40>();
        if (tid == 256) {
            for (int ks = 0; ks < K3_KSTEPS; ks++) {
                const int st = ks % K3_STAGES;
                if (ks >= K3_STAGES) mbar_wait(empty + 8 * st, ((ks / K3_STAGES) - 1) & 1);
                mbar_expect_tx(full + 8 * st, K3_STAGE);
                const uint32_t dst = sbase + st * K3_STAGE;
                tma_load_2d(dst, &tmA2, ks * 64, rb * 128, full + 8 * st);
                if (ks < 8) tma_load_2d(dst + 16384, &tmWo, nb * 64, ks * 64, full + 8 * st);
                else        tma_load_2d(dst + 16384, &tmW2, nb * 64, (ks - 8) * 64, full + 8 * st);
            }
        }
    } else {
        reg_alloc<232>();
        float acc[32];
        for (int ks = 0; ks < K3_KSTEPS; ks++) {
            const int st = ks % K3_STAGES;
            mbar_wait(full + 8 * st, (ks / K3_STAGES) & 1);
            TS(11, tid == 0 && ks == 0); TS(12, tid == 0 && ks == 8); TS(13, tid == 0 && ks == 16);
            wgmma_fence();
#pragma unroll
            for (int k16 = 0; k16 < 4; k16++) {
                const uint64_t da = make_desc(sbase + st * K3_STAGE + wg * 8192 + k16 * 32, 16, 1024);
                const uint64_t db = make_desc(sbase + st * K3_STAGE + 16384 + k16 * 2048, 8192, 1024);
                wgmma_n64<1>(acc, da, db, (ks | k16) != 0);
            }
            wgmma_commit();
            if (ks > 0) { wgmma_wait<1>(); if (lane == 0) mbar_arrive(empty + 8 * ((ks - 1) % K3_STAGES)); }
        }
        wgmma_wait<0>();
        TS(14, tid == 0);
        const int q = lane & 3;
        const int r = rb * 128 + wg * 64 + (warp & 3) * 16 + (lane >> 2);
        bf16* orow0 = out + (size_t)r * D_ + nb * 64;
        bf16* orow1 = orow0 + 8 * D_;
#pragma unroll
        for (int u = 0; u < 2; u++) {
            uint32_t w0[4], w1[4];
#pragma unroll
            for (int i = 0; i < 4; i++) {
                const int t = u * 4 + i;
                w0[i] = pack_bf16(acc[t * 4 + 0], acc[t * 4 + 1]);
                w1[i] = pack_bf16(acc[t * 4 + 2], acc[t * 4 + 3]);
            }
            quad_transpose(w0, q);
            quad_transpose(w1, q);
            const int c = (u * 4 + q) * 8;
            *(uint4*)(orow0 + c) = make_uint4(w0[0], w0[1], w0[2], w0[3]);
            *(uint4*)(orow1 + c) = make_uint4(w1[0], w1[1], w1[2], w1[3]);
        }
        TS(15, tid == 0);
    }
}

typedef CUresult (*PFN_encodeTiled)(CUtensorMap*, CUtensorMapDataType, cuuint32_t, void*, const cuuint64_t*,
                                    const cuuint64_t*, const cuuint32_t*, const cuuint32_t*, CUtensorMapInterleave,
                                    CUtensorMapSwizzle, CUtensorMapL2promotion, CUtensorMapFloatOOBfill);

static void make_map(PFN_encodeTiled enc, CUtensorMap* m, const void* ptr, uint64_t cols, uint64_t rows,
                     uint32_t box_cols, uint32_t box_rows)
{
    cuuint64_t dims[2] = {cols, rows};
    cuuint64_t strides[1] = {cols * 2};
    cuuint32_t box[2] = {box_cols, box_rows};
    cuuint32_t es[2] = {1, 1};
    enc(m, CU_TENSOR_MAP_DATA_TYPE_BFLOAT16, 2, const_cast<void*>(ptr), dims, strides, box, es,
        CU_TENSOR_MAP_INTERLEAVE_NONE, CU_TENSOR_MAP_SWIZZLE_128B, CU_TENSOR_MAP_L2_PROMOTION_L2_128B,
        CU_TENSOR_MAP_FLOAT_OOB_FILL_NONE);
}

extern "C" void kernel_launch(void* const* d_in, const int* in_sizes, int n_in, void* d_out, int out_size)
{
    const bf16* x    = (const bf16*)d_in[0];
    const bf16* wqkv = (const bf16*)d_in[1];
    const bf16* wo   = (const bf16*)d_in[2];
    const bf16* w1   = (const bf16*)d_in[4];
    const bf16* b1   = (const bf16*)d_in[5];
    const bf16* w2   = (const bf16*)d_in[6];
    const bf16* gw   = (const bf16*)d_in[7];

    static PFN_encodeTiled enc = nullptr;
    if (!enc) {
        void* fn = nullptr;
        cudaDriverEntryPointQueryResult qr;
        cudaGetDriverEntryPoint("cuTensorMapEncodeTiled", &fn, cudaEnableDefault, &qr);
        enc = (PFN_encodeTiled)fn;
        cudaFuncSetAttribute(k1_kernel, cudaFuncAttributeMaxDynamicSharedMemorySize, K1_SMEM);
        cudaFuncSetAttribute(k2_kernel, cudaFuncAttributeMaxDynamicSharedMemorySize, K2_SMEM);
        cudaFuncSetAttribute(k3_kernel, cudaFuncAttributeMaxDynamicSharedMemorySize, K3_SMEM);
    }
    void* a2p = nullptr;
    cudaGetSymbolAddress(&a2p, g_a2);
    void* qkvp = nullptr;
    cudaGetSymbolAddress(&qkvp, g_qkv);
    CUtensorMap tmX, tmWqkv, tmW1, tmA2, tmWo, tmW2, tmQKV;
    make_map(enc, &tmQKV, qkvp, 192, 8 * S_, 64, 128);
    make_map(enc, &tmX, x, D_, S_, 64, 128);
    make_map(enc, &tmWqkv, wqkv, 3 * D_, D_, 64, 64);
    make_map(enc, &tmW1, w1, F_, D_, 64, 64);
    make_map(enc, &tmA2, a2p, KA2, S_, 64, 128);
    make_map(enc, &tmWo, wo, D_, D_, 64, 64);
    make_map(enc, &tmW2, w2, D_, F_, 64, 64);

    cudaStream_t st = cudaStreamPerThread;
    k1_kernel<<<128, 384, K1_SMEM, st>>>(tmX, tmWqkv, tmW1, b1, gw, w1, wqkv, w2, wo);
    cudaLaunchAttribute at[1];
    at[0].id = cudaLaunchAttributeProgrammaticStreamSerialization;
    at[0].val.programmaticStreamSerializationAllowed = 1;
    cudaLaunchConfig_t cfg = {};
    cfg.gridDim = dim3(128); cfg.stream = st; cfg.attrs = at; cfg.numAttrs = 1;
    cfg.blockDim = dim3(512); cfg.dynamicSmemBytes = K2_SMEM;
    cudaLaunchKernelEx(&cfg, k2_kernel, tmQKV);
    k3_kernel<<<128, 384, K3_SMEM, st>>>(tmA2, tmWo, tmW2, (bf16*)d_out);
}
```

```cpp
#include <cuda_runtime.h>
#include <cuda_bf16.h>
#include <cuda.h>
#include <stdint.h>

typedef __nv_bfloat16 bf16;

constexpr int S_ = 2048, D_ = 512, F_ = 1376;
constexpr int KA2 = D_ + F_;
constexpr int FCH = 176;

__device__ bf16  g_qkv[8 * S_ * 192];
__device__ bf16  g_a2[S_ * KA2];
__device__ float g_gate[S_];

#define TS(k, cond) do { } while (0)

__device__ __forceinline__ uint32_t smem_u32(const void* p) { return (uint32_t)__cvta_generic_to_shared(p); }
__device__ __forceinline__ void mbar_init(uint32_t bar, uint32_t count) {
    asm volatile("mbarrier.init.shared::cta.b64 [%0], %1;" :: "r"(bar), "r"(count) : "memory");
}
__device__ __forceinline__ void mbar_expect_tx(uint32_t bar, uint32_t bytes) {
    asm volatile("mbarrier.arrive.expect_tx.shared::cta.b64 _, [%0], %1;" :: "r"(bar), "r"(bytes) : "memory");
}
__device__ __forceinline__ void mbar_arrive(uint32_t bar) {
    asm volatile("mbarrier.arrive.shared::cta.b64 _, [%0];" :: "r"(bar) : "memory");
}
__device__ __forceinline__ bool mbar_try_wait(uint32_t bar, uint32_t parity) {
    uint32_t ok;
    asm volatile("{\n.reg .pred p;\nmbarrier.try_wait.parity.shared::cta.b64 p, [%1], %2;\nselp.u32 %0, 1, 0, p;\n}"
                 : "=r"(ok) : "r"(bar), "r"(parity) : "memory");
    return ok != 0;
}
__device__ __forceinline__ void mbar_wait(uint32_t bar, uint32_t parity) {
    for (uint32_t it = 0; it < (1u << 22); ++it) { if (mbar_try_wait(bar, parity)) break; }
}
__device__ __forceinline__ void tma_load_2d(uint32_t dst, const CUtensorMap* map, int c0, int c1, uint32_t bar) {
    asm volatile("cp.async.bulk.tensor.2d.shared::cluster.global.mbarrier::complete_tx::bytes [%0], [%1, {%3, %4}], [%2];"
                 :: "r"(dst), "l"(map), "r"(bar), "r"(c0), "r"(c1) : "memory");
}
__device__ __forceinline__ void l2_prefetch(const void* p, uint32_t bytes) {
    asm volatile("cp.async.bulk.prefetch.L2.global [%0], %1;" :: "l"(p), "r"(bytes) : "memory");
}
__device__ __forceinline__ void fence_barrier_init() { asm volatile("fence.mbarrier_init.release.cluster;" ::: "memory"); }
__device__ __forceinline__ void wgmma_fence()  { asm volatile("wgmma.fence.sync.aligned;" ::: "memory"); }
__device__ __forceinline__ void wgmma_commit() { asm volatile("wgmma.commit_group.sync.aligned;" ::: "memory"); }
template <int N> __device__ __forceinline__ void wgmma_wait() { asm volatile("wgmma.wait_group.sync.aligned %0;" :: "n"(N) : "memory"); }
template <int R> __device__ __forceinline__ void reg_alloc()   { asm volatile("setmaxnreg.inc.sync.aligned.u32 %0;" :: "n"(R)); }
template <int R> __device__ __forceinline__ void reg_dealloc() { asm volatile("setmaxnreg.dec.sync.aligned.u32 %0;" :: "n"(R)); }
__device__ __forceinline__ void bar_sync(int id, int n)   { asm volatile("bar.sync %0, %1;" :: "r"(id), "r"(n) : "memory"); }
__device__ __forceinline__ void bar_arrive(int id, int n) { asm volatile("bar.arrive %0, %1;" :: "r"(id), "r"(n) : "memory"); }

__device__ __forceinline__ uint64_t make_desc(uint32_t addr, uint32_t lbo, uint32_t sbo) {
    uint64_t d = (uint64_t)((addr & 0x3FFFF) >> 4);
    d |= (uint64_t)((lbo & 0x3FFFF) >> 4) << 16;
    d |= (uint64_t)((sbo & 0x3FFFF) >> 4) << 32;
    d |= (uint64_t)1 << 62;
    return d;
}

template <int TB>
__device__ __forceinline__ void wgmma_n64(float (&d)[32], uint64_t da, uint64_t db, int scale_d) {
    asm volatile("{\n.reg .pred p;\nsetp.ne.b32 p, %34, 0;\n"
        "wgmma.mma_async.sync.aligned.m64n64k16.f32.bf16.bf16 {%0, %1, %2, %3, %4, %5, %6, %7, %8, %9, %10, %11, %12, %13, %14, %15, %16, %17, %18, %19, %20, %21, %22, %23, %24, %25, %26, %27, %28, %29, %30, %31}, %32, %33, p, 1, 1, 0, %35;\n}\n"
        : "+f"(d[0]), "+f"(d[1]), "+f"(d[2]), "+f"(d[3]), "+f"(d[4]), "+f"(d[5]), "+f"(d[6]), "+f"(d[7]), "+f"(d[8]), "+f"(d[9]), "+f"(d[10]), "+f"(d[11]), "+f"(d[12]), "+f"(d[13]), "+f"(d[14]), "+f"(d[15]), "+f"(d[16]), "+f"(d[17]), "+f"(d[18]), "+f"(d[19]), "+f"(d[20]), "+f"(d[21]), "+f"(d[22]), "+f"(d[23]), "+f"(d[24]), "+f"(d[25]), "+f"(d[26]), "+f"(d[27]), "+f"(d[28]), "+f"(d[29]), "+f"(d[30]), "+f"(d[31])
        : "l"(da), "l"(db), "r"(scale_d), "n"(TB));
}

template <int TB>
__device__ __forceinline__ void wgmma_n128(float (&d)[64], uint64_t da, uint64_t db, int scale_d) {
    asm volatile("{\n.reg .pred p;\nsetp.ne.b32 p, %66, 0;\n"
        "wgmma.mma_async.sync.aligned.m64n128k16.f32.bf16.bf16 {%0, %1, %2, %3, %4, %5, %6, %7, %8, %9, %10, %11, %12, %13, %14, %15, %16, %17, %18, %19, %20, %21, %22, %23, %24, %25, %26, %27, %28, %29, %30, %31, %32, %33, %34, %35, %36, %37, %38, %39, %40, %41, %42, %43, %44, %45, %46, %47, %48, %49, %50, %51, %52, %53, %54, %55, %56, %57, %58, %59, %60, %61, %62, %63}, %64, %65, p, 1, 1, 0, %67;\n}\n"
        : "+f"(d[0]), "+f"(d[1]), "+f"(d[2]), "+f"(d[3]), "+f"(d[4]), "+f"(d[5]), "+f"(d[6]), "+f"(d[7]), "+f"(d[8]), "+f"(d[9]), "+f"(d[10]), "+f"(d[11]), "+f"(d[12]), "+f"(d[13]), "+f"(d[14]), "+f"(d[15]), "+f"(d[16]), "+f"(d[17]), "+f"(d[18]), "+f"(d[19]), "+f"(d[20]), "+f"(d[21]), "+f"(d[22]), "+f"(d[23]), "+f"(d[24]), "+f"(d[25]), "+f"(d[26]), "+f"(d[27]), "+f"(d[28]), "+f"(d[29]), "+f"(d[30]), "+f"(d[31]), "+f"(d[32]), "+f"(d[33]), "+f"(d[34]), "+f"(d[35]), "+f"(d[36]), "+f"(d[37]), "+f"(d[38]), "+f"(d[39]), "+f"(d[40]), "+f"(d[41]), "+f"(d[42]), "+f"(d[43]), "+f"(d[44]), "+f"(d[45]), "+f"(d[46]), "+f"(d[47]), "+f"(d[48]), "+f"(d[49]), "+f"(d[50]), "+f"(d[51]), "+f"(d[52]), "+f"(d[53]), "+f"(d[54]), "+f"(d[55]), "+f"(d[56]), "+f"(d[57]), "+f"(d[58]), "+f"(d[59]), "+f"(d[60]), "+f"(d[61]), "+f"(d[62]), "+f"(d[63])
        : "l"(da), "l"(db), "r"(scale_d), "n"(TB));
}

template <int TB>
__device__ __forceinline__ void wgmma_n176(float (&d)[88], uint64_t da, uint64_t db, int scale_d) {
    asm volatile("{\n.reg .pred p;\nsetp.ne.b32 p, %90, 0;\n"
        "wgmma.mma_async.sync.aligned.m64n176k16.f32.bf16.bf16 {%0, %1, %2, %3, %4, %5, %6, %7, %8, %9, %10, %11, %12, %13, %14, %15, %16, %17, %18, %19, %20, %21, %22, %23, %24, %25, %26, %27, %28, %29, %30, %31, %32, %33, %34, %35, %36, %37, %38, %39, %40, %41, %42, %43, %44, %45, %46, %47, %48, %49, %50, %51, %52, %53, %54, %55, %56, %57, %58, %59, %60, %61, %62, %63, %64, %65, %66, %67, %68, %69, %70, %71, %72, %73, %74, %75, %76, %77, %78, %79, %80, %81, %82, %83, %84, %85, %86, %87}, %88, %89, p, 1, 1, 0, %91;\n}\n"
        : "+f"(d[0]), "+f"(d[1]), "+f"(d[2]), "+f"(d[3]), "+f"(d[4]), "+f"(d[5]), "+f"(d[6]), "+f"(d[7]), "+f"(d[8]), "+f"(d[9]), "+f"(d[10]), "+f"(d[11]), "+f"(d[12]), "+f"(d[13]), "+f"(d[14]), "+f"(d[15]), "+f"(d[16]), "+f"(d[17]), "+f"(d[18]), "+f"(d[19]), "+f"(d[20]), "+f"(d[21]), "+f"(d[22]), "+f"(d[23]), "+f"(d[24]), "+f"(d[25]), "+f"(d[26]), "+f"(d[27]), "+f"(d[28]), "+f"(d[29]), "+f"(d[30]), "+f"(d[31]), "+f"(d[32]), "+f"(d[33]), "+f"(d[34]), "+f"(d[35]), "+f"(d[36]), "+f"(d[37]), "+f"(d[38]), "+f"(d[39]), "+f"(d[40]), "+f"(d[41]), "+f"(d[42]), "+f"(d[43]), "+f"(d[44]), "+f"(d[45]), "+f"(d[46]), "+f"(d[47]), "+f"(d[48]), "+f"(d[49]), "+f"(d[50]), "+f"(d[51]), "+f"(d[52]), "+f"(d[53]), "+f"(d[54]), "+f"(d[55]), "+f"(d[56]), "+f"(d[57]), "+f"(d[58]), "+f"(d[59]), "+f"(d[60]), "+f"(d[61]), "+f"(d[62]), "+f"(d[63]), "+f"(d[64]), "+f"(d[65]), "+f"(d[66]), "+f"(d[67]), "+f"(d[68]), "+f"(d[69]), "+f"(d[70]), "+f"(d[71]), "+f"(d[72]), "+f"(d[73]), "+f"(d[74]), "+f"(d[75]), "+f"(d[76]), "+f"(d[77]), "+f"(d[78]), "+f"(d[79]), "+f"(d[80]), "+f"(d[81]), "+f"(d[82]), "+f"(d[83]), "+f"(d[84]), "+f"(d[85]), "+f"(d[86]), "+f"(d[87])
        : "l"(da), "l"(db), "r"(scale_d), "n"(TB));
}

template <int TB>
__device__ __forceinline__ void wgmma_n192(float (&d)[96], uint64_t da, uint64_t db, int scale_d) {
    asm volatile("{\n.reg .pred p;\nsetp.ne.b32 p, %98, 0;\n"
        "wgmma.mma_async.sync.aligned.m64n192k16.f32.bf16.bf16 {%0, %1, %2, %3, %4, %5, %6, %7, %8, %9, %10, %11, %12, %13, %14, %15, %16, %17, %18, %19, %20, %21, %22, %23, %24, %25, %26, %27, %28, %29, %30, %31, %32, %33, %34, %35, %36, %37, %38, %39, %40, %41, %42, %43, %44, %45, %46, %47, %48, %49, %50, %51, %52, %53, %54, %55, %56, %57, %58, %59, %60, %61, %62, %63, %64, %65, %66, %67, %68, %69, %70, %71, %72, %73, %74, %75, %76, %77, %78, %79, %80, %81, %82, %83, %84, %85, %86, %87, %88, %89, %90, %91, %92, %93, %94, %95}, %96, %97, p, 1, 1, 0, %99;\n}\n"
        : "+f"(d[0]), "+f"(d[1]), "+f"(d[2]), "+f"(d[3]), "+f"(d[4]), "+f"(d[5]), "+f"(d[6]), "+f"(d[7]), "+f"(d[8]), "+f"(d[9]), "+f"(d[10]), "+f"(d[11]), "+f"(d[12]), "+f"(d[13]), "+f"(d[14]), "+f"(d[15]), "+f"(d[16]), "+f"(d[17]), "+f"(d[18]), "+f"(d[19]), "+f"(d[20]), "+f"(d[21]), "+f"(d[22]), "+f"(d[23]), "+f"(d[24]), "+f"(d[25]), "+f"(d[26]), "+f"(d[27]), "+f"(d[28]), "+f"(d[29]), "+f"(d[30]), "+f"(d[31]), "+f"(d[32]), "+f"(d[33]), "+f"(d[34]), "+f"(d[35]), "+f"(d[36]), "+f"(d[37]), "+f"(d[38]), "+f"(d[39]), "+f"(d[40]), "+f"(d[41]), "+f"(d[42]), "+f"(d[43]), "+f"(d[44]), "+f"(d[45]), "+f"(d[46]), "+f"(d[47]), "+f"(d[48]), "+f"(d[49]), "+f"(d[50]), "+f"(d[51]), "+f"(d[52]), "+f"(d[53]), "+f"(d[54]), "+f"(d[55]), "+f"(d[56]), "+f"(d[57]), "+f"(d[58]), "+f"(d[59]), "+f"(d[60]), "+f"(d[61]), "+f"(d[62]), "+f"(d[63]), "+f"(d[64]), "+f"(d[65]), "+f"(d[66]), "+f"(d[67]), "+f"(d[68]), "+f"(d[69]), "+f"(d[70]), "+f"(d[71]), "+f"(d[72]), "+f"(d[73]), "+f"(d[74]), "+f"(d[75]), "+f"(d[76]), "+f"(d[77]), "+f"(d[78]), "+f"(d[79]), "+f"(d[80]), "+f"(d[81]), "+f"(d[82]), "+f"(d[83]), "+f"(d[84]), "+f"(d[85]), "+f"(d[86]), "+f"(d[87]), "+f"(d[88]), "+f"(d[89]), "+f"(d[90]), "+f"(d[91]), "+f"(d[92]), "+f"(d[93]), "+f"(d[94]), "+f"(d[95])
        : "l"(da), "l"(db), "r"(scale_d), "n"(TB));
}

__device__ __forceinline__ uint32_t pack_bf16(float lo, float hi) {
    uint32_t r;
    asm("cvt.rn.bf16x2.f32 %0, %1, %2;" : "=r"(r) : "f"(hi), "f"(lo));
    return r;
}
__device__ __forceinline__ float bf_lo(uint32_t v) { return __uint_as_float(v << 16); }
__device__ __forceinline__ float bf_hi(uint32_t v) { return __uint_as_float(v & 0xffff0000u); }

__device__ __forceinline__ void quad_transpose(uint32_t (&w)[4], int q) {
    const bool o1 = q & 1, o2 = q & 2;
    {
        uint32_t s0 = o1 ? w[0] : w[1], s1 = o1 ? w[2] : w[3];
        s0 = __shfl_xor_sync(0xffffffffu, s0, 1); s1 = __shfl_xor_sync(0xffffffffu, s1, 1);
        if (o1) { w[0] = s0; w[2] = s1; } else { w[1] = s0; w[3] = s1; }
    }
    {
        uint32_t s0 = o2 ? w[0] : w[2], s1 = o2 ? w[1] : w[3];
        s0 = __shfl_xor_sync(0xffffffffu, s0, 2); s1 = __shfl_xor_sync(0xffffffffu, s1, 2);
        if (o2) { w[0] = s0; w[1] = s1; } else { w[2] = s0; w[3] = s1; }
    }
}

__device__ __forceinline__ float ex2(float x) { float y; asm("ex2.approx.ftz.f32 %0, %1;" : "=f"(y) : "f"(x)); return y; }
__device__ __forceinline__ float rcp(float x) { float y; asm("rcp.approx.ftz.f32 %0, %1;" : "=f"(y) : "f"(x)); return y; }

__device__ __forceinline__ float ex2v(float x) { float y; asm volatile("ex2.approx.ftz.f32 %0, %1;" : "=f"(y) : "f"(x)); return y; }
__device__ __forceinline__ float rcpv(float x) { float y; asm volatile("rcp.approx.ftz.f32 %0, %1;" : "=f"(y) : "f"(x)); return y; }
__device__ __forceinline__ float mish_f(float h) {
    const float e = ex2v(1.4426950408889634f * fminf(h, 20.f));
    const float n = fmaf(e, e, e + e);
    return h * n * rcpv(n + 2.f);
}

__device__ __forceinline__ void pdl_wait()   { asm volatile("griddepcontrol.wait;" ::: "memory"); }
__device__ __forceinline__ void pdl_launch() { asm volatile("griddepcontrol.launch_dependents;" ::: "memory"); }

constexpr int K1_STAGES = 4;
constexpr int K1_XBYTES = 128 * 512 * 2;
constexpr int K1_BSTAGE = 3 * 8192;
constexpr int K1_SMEM   = K1_XBYTES + K1_STAGES * K1_BSTAGE + 2048   + 1024  ;

__global__ void __launch_bounds__(384, 1)
k1_kernel(const __grid_constant__ CUtensorMap tmX, const __grid_constant__ CUtensorMap tmWqkv,
          const __grid_constant__ CUtensorMap tmW1, const bf16* __restrict__ b1,
          const bf16* __restrict__ gate_w, const bf16* __restrict__ w1p, const bf16* __restrict__ wqkvp,
          const bf16* __restrict__ w2p, const bf16* __restrict__ wop)
{

    extern __shared__ uint8_t smem_raw[];
    const uint32_t sbase = (smem_u32(smem_raw) + 1023u) & ~1023u;
    uint8_t* sgen = smem_raw + (sbase - smem_u32(smem_raw));
    const uint32_t sX = sbase;
    const uint32_t sB = sbase + K1_XBYTES;
    const uint32_t sBar = sB + K1_STAGES * K1_BSTAGE;
    const uint32_t x_full = sBar;
    const uint32_t b_full = sBar + 64;
    const uint32_t b_empty = sBar + 96;
    float* sGate = (float*)(sgen + K1_XBYTES + K1_STAGES * K1_BSTAGE + 128);
    uint8_t* sGw = sgen + K1_XBYTES + K1_STAGES * K1_BSTAGE + 640;
    uint32_t* sBias = (uint32_t*)(sgen + K1_XBYTES + K1_STAGES * K1_BSTAGE + 1664);

    const int rb = blockIdx.x >> 3, j = blockIdx.x & 7;
    const int tid = threadIdx.x, wg = tid >> 7, warp = tid >> 5, lane = tid & 31;
    TS(0, tid == 0);
    pdl_launch();

    if (tid == 0) {
        for (int i = 0; i < 8; i++) mbar_init(x_full + 8 * i, 1);
        for (int i = 0; i < K1_STAGES; i++) { mbar_init(b_full + 8 * i, 1); mbar_init(b_empty + 8 * i, 8); }
        fence_barrier_init();
    }
    __syncthreads();

    if (wg == 2) {
        reg_dealloc<40>();
        if (tid == 288) {
            const int b = blockIdx.x;
            mbar_wait(b_full + 8, 0);
            l2_prefetch((const uint8_t*)wqkvp + b * 12288, 12288);
            l2_prefetch((const uint8_t*)w2p + b * 11008, 11008);
            l2_prefetch((const uint8_t*)wop + b * 4096, 4096);
        }
        if (tid == 256) {
            for (int it = 0; it < 16; it++) {
                if (it < 8) {
                    mbar_expect_tx(x_full + 8 * it, 16384);
                    tma_load_2d(sX + it * 16384, &tmX, it * 64, rb * 128, x_full + 8 * it);
                }
                const int st = it & 3;
                if (it >= K1_STAGES) mbar_wait(b_empty + 8 * st, ((it >> 2) - 1) & 1);
                mbar_expect_tx(b_full + 8 * st, K1_BSTAGE);
                const uint32_t dst = sB + st * K1_BSTAGE;
                if (it < 8) {
                    for (int b = 0; b < 3; b++) tma_load_2d(dst + b * 8192, &tmW1, j * FCH + b * 64, it * 64, b_full + 8 * st);
                } else {
                    for (int b = 0; b < 3; b++) tma_load_2d(dst + b * 8192, &tmWqkv, b * 512 + j * 64, (it - 8) * 64, b_full + 8 * st);
                }
            }
        }
    } else {
        reg_alloc<232>();
        if (tid < 64) ((uint4*)sGw)[tid] = __ldg((const uint4*)gate_w + tid);
        else if (tid < 64 + 88) {
            const int c = j * FCH + (tid - 64) * 2;
            sBias[tid - 64] = c < F_ ? __ldg((const uint32_t*)(b1 + c)) : 0u;
        }
        bar_sync(3, 256);
        const int t128 = tid & 127, w4 = warp & 3, q = lane & 3;
        float accF[88], accQ[96];
        float gs = 0.f;
        const int grow = wg * 64 + (t128 >> 1), ghalf = t128 & 1;
#pragma unroll
        for (int kc = 0; kc < 8; kc++) {
            const int st = kc & 3;
            mbar_wait(x_full + 8 * kc, 0);
            mbar_wait(b_full + 8 * st, (kc >> 2) & 1);
            TS(1, tid == 0 && kc == 0); TS(2, tid == 0 && kc == 4);
            wgmma_fence();
#pragma unroll
            for (int k16 = 0; k16 < 4; k16++) {
                const uint64_t db = make_desc(sB + st * K1_BSTAGE + k16 * 2048, 8192, 1024);
                const uint64_t da = make_desc(sX + kc * 16384 + wg * 8192 + k16 * 32, 16, 1024);
                wgmma_n176<1>(accF, da, db, (kc | k16) != 0);
            }
            wgmma_commit();
#pragma unroll
            for (int c = 0; c < 4; c++) {
                const int cc = ghalf * 4 + c;
                const uint4 xv = *(const uint4*)(sgen + kc * 16384 + grow * 128 + ((cc ^ (grow & 7)) << 4));
                const uint4 gv = *(const uint4*)(sGw + kc * 128 + cc * 16);
                gs = fmaf(bf_lo(xv.x), bf_lo(gv.x), gs); gs = fmaf(bf_hi(xv.x), bf_hi(gv.x), gs);
                gs = fmaf(bf_lo(xv.y), bf_lo(gv.y), gs); gs = fmaf(bf_hi(xv.y), bf_hi(gv.y), gs);
                gs = fmaf(bf_lo(xv.z), bf_lo(gv.z), gs); gs = fmaf(bf_hi(xv.z), bf_hi(gv.z), gs);
                gs = fmaf(bf_lo(xv.w), bf_lo(gv.w), gs); gs = fmaf(bf_hi(xv.w), bf_hi(gv.w), gs);
            }
            if (kc > 0) { wgmma_wait<1>(); if (lane == 0) mbar_arrive(b_empty + 8 * ((kc - 1) & 3)); }
        }
        gs += __shfl_xor_sync(0xffffffffu, gs, 1);
        {
            const float g = 1.f / (1.f + __expf(-gs));
            if (ghalf == 0) {
                sGate[grow] = g;
                if (j == 0) g_gate[rb * 128 + grow] = g;
            }
        }
        wgmma_wait<0>();
        if (lane == 0) mbar_arrive(b_empty + 8 * 3);
        bar_sync(1 + wg, 128);
        TS(3, tid == 0);
        const int n0 = j * FCH;
        const int rl = wg * 64 + w4 * 16 + (lane >> 2);
        const float om0 = 1.f - sGate[rl], om1 = 1.f - sGate[rl + 8];
        bf16* frow0 = g_a2 + (size_t)(rb * 128 + rl) * KA2 + D_ + n0;
        bf16* frow1 = frow0 + 8 * KA2;
        auto ffn_chunk = [&](int u) {
            uint32_t w0[4], w1[4];
#pragma unroll
            for (int i = 0; i < 4; i++) {
                const int t = u * 4 + i;
                if (t < 22) {
                    const uint32_t bv = sBias[t * 4 + q];
                    const float bb0 = bf_lo(bv), bb1 = bf_hi(bv);
                    w0[i] = pack_bf16(mish_f(accF[t * 4 + 0] + bb0) * om0, mish_f(accF[t * 4 + 1] + bb1) * om0);
                    w1[i] = pack_bf16(mish_f(accF[t * 4 + 2] + bb0) * om1, mish_f(accF[t * 4 + 3] + bb1) * om1);
                } else { w0[i] = 0; w1[i] = 0; }
            }
            quad_transpose(w0, q);
            quad_transpose(w1, q);
            const int c = (u * 4 + q) * 8;
            if (c < FCH && n0 + c < F_) {
                *(uint4*)(frow0 + c) = make_uint4(w0[0], w0[1], w0[2], w0[3]);
                *(uint4*)(frow1 + c) = make_uint4(w1[0], w1[1], w1[2], w1[3]);
            }
        };
#pragma unroll
        for (int kc = 0; kc < 8; kc++) {
            const int st = kc & 3;
            mbar_wait(b_full + 8 * st, ((kc + 8) >> 2) & 1);
            wgmma_fence();
#pragma unroll
            for (int k16 = 0; k16 < 4; k16++) {
                const uint64_t db = make_desc(sB + st * K1_BSTAGE + k16 * 2048, 8192, 1024);
                const uint64_t da = make_desc(sX + kc * 16384 + wg * 8192 + k16 * 32, 16, 1024);
                wgmma_n192<1>(accQ, da, db, (kc | k16) != 0);
            }
            wgmma_commit();
            if (kc < 6) ffn_chunk(kc);
            if (kc > 0) { wgmma_wait<1>(); if (lane == 0) mbar_arrive(b_empty + 8 * ((kc - 1) & 3)); }
        }
        wgmma_wait<0>();
        TS(4, tid == 0);
        {
            bf16* orow0 = g_qkv + ((size_t)j * S_ + rb * 128 + rl) * 192;
            bf16* orow1 = orow0 + 8 * 192;
#pragma unroll
            for (int u = 0; u < 6; u++) {
                uint32_t w0[4], w1[4];
#pragma unroll
                for (int i = 0; i < 4; i++) {
                    const int t = u * 4 + i;
                    w0[i] = pack_bf16(accQ[t * 4 + 0], accQ[t * 4 + 1]);
                    w1[i] = pack_bf16(accQ[t * 4 + 2], accQ[t * 4 + 3]);
                }
                quad_transpose(w0, q);
                quad_transpose(w1, q);
                const int c = (u * 4 + q) * 8;
                *(uint4*)(orow0 + c) = make_uint4(w0[0], w0[1], w0[2], w0[3]);
                *(uint4*)(orow1 + c) = make_uint4(w1[0], w1[1], w1[2], w1[3]);
            }
        }
        TS(5, tid == 0);
    }
}

__device__ __forceinline__ void ldsm_x4(uint32_t (&r)[4], uint32_t addr) {
    asm("ldmatrix.sync.aligned.m8n8.x4.shared.b16 {%0,%1,%2,%3}, [%4];"
                 : "=r"(r[0]), "=r"(r[1]), "=r"(r[2]), "=r"(r[3]) : "r"(addr));
}
__device__ __forceinline__ void ldsm_x4_t(uint32_t (&r)[4], uint32_t addr) {
    asm("ldmatrix.sync.aligned.m8n8.x4.trans.shared.b16 {%0,%1,%2,%3}, [%4];"
                 : "=r"(r[0]), "=r"(r[1]), "=r"(r[2]), "=r"(r[3]) : "r"(addr));
}
__device__ __forceinline__ void mma16816(float (&d)[4], const uint32_t (&a)[4], uint32_t b0, uint32_t b1) {
    asm("mma.sync.aligned.m16n8k16.row.col.f32.bf16.bf16.f32 {%0,%1,%2,%3}, {%4,%5,%6,%7}, {%8,%9}, {%0,%1,%2,%3};"
                 : "+f"(d[0]), "+f"(d[1]), "+f"(d[2]), "+f"(d[3])
                 : "r"(a[0]), "r"(a[1]), "r"(a[2]), "r"(a[3]), "r"(b0), "r"(b1));
}
__device__ __forceinline__ void mma16816_z(float (&d)[4], const uint32_t (&a)[4], uint32_t b0, uint32_t b1) {
    asm("mma.sync.aligned.m16n8k16.row.col.f32.bf16.bf16.f32 {%0,%1,%2,%3}, {%4,%5,%6,%7}, {%8,%9}, {%10,%10,%10,%10};"
                 : "=f"(d[0]), "=f"(d[1]), "=f"(d[2]), "=f"(d[3])
                 : "r"(a[0]), "r"(a[1]), "r"(a[2]), "r"(a[3]), "r"(b0), "r"(b1), "f"(0.f));
}

constexpr int KV_PITCH = 128;

template <int EDGE, bool HEAD>
__device__ __forceinline__ void blk_scores(float (&s)[2][4], const uint32_t (&qa)[4], uint32_t kaddr, bool dead, int r0, int c0)
{
    uint32_t kf[4];
    ldsm_x4(kf, kaddr);
    mma16816_z(s[0], qa, kf[0], kf[1]);
    mma16816_z(s[1], qa, kf[2], kf[3]);
#pragma unroll
    for (int t = 0; t < 2; t++)
#pragma unroll
        for (int e = 0; e < 4; e++) {
            const int r = r0 + (e >> 1) * 8, c = t * 8 + c0 + (e & 1);
            if (EDGE == 1 && c <= r) s[t][e] = -1e30f;
            if (EDGE == 2 && c > r) s[t][e] = -1e30f;
            if (HEAD && dead) s[t][e] = -1e30f;
        }
}
__device__ __forceinline__ void blk_max(const float (&s)[2][4], float& n0, float& n1) {
    n0 = fmaxf(n0, fmaxf(fmaxf(s[0][0], s[0][1]), fmaxf(s[1][0], s[1][1])));
    n1 = fmaxf(n1, fmaxf(fmaxf(s[0][2], s[0][3]), fmaxf(s[1][2], s[1][3])));
}
__device__ __forceinline__ void blk_pv(const float (&s)[2][4], float mc0, float mc1, float (&l)[4],
                                       float (&o)[2][4], uint32_t vaddr) {
    const float C = 0.25f * 1.4426950408889634f;
    uint32_t pa[4];
#pragma unroll
    for (int t = 0; t < 2; t++) {
        const float p0 = ex2(fmaf(s[t][0], C, -mc0)), p1 = ex2(fmaf(s[t][1], C, -mc0));
        const float p2 = ex2(fmaf(s[t][2], C, -mc1)), p3 = ex2(fmaf(s[t][3], C, -mc1));
        pa[2 * t] = pack_bf16(p0, p1); pa[2 * t + 1] = pack_bf16(p2, p3);
    }
    uint32_t vf[4];
    ldsm_x4_t(vf, vaddr);
    mma16816(o[0], pa, vf[0], vf[1]);
    mma16816(o[1], pa, vf[2], vf[3]);
    mma16816(l, pa, 0x3F803F80u, 0x3F803F80u);
}
__device__ __forceinline__ void quad_max(float& n0, float& n1) {
    n0 = fmaxf(n0, __shfl_xor_sync(0xffffffffu, n0, 1)); n1 = fmaxf(n1, __shfl_xor_sync(0xffffffffu, n1, 1));
    n0 = fmaxf(n0, __shfl_xor_sync(0xffffffffu, n0, 2)); n1 = fmaxf(n1, __shfl_xor_sync(0xffffffffu, n1, 2));
}
template <int NC, int NN, bool FIRST, bool NEXT_IS_EDGE, bool HEAD>
__device__ __forceinline__ void pipe_step(const float (&sc)[5][2][4], float (&sn)[5][2][4], const uint32_t (&qa)[4],
                                          uint32_t ka, uint32_t va, int kc, int kn, int kb0, int r0, int c0,
                                          float& m0, float& m1, float& n0, float& n1, float (&l)[4], float (&o)[2][4])
{
    const float C = 0.25f * 1.4426950408889634f;
    const float mc0 = n0 * C, mc1 = n1 * C;
    if (!FIRST) {
        const float a0 = ex2(fmaf(m0, C, -mc0)), a1 = ex2(fmaf(m1, C, -mc1));
        l[0] *= a0; l[2] *= a1;
        o[0][0] *= a0; o[0][1] *= a0; o[1][0] *= a0; o[1][1] *= a0;
        o[0][2] *= a1; o[0][3] *= a1; o[1][2] *= a1; o[1][3] *= a1;
    }
    m0 = n0; m1 = n1;
#pragma unroll
    for (int b = 0; b < NC; b++) {
        if (b < NN) {
            if (NEXT_IS_EDGE && b == 0) blk_scores<1, HEAD>(sn[b], qa, ka + (kn + b) * 16 * KV_PITCH, kn + b < kb0, r0, c0);
            else                        blk_scores<0, HEAD>(sn[b], qa, ka + (kn + b) * 16 * KV_PITCH, kn + b < kb0, r0, c0);
        }
        blk_pv(sc[b], mc0, mc1, l, o, va + (kc + b) * 16 * KV_PITCH);
        if (b < NN) blk_max(sn[b], n0, n1);
    }
    if (NN > 0) quad_max(n0, n1);
}

__device__ __forceinline__ void kv_need(uint32_t kvbar, int blk, uint32_t& ka, uint32_t& va) {
    mbar_wait(kvbar + 8 * blk, 0);
    asm volatile("" : "+r"(ka), "+r"(va) :: "memory");
}
template <bool HEAD>
__device__ __forceinline__ void attn_task(const uint32_t (&qa)[4], uint32_t ka, uint32_t va, int kb0, int lane, int qt, uint32_t kvbar,
                                          bf16* __restrict__ out  , float g0, float g1)
{
    const int r0 = lane >> 2, c0 = (lane & 3) * 2;
    float m0 = -1e30f, m1 = -1e30f, n0 = -1e30f, n1 = -1e30f;
    float l[4] = {0.f, 0.f, 0.f, 0.f};
    float o[2][4] = {{0.f, 0.f, 0.f, 0.f}, {0.f, 0.f, 0.f, 0.f}};
    float sa[5][2][4], sb[5][2][4];
    kv_need(kvbar, 2, ka, va);
    if (qt < 4) kv_need(kvbar, 1, ka, va);
#pragma unroll
    for (int b = 0; b < 5; b++) {
        if (b == 4) blk_scores<2, HEAD>(sa[b], qa, ka + (12 + b) * 16 * KV_PITCH, false, r0, c0);
        else        blk_scores<0, HEAD>(sa[b], qa, ka + (12 + b) * 16 * KV_PITCH, 12 + b < kb0, r0, c0);
        blk_max(sa[b], n0, n1);
    }
    quad_max(n0, n1);
    kv_need(kvbar, 1, ka, va);
    pipe_step<5, 4, true,  false, HEAD>(sa, sb, qa, ka, va, 12, 8, kb0, r0, c0, m0, m1, n0, n1, l, o);
    if (qt < 4) kv_need(kvbar, 0, ka, va);
    pipe_step<4, 4, false, false, HEAD>(sb, sa, qa, ka, va, 8, 4, kb0, r0, c0, m0, m1, n0, n1, l, o);
    kv_need(kvbar, 0, ka, va);
    pipe_step<4, 4, false, true,  HEAD>(sa, sb, qa, ka, va, 4, 0, kb0, r0, c0, m0, m1, n0, n1, l, o);
    pipe_step<4, 0, false, false, HEAD>(sb, sa, qa, ka, va, 0, 0, kb0, r0, c0, m0, m1, n0, n1, l, o);
    const float f0 = __fdividef(g0, l[0]), f1 = __fdividef(g1, l[2]);
#pragma unroll
    for (int t = 0; t < 2; t++) {
        *(uint32_t*)(out + (size_t)r0 * KA2 + t * 8 + c0) = pack_bf16(o[t][0] * f0, o[t][1] * f0);
        *(uint32_t*)(out + (size_t)(r0 + 8) * KA2 + t * 8 + c0) = pack_bf16(o[t][2] * f1, o[t][3] * f1);
    }
}

constexpr int K2_SMEM = 2 * 384 * KV_PITCH + 1024 + 64;

__global__ void __launch_bounds__(512, 1) k2_kernel(const __grid_constant__ CUtensorMap tmQKV)
{
    extern __shared__ uint8_t smem_raw[];
    const uint32_t sbase = (smem_u32(smem_raw) + 1023u) & ~1023u;
    uint8_t* sgen = smem_raw + (sbase - smem_u32(smem_raw));
    const uint32_t sK = sbase, sV = sK + 384 * KV_PITCH, kv_full = sbase + 2 * 384 * KV_PITCH;
    const int rb = blockIdx.x >> 3, j = blockIdx.x & 7;
    const int tid = threadIdx.x, warp = tid >> 5, lane = tid & 31;
    pdl_launch();
    if (tid == 0) {
        for (int i = 0; i < 3; i++) mbar_init(kv_full + 8 * i, 1);
        fence_barrier_init();
    }
    pdl_wait();
    TS(6, tid == 0);
    if (tid == 0) {
        for (int i = 0; i < 3; i++) {
            const uint32_t bar = kv_full + 8 * (2 - i);
            if (rb - i >= 0) {
                const int row = j * S_ + (rb - i) * 128;
                mbar_expect_tx(bar, 2 * 16384);
                tma_load_2d(sK + (2 - i) * 16384, &tmQKV, 64, row, bar);
                tma_load_2d(sV + (2 - i) * 16384, &tmQKV, 128, row, bar);
            } else {
                mbar_arrive(bar);
            }
        }
    }
    if (rb < 2) {
        for (int i = tid; i < (2 - rb) * 1024; i += 512) {
            *(uint4*)(sgen + i * 16) = make_uint4(0, 0, 0, 0);
            *(uint4*)(sgen + 384 * KV_PITCH + i * 16) = make_uint4(0, 0, 0, 0);
        }
    }
    const int qt = warp & 7, h0 = (warp >> 3) * 2;
    const int q0g = rb * 128 + qt * 16;
    const int r0 = lane >> 2, c0 = (lane & 3) * 2;
    const bf16* qsrc = g_qkv + ((size_t)j * S_ + q0g) * 192 + h0 * 16;
    uint32_t qa[4], qn[4];
    qa[0] = *(const uint32_t*)(qsrc + (size_t)r0 * 192 + c0);
    qa[1] = *(const uint32_t*)(qsrc + (size_t)(r0 + 8) * 192 + c0);
    qa[2] = *(const uint32_t*)(qsrc + (size_t)r0 * 192 + c0 + 8);
    qa[3] = *(const uint32_t*)(qsrc + (size_t)(r0 + 8) * 192 + c0 + 8);
    qn[0] = *(const uint32_t*)(qsrc + (size_t)r0 * 192 + 16 + c0);
    qn[1] = *(const uint32_t*)(qsrc + (size_t)(r0 + 8) * 192 + 16 + c0);
    qn[2] = *(const uint32_t*)(qsrc + (size_t)r0 * 192 + 16 + c0 + 8);
    qn[3] = *(const uint32_t*)(qsrc + (size_t)(r0 + 8) * 192 + 16 + c0 + 8);
    const float g0 = g_gate[q0g + r0], g1 = g_gate[q0g + r0 + 8];
    const int kb0 = q0g < 256 ? (256 - q0g) >> 4 : 0;
    __syncthreads();
    const uint32_t sKd = sK, sVd = sV;
    TS(7, tid == 0);
    const int krow = qt * 16 + (lane & 7) + ((lane >> 4) << 3);
    const int vrow = qt * 16 + (lane & 15);
#pragma unroll 1
    for (int hh = 0; hh < 2; hh++) {
        const int hl = h0 + hh;
        const uint32_t ka = sKd + krow * KV_PITCH + (((2 * hl + ((lane >> 3) & 1)) ^ (lane & 7)) << 4);
        const uint32_t va = sVd + vrow * KV_PITCH + (((2 * hl + (lane >> 4)) ^ (lane & 7)) << 4);
        if (rb < 2) attn_task<true>(qa, ka, va, kb0, lane, qt, kv_full, g_a2 + (size_t)q0g * KA2 + (j * 4 + hl) * 16, g0, g1);
        else        attn_task<false>(qa, ka, va, kb0, lane, qt, kv_full, g_a2 + (size_t)q0g * KA2 + (j * 4 + hl) * 16, g0, g1);
        TS(8 + hh, tid == 0);
        qa[0] = qn[0]; qa[1] = qn[1]; qa[2] = qn[2]; qa[3] = qn[3];
    }
}

constexpr int K3_STAGES = 8;
constexpr int K3_STAGE = 16384 + 8192;
constexpr int K3_SMEM = K3_STAGES * K3_STAGE + 1024 + 1024;
constexpr int K3_KSTEPS = 30;

__global__ void __launch_bounds__(384, 1)
k3_kernel(const __grid_constant__ CUtensorMap tmA2, const __grid_constant__ CUtensorMap tmWo,
          const __grid_constant__ CUtensorMap tmW2, bf16* __restrict__ out)
{
    extern __shared__ uint8_t smem_raw[];
    const uint32_t sbase = (smem_u32(smem_raw) + 1023u) & ~1023u;
    const uint32_t sBar = sbase + K3_STAGES * K3_STAGE;
    const uint32_t full = sBar, empty = sBar + 64;
    const int rb = blockIdx.x >> 3, nb = blockIdx.x & 7;
    const int tid = threadIdx.x, wg = tid >> 7, warp = tid >> 5, lane = tid & 31;
    if (tid == 0) {
        for (int i = 0; i < K3_STAGES; i++) { mbar_init(full + 8 * i, 1); mbar_init(empty + 8 * i, 8); }
        fence_barrier_init();
    }
    __syncthreads();
    pdl_wait();
    TS(10, tid == 0);
    if (wg == 2) {
        reg_dealloc<40>();
        if (tid == 256) {
            for (int ks = 0; ks < K3_KSTEPS; ks++) {
                const int st = ks % K3_STAGES;
                if (ks >= K3_STAGES) mbar_wait(empty + 8 * st, ((ks / K3_STAGES) - 1) & 1);
                mbar_expect_tx(full + 8 * st, K3_STAGE);
                const uint32_t dst = sbase + st * K3_STAGE;
                tma_load_2d(dst, &tmA2, ks * 64, rb * 128, full + 8 * st);
                if (ks < 8) tma_load_2d(dst + 16384, &tmWo, nb * 64, ks * 64, full + 8 * st);
                else        tma_load_2d(dst + 16384, &tmW2, nb * 64, (ks - 8) * 64, full + 8 * st);
            }
        }
    } else {
        reg_alloc<232>();
        float acc[32];
        for (int ks = 0; ks < K3_KSTEPS; ks++) {
            const int st = ks % K3_STAGES;
            mbar_wait(full + 8 * st, (ks / K3_STAGES) & 1);
            TS(11, tid == 0 && ks == 0); TS(12, tid == 0 && ks == 8); TS(13, tid == 0 && ks == 16);
            wgmma_fence();
#pragma unroll
            for (int k16 = 0; k16 < 4; k16++) {
                const uint64_t da = make_desc(sbase + st * K3_STAGE + wg * 8192 + k16 * 32, 16, 1024);
                const uint64_t db = make_desc(sbase + st * K3_STAGE + 16384 + k16 * 2048, 8192, 1024);
                wgmma_n64<1>(acc, da, db, (ks | k16) != 0);
            }
            wgmma_commit();
            if (ks > 0) { wgmma_wait<1>(); if (lane == 0) mbar_arrive(empty + 8 * ((ks - 1) % K3_STAGES)); }
        }
        wgmma_wait<0>();
        TS(14, tid == 0);
        const int q = lane & 3;
        const int r = rb * 128 + wg * 64 + (warp & 3) * 16 + (lane >> 2);
        bf16* orow0 = out + (size_t)r * D_ + nb * 64;
        bf16* orow1 = orow0 + 8 * D_;
#pragma unroll
        for (int u = 0; u < 2; u++) {
            uint32_t w0[4], w1[4];
#pragma unroll
            for (int i = 0; i < 4; i++) {
                const int t = u * 4 + i;
                w0[i] = pack_bf16(acc[t * 4 + 0], acc[t * 4 + 1]);
                w1[i] = pack_bf16(acc[t * 4 + 2], acc[t * 4 + 3]);
            }
            quad_transpose(w0, q);
            quad_transpose(w1, q);
            const int c = (u * 4 + q) * 8;
            *(uint4*)(orow0 + c) = make_uint4(w0[0], w0[1], w0[2], w0[3]);
            *(uint4*)(orow1 + c) = make_uint4(w1[0], w1[1], w1[2], w1[3]);
        }
        TS(15, tid == 0);
    }
}

typedef CUresult (*PFN_encodeTiled)(CUtensorMap*, CUtensorMapDataType, cuuint32_t, void*, const cuuint64_t*,
                                    const cuuint64_t*, const cuuint32_t*, const cuuint32_t*, CUtensorMapInterleave,
                                    CUtensorMapSwizzle, CUtensorMapL2promotion, CUtensorMapFloatOOBfill);

static void make_map(PFN_encodeTiled enc, CUtensorMap* m, const void* ptr, uint64_t cols, uint64_t rows,
                     uint32_t box_cols, uint32_t box_rows)
{
    cuuint64_t dims[2] = {cols, rows};
    cuuint64_t strides[1] = {cols * 2};
    cuuint32_t box[2] = {box_cols, box_rows};
    cuuint32_t es[2] = {1, 1};
    enc(m, CU_TENSOR_MAP_DATA_TYPE_BFLOAT16, 2, const_cast<void*>(ptr), dims, strides, box, es,
        CU_TENSOR_MAP_INTERLEAVE_NONE, CU_TENSOR_MAP_SWIZZLE_128B, CU_TENSOR_MAP_L2_PROMOTION_L2_128B,
        CU_TENSOR_MAP_FLOAT_OOB_FILL_NONE);
}

extern "C" void kernel_launch(void* const* d_in, const int* in_sizes, int n_in, void* d_out, int out_size)
{
    const bf16* x    = (const bf16*)d_in[0];
    const bf16* wqkv = (const bf16*)d_in[1];
    const bf16* wo   = (const bf16*)d_in[2];
    const bf16* w1   = (const bf16*)d_in[4];
    const bf16* b1   = (const bf16*)d_in[5];
    const bf16* w2   = (const bf16*)d_in[6];
    const bf16* gw   = (const bf16*)d_in[7];

    static PFN_encodeTiled enc = nullptr;
    if (!enc) {
        void* fn = nullptr;
        cudaDriverEntryPointQueryResult qr;
        cudaGetDriverEntryPoint("cuTensorMapEncodeTiled", &fn, cudaEnableDefault, &qr);
        enc = (PFN_encodeTiled)fn;
        cudaFuncSetAttribute(k1_kernel, cudaFuncAttributeMaxDynamicSharedMemorySize, K1_SMEM);
        cudaFuncSetAttribute(k2_kernel, cudaFuncAttributeMaxDynamicSharedMemorySize, K2_SMEM);
        cudaFuncSetAttribute(k3_kernel, cudaFuncAttributeMaxDynamicSharedMemorySize, K3_SMEM);
    }
    void* a2p = nullptr;
    cudaGetSymbolAddress(&a2p, g_a2);
    void* qkvp = nullptr;
    cudaGetSymbolAddress(&qkvp, g_qkv);
    CUtensorMap tmX, tmWqkv, tmW1, tmA2, tmWo, tmW2, tmQKV;
    make_map(enc, &tmQKV, qkvp, 192, 8 * S_, 64, 128);
    make_map(enc, &tmX, x, D_, S_, 64, 128);
    make_map(enc, &tmWqkv, wqkv, 3 * D_, D_, 64, 64);
    make_map(enc, &tmW1, w1, F_, D_, 64, 64);
    make_map(enc, &tmA2, a2p, KA2, S_, 64, 128);
    make_map(enc, &tmWo, wo, D_, D_, 64, 64);
    make_map(enc, &tmW2, w2, D_, F_, 64, 64);

    cudaStream_t st = cudaStreamPerThread;
    k1_kernel<<<128, 384, K1_SMEM, st>>>(tmX, tmWqkv, tmW1, b1, gw, w1, wqkv, w2, wo);
    cudaLaunchAttribute at[1];
    at[0].id = cudaLaunchAttributeProgrammaticStreamSerialization;
    at[0].val.programmaticStreamSerializationAllowed = 1;
    cudaLaunchConfig_t cfg = {};
    cfg.gridDim = dim3(128); cfg.stream = st; cfg.attrs = at; cfg.numAttrs = 1;
    cfg.blockDim = dim3(512); cfg.dynamicSmemBytes = K2_SMEM;
    cudaLaunchKernelEx(&cfg, k2_kernel, tmQKV);
    k3_kernel<<<128, 384, K3_SMEM, st>>>(tmA2, tmWo, tmW2, (bf16*)d_out);
}
```

```cpp
#include <cuda_runtime.h>
#include <cuda_bf16.h>
#include <cuda.h>
#include <stdint.h>

typedef __nv_bfloat16 bf16;

constexpr int S_ = 2048, D_ = 512, F_ = 1376;
constexpr int KA2 = D_ + F_;
constexpr int FCH = 176;

__device__ bf16  g_qkv[8 * S_ * 192];
__device__ bf16  g_a2[S_ * KA2];
__device__ float g_gate[S_];

#define TS(k, cond) do { } while (0)

__device__ __forceinline__ uint32_t smem_u32(const void* p) { return (uint32_t)__cvta_generic_to_shared(p); }
__device__ __forceinline__ void mbar_init(uint32_t bar, uint32_t count) {
    asm volatile("mbarrier.init.shared::cta.b64 [%0], %1;" :: "r"(bar), "r"(count) : "memory");
}
__device__ __forceinline__ void mbar_expect_tx(uint32_t bar, uint32_t bytes) {
    asm volatile("mbarrier.arrive.expect_tx.shared::cta.b64 _, [%0], %1;" :: "r"(bar), "r"(bytes) : "memory");
}
__device__ __forceinline__ void mbar_arrive(uint32_t bar) {
    asm volatile("mbarrier.arrive.shared::cta.b64 _, [%0];" :: "r"(bar) : "memory");
}
__device__ __forceinline__ bool mbar_try_wait(uint32_t bar, uint32_t parity) {
    uint32_t ok;
    asm volatile("{\n.reg .pred p;\nmbarrier.try_wait.parity.shared::cta.b64 p, [%1], %2;\nselp.u32 %0, 1, 0, p;\n}"
                 : "=r"(ok) : "r"(bar), "r"(parity) : "memory");
    return ok != 0;
}
__device__ __forceinline__ void mbar_wait(uint32_t bar, uint32_t parity) {
    for (uint32_t it = 0; it < (1u << 22); ++it) { if (mbar_try_wait(bar, parity)) break; }
}
__device__ __forceinline__ void tma_load_2d(uint32_t dst, const CUtensorMap* map, int c0, int c1, uint32_t bar) {
    asm volatile("cp.async.bulk.tensor.2d.shared::cluster.global.mbarrier::complete_tx::bytes [%0], [%1, {%3, %4}], [%2];"
                 :: "r"(dst), "l"(map), "r"(bar), "r"(c0), "r"(c1) : "memory");
}
__device__ __forceinline__ void l2_prefetch(const void* p, uint32_t bytes) {
    asm volatile("cp.async.bulk.prefetch.L2.global [%0], %1;" :: "l"(p), "r"(bytes) : "memory");
}
__device__ __forceinline__ void fence_barrier_init() { asm volatile("fence.mbarrier_init.release.cluster;" ::: "memory"); }
__device__ __forceinline__ void wgmma_fence()  { asm volatile("wgmma.fence.sync.aligned;" ::: "memory"); }
__device__ __forceinline__ void wgmma_commit() { asm volatile("wgmma.commit_group.sync.aligned;" ::: "memory"); }
template <int N> __device__ __forceinline__ void wgmma_wait() { asm volatile("wgmma.wait_group.sync.aligned %0;" :: "n"(N) : "memory"); }
template <int R> __device__ __forceinline__ void reg_alloc()   { asm volatile("setmaxnreg.inc.sync.aligned.u32 %0;" :: "n"(R)); }
template <int R> __device__ __forceinline__ void reg_dealloc() { asm volatile("setmaxnreg.dec.sync.aligned.u32 %0;" :: "n"(R)); }
__device__ __forceinline__ void bar_sync(int id, int n)   { asm volatile("bar.sync %0, %1;" :: "r"(id), "r"(n) : "memory"); }
__device__ __forceinline__ void bar_arrive(int id, int n) { asm volatile("bar.arrive %0, %1;" :: "r"(id), "r"(n) : "memory"); }

__device__ __forceinline__ uint64_t make_desc(uint32_t addr, uint32_t lbo, uint32_t sbo) {
    uint64_t d = (uint64_t)((addr & 0x3FFFF) >> 4);
    d |= (uint64_t)((lbo & 0x3FFFF) >> 4) << 16;
    d |= (uint64_t)((sbo & 0x3FFFF) >> 4) << 32;
    d |= (uint64_t)1 << 62;
    return d;
}

template <int TB>
__device__ __forceinline__ void wgmma_n64(float (&d)[32], uint64_t da, uint64_t db, int scale_d) {
    asm volatile("{\n.reg .pred p;\nsetp.ne.b32 p, %34, 0;\n"
        "wgmma.mma_async.sync.aligned.m64n64k16.f32.bf16.bf16 {%0, %1, %2, %3, %4, %5, %6, %7, %8, %9, %10, %11, %12, %13, %14, %15, %16, %17, %18, %19, %20, %21, %22, %23, %24, %25, %26, %27, %28, %29, %30, %31}, %32, %33, p, 1, 1, 0, %35;\n}\n"
        : "+f"(d[0]), "+f"(d[1]), "+f"(d[2]), "+f"(d[3]), "+f"(d[4]), "+f"(d[5]), "+f"(d[6]), "+f"(d[7]), "+f"(d[8]), "+f"(d[9]), "+f"(d[10]), "+f"(d[11]), "+f"(d[12]), "+f"(d[13]), "+f"(d[14]), "+f"(d[15]), "+f"(d[16]), "+f"(d[17]), "+f"(d[18]), "+f"(d[19]), "+f"(d[20]), "+f"(d[21]), "+f"(d[22]), "+f"(d[23]), "+f"(d[24]), "+f"(d[25]), "+f"(d[26]), "+f"(d[27]), "+f"(d[28]), "+f"(d[29]), "+f"(d[30]), "+f"(d[31])
        : "l"(da), "l"(db), "r"(scale_d), "n"(TB));
}

template <int TB>
__device__ __forceinline__ void wgmma_n128(float (&d)[64], uint64_t da, uint64_t db, int scale_d) {
    asm volatile("{\n.reg .pred p;\nsetp.ne.b32 p, %66, 0;\n"
        "wgmma.mma_async.sync.aligned.m64n128k16.f32.bf16.bf16 {%0, %1, %2, %3, %4, %5, %6, %7, %8, %9, %10, %11, %12, %13, %14, %15, %16, %17, %18, %19, %20, %21, %22, %23, %24, %25, %26, %27, %28, %29, %30, %31, %32, %33, %34, %35, %36, %37, %38, %39, %40, %41, %42, %43, %44, %45, %46, %47, %48, %49, %50, %51, %52, %53, %54, %55, %56, %57, %58, %59, %60, %61, %62, %63}, %64, %65, p, 1, 1, 0, %67;\n}\n"
        : "+f"(d[0]), "+f"(d[1]), "+f"(d[2]), "+f"(d[3]), "+f"(d[4]), "+f"(d[5]), "+f"(d[6]), "+f"(d[7]), "+f"(d[8]), "+f"(d[9]), "+f"(d[10]), "+f"(d[11]), "+f"(d[12]), "+f"(d[13]), "+f"(d[14]), "+f"(d[15]), "+f"(d[16]), "+f"(d[17]), "+f"(d[18]), "+f"(d[19]), "+f"(d[20]), "+f"(d[21]), "+f"(d[22]), "+f"(d[23]), "+f"(d[24]), "+f"(d[25]), "+f"(d[26]), "+f"(d[27]), "+f"(d[28]), "+f"(d[29]), "+f"(d[30]), "+f"(d[31]), "+f"(d[32]), "+f"(d[33]), "+f"(d[34]), "+f"(d[35]), "+f"(d[36]), "+f"(d[37]), "+f"(d[38]), "+f"(d[39]), "+f"(d[40]), "+f"(d[41]), "+f"(d[42]), "+f"(d[43]), "+f"(d[44]), "+f"(d[45]), "+f"(d[46]), "+f"(d[47]), "+f"(d[48]), "+f"(d[49]), "+f"(d[50]), "+f"(d[51]), "+f"(d[52]), "+f"(d[53]), "+f"(d[54]), "+f"(d[55]), "+f"(d[56]), "+f"(d[57]), "+f"(d[58]), "+f"(d[59]), "+f"(d[60]), "+f"(d[61]), "+f"(d[62]), "+f"(d[63])
        : "l"(da), "l"(db), "r"(scale_d), "n"(TB));
}

template <int TB>
__device__ __forceinline__ void wgmma_n176(float (&d)[88], uint64_t da, uint64_t db, int scale_d) {
    asm volatile("{\n.reg .pred p;\nsetp.ne.b32 p, %90, 0;\n"
        "wgmma.mma_async.sync.aligned.m64n176k16.f32.bf16.bf16 {%0, %1, %2, %3, %4, %5, %6, %7, %8, %9, %10, %11, %12, %13, %14, %15, %16, %17, %18, %19, %20, %21, %22, %23, %24, %25, %26, %27, %28, %29, %30, %31, %32, %33, %34, %35, %36, %37, %38, %39, %40, %41, %42, %43, %44, %45, %46, %47, %48, %49, %50, %51, %52, %53, %54, %55, %56, %57, %58, %59, %60, %61, %62, %63, %64, %65, %66, %67, %68, %69, %70, %71, %72, %73, %74, %75, %76, %77, %78, %79, %80, %81, %82, %83, %84, %85, %86, %87}, %88, %89, p, 1, 1, 0, %91;\n}\n"
        : "+f"(d[0]), "+f"(d[1]), "+f"(d[2]), "+f"(d[3]), "+f"(d[4]), "+f"(d[5]), "+f"(d[6]), "+f"(d[7]), "+f"(d[8]), "+f"(d[9]), "+f"(d[10]), "+f"(d[11]), "+f"(d[12]), "+f"(d[13]), "+f"(d[14]), "+f"(d[15]), "+f"(d[16]), "+f"(d[17]), "+f"(d[18]), "+f"(d[19]), "+f"(d[20]), "+f"(d[21]), "+f"(d[22]), "+f"(d[23]), "+f"(d[24]), "+f"(d[25]), "+f"(d[26]), "+f"(d[27]), "+f"(d[28]), "+f"(d[29]), "+f"(d[30]), "+f"(d[31]), "+f"(d[32]), "+f"(d[33]), "+f"(d[34]), "+f"(d[35]), "+f"(d[36]), "+f"(d[37]), "+f"(d[38]), "+f"(d[39]), "+f"(d[40]), "+f"(d[41]), "+f"(d[42]), "+f"(d[43]), "+f"(d[44]), "+f"(d[45]), "+f"(d[46]), "+f"(d[47]), "+f"(d[48]), "+f"(d[49]), "+f"(d[50]), "+f"(d[51]), "+f"(d[52]), "+f"(d[53]), "+f"(d[54]), "+f"(d[55]), "+f"(d[56]), "+f"(d[57]), "+f"(d[58]), "+f"(d[59]), "+f"(d[60]), "+f"(d[61]), "+f"(d[62]), "+f"(d[63]), "+f"(d[64]), "+f"(d[65]), "+f"(d[66]), "+f"(d[67]), "+f"(d[68]), "+f"(d[69]), "+f"(d[70]), "+f"(d[71]), "+f"(d[72]), "+f"(d[73]), "+f"(d[74]), "+f"(d[75]), "+f"(d[76]), "+f"(d[77]), "+f"(d[78]), "+f"(d[79]), "+f"(d[80]), "+f"(d[81]), "+f"(d[82]), "+f"(d[83]), "+f"(d[84]), "+f"(d[85]), "+f"(d[86]), "+f"(d[87])
        : "l"(da), "l"(db), "r"(scale_d), "n"(TB));
}

template <int TB>
__device__ __forceinline__ void wgmma_n192(float (&d)[96], uint64_t da, uint64_t db, int scale_d) {
    asm volatile("{\n.reg .pred p;\nsetp.ne.b32 p, %98, 0;\n"
        "wgmma.mma_async.sync.aligned.m64n192k16.f32.bf16.bf16 {%0, %1, %2, %3, %4, %5, %6, %7, %8, %9, %10, %11, %12, %13, %14, %15, %16, %17, %18, %19, %20, %21, %22, %23, %24, %25, %26, %27, %28, %29, %30, %31, %32, %33, %34, %35, %36, %37, %38, %39, %40, %41, %42, %43, %44, %45, %46, %47, %48, %49, %50, %51, %52, %53, %54, %55, %56, %57, %58, %59, %60, %61, %62, %63, %64, %65, %66, %67, %68, %69, %70, %71, %72, %73, %74, %75, %76, %77, %78, %79, %80, %81, %82, %83, %84, %85, %86, %87, %88, %89, %90, %91, %92, %93, %94, %95}, %96, %97, p, 1, 1, 0, %99;\n}\n"
        : "+f"(d[0]), "+f"(d[1]), "+f"(d[2]), "+f"(d[3]), "+f"(d[4]), "+f"(d[5]), "+f"(d[6]), "+f"(d[7]), "+f"(d[8]), "+f"(d[9]), "+f"(d[10]), "+f"(d[11]), "+f"(d[12]), "+f"(d[13]), "+f"(d[14]), "+f"(d[15]), "+f"(d[16]), "+f"(d[17]), "+f"(d[18]), "+f"(d[19]), "+f"(d[20]), "+f"(d[21]), "+f"(d[22]), "+f"(d[23]), "+f"(d[24]), "+f"(d[25]), "+f"(d[26]), "+f"(d[27]), "+f"(d[28]), "+f"(d[29]), "+f"(d[30]), "+f"(d[31]), "+f"(d[32]), "+f"(d[33]), "+f"(d[34]), "+f"(d[35]), "+f"(d[36]), "+f"(d[37]), "+f"(d[38]), "+f"(d[39]), "+f"(d[40]), "+f"(d[41]), "+f"(d[42]), "+f"(d[43]), "+f"(d[44]), "+f"(d[45]), "+f"(d[46]), "+f"(d[47]), "+f"(d[48]), "+f"(d[49]), "+f"(d[50]), "+f"(d[51]), "+f"(d[52]), "+f"(d[53]), "+f"(d[54]), "+f"(d[55]), "+f"(d[56]), "+f"(d[57]), "+f"(d[58]), "+f"(d[59]), "+f"(d[60]), "+f"(d[61]), "+f"(d[62]), "+f"(d[63]), "+f"(d[64]), "+f"(d[65]), "+f"(d[66]), "+f"(d[67]), "+f"(d[68]), "+f"(d[69]), "+f"(d[70]), "+f"(d[71]), "+f"(d[72]), "+f"(d[73]), "+f"(d[74]), "+f"(d[75]), "+f"(d[76]), "+f"(d[77]), "+f"(d[78]), "+f"(d[79]), "+f"(d[80]), "+f"(d[81]), "+f"(d[82]), "+f"(d[83]), "+f"(d[84]), "+f"(d[85]), "+f"(d[86]), "+f"(d[87]), "+f"(d[88]), "+f"(d[89]), "+f"(d[90]), "+f"(d[91]), "+f"(d[92]), "+f"(d[93]), "+f"(d[94]), "+f"(d[95])
        : "l"(da), "l"(db), "r"(scale_d), "n"(TB));
}

__device__ __forceinline__ uint32_t pack_bf16(float lo, float hi) {
    uint32_t r;
    asm("cvt.rn.bf16x2.f32 %0, %1, %2;" : "=r"(r) : "f"(hi), "f"(lo));
    return r;
}
__device__ __forceinline__ float bf_lo(uint32_t v) { return __uint_as_float(v << 16); }
__device__ __forceinline__ float bf_hi(uint32_t v) { return __uint_as_float(v & 0xffff0000u); }

__device__ __forceinline__ void quad_transpose(uint32_t (&w)[4], int q) {
    const bool o1 = q & 1, o2 = q & 2;
    {
        uint32_t s0 = o1 ? w[0] : w[1], s1 = o1 ? w[2] : w[3];
        s0 = __shfl_xor_sync(0xffffffffu, s0, 1); s1 = __shfl_xor_sync(0xffffffffu, s1, 1);
        if (o1) { w[0] = s0; w[2] = s1; } else { w[1] = s0; w[3] = s1; }
    }
    {
        uint32_t s0 = o2 ? w[0] : w[2], s1 = o2 ? w[1] : w[3];
        s0 = __shfl_xor_sync(0xffffffffu, s0, 2); s1 = __shfl_xor_sync(0xffffffffu, s1, 2);
        if (o2) { w[0] = s0; w[1] = s1; } else { w[2] = s0; w[3] = s1; }
    }
}

__device__ __forceinline__ float ex2(float x) { float y; asm("ex2.approx.ftz.f32 %0, %1;" : "=f"(y) : "f"(x)); return y; }
__device__ __forceinline__ float rcp(float x) { float y; asm("rcp.approx.ftz.f32 %0, %1;" : "=f"(y) : "f"(x)); return y; }

__device__ __forceinline__ float ex2v(float x) { float y; asm volatile("ex2.approx.ftz.f32 %0, %1;" : "=f"(y) : "f"(x)); return y; }
__device__ __forceinline__ float rcpv(float x) { float y; asm volatile("rcp.approx.ftz.f32 %0, %1;" : "=f"(y) : "f"(x)); return y; }
__device__ __forceinline__ float mish_f(float h) {
    const float e = ex2v(1.4426950408889634f * fminf(h, 20.f));
    const float n = fmaf(e, e, e + e);
    return h * n * rcpv(n + 2.f);
}

__device__ __forceinline__ void pdl_wait()   { asm volatile("griddepcontrol.wait;" ::: "memory"); }
__device__ __forceinline__ void pdl_launch() { asm volatile("griddepcontrol.launch_dependents;" ::: "memory"); }

constexpr int K1_STAGES = 4;
constexpr int K1_XBYTES = 128 * 512 * 2;
constexpr int K1_BSTAGE = 3 * 8192;
constexpr int K1_SMEM   = K1_XBYTES + K1_STAGES * K1_BSTAGE + 2048   + 1024  ;

__global__ void __launch_bounds__(384, 1)
k1_kernel(const __grid_constant__ CUtensorMap tmX, const __grid_constant__ CUtensorMap tmWqkv,
          const __grid_constant__ CUtensorMap tmW1, const bf16* __restrict__ b1,
          const bf16* __restrict__ gate_w, const bf16* __restrict__ w1p, const bf16* __restrict__ wqkvp,
          const bf16* __restrict__ w2p, const bf16* __restrict__ wop)
{

    extern __shared__ uint8_t smem_raw[];
    const uint32_t sbase = (smem_u32(smem_raw) + 1023u) & ~1023u;
    uint8_t* sgen = smem_raw + (sbase - smem_u32(smem_raw));
    const uint32_t sX = sbase;
    const uint32_t sB = sbase + K1_XBYTES;
    const uint32_t sBar = sB + K1_STAGES * K1_BSTAGE;
    const uint32_t x_full = sBar;
    const uint32_t b_full = sBar + 64;
    const uint32_t b_empty = sBar + 96;
    float* sGate = (float*)(sgen + K1_XBYTES + K1_STAGES * K1_BSTAGE + 128);
    uint8_t* sGw = sgen + K1_XBYTES + K1_STAGES * K1_BSTAGE + 640;
    uint32_t* sBias = (uint32_t*)(sgen + K1_XBYTES + K1_STAGES * K1_BSTAGE + 1664);

    const int rb = blockIdx.x >> 3, j = blockIdx.x & 7;
    const int tid = threadIdx.x, wg = tid >> 7, warp = tid >> 5, lane = tid & 31;
    TS(0, tid == 0);
    pdl_launch();

    if (tid == 0) {
        for (int i = 0; i < 8; i++) mbar_init(x_full + 8 * i, 1);
        for (int i = 0; i < K1_STAGES; i++) { mbar_init(b_full + 8 * i, 1); mbar_init(b_empty + 8 * i, 8); }
        fence_barrier_init();
    }
    __syncthreads();

    if (wg == 2) {
        reg_dealloc<40>();
        if (tid == 288) {
            const int b = blockIdx.x;
            mbar_wait(b_full + 8, 0);
            l2_prefetch((const uint8_t*)wqkvp + b * 12288, 12288);
            l2_prefetch((const uint8_t*)w2p + b * 11008, 11008);
            l2_prefetch((const uint8_t*)wop + b * 4096, 4096);
        }
        if (tid == 256) {
            for (int it = 0; it < 16; it++) {
                if (it < 8) {
                    mbar_expect_tx(x_full + 8 * it, 16384);
                    tma_load_2d(sX + it * 16384, &tmX, it * 64, rb * 128, x_full + 8 * it);
                }
                const int st = it & 3;
                if (it >= K1_STAGES) mbar_wait(b_empty + 8 * st, ((it >> 2) - 1) & 1);
                mbar_expect_tx(b_full + 8 * st, K1_BSTAGE);
                const uint32_t dst = sB + st * K1_BSTAGE;
                if (it < 8) {
                    for (int b = 0; b < 3; b++) tma_load_2d(dst + b * 8192, &tmW1, j * FCH + b * 64, it * 64, b_full + 8 * st);
                } else {
                    for (int b = 0; b < 3; b++) tma_load_2d(dst + b * 8192, &tmWqkv, b * 512 + j * 64, (it - 8) * 64, b_full + 8 * st);
                }
            }
        }
    } else {
        reg_alloc<232>();
        if (tid < 64) ((uint4*)sGw)[tid] = __ldg((const uint4*)gate_w + tid);
        else if (tid < 64 + 88) {
            const int c = j * FCH + (tid - 64) * 2;
            sBias[tid - 64] = c < F_ ? __ldg((const uint32_t*)(b1 + c)) : 0u;
        }
        bar_sync(3, 256);
        const int t128 = tid & 127, w4 = warp & 3, q = lane & 3;
        float accF[88], accQ[96];
        float gs = 0.f;
        const int grow = wg * 64 + (t128 >> 1), ghalf = t128 & 1;
#pragma unroll
        for (int kc = 0; kc < 8; kc++) {
            const int st = kc & 3;
            mbar_wait(x_full + 8 * kc, 0);
            mbar_wait(b_full + 8 * st, (kc >> 2) & 1);
            TS(1, tid == 0 && kc == 0); TS(2, tid == 0 && kc == 4);
            wgmma_fence();
#pragma unroll
            for (int k16 = 0; k16 < 4; k16++) {
                const uint64_t db = make_desc(sB + st * K1_BSTAGE + k16 * 2048, 8192, 1024);
                const uint64_t da = make_desc(sX + kc * 16384 + wg * 8192 + k16 * 32, 16, 1024);
                wgmma_n176<1>(accF, da, db, (kc | k16) != 0);
            }
            wgmma_commit();
#pragma unroll
            for (int c = 0; c < 4; c++) {
                const int cc = ghalf * 4 + c;
                const uint4 xv = *(const uint4*)(sgen + kc * 16384 + grow * 128 + ((cc ^ (grow & 7)) << 4));
                const uint4 gv = *(const uint4*)(sGw + kc * 128 + cc * 16);
                gs = fmaf(bf_lo(xv.x), bf_lo(gv.x), gs); gs = fmaf(bf_hi(xv.x), bf_hi(gv.x), gs);
                gs = fmaf(bf_lo(xv.y), bf_lo(gv.y), gs); gs = fmaf(bf_hi(xv.y), bf_hi(gv.y), gs);
                gs = fmaf(bf_lo(xv.z), bf_lo(gv.z), gs); gs = fmaf(bf_hi(xv.z), bf_hi(gv.z), gs);
                gs = fmaf(bf_lo(xv.w), bf_lo(gv.w), gs); gs = fmaf(bf_hi(xv.w), bf_hi(gv.w), gs);
            }
            if (kc > 0) { wgmma_wait<1>(); if (lane == 0) mbar_arrive(b_empty + 8 * ((kc - 1) & 3)); }
        }
        gs += __shfl_xor_sync(0xffffffffu, gs, 1);
        {
            const float g = 1.f / (1.f + __expf(-gs));
            if (ghalf == 0) {
                sGate[grow] = g;
                if (j == 0) g_gate[rb * 128 + grow] = g;
            }
        }
        wgmma_wait<0>();
        if (lane == 0) mbar_arrive(b_empty + 8 * 3);
        bar_sync(1 + wg, 128);
        TS(3, tid == 0);
        const int n0 = j * FCH;
        const int rl = wg * 64 + w4 * 16 + (lane >> 2);
        const float om0 = 1.f - sGate[rl], om1 = 1.f - sGate[rl + 8];
        bf16* frow0 = g_a2 + (size_t)(rb * 128 + rl) * KA2 + D_ + n0;
        bf16* frow1 = frow0 + 8 * KA2;
        auto ffn_chunk = [&](int u) {
            uint32_t w0[4], w1[4];
#pragma unroll
            for (int i = 0; i < 4; i++) {
                const int t = u * 4 + i;
                if (t < 22) {
                    const uint32_t bv = sBias[t * 4 + q];
                    const float bb0 = bf_lo(bv), bb1 = bf_hi(bv);
                    w0[i] = pack_bf16(mish_f(accF[t * 4 + 0] + bb0) * om0, mish_f(accF[t * 4 + 1] + bb1) * om0);
                    w1[i] = pack_bf16(mish_f(accF[t * 4 + 2] + bb0) * om1, mish_f(accF[t * 4 + 3] + bb1) * om1);
                } else { w0[i] = 0; w1[i] = 0; }
            }
            quad_transpose(w0, q);
            quad_transpose(w1, q);
            const int c = (u * 4 + q) * 8;
            if (c < FCH && n0 + c < F_) {
                *(uint4*)(frow0 + c) = make_uint4(w0[0], w0[1], w0[2], w0[3]);
                *(uint4*)(frow1 + c) = make_uint4(w1[0], w1[1], w1[2], w1[3]);
            }
        };
#pragma unroll
        for (int kc = 0; kc < 8; kc++) {
            const int st = kc & 3;
            mbar_wait(b_full + 8 * st, ((kc + 8) >> 2) & 1);
            wgmma_fence();
#pragma unroll
            for (int k16 = 0; k16 < 4; k16++) {
                const uint64_t db = make_desc(sB + st * K1_BSTAGE + k16 * 2048, 8192, 1024);
                const uint64_t da = make_desc(sX + kc * 16384 + wg * 8192 + k16 * 32, 16, 1024);
                wgmma_n192<1>(accQ, da, db, (kc | k16) != 0);
            }
            wgmma_commit();
            if (kc < 6) ffn_chunk(kc);
            if (kc > 0) { wgmma_wait<1>(); if (lane == 0) mbar_arrive(b_empty + 8 * ((kc - 1) & 3)); }
        }
        wgmma_wait<0>();
        TS(4, tid == 0);
        {
            bf16* orow0 = g_qkv + ((size_t)j * S_ + rb * 128 + rl) * 192;
            bf16* orow1 = orow0 + 8 * 192;
#pragma unroll
            for (int u = 0; u < 6; u++) {
                uint32_t w0[4], w1[4];
#pragma unroll
                for (int i = 0; i < 4; i++) {
                    const int t = u * 4 + i;
                    w0[i] = pack_bf16(accQ[t * 4 + 0], accQ[t * 4 + 1]);
                    w1[i] = pack_bf16(accQ[t * 4 + 2], accQ[t * 4 + 3]);
                }
                quad_transpose(w0, q);
                quad_transpose(w1, q);
                const int c = (u * 4 + q) * 8;
                *(uint4*)(orow0 + c) = make_uint4(w0[0], w0[1], w0[2], w0[3]);
                *(uint4*)(orow1 + c) = make_uint4(w1[0], w1[1], w1[2], w1[3]);
            }
        }
        TS(5, tid == 0);
    }
}

__device__ __forceinline__ void ldsm_x4(uint32_t (&r)[4], uint32_t addr) {
    asm("ldmatrix.sync.aligned.m8n8.x4.shared.b16 {%0,%1,%2,%3}, [%4];"
                 : "=r"(r[0]), "=r"(r[1]), "=r"(r[2]), "=r"(r[3]) : "r"(addr));
}
__device__ __forceinline__ void ldsm_x4_t(uint32_t (&r)[4], uint32_t addr) {
    asm("ldmatrix.sync.aligned.m8n8.x4.trans.shared.b16 {%0,%1,%2,%3}, [%4];"
                 : "=r"(r[0]), "=r"(r[1]), "=r"(r[2]), "=r"(r[3]) : "r"(addr));
}
__device__ __forceinline__ void mma16816(float (&d)[4], const uint32_t (&a)[4], uint32_t b0, uint32_t b1) {
    asm("mma.sync.aligned.m16n8k16.row.col.f32.bf16.bf16.f32 {%0,%1,%2,%3}, {%4,%5,%6,%7}, {%8,%9}, {%0,%1,%2,%3};"
                 : "+f"(d[0]), "+f"(d[1]), "+f"(d[2]), "+f"(d[3])
                 : "r"(a[0]), "r"(a[1]), "r"(a[2]), "r"(a[3]), "r"(b0), "r"(b1));
}
__device__ __forceinline__ void mma16816_z(float (&d)[4], const uint32_t (&a)[4], uint32_t b0, uint32_t b1) {
    asm("mma.sync.aligned.m16n8k16.row.col.f32.bf16.bf16.f32 {%0,%1,%2,%3}, {%4,%5,%6,%7}, {%8,%9}, {%10,%10,%10,%10};"
                 : "=f"(d[0]), "=f"(d[1]), "=f"(d[2]), "=f"(d[3])
                 : "r"(a[0]), "r"(a[1]), "r"(a[2]), "r"(a[3]), "r"(b0), "r"(b1), "f"(0.f));
}

constexpr int KV_PITCH = 128;

template <int EDGE, bool HEAD>
__device__ __forceinline__ void blk_scores(float (&s)[2][4], const uint32_t (&qa)[4], uint32_t kaddr, bool dead, int r0, int c0)
{
    uint32_t kf[4];
    ldsm_x4(kf, kaddr);
    mma16816_z(s[0], qa, kf[0], kf[1]);
    mma16816_z(s[1], qa, kf[2], kf[3]);
#pragma unroll
    for (int t = 0; t < 2; t++)
#pragma unroll
        for (int e = 0; e < 4; e++) {
            const int r = r0 + (e >> 1) * 8, c = t * 8 + c0 + (e & 1);
            if (EDGE == 1 && c <= r) s[t][e] = -1e30f;
            if (EDGE == 2 && c > r) s[t][e] = -1e30f;
            if (HEAD && dead) s[t][e] = -1e30f;
        }
}
__device__ __forceinline__ void blk_max(const float (&s)[2][4], float& n0, float& n1) {
    n0 = fmaxf(n0, fmaxf(fmaxf(s[0][0], s[0][1]), fmaxf(s[1][0], s[1][1])));
    n1 = fmaxf(n1, fmaxf(fmaxf(s[0][2], s[0][3]), fmaxf(s[1][2], s[1][3])));
}
__device__ __forceinline__ void blk_pv(const float (&s)[2][4], float mc0, float mc1, float (&l)[4],
                                       float (&o)[2][4], uint32_t vaddr) {
    const float C = 0.25f * 1.4426950408889634f;
    uint32_t pa[4];
#pragma unroll
    for (int t = 0; t < 2; t++) {
        const float p0 = ex2(fmaf(s[t][0], C, -mc0)), p1 = ex2(fmaf(s[t][1], C, -mc0));
        const float p2 = ex2(fmaf(s[t][2], C, -mc1)), p3 = ex2(fmaf(s[t][3], C, -mc1));
        pa[2 * t] = pack_bf16(p0, p1); pa[2 * t + 1] = pack_bf16(p2, p3);
    }
    uint32_t vf[4];
    ldsm_x4_t(vf, vaddr);
    mma16816(o[0], pa, vf[0], vf[1]);
    mma16816(o[1], pa, vf[2], vf[3]);
    mma16816(l, pa, 0x3F803F80u, 0x3F803F80u);
}
__device__ __forceinline__ void quad_max(float& n0, float& n1) {
    n0 = fmaxf(n0, __shfl_xor_sync(0xffffffffu, n0, 1)); n1 = fmaxf(n1, __shfl_xor_sync(0xffffffffu, n1, 1));
    n0 = fmaxf(n0, __shfl_xor_sync(0xffffffffu, n0, 2)); n1 = fmaxf(n1, __shfl_xor_sync(0xffffffffu, n1, 2));
}
template <int NC, int NN, bool FIRST, bool NEXT_IS_EDGE, bool HEAD>
__device__ __forceinline__ void pipe_step(const float (&sc)[5][2][4], float (&sn)[5][2][4], const uint32_t (&qa)[4],
                                          uint32_t ka, uint32_t va, int kc, int kn, int kb0, int r0, int c0,
                                          float& m0, float& m1, float& n0, float& n1, float (&l)[4], float (&o)[2][4])
{
    const float C = 0.25f * 1.4426950408889634f;
    const float mc0 = n0 * C, mc1 = n1 * C;
    if (!FIRST) {
        const float a0 = ex2(fmaf(m0, C, -mc0)), a1 = ex2(fmaf(m1, C, -mc1));
        l[0] *= a0; l[2] *= a1;
        o[0][0] *= a0; o[0][1] *= a0; o[1][0] *= a0; o[1][1] *= a0;
        o[0][2] *= a1; o[0][3] *= a1; o[1][2] *= a1; o[1][3] *= a1;
    }
    m0 = n0; m1 = n1;
#pragma unroll
    for (int b = 0; b < NC; b++) {
        if (b < NN) {
            if (NEXT_IS_EDGE && b == 0) blk_scores<1, HEAD>(sn[b], qa, ka + (kn + b) * 16 * KV_PITCH, kn + b < kb0, r0, c0);
            else                        blk_scores<0, HEAD>(sn[b], qa, ka + (kn + b) * 16 * KV_PITCH, kn + b < kb0, r0, c0);
        }
        blk_pv(sc[b], mc0, mc1, l, o, va + (kc + b) * 16 * KV_PITCH);
        if (b < NN) blk_max(sn[b], n0, n1);
    }
    if (NN > 0) quad_max(n0, n1);
}

__device__ __forceinline__ void kv_need(uint32_t kvbar, int blk, uint32_t& ka, uint32_t& va) {
    mbar_wait(kvbar + 8 * blk, 0);
    asm volatile("" : "+r"(ka), "+r"(va) :: "memory");
}
template <bool HEAD>
__device__ __forceinline__ void attn_task(const uint32_t (&qa)[4], uint32_t ka, uint32_t va, int kb0, int lane, int qt, uint32_t kvbar,
                                          bf16* __restrict__ out  , float g0, float g1)
{
    const int r0 = lane >> 2, c0 = (lane & 3) * 2;
    float m0 = -1e30f, m1 = -1e30f, n0 = -1e30f, n1 = -1e30f;
    float l[4] = {0.f, 0.f, 0.f, 0.f};
    float o[2][4] = {{0.f, 0.f, 0.f, 0.f}, {0.f, 0.f, 0.f, 0.f}};
    float sa[5][2][4], sb[5][2][4];
    kv_need(kvbar, 2, ka, va);
    if (qt < 4) kv_need(kvbar, 1, ka, va);
#pragma unroll
    for (int b = 0; b < 5; b++) {
        if (b == 4) blk_scores<2, HEAD>(sa[b], qa, ka + (12 + b) * 16 * KV_PITCH, false, r0, c0);
        else        blk_scores<0, HEAD>(sa[b], qa, ka + (12 + b) * 16 * KV_PITCH, 12 + b < kb0, r0, c0);
        blk_max(sa[b], n0, n1);
    }
    quad_max(n0, n1);
    kv_need(kvbar, 1, ka, va);
    if (HEAD) {
        pipe_step<5, 0, true, false, HEAD>(sa, sb, qa, ka, va, 12, 0, kb0, r0, c0, m0, m1, n0, n1, l, o);
        kv_need(kvbar, 0, ka, va);
#pragma unroll 1
        for (int kc = 8; kc >= 0 && kb0 < kc + 4; kc -= 4) {
#pragma unroll
            for (int b = 0; b < 4; b++) {
                blk_scores<0, HEAD>(sa[b], qa, ka + (kc + b) * 16 * KV_PITCH, kc + b < kb0, r0, c0);
                blk_max(sa[b], n0, n1);
            }
            quad_max(n0, n1);
            pipe_step<4, 0, false, false, HEAD>(sa, sb, qa, ka, va, kc, 0, kb0, r0, c0, m0, m1, n0, n1, l, o);
        }
    } else {
        pipe_step<5, 4, true,  false, HEAD>(sa, sb, qa, ka, va, 12, 8, kb0, r0, c0, m0, m1, n0, n1, l, o);
        if (qt < 4) kv_need(kvbar, 0, ka, va);
        pipe_step<4, 4, false, false, HEAD>(sb, sa, qa, ka, va, 8, 4, kb0, r0, c0, m0, m1, n0, n1, l, o);
        kv_need(kvbar, 0, ka, va);
        pipe_step<4, 4, false, true,  HEAD>(sa, sb, qa, ka, va, 4, 0, kb0, r0, c0, m0, m1, n0, n1, l, o);
        pipe_step<4, 0, false, false, HEAD>(sb, sa, qa, ka, va, 0, 0, kb0, r0, c0, m0, m1, n0, n1, l, o);
    }
    const float f0 = __fdividef(g0, l[0]), f1 = __fdividef(g1, l[2]);
#pragma unroll
    for (int t = 0; t < 2; t++) {
        *(uint32_t*)(out + (size_t)r0 * KA2 + t * 8 + c0) = pack_bf16(o[t][0] * f0, o[t][1] * f0);
        *(uint32_t*)(out + (size_t)(r0 + 8) * KA2 + t * 8 + c0) = pack_bf16(o[t][2] * f1, o[t][3] * f1);
    }
}

constexpr int K2_SMEM = 2 * 384 * KV_PITCH + 1024 + 64;

__global__ void __launch_bounds__(512, 1) k2_kernel(const __grid_constant__ CUtensorMap tmQKV)
{
    extern __shared__ uint8_t smem_raw[];
    const uint32_t sbase = (smem_u32(smem_raw) + 1023u) & ~1023u;
    uint8_t* sgen = smem_raw + (sbase - smem_u32(smem_raw));
    const uint32_t sK = sbase, sV = sK + 384 * KV_PITCH, kv_full = sbase + 2 * 384 * KV_PITCH;
    const int rb = blockIdx.x >> 3, j = blockIdx.x & 7;
    const int tid = threadIdx.x, warp = tid >> 5, lane = tid & 31;
    pdl_launch();
    if (tid == 0) {
        for (int i = 0; i < 3; i++) mbar_init(kv_full + 8 * i, 1);
        fence_barrier_init();
    }
    pdl_wait();
    TS(6, tid == 0);
    if (tid == 0) {
        for (int i = 0; i < 3; i++) {
            const uint32_t bar = kv_full + 8 * (2 - i);
            if (rb - i >= 0) {
                const int row = j * S_ + (rb - i) * 128;
                mbar_expect_tx(bar, 2 * 16384);
                tma_load_2d(sK + (2 - i) * 16384, &tmQKV, 64, row, bar);
                tma_load_2d(sV + (2 - i) * 16384, &tmQKV, 128, row, bar);
            } else {
                mbar_arrive(bar);
            }
        }
    }
    if (rb < 2) {
        for (int i = tid; i < (2 - rb) * 1024; i += 512) {
            *(uint4*)(sgen + i * 16) = make_uint4(0, 0, 0, 0);
            *(uint4*)(sgen + 384 * KV_PITCH + i * 16) = make_uint4(0, 0, 0, 0);
        }
    }
    const int qt = warp & 7, h0 = (warp >> 3) * 2;
    const int q0g = rb * 128 + qt * 16;
    const int r0 = lane >> 2, c0 = (lane & 3) * 2;
    const bf16* qsrc = g_qkv + ((size_t)j * S_ + q0g) * 192 + h0 * 16;
    uint32_t qa[4], qn[4];
    qa[0] = *(const uint32_t*)(qsrc + (size_t)r0 * 192 + c0);
    qa[1] = *(const uint32_t*)(qsrc + (size_t)(r0 + 8) * 192 + c0);
    qa[2] = *(const uint32_t*)(qsrc + (size_t)r0 * 192 + c0 + 8);
    qa[3] = *(const uint32_t*)(qsrc + (size_t)(r0 + 8) * 192 + c0 + 8);
    qn[0] = *(const uint32_t*)(qsrc + (size_t)r0 * 192 + 16 + c0);
    qn[1] = *(const uint32_t*)(qsrc + (size_t)(r0 + 8) * 192 + 16 + c0);
    qn[2] = *(const uint32_t*)(qsrc + (size_t)r0 * 192 + 16 + c0 + 8);
    qn[3] = *(const uint32_t*)(qsrc + (size_t)(r0 + 8) * 192 + 16 + c0 + 8);
    const float g0 = g_gate[q0g + r0], g1 = g_gate[q0g + r0 + 8];
    const int kb0 = q0g < 256 ? (256 - q0g) >> 4 : 0;
    __syncthreads();
    const uint32_t sKd = sK, sVd = sV;
    TS(7, tid == 0);
    const int krow = qt * 16 + (lane & 7) + ((lane >> 4) << 3);
    const int vrow = qt * 16 + (lane & 15);
#pragma unroll 1
    for (int hh = 0; hh < 2; hh++) {
        const int hl = h0 + hh;
        const uint32_t ka = sKd + krow * KV_PITCH + (((2 * hl + ((lane >> 3) & 1)) ^ (lane & 7)) << 4);
        const uint32_t va = sVd + vrow * KV_PITCH + (((2 * hl + (lane >> 4)) ^ (lane & 7)) << 4);
        if (rb < 2) attn_task<true>(qa, ka, va, kb0, lane, qt, kv_full, g_a2 + (size_t)q0g * KA2 + (j * 4 + hl) * 16, g0, g1);
        else        attn_task<false>(qa, ka, va, kb0, lane, qt, kv_full, g_a2 + (size_t)q0g * KA2 + (j * 4 + hl) * 16, g0, g1);
        TS(8 + hh, tid == 0);
        qa[0] = qn[0]; qa[1] = qn[1]; qa[2] = qn[2]; qa[3] = qn[3];
    }
}

constexpr int K3_STAGES = 8;
constexpr int K3_STAGE = 16384 + 8192;
constexpr int K3_SMEM = K3_STAGES * K3_STAGE + 1024 + 1024;
constexpr int K3_KSTEPS = 30;

__global__ void __launch_bounds__(384, 1)
k3_kernel(const __grid_constant__ CUtensorMap tmA2, const __grid_constant__ CUtensorMap tmWo,
          const __grid_constant__ CUtensorMap tmW2, bf16* __restrict__ out)
{
    extern __shared__ uint8_t smem_raw[];
    const uint32_t sbase = (smem_u32(smem_raw) + 1023u) & ~1023u;
    const uint32_t sBar = sbase + K3_STAGES * K3_STAGE;
    const uint32_t full = sBar, empty = sBar + 64;
    const int rb = blockIdx.x >> 3, nb = blockIdx.x & 7;
    const int tid = threadIdx.x, wg = tid >> 7, warp = tid >> 5, lane = tid & 31;
    if (tid == 0) {
        for (int i = 0; i < K3_STAGES; i++) { mbar_init(full + 8 * i, 1); mbar_init(empty + 8 * i, 8); }
        fence_barrier_init();
    }
    __syncthreads();
    pdl_wait();
    TS(10, tid == 0);
    if (wg == 2) {
        reg_dealloc<40>();
        if (tid == 256) {
            for (int ks = 0; ks < K3_KSTEPS; ks++) {
                const int st = ks % K3_STAGES;
                if (ks >= K3_STAGES) mbar_wait(empty + 8 * st, ((ks / K3_STAGES) - 1) & 1);
                mbar_expect_tx(full + 8 * st, K3_STAGE);
                const uint32_t dst = sbase + st * K3_STAGE;
                tma_load_2d(dst, &tmA2, ks * 64, rb * 128, full + 8 * st);
                if (ks < 8) tma_load_2d(dst + 16384, &tmWo, nb * 64, ks * 64, full + 8 * st);
                else        tma_load_2d(dst + 16384, &tmW2, nb * 64, (ks - 8) * 64, full + 8 * st);
            }
        }
    } else {
        reg_alloc<232>();
        float acc[32];
        for (int ks = 0; ks < K3_KSTEPS; ks++) {
            const int st = ks % K3_STAGES;
            mbar_wait(full + 8 * st, (ks / K3_STAGES) & 1);
            TS(11, tid == 0 && ks == 0); TS(12, tid == 0 && ks == 8); TS(13, tid == 0 && ks == 16);
            wgmma_fence();
#pragma unroll
            for (int k16 = 0; k16 < 4; k16++) {
                const uint64_t da = make_desc(sbase + st * K3_STAGE + wg * 8192 + k16 * 32, 16, 1024);
                const uint64_t db = make_desc(sbase + st * K3_STAGE + 16384 + k16 * 2048, 8192, 1024);
                wgmma_n64<1>(acc, da, db, (ks | k16) != 0);
            }
            wgmma_commit();
            if (ks > 0) { wgmma_wait<1>(); if (lane == 0) mbar_arrive(empty + 8 * ((ks - 1) % K3_STAGES)); }
        }
        wgmma_wait<0>();
        TS(14, tid == 0);
        const int q = lane & 3;
        const int r = rb * 128 + wg * 64 + (warp & 3) * 16 + (lane >> 2);
        bf16* orow0 = out + (size_t)r * D_ + nb * 64;
        bf16* orow1 = orow0 + 8 * D_;
#pragma unroll
        for (int u = 0; u < 2; u++) {
            uint32_t w0[4], w1[4];
#pragma unroll
            for (int i = 0; i < 4; i++) {
                const int t = u * 4 + i;
                w0[i] = pack_bf16(acc[t * 4 + 0], acc[t * 4 + 1]);
                w1[i] = pack_bf16(acc[t * 4 + 2], acc[t * 4 + 3]);
            }
            quad_transpose(w0, q);
            quad_transpose(w1, q);
            const int c = (u * 4 + q) * 8;
            *(uint4*)(orow0 + c) = make_uint4(w0[0], w0[1], w0[2], w0[3]);
            *(uint4*)(orow1 + c) = make_uint4(w1[0], w1[1], w1[2], w1[3]);
        }
        TS(15, tid == 0);
    }
}

typedef CUresult (*PFN_encodeTiled)(CUtensorMap*, CUtensorMapDataType, cuuint32_t, void*, const cuuint64_t*,
                                    const cuuint64_t*, const cuuint32_t*, const cuuint32_t*, CUtensorMapInterleave,
                                    CUtensorMapSwizzle, CUtensorMapL2promotion, CUtensorMapFloatOOBfill);

static void make_map(PFN_encodeTiled enc, CUtensorMap* m, const void* ptr, uint64_t cols, uint64_t rows,
                     uint32_t box_cols, uint32_t box_rows)
{
    cuuint64_t dims[2] = {cols, rows};
    cuuint64_t strides[1] = {cols * 2};
    cuuint32_t box[2] = {box_cols, box_rows};
    cuuint32_t es[2] = {1, 1};
    enc(m, CU_TENSOR_MAP_DATA_TYPE_BFLOAT16, 2, const_cast<void*>(ptr), dims, strides, box, es,
        CU_TENSOR_MAP_INTERLEAVE_NONE, CU_TENSOR_MAP_SWIZZLE_128B, CU_TENSOR_MAP_L2_PROMOTION_L2_128B,
        CU_TENSOR_MAP_FLOAT_OOB_FILL_NONE);
}

extern "C" void kernel_launch(void* const* d_in, const int* in_sizes, int n_in, void* d_out, int out_size)
{
    const bf16* x    = (const bf16*)d_in[0];
    const bf16* wqkv = (const bf16*)d_in[1];
    const bf16* wo   = (const bf16*)d_in[2];
    const bf16* w1   = (const bf16*)d_in[4];
    const bf16* b1   = (const bf16*)d_in[5];
    const bf16* w2   = (const bf16*)d_in[6];
    const bf16* gw   = (const bf16*)d_in[7];

    static PFN_encodeTiled enc = nullptr;
    if (!enc) {
        void* fn = nullptr;
        cudaDriverEntryPointQueryResult qr;
        cudaGetDriverEntryPoint("cuTensorMapEncodeTiled", &fn, cudaEnableDefault, &qr);
        enc = (PFN_encodeTiled)fn;
        cudaFuncSetAttribute(k1_kernel, cudaFuncAttributeMaxDynamicSharedMemorySize, K1_SMEM);
        cudaFuncSetAttribute(k2_kernel, cudaFuncAttributeMaxDynamicSharedMemorySize, K2_SMEM);
        cudaFuncSetAttribute(k3_kernel, cudaFuncAttributeMaxDynamicSharedMemorySize, K3_SMEM);
    }
    void* a2p = nullptr;
    cudaGetSymbolAddress(&a2p, g_a2);
    void* qkvp = nullptr;
    cudaGetSymbolAddress(&qkvp, g_qkv);
    CUtensorMap tmX, tmWqkv, tmW1, tmA2, tmWo, tmW2, tmQKV;
    make_map(enc, &tmQKV, qkvp, 192, 8 * S_, 64, 128);
    make_map(enc, &tmX, x, D_, S_, 64, 128);
    make_map(enc, &tmWqkv, wqkv, 3 * D_, D_, 64, 64);
    make_map(enc, &tmW1, w1, F_, D_, 64, 64);
    make_map(enc, &tmA2, a2p, KA2, S_, 64, 128);
    make_map(enc, &tmWo, wo, D_, D_, 64, 64);
    make_map(enc, &tmW2, w2, D_, F_, 64, 64);

    cudaStream_t st = cudaStreamPerThread;
    k1_kernel<<<128, 384, K1_SMEM, st>>>(tmX, tmWqkv, tmW1, b1, gw, w1, wqkv, w2, wo);
    cudaLaunchAttribute at[1];
    at[0].id = cudaLaunchAttributeProgrammaticStreamSerialization;
    at[0].val.programmaticStreamSerializationAllowed = 1;
    cudaLaunchConfig_t cfg = {};
    cfg.gridDim = dim3(128); cfg.stream = st; cfg.attrs = at; cfg.numAttrs = 1;
    cfg.blockDim = dim3(512); cfg.dynamicSmemBytes = K2_SMEM;
    cudaLaunchKernelEx(&cfg, k2_kernel, tmQKV);
    k3_kernel<<<128, 384, K3_SMEM, st>>>(tmA2, tmWo, tmW2, (bf16*)d_out);
}
```

```cpp
#include <cuda_runtime.h>
#include <cuda_bf16.h>
#include <cuda.h>
#include <stdint.h>

typedef __nv_bfloat16 bf16;

constexpr int S_ = 2048, D_ = 512, F_ = 1376;
constexpr int KA2 = D_ + F_;
constexpr int FCH = 176;

__device__ bf16  g_qkv[8 * S_ * 192];
__device__ bf16  g_a2[S_ * KA2];
__device__ float g_gate[S_];

#define TS(k, cond) do { } while (0)

__device__ __forceinline__ uint32_t smem_u32(const void* p) { return (uint32_t)__cvta_generic_to_shared(p); }
__device__ __forceinline__ void mbar_init(uint32_t bar, uint32_t count) {
    asm volatile("mbarrier.init.shared::cta.b64 [%0], %1;" :: "r"(bar), "r"(count) : "memory");
}
__device__ __forceinline__ void mbar_expect_tx(uint32_t bar, uint32_t bytes) {
    asm volatile("mbarrier.arrive.expect_tx.shared::cta.b64 _, [%0], %1;" :: "r"(bar), "r"(bytes) : "memory");
}
__device__ __forceinline__ void mbar_arrive(uint32_t bar) {
    asm volatile("mbarrier.arrive.shared::cta.b64 _, [%0];" :: "r"(bar) : "memory");
}
__device__ __forceinline__ bool mbar_try_wait(uint32_t bar, uint32_t parity) {
    uint32_t ok;
    asm volatile("{\n.reg .pred p;\nmbarrier.try_wait.parity.shared::cta.b64 p, [%1], %2;\nselp.u32 %0, 1, 0, p;\n}"
                 : "=r"(ok) : "r"(bar), "r"(parity) : "memory");
    return ok != 0;
}
__device__ __forceinline__ void mbar_wait(uint32_t bar, uint32_t parity) {
    for (uint32_t it = 0; it < (1u << 22); ++it) { if (mbar_try_wait(bar, parity)) break; }
}
__device__ __forceinline__ void tma_load_2d(uint32_t dst, const CUtensorMap* map, int c0, int c1, uint32_t bar) {
    asm volatile("cp.async.bulk.tensor.2d.shared::cluster.global.mbarrier::complete_tx::bytes [%0], [%1, {%3, %4}], [%2];"
                 :: "r"(dst), "l"(map), "r"(bar), "r"(c0), "r"(c1) : "memory");
}
__device__ __forceinline__ void l2_prefetch(const void* p, uint32_t bytes) {
    asm volatile("cp.async.bulk.prefetch.L2.global [%0], %1;" :: "l"(p), "r"(bytes) : "memory");
}
__device__ __forceinline__ void fence_barrier_init() { asm volatile("fence.mbarrier_init.release.cluster;" ::: "memory"); }
__device__ __forceinline__ void wgmma_fence()  { asm volatile("wgmma.fence.sync.aligned;" ::: "memory"); }
__device__ __forceinline__ void wgmma_commit() { asm volatile("wgmma.commit_group.sync.aligned;" ::: "memory"); }
template <int N> __device__ __forceinline__ void wgmma_wait() { asm volatile("wgmma.wait_group.sync.aligned %0;" :: "n"(N) : "memory"); }
template <int R> __device__ __forceinline__ void reg_alloc()   { asm volatile("setmaxnreg.inc.sync.aligned.u32 %0;" :: "n"(R)); }
template <int R> __device__ __forceinline__ void reg_dealloc() { asm volatile("setmaxnreg.dec.sync.aligned.u32 %0;" :: "n"(R)); }
__device__ __forceinline__ void bar_sync(int id, int n)   { asm volatile("bar.sync %0, %1;" :: "r"(id), "r"(n) : "memory"); }
__device__ __forceinline__ void bar_arrive(int id, int n) { asm volatile("bar.arrive %0, %1;" :: "r"(id), "r"(n) : "memory"); }

__device__ __forceinline__ uint64_t make_desc(uint32_t addr, uint32_t lbo, uint32_t sbo) {
    uint64_t d = (uint64_t)((addr & 0x3FFFF) >> 4);
    d |= (uint64_t)((lbo & 0x3FFFF) >> 4) << 16;
    d |= (uint64_t)((sbo & 0x3FFFF) >> 4) << 32;
    d |= (uint64_t)1 << 62;
    return d;
}

template <int TB>
__device__ __forceinline__ void wgmma_n64(float (&d)[32], uint64_t da, uint64_t db, int scale_d) {
    asm volatile("{\n.reg .pred p;\nsetp.ne.b32 p, %34, 0;\n"
        "wgmma.mma_async.sync.aligned.m64n64k16.f32.bf16.bf16 {%0, %1, %2, %3, %4, %5, %6, %7, %8, %9, %10, %11, %12, %13, %14, %15, %16, %17, %18, %19, %20, %21, %22, %23, %24, %25, %26, %27, %28, %29, %30, %31}, %32, %33, p, 1, 1, 0, %35;\n}\n"
        : "+f"(d[0]), "+f"(d[1]), "+f"(d[2]), "+f"(d[3]), "+f"(d[4]), "+f"(d[5]), "+f"(d[6]), "+f"(d[7]), "+f"(d[8]), "+f"(d[9]), "+f"(d[10]), "+f"(d[11]), "+f"(d[12]), "+f"(d[13]), "+f"(d[14]), "+f"(d[15]), "+f"(d[16]), "+f"(d[17]), "+f"(d[18]), "+f"(d[19]), "+f"(d[20]), "+f"(d[21]), "+f"(d[22]), "+f"(d[23]), "+f"(d[24]), "+f"(d[25]), "+f"(d[26]), "+f"(d[27]), "+f"(d[28]), "+f"(d[29]), "+f"(d[30]), "+f"(d[31])
        : "l"(da), "l"(db), "r"(scale_d), "n"(TB));
}

template <int TB>
__device__ __forceinline__ void wgmma_n128(float (&d)[64], uint64_t da, uint64_t db, int scale_d) {
    asm volatile("{\n.reg .pred p;\nsetp.ne.b32 p, %66, 0;\n"
        "wgmma.mma_async.sync.aligned.m64n128k16.f32.bf16.bf16 {%0, %1, %2, %3, %4, %5, %6, %7, %8, %9, %10, %11, %12, %13, %14, %15, %16, %17, %18, %19, %20, %21, %22, %23, %24, %25, %26, %27, %28, %29, %30, %31, %32, %33, %34, %35, %36, %37, %38, %39, %40, %41, %42, %43, %44, %45, %46, %47, %48, %49, %50, %51, %52, %53, %54, %55, %56, %57, %58, %59, %60, %61, %62, %63}, %64, %65, p, 1, 1, 0, %67;\n}\n"
        : "+f"(d[0]), "+f"(d[1]), "+f"(d[2]), "+f"(d[3]), "+f"(d[4]), "+f"(d[5]), "+f"(d[6]), "+f"(d[7]), "+f"(d[8]), "+f"(d[9]), "+f"(d[10]), "+f"(d[11]), "+f"(d[12]), "+f"(d[13]), "+f"(d[14]), "+f"(d[15]), "+f"(d[16]), "+f"(d[17]), "+f"(d[18]), "+f"(d[19]), "+f"(d[20]), "+f"(d[21]), "+f"(d[22]), "+f"(d[23]), "+f"(d[24]), "+f"(d[25]), "+f"(d[26]), "+f"(d[27]), "+f"(d[28]), "+f"(d[29]), "+f"(d[30]), "+f"(d[31]), "+f"(d[32]), "+f"(d[33]), "+f"(d[34]), "+f"(d[35]), "+f"(d[36]), "+f"(d[37]), "+f"(d[38]), "+f"(d[39]), "+f"(d[40]), "+f"(d[41]), "+f"(d[42]), "+f"(d[43]), "+f"(d[44]), "+f"(d[45]), "+f"(d[46]), "+f"(d[47]), "+f"(d[48]), "+f"(d[49]), "+f"(d[50]), "+f"(d[51]), "+f"(d[52]), "+f"(d[53]), "+f"(d[54]), "+f"(d[55]), "+f"(d[56]), "+f"(d[57]), "+f"(d[58]), "+f"(d[59]), "+f"(d[60]), "+f"(d[61]), "+f"(d[62]), "+f"(d[63])
        : "l"(da), "l"(db), "r"(scale_d), "n"(TB));
}

template <int TB>
__device__ __forceinline__ void wgmma_n176(float (&d)[88], uint64_t da, uint64_t db, int scale_d) {
    asm volatile("{\n.reg .pred p;\nsetp.ne.b32 p, %90, 0;\n"
        "wgmma.mma_async.sync.aligned.m64n176k16.f32.bf16.bf16 {%0, %1, %2, %3, %4, %5, %6, %7, %8, %9, %10, %11, %12, %13, %14, %15, %16, %17, %18, %19, %20, %21, %22, %23, %24, %25, %26, %27, %28, %29, %30, %31, %32, %33, %34, %35, %36, %37, %38, %39, %40, %41, %42, %43, %44, %45, %46, %47, %48, %49, %50, %51, %52, %53, %54, %55, %56, %57, %58, %59, %60, %61, %62, %63, %64, %65, %66, %67, %68, %69, %70, %71, %72, %73, %74, %75, %76, %77, %78, %79, %80, %81, %82, %83, %84, %85, %86, %87}, %88, %89, p, 1, 1, 0, %91;\n}\n"
        : "+f"(d[0]), "+f"(d[1]), "+f"(d[2]), "+f"(d[3]), "+f"(d[4]), "+f"(d[5]), "+f"(d[6]), "+f"(d[7]), "+f"(d[8]), "+f"(d[9]), "+f"(d[10]), "+f"(d[11]), "+f"(d[12]), "+f"(d[13]), "+f"(d[14]), "+f"(d[15]), "+f"(d[16]), "+f"(d[17]), "+f"(d[18]), "+f"(d[19]), "+f"(d[20]), "+f"(d[21]), "+f"(d[22]), "+f"(d[23]), "+f"(d[24]), "+f"(d[25]), "+f"(d[26]), "+f"(d[27]), "+f"(d[28]), "+f"(d[29]), "+f"(d[30]), "+f"(d[31]), "+f"(d[32]), "+f"(d[33]), "+f"(d[34]), "+f"(d[35]), "+f"(d[36]), "+f"(d[37]), "+f"(d[38]), "+f"(d[39]), "+f"(d[40]), "+f"(d[41]), "+f"(d[42]), "+f"(d[43]), "+f"(d[44]), "+f"(d[45]), "+f"(d[46]), "+f"(d[47]), "+f"(d[48]), "+f"(d[49]), "+f"(d[50]), "+f"(d[51]), "+f"(d[52]), "+f"(d[53]), "+f"(d[54]), "+f"(d[55]), "+f"(d[56]), "+f"(d[57]), "+f"(d[58]), "+f"(d[59]), "+f"(d[60]), "+f"(d[61]), "+f"(d[62]), "+f"(d[63]), "+f"(d[64]), "+f"(d[65]), "+f"(d[66]), "+f"(d[67]), "+f"(d[68]), "+f"(d[69]), "+f"(d[70]), "+f"(d[71]), "+f"(d[72]), "+f"(d[73]), "+f"(d[74]), "+f"(d[75]), "+f"(d[76]), "+f"(d[77]), "+f"(d[78]), "+f"(d[79]), "+f"(d[80]), "+f"(d[81]), "+f"(d[82]), "+f"(d[83]), "+f"(d[84]), "+f"(d[85]), "+f"(d[86]), "+f"(d[87])
        : "l"(da), "l"(db), "r"(scale_d), "n"(TB));
}

template <int TB>
__device__ __forceinline__ void wgmma_n192(float (&d)[96], uint64_t da, uint64_t db, int scale_d) {
    asm volatile("{\n.reg .pred p;\nsetp.ne.b32 p, %98, 0;\n"
        "wgmma.mma_async.sync.aligned.m64n192k16.f32.bf16.bf16 {%0, %1, %2, %3, %4, %5, %6, %7, %8, %9, %10, %11, %12, %13, %14, %15, %16, %17, %18, %19, %20, %21, %22, %23, %24, %25, %26, %27, %28, %29, %30, %31, %32, %33, %34, %35, %36, %37, %38, %39, %40, %41, %42, %43, %44, %45, %46, %47, %48, %49, %50, %51, %52, %53, %54, %55, %56, %57, %58, %59, %60, %61, %62, %63, %64, %65, %66, %67, %68, %69, %70, %71, %72, %73, %74, %75, %76, %77, %78, %79, %80, %81, %82, %83, %84, %85, %86, %87, %88, %89, %90, %91, %92, %93, %94, %95}, %96, %97, p, 1, 1, 0, %99;\n}\n"
        : "+f"(d[0]), "+f"(d[1]), "+f"(d[2]), "+f"(d[3]), "+f"(d[4]), "+f"(d[5]), "+f"(d[6]), "+f"(d[7]), "+f"(d[8]), "+f"(d[9]), "+f"(d[10]), "+f"(d[11]), "+f"(d[12]), "+f"(d[13]), "+f"(d[14]), "+f"(d[15]), "+f"(d[16]), "+f"(d[17]), "+f"(d[18]), "+f"(d[19]), "+f"(d[20]), "+f"(d[21]), "+f"(d[22]), "+f"(d[23]), "+f"(d[24]), "+f"(d[25]), "+f"(d[26]), "+f"(d[27]), "+f"(d[28]), "+f"(d[29]), "+f"(d[30]), "+f"(d[31]), "+f"(d[32]), "+f"(d[33]), "+f"(d[34]), "+f"(d[35]), "+f"(d[36]), "+f"(d[37]), "+f"(d[38]), "+f"(d[39]), "+f"(d[40]), "+f"(d[41]), "+f"(d[42]), "+f"(d[43]), "+f"(d[44]), "+f"(d[45]), "+f"(d[46]), "+f"(d[47]), "+f"(d[48]), "+f"(d[49]), "+f"(d[50]), "+f"(d[51]), "+f"(d[52]), "+f"(d[53]), "+f"(d[54]), "+f"(d[55]), "+f"(d[56]), "+f"(d[57]), "+f"(d[58]), "+f"(d[59]), "+f"(d[60]), "+f"(d[61]), "+f"(d[62]), "+f"(d[63]), "+f"(d[64]), "+f"(d[65]), "+f"(d[66]), "+f"(d[67]), "+f"(d[68]), "+f"(d[69]), "+f"(d[70]), "+f"(d[71]), "+f"(d[72]), "+f"(d[73]), "+f"(d[74]), "+f"(d[75]), "+f"(d[76]), "+f"(d[77]), "+f"(d[78]), "+f"(d[79]), "+f"(d[80]), "+f"(d[81]), "+f"(d[82]), "+f"(d[83]), "+f"(d[84]), "+f"(d[85]), "+f"(d[86]), "+f"(d[87]), "+f"(d[88]), "+f"(d[89]), "+f"(d[90]), "+f"(d[91]), "+f"(d[92]), "+f"(d[93]), "+f"(d[94]), "+f"(d[95])
        : "l"(da), "l"(db), "r"(scale_d), "n"(TB));
}

__device__ __forceinline__ uint32_t pack_bf16(float lo, float hi) {
    uint32_t r;
    asm("cvt.rn.bf16x2.f32 %0, %1, %2;" : "=r"(r) : "f"(hi), "f"(lo));
    return r;
}
__device__ __forceinline__ float bf_lo(uint32_t v) { return __uint_as_float(v << 16); }
__device__ __forceinline__ float bf_hi(uint32_t v) { return __uint_as_float(v & 0xffff0000u); }

__device__ __forceinline__ void quad_transpose(uint32_t (&w)[4], int q) {
    const bool o1 = q & 1, o2 = q & 2;
    {
        uint32_t s0 = o1 ? w[0] : w[1], s1 = o1 ? w[2] : w[3];
        s0 = __shfl_xor_sync(0xffffffffu, s0, 1); s1 = __shfl_xor_sync(0xffffffffu, s1, 1);
        if (o1) { w[0] = s0; w[2] = s1; } else { w[1] = s0; w[3] = s1; }
    }
    {
        uint32_t s0 = o2 ? w[0] : w[2], s1 = o2 ? w[1] : w[3];
        s0 = __shfl_xor_sync(0xffffffffu, s0, 2); s1 = __shfl_xor_sync(0xffffffffu, s1, 2);
        if (o2) { w[0] = s0; w[1] = s1; } else { w[2] = s0; w[3] = s1; }
    }
}

__device__ __forceinline__ float ex2(float x) { float y; asm("ex2.approx.ftz.f32 %0, %1;" : "=f"(y) : "f"(x)); return y; }
__device__ __forceinline__ float rcp(float x) { float y; asm("rcp.approx.ftz.f32 %0, %1;" : "=f"(y) : "f"(x)); return y; }

__device__ __forceinline__ float ex2v(float x) { float y; asm volatile("ex2.approx.ftz.f32 %0, %1;" : "=f"(y) : "f"(x)); return y; }
__device__ __forceinline__ float rcpv(float x) { float y; asm volatile("rcp.approx.ftz.f32 %0, %1;" : "=f"(y) : "f"(x)); return y; }
__device__ __forceinline__ float mish_f(float h) {
    const float e = ex2v(1.4426950408889634f * fminf(h, 20.f));
    const float n = fmaf(e, e, e + e);
    return h * n * rcpv(n + 2.f);
}

__device__ __forceinline__ void pdl_wait()   { asm volatile("griddepcontrol.wait;" ::: "memory"); }
__device__ __forceinline__ void pdl_launch() { asm volatile("griddepcontrol.launch_dependents;" ::: "memory"); }

constexpr int K1_STAGES = 4;
constexpr int K1_XBYTES = 128 * 512 * 2;
constexpr int K1_BSTAGE = 3 * 8192;
constexpr int K1_SMEM   = K1_XBYTES + K1_STAGES * K1_BSTAGE + 2048   + 1024  ;

__global__ void __launch_bounds__(384, 1)
k1_kernel(const __grid_constant__ CUtensorMap tmX, const __grid_constant__ CUtensorMap tmWqkv,
          const __grid_constant__ CUtensorMap tmW1, const bf16* __restrict__ b1,
          const bf16* __restrict__ gate_w, const bf16* __restrict__ w1p, const bf16* __restrict__ wqkvp,
          const bf16* __restrict__ w2p, const bf16* __restrict__ wop)
{

    extern __shared__ uint8_t smem_raw[];
    const uint32_t sbase = (smem_u32(smem_raw) + 1023u) & ~1023u;
    uint8_t* sgen = smem_raw + (sbase - smem_u32(smem_raw));
    const uint32_t sX = sbase;
    const uint32_t sB = sbase + K1_XBYTES;
    const uint32_t sBar = sB + K1_STAGES * K1_BSTAGE;
    const uint32_t x_full = sBar;
    const uint32_t b_full = sBar + 64;
    const uint32_t b_empty = sBar + 96;
    float* sGate = (float*)(sgen + K1_XBYTES + K1_STAGES * K1_BSTAGE + 128);
    uint8_t* sGw = sgen + K1_XBYTES + K1_STAGES * K1_BSTAGE + 640;
    uint32_t* sBias = (uint32_t*)(sgen + K1_XBYTES + K1_STAGES * K1_BSTAGE + 1664);

    const int rb = blockIdx.x >> 3, j = blockIdx.x & 7;
    const int tid = threadIdx.x, wg = tid >> 7, warp = tid >> 5, lane = tid & 31;
    TS(0, tid == 0);
    pdl_launch();

    if (tid == 0) {
        for (int i = 0; i < 8; i++) mbar_init(x_full + 8 * i, 1);
        for (int i = 0; i < K1_STAGES; i++) { mbar_init(b_full + 8 * i, 1); mbar_init(b_empty + 8 * i, 8); }
        fence_barrier_init();
    }
    __syncthreads();

    if (wg == 2) {
        reg_dealloc<40>();
        if (tid == 288) {
            const int b = blockIdx.x;
            mbar_wait(b_full + 8, 0);
            l2_prefetch((const uint8_t*)wqkvp + b * 12288, 12288);
            l2_prefetch((const uint8_t*)w2p + b * 11008, 11008);
            l2_prefetch((const uint8_t*)wop + b * 4096, 4096);
        }
        if (tid == 256) {
            for (int it = 0; it < 16; it++) {
                if (it < 8) {
                    mbar_expect_tx(x_full + 8 * it, 16384);
                    tma_load_2d(sX + it * 16384, &tmX, it * 64, rb * 128, x_full + 8 * it);
                }
                const int st = it & 3;
                if (it >= K1_STAGES) mbar_wait(b_empty + 8 * st, ((it >> 2) - 1) & 1);
                mbar_expect_tx(b_full + 8 * st, K1_BSTAGE);
                const uint32_t dst = sB + st * K1_BSTAGE;
                if (it < 8) {
                    for (int b = 0; b < 3; b++) tma_load_2d(dst + b * 8192, &tmW1, j * FCH + b * 64, it * 64, b_full + 8 * st);
                } else {
                    for (int b = 0; b < 3; b++) tma_load_2d(dst + b * 8192, &tmWqkv, b * 512 + j * 64, (it - 8) * 64, b_full + 8 * st);
                }
            }
        }
    } else {
        reg_alloc<232>();
        if (tid < 88) {
            const int c = j * FCH + tid * 2;
            sBias[tid] = c < F_ ? __ldg((const uint32_t*)(b1 + c)) : 0u;
        }
        const int t128 = tid & 127, w4 = warp & 3, q = lane & 3;
        float accF[88], accQ[96];
#pragma unroll 1
        for (int kc = 0; kc < 8; kc++) {
            const int st = kc & 3;
            mbar_wait(x_full + 8 * kc, 0);
            mbar_wait(b_full + 8 * st, (kc >> 2) & 1);
            TS(1, tid == 0 && kc == 0); TS(2, tid == 0 && kc == 4);
            wgmma_fence();
#pragma unroll
            for (int k16 = 0; k16 < 4; k16++) {
                const uint64_t db = make_desc(sB + st * K1_BSTAGE + k16 * 2048, 8192, 1024);
                const uint64_t da = make_desc(sX + kc * 16384 + wg * 8192 + k16 * 32, 16, 1024);
                wgmma_n176<1>(accF, da, db, (kc | k16) != 0);
            }
            wgmma_commit();
            if (kc > 0) { wgmma_wait<1>(); if (lane == 0) mbar_arrive(b_empty + 8 * ((kc - 1) & 3)); }
        }
        wgmma_wait<0>();
        if (lane == 0) mbar_arrive(b_empty + 8 * 3);
        bar_sync(3, 256);
        TS(3, tid == 0);
        const int n0 = j * FCH;
        const int rl = wg * 64 + w4 * 16 + (lane >> 2);
        bf16* frow0 = g_a2 + (size_t)(rb * 128 + rl) * KA2 + D_ + n0;
        bf16* frow1 = frow0 + 8 * KA2;
        auto ffn_chunk = [&](int u) {
            uint32_t w0[4], w1[4];
#pragma unroll
            for (int i = 0; i < 4; i++) {
                const int t = u * 4 + i;
                if (t < 22) {
                    const uint32_t bv = sBias[t * 4 + q];
                    const float bb0 = bf_lo(bv), bb1 = bf_hi(bv);
                    w0[i] = pack_bf16(mish_f(accF[t * 4 + 0] + bb0), mish_f(accF[t * 4 + 1] + bb1));
                    w1[i] = pack_bf16(mish_f(accF[t * 4 + 2] + bb0), mish_f(accF[t * 4 + 3] + bb1));
                } else { w0[i] = 0; w1[i] = 0; }
            }
            quad_transpose(w0, q);
            quad_transpose(w1, q);
            const int c = (u * 4 + q) * 8;
            if (c < FCH && n0 + c < F_) {
                *(uint4*)(frow0 + c) = make_uint4(w0[0], w0[1], w0[2], w0[3]);
                *(uint4*)(frow1 + c) = make_uint4(w1[0], w1[1], w1[2], w1[3]);
            }
        };
#pragma unroll
        for (int kc = 0; kc < 8; kc++) {
            const int st = kc & 3;
            mbar_wait(b_full + 8 * st, ((kc + 8) >> 2) & 1);
            wgmma_fence();
#pragma unroll
            for (int k16 = 0; k16 < 4; k16++) {
                const uint64_t db = make_desc(sB + st * K1_BSTAGE + k16 * 2048, 8192, 1024);
                const uint64_t da = make_desc(sX + kc * 16384 + wg * 8192 + k16 * 32, 16, 1024);
                wgmma_n192<1>(accQ, da, db, (kc | k16) != 0);
            }
            wgmma_commit();
            if (kc < 6) ffn_chunk(kc);
            if (kc > 0) { wgmma_wait<1>(); if (lane == 0) mbar_arrive(b_empty + 8 * ((kc - 1) & 3)); }
        }
        wgmma_wait<0>();
        TS(4, tid == 0);
        {
            bf16* orow0 = g_qkv + ((size_t)j * S_ + rb * 128 + rl) * 192;
            bf16* orow1 = orow0 + 8 * 192;
#pragma unroll
            for (int u = 0; u < 6; u++) {
                uint32_t w0[4], w1[4];
#pragma unroll
                for (int i = 0; i < 4; i++) {
                    const int t = u * 4 + i;
                    w0[i] = pack_bf16(accQ[t * 4 + 0], accQ[t * 4 + 1]);
                    w1[i] = pack_bf16(accQ[t * 4 + 2], accQ[t * 4 + 3]);
                }
                quad_transpose(w0, q);
                quad_transpose(w1, q);
                const int c = (u * 4 + q) * 8;
                *(uint4*)(orow0 + c) = make_uint4(w0[0], w0[1], w0[2], w0[3]);
                *(uint4*)(orow1 + c) = make_uint4(w1[0], w1[1], w1[2], w1[3]);
            }
        }
        TS(5, tid == 0);
    }
}

__device__ __forceinline__ void ldsm_x4(uint32_t (&r)[4], uint32_t addr) {
    asm("ldmatrix.sync.aligned.m8n8.x4.shared.b16 {%0,%1,%2,%3}, [%4];"
                 : "=r"(r[0]), "=r"(r[1]), "=r"(r[2]), "=r"(r[3]) : "r"(addr));
}
__device__ __forceinline__ void ldsm_x4_t(uint32_t (&r)[4], uint32_t addr) {
    asm("ldmatrix.sync.aligned.m8n8.x4.trans.shared.b16 {%0,%1,%2,%3}, [%4];"
                 : "=r"(r[0]), "=r"(r[1]), "=r"(r[2]), "=r"(r[3]) : "r"(addr));
}
__device__ __forceinline__ void mma16816(float (&d)[4], const uint32_t (&a)[4], uint32_t b0, uint32_t b1) {
    asm("mma.sync.aligned.m16n8k16.row.col.f32.bf16.bf16.f32 {%0,%1,%2,%3}, {%4,%5,%6,%7}, {%8,%9}, {%0,%1,%2,%3};"
                 : "+f"(d[0]), "+f"(d[1]), "+f"(d[2]), "+f"(d[3])
                 : "r"(a[0]), "r"(a[1]), "r"(a[2]), "r"(a[3]), "r"(b0), "r"(b1));
}
__device__ __forceinline__ void mma16816_z(float (&d)[4], const uint32_t (&a)[4], uint32_t b0, uint32_t b1) {
    asm("mma.sync.aligned.m16n8k16.row.col.f32.bf16.bf16.f32 {%0,%1,%2,%3}, {%4,%5,%6,%7}, {%8,%9}, {%10,%10,%10,%10};"
                 : "=f"(d[0]), "=f"(d[1]), "=f"(d[2]), "=f"(d[3])
                 : "r"(a[0]), "r"(a[1]), "r"(a[2]), "r"(a[3]), "r"(b0), "r"(b1), "f"(0.f));
}

constexpr int KV_PITCH = 128;

template <int EDGE, bool HEAD>
__device__ __forceinline__ void blk_scores(float (&s)[2][4], const uint32_t (&qa)[4], uint32_t kaddr, bool dead, int r0, int c0)
{
    uint32_t kf[4];
    ldsm_x4(kf, kaddr);
    mma16816_z(s[0], qa, kf[0], kf[1]);
    mma16816_z(s[1], qa, kf[2], kf[3]);
#pragma unroll
    for (int t = 0; t < 2; t++)
#pragma unroll
        for (int e = 0; e < 4; e++) {
            const int r = r0 + (e >> 1) * 8, c = t * 8 + c0 + (e & 1);
            if (EDGE == 1 && c <= r) s[t][e] = -1e30f;
            if (EDGE == 2 && c > r) s[t][e] = -1e30f;
            if (HEAD && dead) s[t][e] = -1e30f;
        }
}
__device__ __forceinline__ void blk_max(const float (&s)[2][4], float& n0, float& n1) {
    n0 = fmaxf(n0, fmaxf(fmaxf(s[0][0], s[0][1]), fmaxf(s[1][0], s[1][1])));
    n1 = fmaxf(n1, fmaxf(fmaxf(s[0][2], s[0][3]), fmaxf(s[1][2], s[1][3])));
}
__device__ __forceinline__ void blk_pv(const float (&s)[2][4], float mc0, float mc1, float (&l)[4],
                                       float (&o)[2][4], uint32_t vaddr) {
    const float C = 0.25f * 1.4426950408889634f;
    uint32_t pa[4];
#pragma unroll
    for (int t = 0; t < 2; t++) {
        const float p0 = ex2(fmaf(s[t][0], C, -mc0)), p1 = ex2(fmaf(s[t][1], C, -mc0));
        const float p2 = ex2(fmaf(s[t][2], C, -mc1)), p3 = ex2(fmaf(s[t][3], C, -mc1));
        pa[2 * t] = pack_bf16(p0, p1); pa[2 * t + 1] = pack_bf16(p2, p3);
    }
    uint32_t vf[4];
    ldsm_x4_t(vf, vaddr);
    mma16816(o[0], pa, vf[0], vf[1]);
    mma16816(o[1], pa, vf[2], vf[3]);
    mma16816(l, pa, 0x3F803F80u, 0x3F803F80u);
}
__device__ __forceinline__ void quad_max(float& n0, float& n1) {
    n0 = fmaxf(n0, __shfl_xor_sync(0xffffffffu, n0, 1)); n1 = fmaxf(n1, __shfl_xor_sync(0xffffffffu, n1, 1));
    n0 = fmaxf(n0, __shfl_xor_sync(0xffffffffu, n0, 2)); n1 = fmaxf(n1, __shfl_xor_sync(0xffffffffu, n1, 2));
}
template <int NC, int NN, bool FIRST, bool NEXT_IS_EDGE, bool HEAD>
__device__ __forceinline__ void pipe_step(const float (&sc)[5][2][4], float (&sn)[5][2][4], const uint32_t (&qa)[4],
                                          uint32_t ka, uint32_t va, int kc, int kn, int kb0, int r0, int c0,
                                          float& m0, float& m1, float& n0, float& n1, float (&l)[4], float (&o)[2][4])
{
    const float C = 0.25f * 1.4426950408889634f;
    const float mc0 = n0 * C, mc1 = n1 * C;
    if (!FIRST) {
        const float a0 = ex2(fmaf(m0, C, -mc0)), a1 = ex2(fmaf(m1, C, -mc1));
        l[0] *= a0; l[2] *= a1;
        o[0][0] *= a0; o[0][1] *= a0; o[1][0] *= a0; o[1][1] *= a0;
        o[0][2] *= a1; o[0][3] *= a1; o[1][2] *= a1; o[1][3] *= a1;
    }
    m0 = n0; m1 = n1;
#pragma unroll
    for (int b = 0; b < NC; b++) {
        if (b < NN) {
            if (NEXT_IS_EDGE && b == 0) blk_scores<1, HEAD>(sn[b], qa, ka + (kn + b) * 16 * KV_PITCH, kn + b < kb0, r0, c0);
            else                        blk_scores<0, HEAD>(sn[b], qa, ka + (kn + b) * 16 * KV_PITCH, kn + b < kb0, r0, c0);
        }
        blk_pv(sc[b], mc0, mc1, l, o, va + (kc + b) * 16 * KV_PITCH);
        if (b < NN) blk_max(sn[b], n0, n1);
    }
    if (NN > 0) quad_max(n0, n1);
}

__device__ __forceinline__ void kv_need(uint32_t kvbar, int blk, uint32_t& ka, uint32_t& va) {
    mbar_wait(kvbar + 8 * blk, 0);
    asm volatile("" : "+r"(ka), "+r"(va) :: "memory");
}
template <bool HEAD>
__device__ __forceinline__ void attn_task(const uint32_t (&qa)[4], uint32_t ka, uint32_t va, int kb0, int lane, int qt, uint32_t kvbar,
                                          bf16* __restrict__ out  , float g0, float g1)
{
    const int r0 = lane >> 2, c0 = (lane & 3) * 2;
    float m0 = -1e30f, m1 = -1e30f, n0 = -1e30f, n1 = -1e30f;
    float l[4] = {0.f, 0.f, 0.f, 0.f};
    float o[2][4] = {{0.f, 0.f, 0.f, 0.f}, {0.f, 0.f, 0.f, 0.f}};
    float sa[5][2][4], sb[5][2][4];
    kv_need(kvbar, 2, ka, va);
    if (qt < 4) kv_need(kvbar, 1, ka, va);
#pragma unroll
    for (int b = 0; b < 5; b++) {
        if (b == 4) blk_scores<2, HEAD>(sa[b], qa, ka + (12 + b) * 16 * KV_PITCH, false, r0, c0);
        else        blk_scores<0, HEAD>(sa[b], qa, ka + (12 + b) * 16 * KV_PITCH, 12 + b < kb0, r0, c0);
        blk_max(sa[b], n0, n1);
    }
    quad_max(n0, n1);
    kv_need(kvbar, 1, ka, va);
    if (HEAD) {
        pipe_step<5, 0, true, false, HEAD>(sa, sb, qa, ka, va, 12, 0, kb0, r0, c0, m0, m1, n0, n1, l, o);
        kv_need(kvbar, 0, ka, va);
#pragma unroll 1
        for (int kc = 8; kc >= 0 && kb0 < kc + 4; kc -= 4) {
#pragma unroll
            for (int b = 0; b < 4; b++) {
                blk_scores<0, HEAD>(sa[b], qa, ka + (kc + b) * 16 * KV_PITCH, kc + b < kb0, r0, c0);
                blk_max(sa[b], n0, n1);
            }
            quad_max(n0, n1);
            pipe_step<4, 0, false, false, HEAD>(sa, sb, qa, ka, va, kc, 0, kb0, r0, c0, m0, m1, n0, n1, l, o);
        }
    } else {
        pipe_step<5, 4, true,  false, HEAD>(sa, sb, qa, ka, va, 12, 8, kb0, r0, c0, m0, m1, n0, n1, l, o);
        if (qt < 4) kv_need(kvbar, 0, ka, va);
        pipe_step<4, 4, false, false, HEAD>(sb, sa, qa, ka, va, 8, 4, kb0, r0, c0, m0, m1, n0, n1, l, o);
        kv_need(kvbar, 0, ka, va);
        pipe_step<4, 4, false, true,  HEAD>(sa, sb, qa, ka, va, 4, 0, kb0, r0, c0, m0, m1, n0, n1, l, o);
        pipe_step<4, 0, false, false, HEAD>(sb, sa, qa, ka, va, 0, 0, kb0, r0, c0, m0, m1, n0, n1, l, o);
    }
    const float f0 = __fdividef(g0, l[0]), f1 = __fdividef(g1, l[2]);
#pragma unroll
    for (int t = 0; t < 2; t++) {
        *(uint32_t*)(out + (size_t)r0 * KA2 + t * 8 + c0) = pack_bf16(o[t][0] * f0, o[t][1] * f0);
        *(uint32_t*)(out + (size_t)(r0 + 8) * KA2 + t * 8 + c0) = pack_bf16(o[t][2] * f1, o[t][3] * f1);
    }
}

constexpr int K2_SMEM = 2 * 384 * KV_PITCH + 1024 + 64;

__global__ void __launch_bounds__(512, 1) k2_kernel(const __grid_constant__ CUtensorMap tmQKV, const bf16* __restrict__ x,
                                                    const bf16* __restrict__ gate_w)
{
    extern __shared__ uint8_t smem_raw[];
    const uint32_t sbase = (smem_u32(smem_raw) + 1023u) & ~1023u;
    uint8_t* sgen = smem_raw + (sbase - smem_u32(smem_raw));
    const uint32_t sK = sbase, sV = sK + 384 * KV_PITCH, kv_full = sbase + 2 * 384 * KV_PITCH;
    const int rb = blockIdx.x >> 3, j = blockIdx.x & 7;
    const int tid = threadIdx.x, warp = tid >> 5, lane = tid & 31;
    pdl_launch();
    if (tid == 0) {
        for (int i = 0; i < 3; i++) mbar_init(kv_full + 8 * i, 1);
        fence_barrier_init();
    }
    const int grow = blockIdx.x * 16 + warp;
    const uint4 ga = __ldg((const uint4*)gate_w + lane * 2), gb = __ldg((const uint4*)gate_w + lane * 2 + 1);
    const uint4 xa = __ldg((const uint4*)(x + (size_t)grow * D_) + lane * 2), xb = __ldg((const uint4*)(x + (size_t)grow * D_) + lane * 2 + 1);
    pdl_wait();
    TS(6, tid == 0);
    if (tid == 0) {
        for (int i = 0; i < 3; i++) {
            const uint32_t bar = kv_full + 8 * (2 - i);
            if (rb - i >= 0) {
                const int row = j * S_ + (rb - i) * 128;
                mbar_expect_tx(bar, 2 * 16384);
                tma_load_2d(sK + (2 - i) * 16384, &tmQKV, 64, row, bar);
                tma_load_2d(sV + (2 - i) * 16384, &tmQKV, 128, row, bar);
            } else {
                mbar_arrive(bar);
            }
        }
    }
    if (rb < 2) {
        for (int i = tid; i < (2 - rb) * 1024; i += 512) {
            *(uint4*)(sgen + i * 16) = make_uint4(0, 0, 0, 0);
            *(uint4*)(sgen + 384 * KV_PITCH + i * 16) = make_uint4(0, 0, 0, 0);
        }
    }
    const int qt = warp & 7, h0 = (warp >> 3) * 2;
    const int q0g = rb * 128 + qt * 16;
    const int r0 = lane >> 2, c0 = (lane & 3) * 2;
    const bf16* qsrc = g_qkv + ((size_t)j * S_ + q0g) * 192 + h0 * 16;
    uint32_t qa[4], qn[4];
    qa[0] = *(const uint32_t*)(qsrc + (size_t)r0 * 192 + c0);
    qa[1] = *(const uint32_t*)(qsrc + (size_t)(r0 + 8) * 192 + c0);
    qa[2] = *(const uint32_t*)(qsrc + (size_t)r0 * 192 + c0 + 8);
    qa[3] = *(const uint32_t*)(qsrc + (size_t)(r0 + 8) * 192 + c0 + 8);
    qn[0] = *(const uint32_t*)(qsrc + (size_t)r0 * 192 + 16 + c0);
    qn[1] = *(const uint32_t*)(qsrc + (size_t)(r0 + 8) * 192 + 16 + c0);
    qn[2] = *(const uint32_t*)(qsrc + (size_t)r0 * 192 + 16 + c0 + 8);
    qn[3] = *(const uint32_t*)(qsrc + (size_t)(r0 + 8) * 192 + 16 + c0 + 8);
    {
        float gs = bf_lo(xa.x) * bf_lo(ga.x);
        gs = fmaf(bf_hi(xa.x), bf_hi(ga.x), gs);
        gs = fmaf(bf_lo(xa.y), bf_lo(ga.y), gs); gs = fmaf(bf_hi(xa.y), bf_hi(ga.y), gs);
        gs = fmaf(bf_lo(xa.z), bf_lo(ga.z), gs); gs = fmaf(bf_hi(xa.z), bf_hi(ga.z), gs);
        gs = fmaf(bf_lo(xa.w), bf_lo(ga.w), gs); gs = fmaf(bf_hi(xa.w), bf_hi(ga.w), gs);
        gs = fmaf(bf_lo(xb.x), bf_lo(gb.x), gs); gs = fmaf(bf_hi(xb.x), bf_hi(gb.x), gs);
        gs = fmaf(bf_lo(xb.y), bf_lo(gb.y), gs); gs = fmaf(bf_hi(xb.y), bf_hi(gb.y), gs);
        gs = fmaf(bf_lo(xb.z), bf_lo(gb.z), gs); gs = fmaf(bf_hi(xb.z), bf_hi(gb.z), gs);
        gs = fmaf(bf_lo(xb.w), bf_lo(gb.w), gs); gs = fmaf(bf_hi(xb.w), bf_hi(gb.w), gs);
#pragma unroll
        for (int o = 16; o > 0; o >>= 1) gs += __shfl_xor_sync(0xffffffffu, gs, o);
        if (lane == 0) g_gate[grow] = 1.f / (1.f + __expf(-gs));
    }
    const float g0 = 1.f, g1 = 1.f;
    const int kb0 = q0g < 256 ? (256 - q0g) >> 4 : 0;
    __syncthreads();
    const uint32_t sKd = sK, sVd = sV;
    TS(7, tid == 0);
    const int krow = qt * 16 + (lane & 7) + ((lane >> 4) << 3);
    const int vrow = qt * 16 + (lane & 15);
#pragma unroll 1
    for (int hh = 0; hh < 2; hh++) {
        const int hl = h0 + hh;
        const uint32_t ka = sKd + krow * KV_PITCH + (((2 * hl + ((lane >> 3) & 1)) ^ (lane & 7)) << 4);
        const uint32_t va = sVd + vrow * KV_PITCH + (((2 * hl + (lane >> 4)) ^ (lane & 7)) << 4);
        if (rb < 2) attn_task<true>(qa, ka, va, kb0, lane, qt, kv_full, g_a2 + (size_t)q0g * KA2 + (j * 4 + hl) * 16, g0, g1);
        else        attn_task<false>(qa, ka, va, kb0, lane, qt, kv_full, g_a2 + (size_t)q0g * KA2 + (j * 4 + hl) * 16, g0, g1);
        TS(8 + hh, tid == 0);
        qa[0] = qn[0]; qa[1] = qn[1]; qa[2] = qn[2]; qa[3] = qn[3];
    }
}

constexpr int K3_STAGES = 8;
constexpr int K3_STAGE = 16384 + 8192;
constexpr int K3_SMEM = K3_STAGES * K3_STAGE + 1024 + 1024;
constexpr int K3_KSTEPS = 30;

__global__ void __launch_bounds__(384, 1)
k3_kernel(const __grid_constant__ CUtensorMap tmA2, const __grid_constant__ CUtensorMap tmWo,
          const __grid_constant__ CUtensorMap tmW2, bf16* __restrict__ out)
{
    extern __shared__ uint8_t smem_raw[];
    const uint32_t sbase = (smem_u32(smem_raw) + 1023u) & ~1023u;
    const uint32_t sBar = sbase + K3_STAGES * K3_STAGE;
    const uint32_t full = sBar, empty = sBar + 64;
    const int rb = blockIdx.x >> 3, nb = blockIdx.x & 7;
    const int tid = threadIdx.x, wg = tid >> 7, warp = tid >> 5, lane = tid & 31;
    if (tid == 0) {
        for (int i = 0; i < K3_STAGES; i++) { mbar_init(full + 8 * i, 1); mbar_init(empty + 8 * i, 8); }
        fence_barrier_init();
    }
    __syncthreads();
    TS(10, tid == 0);
    if (wg == 2) {
        reg_dealloc<40>();
        if (warp == 8) {
            if (lane == 0) {
                for (int ks = 0; ks < K3_KSTEPS; ks++) {
                    const int st = ks % K3_STAGES;
                    if (ks >= K3_STAGES) mbar_wait(empty + 8 * st, ((ks / K3_STAGES) - 1) & 1);
                    mbar_expect_tx(full + 8 * st, K3_STAGE);
                    const uint32_t dst = sbase + st * K3_STAGE;
                    tma_load_2d(dst, &tmA2, ks * 64, rb * 128, full + 8 * st);
                    if (ks < 8) tma_load_2d(dst + 16384, &tmWo, nb * 64, ks * 64, full + 8 * st);
                    else        tma_load_2d(dst + 16384, &tmW2, nb * 64, (ks - 8) * 64, full + 8 * st);
                }
            }
        }
    } else {
        reg_alloc<232>();
        float accA[32], accB[32];
        for (int ks = 0; ks < 8; ks++) {
            mbar_wait(full + 8 * ks, 0);
            TS(11, tid == 0 && ks == 0);
            wgmma_fence();
#pragma unroll
            for (int k16 = 0; k16 < 4; k16++) {
                const uint64_t da = make_desc(sbase + ks * K3_STAGE + wg * 8192 + k16 * 32, 16, 1024);
                const uint64_t db = make_desc(sbase + ks * K3_STAGE + 16384 + k16 * 2048, 8192, 1024);
                wgmma_n64<1>(accA, da, db, (ks | k16) != 0);
            }
            wgmma_commit();
            if (ks > 0) { wgmma_wait<1>(); if (lane == 0) mbar_arrive(empty + 8 * (ks - 1)); }
        }
        for (int ks = 8; ks < K3_KSTEPS; ks++) {
            const int st = ks % K3_STAGES;
            mbar_wait(full + 8 * st, (ks / K3_STAGES) & 1);
            TS(12, tid == 0 && ks == 8); TS(13, tid == 0 && ks == 16);
            wgmma_fence();
#pragma unroll
            for (int k16 = 0; k16 < 4; k16++) {
                const uint64_t da = make_desc(sbase + st * K3_STAGE + wg * 8192 + k16 * 32, 16, 1024);
                const uint64_t db = make_desc(sbase + st * K3_STAGE + 16384 + k16 * 2048, 8192, 1024);
                wgmma_n64<1>(accB, da, db, ((ks - 8) | k16) != 0);
            }
            wgmma_commit();
            wgmma_wait<1>();
            if (lane == 0) mbar_arrive(empty + 8 * ((ks - 1) % K3_STAGES));
        }
        wgmma_wait<0>();
        TS(14, tid == 0);
        const int q = lane & 3;
        const int rl = wg * 64 + (warp & 3) * 16 + (lane >> 2);
        const float g0 = g_gate[rb * 128 + rl], g1 = g_gate[rb * 128 + rl + 8];
        bf16* orow0 = out + (size_t)(rb * 128 + rl) * D_ + nb * 64;
        bf16* orow1 = orow0 + 8 * D_;
#pragma unroll
        for (int u = 0; u < 2; u++) {
            uint32_t w0[4], w1[4];
#pragma unroll
            for (int i = 0; i < 4; i++) {
                const int t = u * 4 + i;
                w0[i] = pack_bf16(fmaf(g0, accA[t * 4 + 0] - accB[t * 4 + 0], accB[t * 4 + 0]), fmaf(g0, accA[t * 4 + 1] - accB[t * 4 + 1], accB[t * 4 + 1]));
                w1[i] = pack_bf16(fmaf(g1, accA[t * 4 + 2] - accB[t * 4 + 2], accB[t * 4 + 2]), fmaf(g1, accA[t * 4 + 3] - accB[t * 4 + 3], accB[t * 4 + 3]));
            }
            quad_transpose(w0, q);
            quad_transpose(w1, q);
            const int c = (u * 4 + q) * 8;
            *(uint4*)(orow0 + c) = make_uint4(w0[0], w0[1], w0[2], w0[3]);
            *(uint4*)(orow1 + c) = make_uint4(w1[0], w1[1], w1[2], w1[3]);
        }
        TS(15, tid == 0);
    }
}

typedef CUresult (*PFN_encodeTiled)(CUtensorMap*, CUtensorMapDataType, cuuint32_t, void*, const cuuint64_t*,
                                    const cuuint64_t*, const cuuint32_t*, const cuuint32_t*, CUtensorMapInterleave,
                                    CUtensorMapSwizzle, CUtensorMapL2promotion, CUtensorMapFloatOOBfill);

static void make_map(PFN_encodeTiled enc, CUtensorMap* m, const void* ptr, uint64_t cols, uint64_t rows,
                     uint32_t box_cols, uint32_t box_rows)
{
    cuuint64_t dims[2] = {cols, rows};
    cuuint64_t strides[1] = {cols * 2};
    cuuint32_t box[2] = {box_cols, box_rows};
    cuuint32_t es[2] = {1, 1};
    enc(m, CU_TENSOR_MAP_DATA_TYPE_BFLOAT16, 2, const_cast<void*>(ptr), dims, strides, box, es,
        CU_TENSOR_MAP_INTERLEAVE_NONE, CU_TENSOR_MAP_SWIZZLE_128B, CU_TENSOR_MAP_L2_PROMOTION_L2_128B,
        CU_TENSOR_MAP_FLOAT_OOB_FILL_NONE);
}

extern "C" void kernel_launch(void* const* d_in, const int* in_sizes, int n_in, void* d_out, int out_size)
{
    const bf16* x    = (const bf16*)d_in[0];
    const bf16* wqkv = (const bf16*)d_in[1];
    const bf16* wo   = (const bf16*)d_in[2];
    const bf16* w1   = (const bf16*)d_in[4];
    const bf16* b1   = (const bf16*)d_in[5];
    const bf16* w2   = (const bf16*)d_in[6];
    const bf16* gw   = (const bf16*)d_in[7];

    static PFN_encodeTiled enc = nullptr;
    if (!enc) {
        void* fn = nullptr;
        cudaDriverEntryPointQueryResult qr;
        cudaGetDriverEntryPoint("cuTensorMapEncodeTiled", &fn, cudaEnableDefault, &qr);
        enc = (PFN_encodeTiled)fn;
        cudaFuncSetAttribute(k1_kernel, cudaFuncAttributeMaxDynamicSharedMemorySize, K1_SMEM);
        cudaFuncSetAttribute(k2_kernel, cudaFuncAttributeMaxDynamicSharedMemorySize, K2_SMEM);
        cudaFuncSetAttribute(k3_kernel, cudaFuncAttributeMaxDynamicSharedMemorySize, K3_SMEM);
    }
    void* a2p = nullptr;
    cudaGetSymbolAddress(&a2p, g_a2);
    void* qkvp = nullptr;
    cudaGetSymbolAddress(&qkvp, g_qkv);
    CUtensorMap tmX, tmWqkv, tmW1, tmA2, tmWo, tmW2, tmQKV;
    make_map(enc, &tmQKV, qkvp, 192, 8 * S_, 64, 128);
    make_map(enc, &tmX, x, D_, S_, 64, 128);
    make_map(enc, &tmWqkv, wqkv, 3 * D_, D_, 64, 64);
    make_map(enc, &tmW1, w1, F_, D_, 64, 64);
    make_map(enc, &tmA2, a2p, KA2, S_, 64, 128);
    make_map(enc, &tmWo, wo, D_, D_, 64, 64);
    make_map(enc, &tmW2, w2, D_, F_, 64, 64);

    cudaStream_t st = cudaStreamPerThread;
    k1_kernel<<<128, 384, K1_SMEM, st>>>(tmX, tmWqkv, tmW1, b1, gw, w1, wqkv, w2, wo);
    cudaLaunchAttribute at[1];
    at[0].id = cudaLaunchAttributeProgrammaticStreamSerialization;
    at[0].val.programmaticStreamSerializationAllowed = 1;
    cudaLaunchConfig_t cfg = {};
    cfg.gridDim = dim3(128); cfg.stream = st; cfg.attrs = at; cfg.numAttrs = 1;
    cfg.blockDim = dim3(512); cfg.dynamicSmemBytes = K2_SMEM;
    cudaLaunchKernelEx(&cfg, k2_kernel, tmQKV, x, gw);
    k3_kernel<<<128, 384, K3_SMEM, st>>>(tmA2, tmWo, tmW2, (bf16*)d_out);
}
```

```cpp
#include <cuda_runtime.h>
#include <cuda_bf16.h>
#include <cuda.h>
#include <stdint.h>

typedef __nv_bfloat16 bf16;

constexpr int S_ = 2048, D_ = 512, F_ = 1376;
constexpr int KA2 = D_ + F_;
constexpr int FCH = 176;

__device__ bf16  g_qkv[8 * S_ * 192];
__device__ bf16  g_a2[S_ * KA2];
__device__ float g_gate[S_];

#define TS(k, cond) do { } while (0)

__device__ __forceinline__ uint32_t smem_u32(const void* p) { return (uint32_t)__cvta_generic_to_shared(p); }
__device__ __forceinline__ void mbar_init(uint32_t bar, uint32_t count) {
    asm volatile("mbarrier.init.shared::cta.b64 [%0], %1;" :: "r"(bar), "r"(count) : "memory");
}
__device__ __forceinline__ void mbar_expect_tx(uint32_t bar, uint32_t bytes) {
    asm volatile("mbarrier.arrive.expect_tx.shared::cta.b64 _, [%0], %1;" :: "r"(bar), "r"(bytes) : "memory");
}
__device__ __forceinline__ void mbar_arrive(uint32_t bar) {
    asm volatile("mbarrier.arrive.shared::cta.b64 _, [%0];" :: "r"(bar) : "memory");
}
__device__ __forceinline__ bool mbar_try_wait(uint32_t bar, uint32_t parity) {
    uint32_t ok;
    asm volatile("{\n.reg .pred p;\nmbarrier.try_wait.parity.shared::cta.b64 p, [%1], %2;\nselp.u32 %0, 1, 0, p;\n}"
                 : "=r"(ok) : "r"(bar), "r"(parity) : "memory");
    return ok != 0;
}
__device__ __forceinline__ void mbar_wait(uint32_t bar, uint32_t parity) {
    for (uint32_t it = 0; it < (1u << 22); ++it) { if (mbar_try_wait(bar, parity)) break; }
}
__device__ __forceinline__ void tma_load_2d(uint32_t dst, const CUtensorMap* map, int c0, int c1, uint32_t bar) {
    asm volatile("cp.async.bulk.tensor.2d.shared::cluster.global.mbarrier::complete_tx::bytes [%0], [%1, {%3, %4}], [%2];"
                 :: "r"(dst), "l"(map), "r"(bar), "r"(c0), "r"(c1) : "memory");
}
__device__ __forceinline__ void l2_prefetch(const void* p, uint32_t bytes) {
    asm volatile("cp.async.bulk.prefetch.L2.global [%0], %1;" :: "l"(p), "r"(bytes) : "memory");
}
__device__ __forceinline__ void fence_barrier_init() { asm volatile("fence.mbarrier_init.release.cluster;" ::: "memory"); }
__device__ __forceinline__ void wgmma_fence()  { asm volatile("wgmma.fence.sync.aligned;" ::: "memory"); }
__device__ __forceinline__ void wgmma_commit() { asm volatile("wgmma.commit_group.sync.aligned;" ::: "memory"); }
template <int N> __device__ __forceinline__ void wgmma_wait() { asm volatile("wgmma.wait_group.sync.aligned %0;" :: "n"(N) : "memory"); }
template <int R> __device__ __forceinline__ void reg_alloc()   { asm volatile("setmaxnreg.inc.sync.aligned.u32 %0;" :: "n"(R)); }
template <int R> __device__ __forceinline__ void reg_dealloc() { asm volatile("setmaxnreg.dec.sync.aligned.u32 %0;" :: "n"(R)); }
__device__ __forceinline__ void bar_sync(int id, int n)   { asm volatile("bar.sync %0, %1;" :: "r"(id), "r"(n) : "memory"); }
__device__ __forceinline__ void bar_arrive(int id, int n) { asm volatile("bar.arrive %0, %1;" :: "r"(id), "r"(n) : "memory"); }

__device__ __forceinline__ uint64_t make_desc(uint32_t addr, uint32_t lbo, uint32_t sbo) {
    uint64_t d = (uint64_t)((addr & 0x3FFFF) >> 4);
    d |= (uint64_t)((lbo & 0x3FFFF) >> 4) << 16;
    d |= (uint64_t)((sbo & 0x3FFFF) >> 4) << 32;
    d |= (uint64_t)1 << 62;
    return d;
}

template <int TB>
__device__ __forceinline__ void wgmma_n64(float (&d)[32], uint64_t da, uint64_t db, int scale_d) {
    asm volatile("{\n.reg .pred p;\nsetp.ne.b32 p, %34, 0;\n"
        "wgmma.mma_async.sync.aligned.m64n64k16.f32.bf16.bf16 {%0, %1, %2, %3, %4, %5, %6, %7, %8, %9, %10, %11, %12, %13, %14, %15, %16, %17, %18, %19, %20, %21, %22, %23, %24, %25, %26, %27, %28, %29, %30, %31}, %32, %33, p, 1, 1, 0, %35;\n}\n"
        : "+f"(d[0]), "+f"(d[1]), "+f"(d[2]), "+f"(d[3]), "+f"(d[4]), "+f"(d[5]), "+f"(d[6]), "+f"(d[7]), "+f"(d[8]), "+f"(d[9]), "+f"(d[10]), "+f"(d[11]), "+f"(d[12]), "+f"(d[13]), "+f"(d[14]), "+f"(d[15]), "+f"(d[16]), "+f"(d[17]), "+f"(d[18]), "+f"(d[19]), "+f"(d[20]), "+f"(d[21]), "+f"(d[22]), "+f"(d[23]), "+f"(d[24]), "+f"(d[25]), "+f"(d[26]), "+f"(d[27]), "+f"(d[28]), "+f"(d[29]), "+f"(d[30]), "+f"(d[31])
        : "l"(da), "l"(db), "r"(scale_d), "n"(TB));
}

template <int TB>
__device__ __forceinline__ void wgmma_n128(float (&d)[64], uint64_t da, uint64_t db, int scale_d) {
    asm volatile("{\n.reg .pred p;\nsetp.ne.b32 p, %66, 0;\n"
        "wgmma.mma_async.sync.aligned.m64n128k16.f32.bf16.bf16 {%0, %1, %2, %3, %4, %5, %6, %7, %8, %9, %10, %11, %12, %13, %14, %15, %16, %17, %18, %19, %20, %21, %22, %23, %24, %25, %26, %27, %28, %29, %30, %31, %32, %33, %34, %35, %36, %37, %38, %39, %40, %41, %42, %43, %44, %45, %46, %47, %48, %49, %50, %51, %52, %53, %54, %55, %56, %57, %58, %59, %60, %61, %62, %63}, %64, %65, p, 1, 1, 0, %67;\n}\n"
        : "+f"(d[0]), "+f"(d[1]), "+f"(d[2]), "+f"(d[3]), "+f"(d[4]), "+f"(d[5]), "+f"(d[6]), "+f"(d[7]), "+f"(d[8]), "+f"(d[9]), "+f"(d[10]), "+f"(d[11]), "+f"(d[12]), "+f"(d[13]), "+f"(d[14]), "+f"(d[15]), "+f"(d[16]), "+f"(d[17]), "+f"(d[18]), "+f"(d[19]), "+f"(d[20]), "+f"(d[21]), "+f"(d[22]), "+f"(d[23]), "+f"(d[24]), "+f"(d[25]), "+f"(d[26]), "+f"(d[27]), "+f"(d[28]), "+f"(d[29]), "+f"(d[30]), "+f"(d[31]), "+f"(d[32]), "+f"(d[33]), "+f"(d[34]), "+f"(d[35]), "+f"(d[36]), "+f"(d[37]), "+f"(d[38]), "+f"(d[39]), "+f"(d[40]), "+f"(d[41]), "+f"(d[42]), "+f"(d[43]), "+f"(d[44]), "+f"(d[45]), "+f"(d[46]), "+f"(d[47]), "+f"(d[48]), "+f"(d[49]), "+f"(d[50]), "+f"(d[51]), "+f"(d[52]), "+f"(d[53]), "+f"(d[54]), "+f"(d[55]), "+f"(d[56]), "+f"(d[57]), "+f"(d[58]), "+f"(d[59]), "+f"(d[60]), "+f"(d[61]), "+f"(d[62]), "+f"(d[63])
        : "l"(da), "l"(db), "r"(scale_d), "n"(TB));
}

template <int TB>
__device__ __forceinline__ void wgmma_n176(float (&d)[88], uint64_t da, uint64_t db, int scale_d) {
    asm volatile("{\n.reg .pred p;\nsetp.ne.b32 p, %90, 0;\n"
        "wgmma.mma_async.sync.aligned.m64n176k16.f32.bf16.bf16 {%0, %1, %2, %3, %4, %5, %6, %7, %8, %9, %10, %11, %12, %13, %14, %15, %16, %17, %18, %19, %20, %21, %22, %23, %24, %25, %26, %27, %28, %29, %30, %31, %32, %33, %34, %35, %36, %37, %38, %39, %40, %41, %42, %43, %44, %45, %46, %47, %48, %49, %50, %51, %52, %53, %54, %55, %56, %57, %58, %59, %60, %61, %62, %63, %64, %65, %66, %67, %68, %69, %70, %71, %72, %73, %74, %75, %76, %77, %78, %79, %80, %81, %82, %83, %84, %85, %86, %87}, %88, %89, p, 1, 1, 0, %91;\n}\n"
        : "+f"(d[0]), "+f"(d[1]), "+f"(d[2]), "+f"(d[3]), "+f"(d[4]), "+f"(d[5]), "+f"(d[6]), "+f"(d[7]), "+f"(d[8]), "+f"(d[9]), "+f"(d[10]), "+f"(d[11]), "+f"(d[12]), "+f"(d[13]), "+f"(d[14]), "+f"(d[15]), "+f"(d[16]), "+f"(d[17]), "+f"(d[18]), "+f"(d[19]), "+f"(d[20]), "+f"(d[21]), "+f"(d[22]), "+f"(d[23]), "+f"(d[24]), "+f"(d[25]), "+f"(d[26]), "+f"(d[27]), "+f"(d[28]), "+f"(d[29]), "+f"(d[30]), "+f"(d[31]), "+f"(d[32]), "+f"(d[33]), "+f"(d[34]), "+f"(d[35]), "+f"(d[36]), "+f"(d[37]), "+f"(d[38]), "+f"(d[39]), "+f"(d[40]), "+f"(d[41]), "+f"(d[42]), "+f"(d[43]), "+f"(d[44]), "+f"(d[45]), "+f"(d[46]), "+f"(d[47]), "+f"(d[48]), "+f"(d[49]), "+f"(d[50]), "+f"(d[51]), "+f"(d[52]), "+f"(d[53]), "+f"(d[54]), "+f"(d[55]), "+f"(d[56]), "+f"(d[57]), "+f"(d[58]), "+f"(d[59]), "+f"(d[60]), "+f"(d[61]), "+f"(d[62]), "+f"(d[63]), "+f"(d[64]), "+f"(d[65]), "+f"(d[66]), "+f"(d[67]), "+f"(d[68]), "+f"(d[69]), "+f"(d[70]), "+f"(d[71]), "+f"(d[72]), "+f"(d[73]), "+f"(d[74]), "+f"(d[75]), "+f"(d[76]), "+f"(d[77]), "+f"(d[78]), "+f"(d[79]), "+f"(d[80]), "+f"(d[81]), "+f"(d[82]), "+f"(d[83]), "+f"(d[84]), "+f"(d[85]), "+f"(d[86]), "+f"(d[87])
        : "l"(da), "l"(db), "r"(scale_d), "n"(TB));
}

template <int TB>
__device__ __forceinline__ void wgmma_n192(float (&d)[96], uint64_t da, uint64_t db, int scale_d) {
    asm volatile("{\n.reg .pred p;\nsetp.ne.b32 p, %98, 0;\n"
        "wgmma.mma_async.sync.aligned.m64n192k16.f32.bf16.bf16 {%0, %1, %2, %3, %4, %5, %6, %7, %8, %9, %10, %11, %12, %13, %14, %15, %16, %17, %18, %19, %20, %21, %22, %23, %24, %25, %26, %27, %28, %29, %30, %31, %32, %33, %34, %35, %36, %37, %38, %39, %40, %41, %42, %43, %44, %45, %46, %47, %48, %49, %50, %51, %52, %53, %54, %55, %56, %57, %58, %59, %60, %61, %62, %63, %64, %65, %66, %67, %68, %69, %70, %71, %72, %73, %74, %75, %76, %77, %78, %79, %80, %81, %82, %83, %84, %85, %86, %87, %88, %89, %90, %91, %92, %93, %94, %95}, %96, %97, p, 1, 1, 0, %99;\n}\n"
        : "+f"(d[0]), "+f"(d[1]), "+f"(d[2]), "+f"(d[3]), "+f"(d[4]), "+f"(d[5]), "+f"(d[6]), "+f"(d[7]), "+f"(d[8]), "+f"(d[9]), "+f"(d[10]), "+f"(d[11]), "+f"(d[12]), "+f"(d[13]), "+f"(d[14]), "+f"(d[15]), "+f"(d[16]), "+f"(d[17]), "+f"(d[18]), "+f"(d[19]), "+f"(d[20]), "+f"(d[21]), "+f"(d[22]), "+f"(d[23]), "+f"(d[24]), "+f"(d[25]), "+f"(d[26]), "+f"(d[27]), "+f"(d[28]), "+f"(d[29]), "+f"(d[30]), "+f"(d[31]), "+f"(d[32]), "+f"(d[33]), "+f"(d[34]), "+f"(d[35]), "+f"(d[36]), "+f"(d[37]), "+f"(d[38]), "+f"(d[39]), "+f"(d[40]), "+f"(d[41]), "+f"(d[42]), "+f"(d[43]), "+f"(d[44]), "+f"(d[45]), "+f"(d[46]), "+f"(d[47]), "+f"(d[48]), "+f"(d[49]), "+f"(d[50]), "+f"(d[51]), "+f"(d[52]), "+f"(d[53]), "+f"(d[54]), "+f"(d[55]), "+f"(d[56]), "+f"(d[57]), "+f"(d[58]), "+f"(d[59]), "+f"(d[60]), "+f"(d[61]), "+f"(d[62]), "+f"(d[63]), "+f"(d[64]), "+f"(d[65]), "+f"(d[66]), "+f"(d[67]), "+f"(d[68]), "+f"(d[69]), "+f"(d[70]), "+f"(d[71]), "+f"(d[72]), "+f"(d[73]), "+f"(d[74]), "+f"(d[75]), "+f"(d[76]), "+f"(d[77]), "+f"(d[78]), "+f"(d[79]), "+f"(d[80]), "+f"(d[81]), "+f"(d[82]), "+f"(d[83]), "+f"(d[84]), "+f"(d[85]), "+f"(d[86]), "+f"(d[87]), "+f"(d[88]), "+f"(d[89]), "+f"(d[90]), "+f"(d[91]), "+f"(d[92]), "+f"(d[93]), "+f"(d[94]), "+f"(d[95])
        : "l"(da), "l"(db), "r"(scale_d), "n"(TB));
}

__device__ __forceinline__ uint32_t pack_bf16(float lo, float hi) {
    uint32_t r;
    asm("cvt.rn.bf16x2.f32 %0, %1, %2;" : "=r"(r) : "f"(hi), "f"(lo));
    return r;
}
__device__ __forceinline__ float bf_lo(uint32_t v) { return __uint_as_float(v << 16); }
__device__ __forceinline__ float bf_hi(uint32_t v) { return __uint_as_float(v & 0xffff0000u); }

__device__ __forceinline__ void quad_transpose(uint32_t (&w)[4], int q) {
    const bool o1 = q & 1, o2 = q & 2;
    {
        uint32_t s0 = o1 ? w[0] : w[1], s1 = o1 ? w[2] : w[3];
        s0 = __shfl_xor_sync(0xffffffffu, s0, 1); s1 = __shfl_xor_sync(0xffffffffu, s1, 1);
        if (o1) { w[0] = s0; w[2] = s1; } else { w[1] = s0; w[3] = s1; }
    }
    {
        uint32_t s0 = o2 ? w[0] : w[2], s1 = o2 ? w[1] : w[3];
        s0 = __shfl_xor_sync(0xffffffffu, s0, 2); s1 = __shfl_xor_sync(0xffffffffu, s1, 2);
        if (o2) { w[0] = s0; w[1] = s1; } else { w[2] = s0; w[3] = s1; }
    }
}

__device__ __forceinline__ float ex2(float x) { float y; asm("ex2.approx.ftz.f32 %0, %1;" : "=f"(y) : "f"(x)); return y; }
__device__ __forceinline__ float rcp(float x) { float y; asm("rcp.approx.ftz.f32 %0, %1;" : "=f"(y) : "f"(x)); return y; }

__device__ __forceinline__ float ex2v(float x) { float y; asm volatile("ex2.approx.ftz.f32 %0, %1;" : "=f"(y) : "f"(x)); return y; }
__device__ __forceinline__ float rcpv(float x) { float y; asm volatile("rcp.approx.ftz.f32 %0, %1;" : "=f"(y) : "f"(x)); return y; }
__device__ __forceinline__ float mish_f(float h) {
    const float e = ex2v(1.4426950408889634f * fminf(h, 20.f));
    const float n = fmaf(e, e, e + e);
    return h * n * rcpv(n + 2.f);
}

__device__ __forceinline__ void pdl_wait()   { asm volatile("griddepcontrol.wait;" ::: "memory"); }
__device__ __forceinline__ void pdl_launch() { asm volatile("griddepcontrol.launch_dependents;" ::: "memory"); }

constexpr int K1_STAGES = 4;
constexpr int K1_XBYTES = 128 * 512 * 2;
constexpr int K1_BSTAGE = 3 * 8192;
constexpr int K1_SMEM   = K1_XBYTES + K1_STAGES * K1_BSTAGE + 2048   + 1024  ;

__global__ void __launch_bounds__(384, 1)
k1_kernel(const __grid_constant__ CUtensorMap tmX, const __grid_constant__ CUtensorMap tmWqkv,
          const __grid_constant__ CUtensorMap tmW1, const bf16* __restrict__ b1,
          const bf16* __restrict__ gate_w, const bf16* __restrict__ w1p, const bf16* __restrict__ wqkvp,
          const bf16* __restrict__ w2p, const bf16* __restrict__ wop)
{

    extern __shared__ uint8_t smem_raw[];
    const uint32_t sbase = (smem_u32(smem_raw) + 1023u) & ~1023u;
    uint8_t* sgen = smem_raw + (sbase - smem_u32(smem_raw));
    const uint32_t sX = sbase;
    const uint32_t sB = sbase + K1_XBYTES;
    const uint32_t sBar = sB + K1_STAGES * K1_BSTAGE;
    const uint32_t x_full = sBar;
    const uint32_t b_full = sBar + 64;
    const uint32_t b_empty = sBar + 96;
    float* sGate = (float*)(sgen + K1_XBYTES + K1_STAGES * K1_BSTAGE + 128);
    uint8_t* sGw = sgen + K1_XBYTES + K1_STAGES * K1_BSTAGE + 640;
    uint32_t* sBias = (uint32_t*)(sgen + K1_XBYTES + K1_STAGES * K1_BSTAGE + 1664);

    const int rb = blockIdx.x >> 3, j = blockIdx.x & 7;
    const int tid = threadIdx.x, wg = tid >> 7, warp = tid >> 5, lane = tid & 31;
    TS(0, tid == 0);
    pdl_launch();

    if (tid == 0) {
        for (int i = 0; i < 8; i++) mbar_init(x_full + 8 * i, 1);
        for (int i = 0; i < K1_STAGES; i++) { mbar_init(b_full + 8 * i, 1); mbar_init(b_empty + 8 * i, 8); }
        fence_barrier_init();
    }
    __syncthreads();

    if (wg == 2) {
        reg_dealloc<40>();
        if (tid == 288) {
            const int b = blockIdx.x;
            mbar_wait(b_full + 8, 0);
            l2_prefetch((const uint8_t*)wqkvp + b * 12288, 12288);
            l2_prefetch((const uint8_t*)w2p + b * 11008, 11008);
            l2_prefetch((const uint8_t*)wop + b * 4096, 4096);
        }
        if (tid == 256) {
            for (int it = 0; it < 16; it++) {
                if (it < 8) {
                    mbar_expect_tx(x_full + 8 * it, 16384);
                    tma_load_2d(sX + it * 16384, &tmX, it * 64, rb * 128, x_full + 8 * it);
                }
                const int st = it & 3;
                if (it >= K1_STAGES) mbar_wait(b_empty + 8 * st, ((it >> 2) - 1) & 1);
                mbar_expect_tx(b_full + 8 * st, K1_BSTAGE);
                const uint32_t dst = sB + st * K1_BSTAGE;
                if (it < 8) {
                    for (int b = 0; b < 3; b++) tma_load_2d(dst + b * 8192, &tmW1, j * FCH + b * 64, it * 64, b_full + 8 * st);
                } else {
                    for (int b = 0; b < 3; b++) tma_load_2d(dst + b * 8192, &tmWqkv, b * 512 + j * 64, (it - 8) * 64, b_full + 8 * st);
                }
            }
        }
    } else {
        reg_alloc<232>();
        if (tid < 88) {
            const int c = j * FCH + tid * 2;
            sBias[tid] = c < F_ ? __ldg((const uint32_t*)(b1 + c)) : 0u;
        }
        const int t128 = tid & 127, w4 = warp & 3, q = lane & 3;
        float accF[88], accQ[96];
#pragma unroll 1
        for (int kc = 0; kc < 8; kc++) {
            const int st = kc & 3;
            mbar_wait(x_full + 8 * kc, 0);
            mbar_wait(b_full + 8 * st, (kc >> 2) & 1);
            TS(1, tid == 0 && kc == 0); TS(2, tid == 0 && kc == 4);
            wgmma_fence();
#pragma unroll
            for (int k16 = 0; k16 < 4; k16++) {
                const uint64_t db = make_desc(sB + st * K1_BSTAGE + k16 * 2048, 8192, 1024);
                const uint64_t da = make_desc(sX + kc * 16384 + wg * 8192 + k16 * 32, 16, 1024);
                wgmma_n176<1>(accF, da, db, (kc | k16) != 0);
            }
            wgmma_commit();
            if (kc > 0) { wgmma_wait<1>(); if (lane == 0) mbar_arrive(b_empty + 8 * ((kc - 1) & 3)); }
        }
        wgmma_wait<0>();
        if (lane == 0) mbar_arrive(b_empty + 8 * 3);
        bar_sync(3, 256);
        TS(3, tid == 0);
        const int n0 = j * FCH;
        const int rl = wg * 64 + w4 * 16 + (lane >> 2);
        bf16* frow0 = g_a2 + (size_t)(rb * 128 + rl) * KA2 + D_ + n0;
        bf16* frow1 = frow0 + 8 * KA2;
        auto ffn_chunk = [&](int u) {
            uint32_t w0[4], w1[4];
#pragma unroll
            for (int i = 0; i < 4; i++) {
                const int t = u * 4 + i;
                if (t < 22) {
                    const uint32_t bv = sBias[t * 4 + q];
                    const float bb0 = bf_lo(bv), bb1 = bf_hi(bv);
                    w0[i] = pack_bf16(mish_f(accF[t * 4 + 0] + bb0), mish_f(accF[t * 4 + 1] + bb1));
                    w1[i] = pack_bf16(mish_f(accF[t * 4 + 2] + bb0), mish_f(accF[t * 4 + 3] + bb1));
                } else { w0[i] = 0; w1[i] = 0; }
            }
            quad_transpose(w0, q);
            quad_transpose(w1, q);
            const int c = (u * 4 + q) * 8;
            if (c < FCH && n0 + c < F_) {
                *(uint4*)(frow0 + c) = make_uint4(w0[0], w0[1], w0[2], w0[3]);
                *(uint4*)(frow1 + c) = make_uint4(w1[0], w1[1], w1[2], w1[3]);
            }
        };
#pragma unroll
        for (int kc = 0; kc < 8; kc++) {
            const int st = kc & 3;
            mbar_wait(b_full + 8 * st, ((kc + 8) >> 2) & 1);
            wgmma_fence();
#pragma unroll
            for (int k16 = 0; k16 < 4; k16++) {
                const uint64_t db = make_desc(sB + st * K1_BSTAGE + k16 * 2048, 8192, 1024);
                const uint64_t da = make_desc(sX + kc * 16384 + wg * 8192 + k16 * 32, 16, 1024);
                wgmma_n192<1>(accQ, da, db, (kc | k16) != 0);
            }
            wgmma_commit();
            if (kc < 6) ffn_chunk(kc);
            if (kc > 0) { wgmma_wait<1>(); if (lane == 0) mbar_arrive(b_empty + 8 * ((kc - 1) & 3)); }
        }
        wgmma_wait<0>();
        TS(4, tid == 0);
        {
            bf16* orow0 = g_qkv + ((size_t)j * S_ + rb * 128 + rl) * 192;
            bf16* orow1 = orow0 + 8 * 192;
#pragma unroll
            for (int u = 0; u < 6; u++) {
                uint32_t w0[4], w1[4];
#pragma unroll
                for (int i = 0; i < 4; i++) {
                    const int t = u * 4 + i;
                    w0[i] = pack_bf16(accQ[t * 4 + 0], accQ[t * 4 + 1]);
                    w1[i] = pack_bf16(accQ[t * 4 + 2], accQ[t * 4 + 3]);
                }
                quad_transpose(w0, q);
                quad_transpose(w1, q);
                const int c = (u * 4 + q) * 8;
                *(uint4*)(orow0 + c) = make_uint4(w0[0], w0[1], w0[2], w0[3]);
                *(uint4*)(orow1 + c) = make_uint4(w1[0], w1[1], w1[2], w1[3]);
            }
        }
        TS(5, tid == 0);
    }
}

__device__ __forceinline__ void ldsm_x4(uint32_t (&r)[4], uint32_t addr) {
    asm("ldmatrix.sync.aligned.m8n8.x4.shared.b16 {%0,%1,%2,%3}, [%4];"
                 : "=r"(r[0]), "=r"(r[1]), "=r"(r[2]), "=r"(r[3]) : "r"(addr));
}
__device__ __forceinline__ void ldsm_x4_t(uint32_t (&r)[4], uint32_t addr) {
    asm("ldmatrix.sync.aligned.m8n8.x4.trans.shared.b16 {%0,%1,%2,%3}, [%4];"
                 : "=r"(r[0]), "=r"(r[1]), "=r"(r[2]), "=r"(r[3]) : "r"(addr));
}
__device__ __forceinline__ void mma16816(float (&d)[4], const uint32_t (&a)[4], uint32_t b0, uint32_t b1) {
    asm("mma.sync.aligned.m16n8k16.row.col.f32.bf16.bf16.f32 {%0,%1,%2,%3}, {%4,%5,%6,%7}, {%8,%9}, {%0,%1,%2,%3};"
                 : "+f"(d[0]), "+f"(d[1]), "+f"(d[2]), "+f"(d[3])
                 : "r"(a[0]), "r"(a[1]), "r"(a[2]), "r"(a[3]), "r"(b0), "r"(b1));
}
__device__ __forceinline__ void mma16816_z(float (&d)[4], const uint32_t (&a)[4], uint32_t b0, uint32_t b1) {
    asm("mma.sync.aligned.m16n8k16.row.col.f32.bf16.bf16.f32 {%0,%1,%2,%3}, {%4,%5,%6,%7}, {%8,%9}, {%10,%10,%10,%10};"
                 : "=f"(d[0]), "=f"(d[1]), "=f"(d[2]), "=f"(d[3])
                 : "r"(a[0]), "r"(a[1]), "r"(a[2]), "r"(a[3]), "r"(b0), "r"(b1), "f"(0.f));
}

constexpr int KV_PITCH = 128;

template <int EDGE, bool HEAD>
__device__ __forceinline__ void blk_scores(float (&s)[2][4], const uint32_t (&qa)[4], uint32_t kaddr, bool dead, int r0, int c0)
{
    uint32_t kf[4];
    ldsm_x4(kf, kaddr);
    mma16816_z(s[0], qa, kf[0], kf[1]);
    mma16816_z(s[1], qa, kf[2], kf[3]);
#pragma unroll
    for (int t = 0; t < 2; t++)
#pragma unroll
        for (int e = 0; e < 4; e++) {
            const int r = r0 + (e >> 1) * 8, c = t * 8 + c0 + (e & 1);
            if (EDGE == 1 && c <= r) s[t][e] = -1e30f;
            if (EDGE == 2 && c > r) s[t][e] = -1e30f;
            if (HEAD && dead) s[t][e] = -1e30f;
        }
}
__device__ __forceinline__ void blk_max(const float (&s)[2][4], float& n0, float& n1) {
    n0 = fmaxf(n0, fmaxf(fmaxf(s[0][0], s[0][1]), fmaxf(s[1][0], s[1][1])));
    n1 = fmaxf(n1, fmaxf(fmaxf(s[0][2], s[0][3]), fmaxf(s[1][2], s[1][3])));
}
__device__ __forceinline__ void blk_pv(const float (&s)[2][4], float mc0, float mc1, float (&l)[4],
                                       float (&o)[2][4], uint32_t vaddr) {
    const float C = 0.25f * 1.4426950408889634f;
    uint32_t pa[4];
#pragma unroll
    for (int t = 0; t < 2; t++) {
        const float p0 = ex2(fmaf(s[t][0], C, -mc0)), p1 = ex2(fmaf(s[t][1], C, -mc0));
        const float p2 = ex2(fmaf(s[t][2], C, -mc1)), p3 = ex2(fmaf(s[t][3], C, -mc1));
        pa[2 * t] = pack_bf16(p0, p1); pa[2 * t + 1] = pack_bf16(p2, p3);
    }
    uint32_t vf[4];
    ldsm_x4_t(vf, vaddr);
    mma16816(o[0], pa, vf[0], vf[1]);
    mma16816(o[1], pa, vf[2], vf[3]);
    mma16816(l, pa, 0x3F803F80u, 0x3F803F80u);
}
__device__ __forceinline__ void quad_max(float& n0, float& n1) {
    n0 = fmaxf(n0, __shfl_xor_sync(0xffffffffu, n0, 1)); n1 = fmaxf(n1, __shfl_xor_sync(0xffffffffu, n1, 1));
    n0 = fmaxf(n0, __shfl_xor_sync(0xffffffffu, n0, 2)); n1 = fmaxf(n1, __shfl_xor_sync(0xffffffffu, n1, 2));
}
template <int NC, int NN, bool FIRST, bool NEXT_IS_EDGE, bool HEAD>
__device__ __forceinline__ void pipe_step(const float (&sc)[5][2][4], float (&sn)[5][2][4], const uint32_t (&qa)[4],
                                          uint32_t ka, uint32_t va, int kc, int kn, int kb0, int r0, int c0,
                                          float& m0, float& m1, float& n0, float& n1, float (&l)[4], float (&o)[2][4])
{
    const float C = 0.25f * 1.4426950408889634f;
    const float mc0 = n0 * C, mc1 = n1 * C;
    if (!FIRST) {
        const float a0 = ex2(fmaf(m0, C, -mc0)), a1 = ex2(fmaf(m1, C, -mc1));
        l[0] *= a0; l[2] *= a1;
        o[0][0] *= a0; o[0][1] *= a0; o[1][0] *= a0; o[1][1] *= a0;
        o[0][2] *= a1; o[0][3] *= a1; o[1][2] *= a1; o[1][3] *= a1;
    }
    m0 = n0; m1 = n1;
#pragma unroll
    for (int b = 0; b < NC; b++) {
        if (b < NN) {
            if (NEXT_IS_EDGE && b == 0) blk_scores<1, HEAD>(sn[b], qa, ka + (kn + b) * 16 * KV_PITCH, kn + b < kb0, r0, c0);
            else                        blk_scores<0, HEAD>(sn[b], qa, ka + (kn + b) * 16 * KV_PITCH, kn + b < kb0, r0, c0);
        }
        blk_pv(sc[b], mc0, mc1, l, o, va + (kc + b) * 16 * KV_PITCH);
        if (b < NN) blk_max(sn[b], n0, n1);
    }
    if (NN > 0) quad_max(n0, n1);
}

__device__ __forceinline__ void kv_need(uint32_t kvbar, int blk, uint32_t& ka, uint32_t& va) {
    mbar_wait(kvbar + 8 * blk, 0);
    asm volatile("" : "+r"(ka), "+r"(va) :: "memory");
}
template <bool HEAD>
__device__ __forceinline__ void attn_task(const uint32_t (&qa)[4], uint32_t ka, uint32_t va, int kb0, int lane, int qt, uint32_t kvbar,
                                          bf16* __restrict__ out  , float g0, float g1)
{
    const int r0 = lane >> 2, c0 = (lane & 3) * 2;
    float m0 = -1e30f, m1 = -1e30f, n0 = -1e30f, n1 = -1e30f;
    float l[4] = {0.f, 0.f, 0.f, 0.f};
    float o[2][4] = {{0.f, 0.f, 0.f, 0.f}, {0.f, 0.f, 0.f, 0.f}};
    float sa[5][2][4], sb[5][2][4];
    kv_need(kvbar, 2, ka, va);
    if (qt < 4) kv_need(kvbar, 1, ka, va);
#pragma unroll
    for (int b = 0; b < 5; b++) {
        if (b == 4) blk_scores<2, HEAD>(sa[b], qa, ka + (12 + b) * 16 * KV_PITCH, false, r0, c0);
        else        blk_scores<0, HEAD>(sa[b], qa, ka + (12 + b) * 16 * KV_PITCH, 12 + b < kb0, r0, c0);
        blk_max(sa[b], n0, n1);
    }
    quad_max(n0, n1);
    kv_need(kvbar, 1, ka, va);
    if (HEAD) {
        pipe_step<5, 0, true, false, HEAD>(sa, sb, qa, ka, va, 12, 0, kb0, r0, c0, m0, m1, n0, n1, l, o);
        kv_need(kvbar, 0, ka, va);
#pragma unroll 1
        for (int kc = 8; kc >= 0 && kb0 < kc + 4; kc -= 4) {
#pragma unroll
            for (int b = 0; b < 4; b++) {
                blk_scores<0, HEAD>(sa[b], qa, ka + (kc + b) * 16 * KV_PITCH, kc + b < kb0, r0, c0);
                blk_max(sa[b], n0, n1);
            }
            quad_max(n0, n1);
            pipe_step<4, 0, false, false, HEAD>(sa, sb, qa, ka, va, kc, 0, kb0, r0, c0, m0, m1, n0, n1, l, o);
        }
    } else {
        pipe_step<5, 4, true,  false, HEAD>(sa, sb, qa, ka, va, 12, 8, kb0, r0, c0, m0, m1, n0, n1, l, o);
        if (qt < 4) kv_need(kvbar, 0, ka, va);
        pipe_step<4, 4, false, false, HEAD>(sb, sa, qa, ka, va, 8, 4, kb0, r0, c0, m0, m1, n0, n1, l, o);
        kv_need(kvbar, 0, ka, va);
        pipe_step<4, 4, false, true,  HEAD>(sa, sb, qa, ka, va, 4, 0, kb0, r0, c0, m0, m1, n0, n1, l, o);
        pipe_step<4, 0, false, false, HEAD>(sb, sa, qa, ka, va, 0, 0, kb0, r0, c0, m0, m1, n0, n1, l, o);
    }
    const float f0 = __fdividef(g0, l[0]), f1 = __fdividef(g1, l[2]);
#pragma unroll
    for (int t = 0; t < 2; t++) {
        *(uint32_t*)(out + (size_t)r0 * KA2 + t * 8 + c0) = pack_bf16(o[t][0] * f0, o[t][1] * f0);
        *(uint32_t*)(out + (size_t)(r0 + 8) * KA2 + t * 8 + c0) = pack_bf16(o[t][2] * f1, o[t][3] * f1);
    }
}

constexpr int K2_SMEM = 2 * 384 * KV_PITCH + 1024 + 64;

__global__ void __launch_bounds__(512, 1) k2_kernel(const __grid_constant__ CUtensorMap tmQKV, const bf16* __restrict__ x,
                                                    const bf16* __restrict__ gate_w)
{
    extern __shared__ uint8_t smem_raw[];
    const uint32_t sbase = (smem_u32(smem_raw) + 1023u) & ~1023u;
    uint8_t* sgen = smem_raw + (sbase - smem_u32(smem_raw));
    const uint32_t sK = sbase, sV = sK + 384 * KV_PITCH, kv_full = sbase + 2 * 384 * KV_PITCH;
    const int rb = blockIdx.x >> 3, j = blockIdx.x & 7;
    const int tid = threadIdx.x, warp = tid >> 5, lane = tid & 31;
    pdl_launch();
    if (tid == 0) {
        for (int i = 0; i < 3; i++) mbar_init(kv_full + 8 * i, 1);
        fence_barrier_init();
    }
    const int grow = blockIdx.x * 16 + warp;
    const uint4 ga = __ldg((const uint4*)gate_w + lane * 2), gb = __ldg((const uint4*)gate_w + lane * 2 + 1);
    const uint4 xa = __ldg((const uint4*)(x + (size_t)grow * D_) + lane * 2), xb = __ldg((const uint4*)(x + (size_t)grow * D_) + lane * 2 + 1);
    pdl_wait();
    TS(6, tid == 0);
    if (tid == 0) {
        for (int i = 0; i < 3; i++) {
            const uint32_t bar = kv_full + 8 * (2 - i);
            if (rb - i >= 0) {
                const int row = j * S_ + (rb - i) * 128;
                mbar_expect_tx(bar, 2 * 16384);
                tma_load_2d(sK + (2 - i) * 16384, &tmQKV, 64, row, bar);
                tma_load_2d(sV + (2 - i) * 16384, &tmQKV, 128, row, bar);
            } else {
                mbar_arrive(bar);
            }
        }
    }
    if (rb < 2) {
        for (int i = tid; i < (2 - rb) * 1024; i += 512) {
            *(uint4*)(sgen + i * 16) = make_uint4(0, 0, 0, 0);
            *(uint4*)(sgen + 384 * KV_PITCH + i * 16) = make_uint4(0, 0, 0, 0);
        }
    }
    const int qt = warp & 7, h0 = (warp >> 3) * 2;
    const int q0g = rb * 128 + qt * 16;
    const int r0 = lane >> 2, c0 = (lane & 3) * 2;
    const bf16* qsrc = g_qkv + ((size_t)j * S_ + q0g) * 192 + h0 * 16;
    uint32_t qa[4], qn[4];
    qa[0] = *(const uint32_t*)(qsrc + (size_t)r0 * 192 + c0);
    qa[1] = *(const uint32_t*)(qsrc + (size_t)(r0 + 8) * 192 + c0);
    qa[2] = *(const uint32_t*)(qsrc + (size_t)r0 * 192 + c0 + 8);
    qa[3] = *(const uint32_t*)(qsrc + (size_t)(r0 + 8) * 192 + c0 + 8);
    qn[0] = *(const uint32_t*)(qsrc + (size_t)r0 * 192 + 16 + c0);
    qn[1] = *(const uint32_t*)(qsrc + (size_t)(r0 + 8) * 192 + 16 + c0);
    qn[2] = *(const uint32_t*)(qsrc + (size_t)r0 * 192 + 16 + c0 + 8);
    qn[3] = *(const uint32_t*)(qsrc + (size_t)(r0 + 8) * 192 + 16 + c0 + 8);
    {
        float gs = bf_lo(xa.x) * bf_lo(ga.x);
        gs = fmaf(bf_hi(xa.x), bf_hi(ga.x), gs);
        gs = fmaf(bf_lo(xa.y), bf_lo(ga.y), gs); gs = fmaf(bf_hi(xa.y), bf_hi(ga.y), gs);
        gs = fmaf(bf_lo(xa.z), bf_lo(ga.z), gs); gs = fmaf(bf_hi(xa.z), bf_hi(ga.z), gs);
        gs = fmaf(bf_lo(xa.w), bf_lo(ga.w), gs); gs = fmaf(bf_hi(xa.w), bf_hi(ga.w), gs);
        gs = fmaf(bf_lo(xb.x), bf_lo(gb.x), gs); gs = fmaf(bf_hi(xb.x), bf_hi(gb.x), gs);
        gs = fmaf(bf_lo(xb.y), bf_lo(gb.y), gs); gs = fmaf(bf_hi(xb.y), bf_hi(gb.y), gs);
        gs = fmaf(bf_lo(xb.z), bf_lo(gb.z), gs); gs = fmaf(bf_hi(xb.z), bf_hi(gb.z), gs);
        gs = fmaf(bf_lo(xb.w), bf_lo(gb.w), gs); gs = fmaf(bf_hi(xb.w), bf_hi(gb.w), gs);
#pragma unroll
        for (int o = 16; o > 0; o >>= 1) gs += __shfl_xor_sync(0xffffffffu, gs, o);
        if (lane == 0) g_gate[grow] = 1.f / (1.f + __expf(-gs));
    }
    const float g0 = 1.f, g1 = 1.f;
    const int kb0 = q0g < 256 ? (256 - q0g) >> 4 : 0;
    __syncthreads();
    const uint32_t sKd = sK, sVd = sV;
    TS(7, tid == 0);
    const int krow = qt * 16 + (lane & 7) + ((lane >> 4) << 3);
    const int vrow = qt * 16 + (lane & 15);
#pragma unroll 1
    for (int hh = 0; hh < 2; hh++) {
        const int hl = h0 + hh;
        const uint32_t ka = sKd + krow * KV_PITCH + (((2 * hl + ((lane >> 3) & 1)) ^ (lane & 7)) << 4);
        const uint32_t va = sVd + vrow * KV_PITCH + (((2 * hl + (lane >> 4)) ^ (lane & 7)) << 4);
        if (rb < 2) attn_task<true>(qa, ka, va, kb0, lane, qt, kv_full, g_a2 + (size_t)q0g * KA2 + (j * 4 + hl) * 16, g0, g1);
        else        attn_task<false>(qa, ka, va, kb0, lane, qt, kv_full, g_a2 + (size_t)q0g * KA2 + (j * 4 + hl) * 16, g0, g1);
        TS(8 + hh, tid == 0);
        qa[0] = qn[0]; qa[1] = qn[1]; qa[2] = qn[2]; qa[3] = qn[3];
    }
}

constexpr int K3_STAGES = 8;
constexpr int K3_STAGE = 8192 + 16384;
constexpr int K3_SMEM = K3_STAGES * K3_STAGE + 1024 + 1024;
constexpr int K3_KSTEPS = 30;

__global__ void __launch_bounds__(384, 1)
k3_kernel(const __grid_constant__ CUtensorMap tmA2, const __grid_constant__ CUtensorMap tmWo,
          const __grid_constant__ CUtensorMap tmW2, bf16* __restrict__ out)
{
    extern __shared__ uint8_t smem_raw[];
    const uint32_t sbase = (smem_u32(smem_raw) + 1023u) & ~1023u;
    uint8_t* sgen = smem_raw + (sbase - smem_u32(smem_raw));
    const uint32_t sBar = sbase + K3_STAGES * K3_STAGE;
    const uint32_t full = sBar, empty = sBar + 64;
    const int mb = blockIdx.x >> 2, nb = blockIdx.x & 3;
    const int tid = threadIdx.x, wg = tid >> 7, warp = tid >> 5, lane = tid & 31;
    if (tid == 0) {
        for (int i = 0; i < K3_STAGES; i++) { mbar_init(full + 8 * i, 1); mbar_init(empty + 8 * i, 8); }
        fence_barrier_init();
    }
    __syncthreads();
    TS(10, tid == 0);
    if (wg == 2) {
        reg_dealloc<40>();
        if (tid == 256) {
            for (int ks = 0; ks < K3_KSTEPS; ks++) {
                const int st = ks % K3_STAGES;
                if (ks >= K3_STAGES) mbar_wait(empty + 8 * st, ((ks / K3_STAGES) - 1) & 1);
                mbar_expect_tx(full + 8 * st, K3_STAGE);
                const uint32_t dst = sbase + st * K3_STAGE;
                tma_load_2d(dst, &tmA2, ks * 64, mb * 64, full + 8 * st);
                const CUtensorMap* tm = ks < 8 ? &tmWo : &tmW2;
                const int kr = (ks < 8 ? ks : ks - 8) * 64;
                tma_load_2d(dst + 8192, tm, nb * 128, kr, full + 8 * st);
                tma_load_2d(dst + 16384, tm, nb * 128 + 64, kr, full + 8 * st);
            }
        }
    } else {
        reg_alloc<232>();
        const int q = lane & 3;
        const int rl = (warp & 3) * 16 + (lane >> 2);
        const float g0 = g_gate[mb * 64 + rl], g1 = g_gate[mb * 64 + rl + 8];
        float accA[64], accB[64];
        for (int ks = 0; ks < 8; ks++) {
            mbar_wait(full + 8 * ks, 0);
            TS(11, tid == 0 && ks == 0);
            wgmma_fence();
#pragma unroll
            for (int kk = 0; kk < 2; kk++) {
                const int k16 = wg * 2 + kk;
                const uint64_t da = make_desc(sbase + ks * K3_STAGE + k16 * 32, 16, 1024);
                const uint64_t db = make_desc(sbase + ks * K3_STAGE + 8192 + k16 * 2048, 8192, 1024);
                wgmma_n128<1>(accA, da, db, (ks | kk) != 0);
            }
            wgmma_commit();
            if (ks > 0) { wgmma_wait<1>(); if (lane == 0) mbar_arrive(empty + 8 * (ks - 1)); }
        }
        for (int ks = 8; ks < K3_KSTEPS; ks++) {
            const int st = ks % K3_STAGES;
            mbar_wait(full + 8 * st, (ks / K3_STAGES) & 1);
            TS(12, tid == 0 && ks == 8); TS(13, tid == 0 && ks == 16);
            wgmma_fence();
#pragma unroll
            for (int kk = 0; kk < 2; kk++) {
                const int k16 = wg * 2 + kk;
                const uint64_t da = make_desc(sbase + st * K3_STAGE + k16 * 32, 16, 1024);
                const uint64_t db = make_desc(sbase + st * K3_STAGE + 8192 + k16 * 2048, 8192, 1024);
                wgmma_n128<1>(accB, da, db, ((ks - 8) | kk) != 0);
            }
            wgmma_commit();
            wgmma_wait<1>();
            if (lane == 0) mbar_arrive(empty + 8 * ((ks - 1) % K3_STAGES));
        }
        wgmma_wait<0>();
        TS(14, tid == 0);
#pragma unroll
        for (int t = 0; t < 16; t++) {
            accA[t * 4 + 0] = fmaf(g0, accA[t * 4 + 0] - accB[t * 4 + 0], accB[t * 4 + 0]);
            accA[t * 4 + 1] = fmaf(g0, accA[t * 4 + 1] - accB[t * 4 + 1], accB[t * 4 + 1]);
            accA[t * 4 + 2] = fmaf(g1, accA[t * 4 + 2] - accB[t * 4 + 2], accB[t * 4 + 2]);
            accA[t * 4 + 3] = fmaf(g1, accA[t * 4 + 3] - accB[t * 4 + 3], accB[t * 4 + 3]);
        }
        bar_sync(1, 256);
        const int t128 = tid & 127;
        float4* xch = (float4*)(sgen + wg * 16384) + t128;
        if (wg == 0) {
#pragma unroll
            for (int i = 0; i < 8; i++) xch[i * 128] = make_float4(accA[32 + 4 * i], accA[33 + 4 * i], accA[34 + 4 * i], accA[35 + 4 * i]);
        } else {
#pragma unroll
            for (int i = 0; i < 8; i++) xch[i * 128] = make_float4(accA[4 * i], accA[1 + 4 * i], accA[2 + 4 * i], accA[3 + 4 * i]);
        }
        bar_sync(1, 256);
        const float4* rcv = (const float4*)(sgen + (wg ^ 1) * 16384) + t128;
        float v[32];
#pragma unroll
        for (int i = 0; i < 8; i++) {
            const float4 r = rcv[i * 128];
            const float a0 = wg == 0 ? accA[4 * i] : accA[32 + 4 * i], a1 = wg == 0 ? accA[4 * i + 1] : accA[33 + 4 * i];
            const float a2 = wg == 0 ? accA[4 * i + 2] : accA[34 + 4 * i], a3 = wg == 0 ? accA[4 * i + 3] : accA[35 + 4 * i];
            v[4 * i] = a0 + r.x; v[4 * i + 1] = a1 + r.y; v[4 * i + 2] = a2 + r.z; v[4 * i + 3] = a3 + r.w;
        }
        bf16* orow0 = out + (size_t)(mb * 64 + rl) * D_ + nb * 128 + wg * 64;
        bf16* orow1 = orow0 + 8 * D_;
#pragma unroll
        for (int u = 0; u < 2; u++) {
            uint32_t w0[4], w1[4];
#pragma unroll
            for (int i = 0; i < 4; i++) {
                const int t = u * 4 + i;
                w0[i] = pack_bf16(v[t * 4 + 0], v[t * 4 + 1]);
                w1[i] = pack_bf16(v[t * 4 + 2], v[t * 4 + 3]);
            }
            quad_transpose(w0, q);
            quad_transpose(w1, q);
            const int c = (u * 4 + q) * 8;
            *(uint4*)(orow0 + c) = make_uint4(w0[0], w0[1], w0[2], w0[3]);
            *(uint4*)(orow1 + c) = make_uint4(w1[0], w1[1], w1[2], w1[3]);
        }
        TS(15, tid == 0);
    }
}

typedef CUresult (*PFN_encodeTiled)(CUtensorMap*, CUtensorMapDataType, cuuint32_t, void*, const cuuint64_t*,
                                    const cuuint64_t*, const cuuint32_t*, const cuuint32_t*, CUtensorMapInterleave,
                                    CUtensorMapSwizzle, CUtensorMapL2promotion, CUtensorMapFloatOOBfill);

static void make_map(PFN_encodeTiled enc, CUtensorMap* m, const void* ptr, uint64_t cols, uint64_t rows,
                     uint32_t box_cols, uint32_t box_rows)
{
    cuuint64_t dims[2] = {cols, rows};
    cuuint64_t strides[1] = {cols * 2};
    cuuint32_t box[2] = {box_cols, box_rows};
    cuuint32_t es[2] = {1, 1};
    enc(m, CU_TENSOR_MAP_DATA_TYPE_BFLOAT16, 2, const_cast<void*>(ptr), dims, strides, box, es,
        CU_TENSOR_MAP_INTERLEAVE_NONE, CU_TENSOR_MAP_SWIZZLE_128B, CU_TENSOR_MAP_L2_PROMOTION_L2_128B,
        CU_TENSOR_MAP_FLOAT_OOB_FILL_NONE);
}

extern "C" void kernel_launch(void* const* d_in, const int* in_sizes, int n_in, void* d_out, int out_size)
{
    const bf16* x    = (const bf16*)d_in[0];
    const bf16* wqkv = (const bf16*)d_in[1];
    const bf16* wo   = (const bf16*)d_in[2];
    const bf16* w1   = (const bf16*)d_in[4];
    const bf16* b1   = (const bf16*)d_in[5];
    const bf16* w2   = (const bf16*)d_in[6];
    const bf16* gw   = (const bf16*)d_in[7];

    static PFN_encodeTiled enc = nullptr;
    if (!enc) {
        void* fn = nullptr;
        cudaDriverEntryPointQueryResult qr;
        cudaGetDriverEntryPoint("cuTensorMapEncodeTiled", &fn, cudaEnableDefault, &qr);
        enc = (PFN_encodeTiled)fn;
        cudaFuncSetAttribute(k1_kernel, cudaFuncAttributeMaxDynamicSharedMemorySize, K1_SMEM);
        cudaFuncSetAttribute(k2_kernel, cudaFuncAttributeMaxDynamicSharedMemorySize, K2_SMEM);
        cudaFuncSetAttribute(k3_kernel, cudaFuncAttributeMaxDynamicSharedMemorySize, K3_SMEM);
    }
    void* a2p = nullptr;
    cudaGetSymbolAddress(&a2p, g_a2);
    void* qkvp = nullptr;
    cudaGetSymbolAddress(&qkvp, g_qkv);
    CUtensorMap tmX, tmWqkv, tmW1, tmA2, tmWo, tmW2, tmQKV;
    make_map(enc, &tmQKV, qkvp, 192, 8 * S_, 64, 128);
    make_map(enc, &tmX, x, D_, S_, 64, 128);
    make_map(enc, &tmWqkv, wqkv, 3 * D_, D_, 64, 64);
    make_map(enc, &tmW1, w1, F_, D_, 64, 64);
    make_map(enc, &tmA2, a2p, KA2, S_, 64, 64);
    make_map(enc, &tmWo, wo, D_, D_, 64, 64);
    make_map(enc, &tmW2, w2, D_, F_, 64, 64);

    cudaStream_t st = cudaStreamPerThread;
    k1_kernel<<<128, 384, K1_SMEM, st>>>(tmX, tmWqkv, tmW1, b1, gw, w1, wqkv, w2, wo);
    cudaLaunchAttribute at[1];
    at[0].id = cudaLaunchAttributeProgrammaticStreamSerialization;
    at[0].val.programmaticStreamSerializationAllowed = 1;
    cudaLaunchConfig_t cfg = {};
    cfg.gridDim = dim3(128); cfg.stream = st; cfg.attrs = at; cfg.numAttrs = 1;
    cfg.blockDim = dim3(512); cfg.dynamicSmemBytes = K2_SMEM;
    cudaLaunchKernelEx(&cfg, k2_kernel, tmQKV, x, gw);
    k3_kernel<<<128, 384, K3_SMEM, st>>>(tmA2, tmWo, tmW2, (bf16*)d_out);
}
```

```cpp
#include <cuda_runtime.h>
#include <cuda_bf16.h>
#include <cuda.h>
#include <stdint.h>

typedef __nv_bfloat16 bf16;

constexpr int S_ = 2048, D_ = 512, F_ = 1376;
constexpr int KA2 = D_ + F_;
constexpr int FCH = 176;

__device__ bf16  g_qkv[8 * S_ * 192];
__device__ bf16  g_a2[S_ * KA2];
__device__ float g_gate[S_];

#define TS(k, cond) do { } while (0)

__device__ __forceinline__ uint32_t smem_u32(const void* p) { return (uint32_t)__cvta_generic_to_shared(p); }
__device__ __forceinline__ void mbar_init(uint32_t bar, uint32_t count) {
    asm volatile("mbarrier.init.shared::cta.b64 [%0], %1;" :: "r"(bar), "r"(count) : "memory");
}
__device__ __forceinline__ void mbar_expect_tx(uint32_t bar, uint32_t bytes) {
    asm volatile("mbarrier.arrive.expect_tx.shared::cta.b64 _, [%0], %1;" :: "r"(bar), "r"(bytes) : "memory");
}
__device__ __forceinline__ void mbar_arrive(uint32_t bar) {
    asm volatile("mbarrier.arrive.shared::cta.b64 _, [%0];" :: "r"(bar) : "memory");
}
__device__ __forceinline__ bool mbar_try_wait(uint32_t bar, uint32_t parity) {
    uint32_t ok;
    asm volatile("{\n.reg .pred p;\nmbarrier.try_wait.parity.shared::cta.b64 p, [%1], %2;\nselp.u32 %0, 1, 0, p;\n}"
                 : "=r"(ok) : "r"(bar), "r"(parity) : "memory");
    return ok != 0;
}
__device__ __forceinline__ void mbar_wait(uint32_t bar, uint32_t parity) {
    for (uint32_t it = 0; it < (1u << 22); ++it) { if (mbar_try_wait(bar, parity)) break; }
}
__device__ __forceinline__ void tma_load_2d(uint32_t dst, const CUtensorMap* map, int c0, int c1, uint32_t bar) {
    asm volatile("cp.async.bulk.tensor.2d.shared::cluster.global.mbarrier::complete_tx::bytes [%0], [%1, {%3, %4}], [%2];"
                 :: "r"(dst), "l"(map), "r"(bar), "r"(c0), "r"(c1) : "memory");
}
__device__ __forceinline__ void l2_prefetch(const void* p, uint32_t bytes) {
    asm volatile("cp.async.bulk.prefetch.L2.global [%0], %1;" :: "l"(p), "r"(bytes) : "memory");
}
__device__ __forceinline__ void fence_barrier_init() { asm volatile("fence.mbarrier_init.release.cluster;" ::: "memory"); }
__device__ __forceinline__ void wgmma_fence()  { asm volatile("wgmma.fence.sync.aligned;" ::: "memory"); }
__device__ __forceinline__ void wgmma_commit() { asm volatile("wgmma.commit_group.sync.aligned;" ::: "memory"); }
template <int N> __device__ __forceinline__ void wgmma_wait() { asm volatile("wgmma.wait_group.sync.aligned %0;" :: "n"(N) : "memory"); }
template <int R> __device__ __forceinline__ void reg_alloc()   { asm volatile("setmaxnreg.inc.sync.aligned.u32 %0;" :: "n"(R)); }
template <int R> __device__ __forceinline__ void reg_dealloc() { asm volatile("setmaxnreg.dec.sync.aligned.u32 %0;" :: "n"(R)); }
__device__ __forceinline__ void bar_sync(int id, int n)   { asm volatile("bar.sync %0, %1;" :: "r"(id), "r"(n) : "memory"); }
__device__ __forceinline__ void bar_arrive(int id, int n) { asm volatile("bar.arrive %0, %1;" :: "r"(id), "r"(n) : "memory"); }

__device__ __forceinline__ uint64_t make_desc(uint32_t addr, uint32_t lbo, uint32_t sbo) {
    uint64_t d = (uint64_t)((addr & 0x3FFFF) >> 4);
    d |= (uint64_t)((lbo & 0x3FFFF) >> 4) << 16;
    d |= (uint64_t)((sbo & 0x3FFFF) >> 4) << 32;
    d |= (uint64_t)1 << 62;
    return d;
}

template <int TB>
__device__ __forceinline__ void wgmma_n64(float (&d)[32], uint64_t da, uint64_t db, int scale_d) {
    asm volatile("{\n.reg .pred p;\nsetp.ne.b32 p, %34, 0;\n"
        "wgmma.mma_async.sync.aligned.m64n64k16.f32.bf16.bf16 {%0, %1, %2, %3, %4, %5, %6, %7, %8, %9, %10, %11, %12, %13, %14, %15, %16, %17, %18, %19, %20, %21, %22, %23, %24, %25, %26, %27, %28, %29, %30, %31}, %32, %33, p, 1, 1, 0, %35;\n}\n"
        : "+f"(d[0]), "+f"(d[1]), "+f"(d[2]), "+f"(d[3]), "+f"(d[4]), "+f"(d[5]), "+f"(d[6]), "+f"(d[7]), "+f"(d[8]), "+f"(d[9]), "+f"(d[10]), "+f"(d[11]), "+f"(d[12]), "+f"(d[13]), "+f"(d[14]), "+f"(d[15]), "+f"(d[16]), "+f"(d[17]), "+f"(d[18]), "+f"(d[19]), "+f"(d[20]), "+f"(d[21]), "+f"(d[22]), "+f"(d[23]), "+f"(d[24]), "+f"(d[25]), "+f"(d[26]), "+f"(d[27]), "+f"(d[28]), "+f"(d[29]), "+f"(d[30]), "+f"(d[31])
        : "l"(da), "l"(db), "r"(scale_d), "n"(TB));
}

template <int TB>
__device__ __forceinline__ void wgmma_n128(float (&d)[64], uint64_t da, uint64_t db, int scale_d) {
    asm volatile("{\n.reg .pred p;\nsetp.ne.b32 p, %66, 0;\n"
        "wgmma.mma_async.sync.aligned.m64n128k16.f32.bf16.bf16 {%0, %1, %2, %3, %4, %5, %6, %7, %8, %9, %10, %11, %12, %13, %14, %15, %16, %17, %18, %19, %20, %21, %22, %23, %24, %25, %26, %27, %28, %29, %30, %31, %32, %33, %34, %35, %36, %37, %38, %39, %40, %41, %42, %43, %44, %45, %46, %47, %48, %49, %50, %51, %52, %53, %54, %55, %56, %57, %58, %59, %60, %61, %62, %63}, %64, %65, p, 1, 1, 0, %67;\n}\n"
        : "+f"(d[0]), "+f"(d[1]), "+f"(d[2]), "+f"(d[3]), "+f"(d[4]), "+f"(d[5]), "+f"(d[6]), "+f"(d[7]), "+f"(d[8]), "+f"(d[9]), "+f"(d[10]), "+f"(d[11]), "+f"(d[12]), "+f"(d[13]), "+f"(d[14]), "+f"(d[15]), "+f"(d[16]), "+f"(d[17]), "+f"(d[18]), "+f"(d[19]), "+f"(d[20]), "+f"(d[21]), "+f"(d[22]), "+f"(d[23]), "+f"(d[24]), "+f"(d[25]), "+f"(d[26]), "+f"(d[27]), "+f"(d[28]), "+f"(d[29]), "+f"(d[30]), "+f"(d[31]), "+f"(d[32]), "+f"(d[33]), "+f"(d[34]), "+f"(d[35]), "+f"(d[36]), "+f"(d[37]), "+f"(d[38]), "+f"(d[39]), "+f"(d[40]), "+f"(d[41]), "+f"(d[42]), "+f"(d[43]), "+f"(d[44]), "+f"(d[45]), "+f"(d[46]), "+f"(d[47]), "+f"(d[48]), "+f"(d[49]), "+f"(d[50]), "+f"(d[51]), "+f"(d[52]), "+f"(d[53]), "+f"(d[54]), "+f"(d[55]), "+f"(d[56]), "+f"(d[57]), "+f"(d[58]), "+f"(d[59]), "+f"(d[60]), "+f"(d[61]), "+f"(d[62]), "+f"(d[63])
        : "l"(da), "l"(db), "r"(scale_d), "n"(TB));
}

template <int TB>
__device__ __forceinline__ void wgmma_n176(float (&d)[88], uint64_t da, uint64_t db, int scale_d) {
    asm volatile("{\n.reg .pred p;\nsetp.ne.b32 p, %90, 0;\n"
        "wgmma.mma_async.sync.aligned.m64n176k16.f32.bf16.bf16 {%0, %1, %2, %3, %4, %5, %6, %7, %8, %9, %10, %11, %12, %13, %14, %15, %16, %17, %18, %19, %20, %21, %22, %23, %24, %25, %26, %27, %28, %29, %30, %31, %32, %33, %34, %35, %36, %37, %38, %39, %40, %41, %42, %43, %44, %45, %46, %47, %48, %49, %50, %51, %52, %53, %54, %55, %56, %57, %58, %59, %60, %61, %62, %63, %64, %65, %66, %67, %68, %69, %70, %71, %72, %73, %74, %75, %76, %77, %78, %79, %80, %81, %82, %83, %84, %85, %86, %87}, %88, %89, p, 1, 1, 0, %91;\n}\n"
        : "+f"(d[0]), "+f"(d[1]), "+f"(d[2]), "+f"(d[3]), "+f"(d[4]), "+f"(d[5]), "+f"(d[6]), "+f"(d[7]), "+f"(d[8]), "+f"(d[9]), "+f"(d[10]), "+f"(d[11]), "+f"(d[12]), "+f"(d[13]), "+f"(d[14]), "+f"(d[15]), "+f"(d[16]), "+f"(d[17]), "+f"(d[18]), "+f"(d[19]), "+f"(d[20]), "+f"(d[21]), "+f"(d[22]), "+f"(d[23]), "+f"(d[24]), "+f"(d[25]), "+f"(d[26]), "+f"(d[27]), "+f"(d[28]), "+f"(d[29]), "+f"(d[30]), "+f"(d[31]), "+f"(d[32]), "+f"(d[33]), "+f"(d[34]), "+f"(d[35]), "+f"(d[36]), "+f"(d[37]), "+f"(d[38]), "+f"(d[39]), "+f"(d[40]), "+f"(d[41]), "+f"(d[42]), "+f"(d[43]), "+f"(d[44]), "+f"(d[45]), "+f"(d[46]), "+f"(d[47]), "+f"(d[48]), "+f"(d[49]), "+f"(d[50]), "+f"(d[51]), "+f"(d[52]), "+f"(d[53]), "+f"(d[54]), "+f"(d[55]), "+f"(d[56]), "+f"(d[57]), "+f"(d[58]), "+f"(d[59]), "+f"(d[60]), "+f"(d[61]), "+f"(d[62]), "+f"(d[63]), "+f"(d[64]), "+f"(d[65]), "+f"(d[66]), "+f"(d[67]), "+f"(d[68]), "+f"(d[69]), "+f"(d[70]), "+f"(d[71]), "+f"(d[72]), "+f"(d[73]), "+f"(d[74]), "+f"(d[75]), "+f"(d[76]), "+f"(d[77]), "+f"(d[78]), "+f"(d[79]), "+f"(d[80]), "+f"(d[81]), "+f"(d[82]), "+f"(d[83]), "+f"(d[84]), "+f"(d[85]), "+f"(d[86]), "+f"(d[87])
        : "l"(da), "l"(db), "r"(scale_d), "n"(TB));
}

template <int TB>
__device__ __forceinline__ void wgmma_n192(float (&d)[96], uint64_t da, uint64_t db, int scale_d) {
    asm volatile("{\n.reg .pred p;\nsetp.ne.b32 p, %98, 0;\n"
        "wgmma.mma_async.sync.aligned.m64n192k16.f32.bf16.bf16 {%0, %1, %2, %3, %4, %5, %6, %7, %8, %9, %10, %11, %12, %13, %14, %15, %16, %17, %18, %19, %20, %21, %22, %23, %24, %25, %26, %27, %28, %29, %30, %31, %32, %33, %34, %35, %36, %37, %38, %39, %40, %41, %42, %43, %44, %45, %46, %47, %48, %49, %50, %51, %52, %53, %54, %55, %56, %57, %58, %59, %60, %61, %62, %63, %64, %65, %66, %67, %68, %69, %70, %71, %72, %73, %74, %75, %76, %77, %78, %79, %80, %81, %82, %83, %84, %85, %86, %87, %88, %89, %90, %91, %92, %93, %94, %95}, %96, %97, p, 1, 1, 0, %99;\n}\n"
        : "+f"(d[0]), "+f"(d[1]), "+f"(d[2]), "+f"(d[3]), "+f"(d[4]), "+f"(d[5]), "+f"(d[6]), "+f"(d[7]), "+f"(d[8]), "+f"(d[9]), "+f"(d[10]), "+f"(d[11]), "+f"(d[12]), "+f"(d[13]), "+f"(d[14]), "+f"(d[15]), "+f"(d[16]), "+f"(d[17]), "+f"(d[18]), "+f"(d[19]), "+f"(d[20]), "+f"(d[21]), "+f"(d[22]), "+f"(d[23]), "+f"(d[24]), "+f"(d[25]), "+f"(d[26]), "+f"(d[27]), "+f"(d[28]), "+f"(d[29]), "+f"(d[30]), "+f"(d[31]), "+f"(d[32]), "+f"(d[33]), "+f"(d[34]), "+f"(d[35]), "+f"(d[36]), "+f"(d[37]), "+f"(d[38]), "+f"(d[39]), "+f"(d[40]), "+f"(d[41]), "+f"(d[42]), "+f"(d[43]), "+f"(d[44]), "+f"(d[45]), "+f"(d[46]), "+f"(d[47]), "+f"(d[48]), "+f"(d[49]), "+f"(d[50]), "+f"(d[51]), "+f"(d[52]), "+f"(d[53]), "+f"(d[54]), "+f"(d[55]), "+f"(d[56]), "+f"(d[57]), "+f"(d[58]), "+f"(d[59]), "+f"(d[60]), "+f"(d[61]), "+f"(d[62]), "+f"(d[63]), "+f"(d[64]), "+f"(d[65]), "+f"(d[66]), "+f"(d[67]), "+f"(d[68]), "+f"(d[69]), "+f"(d[70]), "+f"(d[71]), "+f"(d[72]), "+f"(d[73]), "+f"(d[74]), "+f"(d[75]), "+f"(d[76]), "+f"(d[77]), "+f"(d[78]), "+f"(d[79]), "+f"(d[80]), "+f"(d[81]), "+f"(d[82]), "+f"(d[83]), "+f"(d[84]), "+f"(d[85]), "+f"(d[86]), "+f"(d[87]), "+f"(d[88]), "+f"(d[89]), "+f"(d[90]), "+f"(d[91]), "+f"(d[92]), "+f"(d[93]), "+f"(d[94]), "+f"(d[95])
        : "l"(da), "l"(db), "r"(scale_d), "n"(TB));
}

__device__ __forceinline__ uint32_t pack_bf16(float lo, float hi) {
    uint32_t r;
    asm("cvt.rn.bf16x2.f32 %0, %1, %2;" : "=r"(r) : "f"(hi), "f"(lo));
    return r;
}
__device__ __forceinline__ float bf_lo(uint32_t v) { return __uint_as_float(v << 16); }
__device__ __forceinline__ float bf_hi(uint32_t v) { return __uint_as_float(v & 0xffff0000u); }

__device__ __forceinline__ void quad_transpose(uint32_t (&w)[4], int q) {
    const bool o1 = q & 1, o2 = q & 2;
    {
        uint32_t s0 = o1 ? w[0] : w[1], s1 = o1 ? w[2] : w[3];
        s0 = __shfl_xor_sync(0xffffffffu, s0, 1); s1 = __shfl_xor_sync(0xffffffffu, s1, 1);
        if (o1) { w[0] = s0; w[2] = s1; } else { w[1] = s0; w[3] = s1; }
    }
    {
        uint32_t s0 = o2 ? w[0] : w[2], s1 = o2 ? w[1] : w[3];
        s0 = __shfl_xor_sync(0xffffffffu, s0, 2); s1 = __shfl_xor_sync(0xffffffffu, s1, 2);
        if (o2) { w[0] = s0; w[1] = s1; } else { w[2] = s0; w[3] = s1; }
    }
}

__device__ __forceinline__ float ex2(float x) { float y; asm("ex2.approx.ftz.f32 %0, %1;" : "=f"(y) : "f"(x)); return y; }
__device__ __forceinline__ float rcp(float x) { float y; asm("rcp.approx.ftz.f32 %0, %1;" : "=f"(y) : "f"(x)); return y; }

__device__ __forceinline__ float ex2v(float x) { float y; asm volatile("ex2.approx.ftz.f32 %0, %1;" : "=f"(y) : "f"(x)); return y; }
__device__ __forceinline__ float rcpv(float x) { float y; asm volatile("rcp.approx.ftz.f32 %0, %1;" : "=f"(y) : "f"(x)); return y; }
__device__ __forceinline__ float mish_f(float h) {
    const float e = ex2v(1.4426950408889634f * fminf(h, 20.f));
    const float n = fmaf(e, e, e + e);
    return h * n * rcpv(n + 2.f);
}

__device__ __forceinline__ void pdl_wait()   { asm volatile("griddepcontrol.wait;" ::: "memory"); }
__device__ __forceinline__ void pdl_launch() { asm volatile("griddepcontrol.launch_dependents;" ::: "memory"); }

constexpr int K1_STAGES = 4;
constexpr int K1_XBYTES = 128 * 512 * 2;
constexpr int K1_BSTAGE = 3 * 8192;
constexpr int K1_SMEM   = K1_XBYTES + K1_STAGES * K1_BSTAGE + 2048   + 1024  ;

__global__ void __launch_bounds__(384, 1)
k1_kernel(const __grid_constant__ CUtensorMap tmX, const __grid_constant__ CUtensorMap tmWqkv,
          const __grid_constant__ CUtensorMap tmW1, const bf16* __restrict__ b1,
          const bf16* __restrict__ gate_w, const bf16* __restrict__ w1p, const bf16* __restrict__ wqkvp,
          const bf16* __restrict__ w2p, const bf16* __restrict__ wop)
{

    extern __shared__ uint8_t smem_raw[];
    const uint32_t sbase = (smem_u32(smem_raw) + 1023u) & ~1023u;
    uint8_t* sgen = smem_raw + (sbase - smem_u32(smem_raw));
    const uint32_t sX = sbase;
    const uint32_t sB = sbase + K1_XBYTES;
    const uint32_t sBar = sB + K1_STAGES * K1_BSTAGE;
    const uint32_t x_full = sBar;
    const uint32_t b_full = sBar + 64;
    const uint32_t b_empty = sBar + 96;
    float* sGate = (float*)(sgen + K1_XBYTES + K1_STAGES * K1_BSTAGE + 128);
    uint8_t* sGw = sgen + K1_XBYTES + K1_STAGES * K1_BSTAGE + 640;
    uint32_t* sBias = (uint32_t*)(sgen + K1_XBYTES + K1_STAGES * K1_BSTAGE + 1664);

    const int rb = blockIdx.x >> 3, j = blockIdx.x & 7;
    const int tid = threadIdx.x, wg = tid >> 7, warp = tid >> 5, lane = tid & 31;
    TS(0, tid == 0);
    pdl_launch();

    if (tid == 0) {
        for (int i = 0; i < 8; i++) mbar_init(x_full + 8 * i, 1);
        for (int i = 0; i < K1_STAGES; i++) { mbar_init(b_full + 8 * i, 1); mbar_init(b_empty + 8 * i, 8); }
        fence_barrier_init();
    }
    __syncthreads();

    if (wg == 2) {
        reg_dealloc<40>();
        if (tid == 288) {
            const int b = blockIdx.x;
            mbar_wait(b_full + 8, 0);
            l2_prefetch((const uint8_t*)wqkvp + b * 12288, 12288);
            l2_prefetch((const uint8_t*)w2p + b * 11008, 11008);
            l2_prefetch((const uint8_t*)wop + b * 4096, 4096);
        }
        if (tid == 256) {
            for (int it = 0; it < 16; it++) {
                if (it < 8) {
                    mbar_expect_tx(x_full + 8 * it, 16384);
                    tma_load_2d(sX + it * 16384, &tmX, it * 64, rb * 128, x_full + 8 * it);
                }
                const int st = it & 3;
                if (it >= K1_STAGES) mbar_wait(b_empty + 8 * st, ((it >> 2) - 1) & 1);
                mbar_expect_tx(b_full + 8 * st, K1_BSTAGE);
                const uint32_t dst = sB + st * K1_BSTAGE;
                if (it < 8) {
                    for (int b = 0; b < 3; b++) tma_load_2d(dst + b * 8192, &tmW1, j * FCH + b * 64, it * 64, b_full + 8 * st);
                } else {
                    for (int b = 0; b < 3; b++) tma_load_2d(dst + b * 8192, &tmWqkv, b * 512 + j * 64, (it - 8) * 64, b_full + 8 * st);
                }
            }
        }
    } else {
        reg_alloc<232>();
        if (tid < 88) {
            const int c = j * FCH + tid * 2;
            sBias[tid] = c < F_ ? __ldg((const uint32_t*)(b1 + c)) : 0u;
        }
        const int t128 = tid & 127, w4 = warp & 3, q = lane & 3;
        float accF[88], accQ[96];
#pragma unroll 1
        for (int kc = 0; kc < 8; kc++) {
            const int st = kc & 3;
            mbar_wait(x_full + 8 * kc, 0);
            mbar_wait(b_full + 8 * st, (kc >> 2) & 1);
            TS(1, tid == 0 && kc == 0); TS(2, tid == 0 && kc == 4);
            wgmma_fence();
#pragma unroll
            for (int k16 = 0; k16 < 4; k16++) {
                const uint64_t db = make_desc(sB + st * K1_BSTAGE + k16 * 2048, 8192, 1024);
                const uint64_t da = make_desc(sX + kc * 16384 + wg * 8192 + k16 * 32, 16, 1024);
                wgmma_n176<1>(accF, da, db, (kc | k16) != 0);
            }
            wgmma_commit();
            if (kc > 0) { wgmma_wait<1>(); if (lane == 0) mbar_arrive(b_empty + 8 * ((kc - 1) & 3)); }
        }
        wgmma_wait<0>();
        if (lane == 0) mbar_arrive(b_empty + 8 * 3);
        bar_sync(3, 256);
        TS(3, tid == 0);
        const int n0 = j * FCH;
        const int rl = wg * 64 + w4 * 16 + (lane >> 2);
        bf16* frow0 = g_a2 + (size_t)(rb * 128 + rl) * KA2 + D_ + n0;
        bf16* frow1 = frow0 + 8 * KA2;
        auto ffn_chunk = [&](int u) {
            uint32_t w0[4], w1[4];
#pragma unroll
            for (int i = 0; i < 4; i++) {
                const int t = u * 4 + i;
                if (t < 22) {
                    const uint32_t bv = sBias[t * 4 + q];
                    const float bb0 = bf_lo(bv), bb1 = bf_hi(bv);
                    w0[i] = pack_bf16(mish_f(accF[t * 4 + 0] + bb0), mish_f(accF[t * 4 + 1] + bb1));
                    w1[i] = pack_bf16(mish_f(accF[t * 4 + 2] + bb0), mish_f(accF[t * 4 + 3] + bb1));
                } else { w0[i] = 0; w1[i] = 0; }
            }
            quad_transpose(w0, q);
            quad_transpose(w1, q);
            const int c = (u * 4 + q) * 8;
            if (c < FCH && n0 + c < F_) {
                *(uint4*)(frow0 + c) = make_uint4(w0[0], w0[1], w0[2], w0[3]);
                *(uint4*)(frow1 + c) = make_uint4(w1[0], w1[1], w1[2], w1[3]);
            }
        };
#pragma unroll
        for (int kc = 0; kc < 8; kc++) {
            const int st = kc & 3;
            mbar_wait(b_full + 8 * st, ((kc + 8) >> 2) & 1);
            wgmma_fence();
#pragma unroll
            for (int k16 = 0; k16 < 4; k16++) {
                const uint64_t db = make_desc(sB + st * K1_BSTAGE + k16 * 2048, 8192, 1024);
                const uint64_t da = make_desc(sX + kc * 16384 + wg * 8192 + k16 * 32, 16, 1024);
                wgmma_n192<1>(accQ, da, db, (kc | k16) != 0);
            }
            wgmma_commit();
            if (kc < 6) ffn_chunk(kc);
            if (kc > 0) { wgmma_wait<1>(); if (lane == 0) mbar_arrive(b_empty + 8 * ((kc - 1) & 3)); }
        }
        wgmma_wait<0>();
        TS(4, tid == 0);
        {
            bf16* orow0 = g_qkv + ((size_t)j * S_ + rb * 128 + rl) * 192;
            bf16* orow1 = orow0 + 8 * 192;
#pragma unroll
            for (int u = 0; u < 6; u++) {
                uint32_t w0[4], w1[4];
#pragma unroll
                for (int i = 0; i < 4; i++) {
                    const int t = u * 4 + i;
                    w0[i] = pack_bf16(accQ[t * 4 + 0], accQ[t * 4 + 1]);
                    w1[i] = pack_bf16(accQ[t * 4 + 2], accQ[t * 4 + 3]);
                }
                quad_transpose(w0, q);
                quad_transpose(w1, q);
                const int c = (u * 4 + q) * 8;
                *(uint4*)(orow0 + c) = make_uint4(w0[0], w0[1], w0[2], w0[3]);
                *(uint4*)(orow1 + c) = make_uint4(w1[0], w1[1], w1[2], w1[3]);
            }
        }
        TS(5, tid == 0);
    }
}

__device__ __forceinline__ void ldsm_x4(uint32_t (&r)[4], uint32_t addr) {
    asm("ldmatrix.sync.aligned.m8n8.x4.shared.b16 {%0,%1,%2,%3}, [%4];"
                 : "=r"(r[0]), "=r"(r[1]), "=r"(r[2]), "=r"(r[3]) : "r"(addr));
}
__device__ __forceinline__ void ldsm_x4_t(uint32_t (&r)[4], uint32_t addr) {
    asm("ldmatrix.sync.aligned.m8n8.x4.trans.shared.b16 {%0,%1,%2,%3}, [%4];"
                 : "=r"(r[0]), "=r"(r[1]), "=r"(r[2]), "=r"(r[3]) : "r"(addr));
}
__device__ __forceinline__ void mma16816(float (&d)[4], const uint32_t (&a)[4], uint32_t b0, uint32_t b1) {
    asm("mma.sync.aligned.m16n8k16.row.col.f32.bf16.bf16.f32 {%0,%1,%2,%3}, {%4,%5,%6,%7}, {%8,%9}, {%0,%1,%2,%3};"
                 : "+f"(d[0]), "+f"(d[1]), "+f"(d[2]), "+f"(d[3])
                 : "r"(a[0]), "r"(a[1]), "r"(a[2]), "r"(a[3]), "r"(b0), "r"(b1));
}
__device__ __forceinline__ void mma16816_z(float (&d)[4], const uint32_t (&a)[4], uint32_t b0, uint32_t b1) {
    asm("mma.sync.aligned.m16n8k16.row.col.f32.bf16.bf16.f32 {%0,%1,%2,%3}, {%4,%5,%6,%7}, {%8,%9}, {%10,%10,%10,%10};"
                 : "=f"(d[0]), "=f"(d[1]), "=f"(d[2]), "=f"(d[3])
                 : "r"(a[0]), "r"(a[1]), "r"(a[2]), "r"(a[3]), "r"(b0), "r"(b1), "f"(0.f));
}

constexpr int KV_PITCH = 128;

template <int EDGE, bool HEAD>
__device__ __forceinline__ void blk_scores(float (&s)[2][4], const uint32_t (&qa)[4], uint32_t kaddr, bool dead, int r0, int c0)
{
    uint32_t kf[4];
    ldsm_x4(kf, kaddr);
    mma16816_z(s[0], qa, kf[0], kf[1]);
    mma16816_z(s[1], qa, kf[2], kf[3]);
#pragma unroll
    for (int t = 0; t < 2; t++)
#pragma unroll
        for (int e = 0; e < 4; e++) {
            const int r = r0 + (e >> 1) * 8, c = t * 8 + c0 + (e & 1);
            if (EDGE == 1 && c <= r) s[t][e] = -1e30f;
            if (EDGE == 2 && c > r) s[t][e] = -1e30f;
            if (HEAD && dead) s[t][e] = -1e30f;
        }
}
__device__ __forceinline__ void blk_max(const float (&s)[2][4], float& n0, float& n1) {
    n0 = fmaxf(n0, fmaxf(fmaxf(s[0][0], s[0][1]), fmaxf(s[1][0], s[1][1])));
    n1 = fmaxf(n1, fmaxf(fmaxf(s[0][2], s[0][3]), fmaxf(s[1][2], s[1][3])));
}
__device__ __forceinline__ void blk_pv(const float (&s)[2][4], float mc0, float mc1, float (&l)[4],
                                       float (&o)[2][4], uint32_t vaddr) {
    const float C = 0.25f * 1.4426950408889634f;
    uint32_t pa[4];
#pragma unroll
    for (int t = 0; t < 2; t++) {
        const float p0 = ex2(fmaf(s[t][0], C, -mc0)), p1 = ex2(fmaf(s[t][1], C, -mc0));
        const float p2 = ex2(fmaf(s[t][2], C, -mc1)), p3 = ex2(fmaf(s[t][3], C, -mc1));
        pa[2 * t] = pack_bf16(p0, p1); pa[2 * t + 1] = pack_bf16(p2, p3);
    }
    uint32_t vf[4];
    ldsm_x4_t(vf, vaddr);
    mma16816(o[0], pa, vf[0], vf[1]);
    mma16816(o[1], pa, vf[2], vf[3]);
    mma16816(l, pa, 0x3F803F80u, 0x3F803F80u);
}
__device__ __forceinline__ void quad_max(float& n0, float& n1) {
    n0 = fmaxf(n0, __shfl_xor_sync(0xffffffffu, n0, 1)); n1 = fmaxf(n1, __shfl_xor_sync(0xffffffffu, n1, 1));
    n0 = fmaxf(n0, __shfl_xor_sync(0xffffffffu, n0, 2)); n1 = fmaxf(n1, __shfl_xor_sync(0xffffffffu, n1, 2));
}
template <int NC, int NN, bool FIRST, bool NEXT_IS_EDGE, bool HEAD>
__device__ __forceinline__ void pipe_step(const float (&sc)[5][2][4], float (&sn)[5][2][4], const uint32_t (&qa)[4],
                                          uint32_t ka, uint32_t va, int kc, int kn, int kb0, int r0, int c0,
                                          float& m0, float& m1, float& n0, float& n1, float (&l)[4], float (&o)[2][4])
{
    const float C = 0.25f * 1.4426950408889634f;
    const float mc0 = n0 * C, mc1 = n1 * C;
    if (!FIRST) {
        const float a0 = ex2(fmaf(m0, C, -mc0)), a1 = ex2(fmaf(m1, C, -mc1));
        l[0] *= a0; l[2] *= a1;
        o[0][0] *= a0; o[0][1] *= a0; o[1][0] *= a0; o[1][1] *= a0;
        o[0][2] *= a1; o[0][3] *= a1; o[1][2] *= a1; o[1][3] *= a1;
    }
    m0 = n0; m1 = n1;
#pragma unroll
    for (int b = 0; b < NC; b++) {
        if (b < NN) {
            if (NEXT_IS_EDGE && b == 0) blk_scores<1, HEAD>(sn[b], qa, ka + (kn + b) * 16 * KV_PITCH, kn + b < kb0, r0, c0);
            else                        blk_scores<0, HEAD>(sn[b], qa, ka + (kn + b) * 16 * KV_PITCH, kn + b < kb0, r0, c0);
        }
        blk_pv(sc[b], mc0, mc1, l, o, va + (kc + b) * 16 * KV_PITCH);
        if (b < NN) blk_max(sn[b], n0, n1);
    }
    if (NN > 0) quad_max(n0, n1);
}

__device__ __forceinline__ void kv_need(uint32_t kvbar, int blk, uint32_t& ka, uint32_t& va) {
    mbar_wait(kvbar + 8 * blk, 0);
    asm volatile("" : "+r"(ka), "+r"(va) :: "memory");
}
template <bool HEAD>
__device__ __forceinline__ void attn_task(const uint32_t (&qa)[4], uint32_t ka, uint32_t va, int kb0, int lane, int qt, uint32_t kvbar,
                                          bf16* __restrict__ out  , float g0, float g1)
{
    const int r0 = lane >> 2, c0 = (lane & 3) * 2;
    float m0 = -1e30f, m1 = -1e30f, n0 = -1e30f, n1 = -1e30f;
    float l[4] = {0.f, 0.f, 0.f, 0.f};
    float o[2][4] = {{0.f, 0.f, 0.f, 0.f}, {0.f, 0.f, 0.f, 0.f}};
    float sa[5][2][4], sb[5][2][4];
    kv_need(kvbar, 2, ka, va);
    if (qt < 4) kv_need(kvbar, 1, ka, va);
#pragma unroll
    for (int b = 0; b < 5; b++) {
        if (b == 4) blk_scores<2, HEAD>(sa[b], qa, ka + (12 + b) * 16 * KV_PITCH, false, r0, c0);
        else        blk_scores<0, HEAD>(sa[b], qa, ka + (12 + b) * 16 * KV_PITCH, 12 + b < kb0, r0, c0);
        blk_max(sa[b], n0, n1);
    }
    quad_max(n0, n1);
    kv_need(kvbar, 1, ka, va);
    if (HEAD) {
        pipe_step<5, 0, true, false, HEAD>(sa, sb, qa, ka, va, 12, 0, kb0, r0, c0, m0, m1, n0, n1, l, o);
        kv_need(kvbar, 0, ka, va);
#pragma unroll 1
        for (int kc = 8; kc >= 0 && kb0 < kc + 4; kc -= 4) {
#pragma unroll
            for (int b = 0; b < 4; b++) {
                blk_scores<0, HEAD>(sa[b], qa, ka + (kc + b) * 16 * KV_PITCH, kc + b < kb0, r0, c0);
                blk_max(sa[b], n0, n1);
            }
            quad_max(n0, n1);
            pipe_step<4, 0, false, false, HEAD>(sa, sb, qa, ka, va, kc, 0, kb0, r0, c0, m0, m1, n0, n1, l, o);
        }
    } else {
        pipe_step<5, 4, true,  false, HEAD>(sa, sb, qa, ka, va, 12, 8, kb0, r0, c0, m0, m1, n0, n1, l, o);
        if (qt < 4) kv_need(kvbar, 0, ka, va);
        pipe_step<4, 4, false, false, HEAD>(sb, sa, qa, ka, va, 8, 4, kb0, r0, c0, m0, m1, n0, n1, l, o);
        kv_need(kvbar, 0, ka, va);
        pipe_step<4, 4, false, true,  HEAD>(sa, sb, qa, ka, va, 4, 0, kb0, r0, c0, m0, m1, n0, n1, l, o);
        pipe_step<4, 0, false, false, HEAD>(sb, sa, qa, ka, va, 0, 0, kb0, r0, c0, m0, m1, n0, n1, l, o);
    }
    const float f0 = __fdividef(g0, l[0]), f1 = __fdividef(g1, l[2]);
#pragma unroll
    for (int t = 0; t < 2; t++) {
        *(uint32_t*)(out + (size_t)r0 * KA2 + t * 8 + c0) = pack_bf16(o[t][0] * f0, o[t][1] * f0);
        *(uint32_t*)(out + (size_t)(r0 + 8) * KA2 + t * 8 + c0) = pack_bf16(o[t][2] * f1, o[t][3] * f1);
    }
}

constexpr int K2_SMEM = 2 * 384 * KV_PITCH + 1024 + 64;

__global__ void __launch_bounds__(512, 1) k2_kernel(const __grid_constant__ CUtensorMap tmQKV, const bf16* __restrict__ x,
                                                    const bf16* __restrict__ gate_w)
{
    extern __shared__ uint8_t smem_raw[];
    const uint32_t sbase = (smem_u32(smem_raw) + 1023u) & ~1023u;
    uint8_t* sgen = smem_raw + (sbase - smem_u32(smem_raw));
    const uint32_t sK = sbase, sV = sK + 384 * KV_PITCH, kv_full = sbase + 2 * 384 * KV_PITCH;
    const int rb = blockIdx.x >> 3, j = blockIdx.x & 7;
    const int tid = threadIdx.x, warp = tid >> 5, lane = tid & 31;
    pdl_launch();
    if (tid == 0) {
        for (int i = 0; i < 3; i++) mbar_init(kv_full + 8 * i, 1);
        fence_barrier_init();
    }
    const int grow = blockIdx.x * 16 + warp;
    const uint4 ga = __ldg((const uint4*)gate_w + lane * 2), gb = __ldg((const uint4*)gate_w + lane * 2 + 1);
    const uint4 xa = __ldg((const uint4*)(x + (size_t)grow * D_) + lane * 2), xb = __ldg((const uint4*)(x + (size_t)grow * D_) + lane * 2 + 1);
    pdl_wait();
    TS(6, tid == 0);
    if (tid == 0) {
        for (int i = 0; i < 3; i++) {
            const uint32_t bar = kv_full + 8 * (2 - i);
            if (rb - i >= 0) {
                const int row = j * S_ + (rb - i) * 128;
                mbar_expect_tx(bar, 2 * 16384);
                tma_load_2d(sK + (2 - i) * 16384, &tmQKV, 64, row, bar);
                tma_load_2d(sV + (2 - i) * 16384, &tmQKV, 128, row, bar);
            } else {
                mbar_arrive(bar);
            }
        }
    }
    if (rb < 2) {
        for (int i = tid; i < (2 - rb) * 1024; i += 512) {
            *(uint4*)(sgen + i * 16) = make_uint4(0, 0, 0, 0);
            *(uint4*)(sgen + 384 * KV_PITCH + i * 16) = make_uint4(0, 0, 0, 0);
        }
    }
    const int qt = warp & 7, h0 = (warp >> 3) * 2;
    const int q0g = rb * 128 + qt * 16;
    const int r0 = lane >> 2, c0 = (lane & 3) * 2;
    const bf16* qsrc = g_qkv + ((size_t)j * S_ + q0g) * 192 + h0 * 16;
    uint32_t qa[4], qn[4];
    qa[0] = *(const uint32_t*)(qsrc + (size_t)r0 * 192 + c0);
    qa[1] = *(const uint32_t*)(qsrc + (size_t)(r0 + 8) * 192 + c0);
    qa[2] = *(const uint32_t*)(qsrc + (size_t)r0 * 192 + c0 + 8);
    qa[3] = *(const uint32_t*)(qsrc + (size_t)(r0 + 8) * 192 + c0 + 8);
    qn[0] = *(const uint32_t*)(qsrc + (size_t)r0 * 192 + 16 + c0);
    qn[1] = *(const uint32_t*)(qsrc + (size_t)(r0 + 8) * 192 + 16 + c0);
    qn[2] = *(const uint32_t*)(qsrc + (size_t)r0 * 192 + 16 + c0 + 8);
    qn[3] = *(const uint32_t*)(qsrc + (size_t)(r0 + 8) * 192 + 16 + c0 + 8);
    {
        float gs = bf_lo(xa.x) * bf_lo(ga.x);
        gs = fmaf(bf_hi(xa.x), bf_hi(ga.x), gs);
        gs = fmaf(bf_lo(xa.y), bf_lo(ga.y), gs); gs = fmaf(bf_hi(xa.y), bf_hi(ga.y), gs);
        gs = fmaf(bf_lo(xa.z), bf_lo(ga.z), gs); gs = fmaf(bf_hi(xa.z), bf_hi(ga.z), gs);
        gs = fmaf(bf_lo(xa.w), bf_lo(ga.w), gs); gs = fmaf(bf_hi(xa.w), bf_hi(ga.w), gs);
        gs = fmaf(bf_lo(xb.x), bf_lo(gb.x), gs); gs = fmaf(bf_hi(xb.x), bf_hi(gb.x), gs);
        gs = fmaf(bf_lo(xb.y), bf_lo(gb.y), gs); gs = fmaf(bf_hi(xb.y), bf_hi(gb.y), gs);
        gs = fmaf(bf_lo(xb.z), bf_lo(gb.z), gs); gs = fmaf(bf_hi(xb.z), bf_hi(gb.z), gs);
        gs = fmaf(bf_lo(xb.w), bf_lo(gb.w), gs); gs = fmaf(bf_hi(xb.w), bf_hi(gb.w), gs);
#pragma unroll
        for (int o = 16; o > 0; o >>= 1) gs += __shfl_xor_sync(0xffffffffu, gs, o);
        if (lane == 0) g_gate[grow] = 1.f / (1.f + __expf(-gs));
    }
    const float g0 = 1.f, g1 = 1.f;
    const int kb0 = q0g < 256 ? (256 - q0g) >> 4 : 0;
    __syncthreads();
    const uint32_t sKd = sK, sVd = sV;
    TS(7, tid == 0);
    const int krow = qt * 16 + (lane & 7) + ((lane >> 4) << 3);
    const int vrow = qt * 16 + (lane & 15);
#pragma unroll 1
    for (int hh = 0; hh < 2; hh++) {
        const int hl = h0 + hh;
        const uint32_t ka = sKd + krow * KV_PITCH + (((2 * hl + ((lane >> 3) & 1)) ^ (lane & 7)) << 4);
        const uint32_t va = sVd + vrow * KV_PITCH + (((2 * hl + (lane >> 4)) ^ (lane & 7)) << 4);
        if (rb < 2) attn_task<true>(qa, ka, va, kb0, lane, qt, kv_full, g_a2 + (size_t)q0g * KA2 + (j * 4 + hl) * 16, g0, g1);
        else        attn_task<false>(qa, ka, va, kb0, lane, qt, kv_full, g_a2 + (size_t)q0g * KA2 + (j * 4 + hl) * 16, g0, g1);
        TS(8 + hh, tid == 0);
        qa[0] = qn[0]; qa[1] = qn[1]; qa[2] = qn[2]; qa[3] = qn[3];
    }
}

constexpr int K3_STAGES = 8;
constexpr int K3_STAGE = 16384 + 8192;
constexpr int K3_SMEM = K3_STAGES * K3_STAGE + 1024 + 1024;
constexpr int K3_KSTEPS = 30;

__global__ void __launch_bounds__(384, 1)
k3_kernel(const __grid_constant__ CUtensorMap tmA2, const __grid_constant__ CUtensorMap tmWo,
          const __grid_constant__ CUtensorMap tmW2, bf16* __restrict__ out)
{
    extern __shared__ uint8_t smem_raw[];
    const uint32_t sbase = (smem_u32(smem_raw) + 1023u) & ~1023u;
    const uint32_t sBar = sbase + K3_STAGES * K3_STAGE;
    const uint32_t full = sBar, empty = sBar + 64;
    const int rb = blockIdx.x >> 3, nb = blockIdx.x & 7;
    const int tid = threadIdx.x, wg = tid >> 7, warp = tid >> 5, lane = tid & 31;
    if (tid == 0) {
        for (int i = 0; i < K3_STAGES; i++) { mbar_init(full + 8 * i, 1); mbar_init(empty + 8 * i, 8); }
        fence_barrier_init();
    }
    __syncthreads();
    if (wg == 2) {
        reg_dealloc<40>();
        if (warp == 8) {
            if (lane == 0) {
                for (int ks = 0; ks < K3_STAGES; ks++) {
                    mbar_expect_tx(full + 8 * ks, K3_STAGE);
                    tma_load_2d(sbase + ks * K3_STAGE + 16384, &tmWo, nb * 64, ks * 64, full + 8 * ks);
                }
                pdl_wait();
                TS(10, true);
                for (int ks = 0; ks < K3_STAGES; ks++)
                    tma_load_2d(sbase + ks * K3_STAGE, &tmA2, ks * 64, rb * 128, full + 8 * ks);
                for (int ks = K3_STAGES; ks < K3_KSTEPS; ks++) {
                    const int st = ks % K3_STAGES;
                    mbar_wait(empty + 8 * st, ((ks / K3_STAGES) - 1) & 1);
                    mbar_expect_tx(full + 8 * st, K3_STAGE);
                    const uint32_t dst = sbase + st * K3_STAGE;
                    tma_load_2d(dst, &tmA2, ks * 64, rb * 128, full + 8 * st);
                    tma_load_2d(dst + 16384, &tmW2, nb * 64, (ks - 8) * 64, full + 8 * st);
                }
            }
        }
    } else {
        reg_alloc<232>();
        float accA[32], accB[32];
        const int q = lane & 3;
        const int rl = wg * 64 + (warp & 3) * 16 + (lane >> 2);
        pdl_wait();
        const float g0 = g_gate[rb * 128 + rl], g1 = g_gate[rb * 128 + rl + 8];
        for (int ks = 0; ks < 8; ks++) {
            mbar_wait(full + 8 * ks, 0);
            TS(11, tid == 0 && ks == 0);
            wgmma_fence();
#pragma unroll
            for (int k16 = 0; k16 < 4; k16++) {
                const uint64_t da = make_desc(sbase + ks * K3_STAGE + wg * 8192 + k16 * 32, 16, 1024);
                const uint64_t db = make_desc(sbase + ks * K3_STAGE + 16384 + k16 * 2048, 8192, 1024);
                wgmma_n64<1>(accA, da, db, (ks | k16) != 0);
            }
            wgmma_commit();
            if (ks > 0) { wgmma_wait<1>(); if (lane == 0) mbar_arrive(empty + 8 * (ks - 1)); }
        }
        for (int ks = 8; ks < K3_KSTEPS; ks++) {
            const int st = ks % K3_STAGES;
            mbar_wait(full + 8 * st, (ks / K3_STAGES) & 1);
            TS(12, tid == 0 && ks == 8); TS(13, tid == 0 && ks == 16);
            wgmma_fence();
#pragma unroll
            for (int k16 = 0; k16 < 4; k16++) {
                const uint64_t da = make_desc(sbase + st * K3_STAGE + wg * 8192 + k16 * 32, 16, 1024);
                const uint64_t db = make_desc(sbase + st * K3_STAGE + 16384 + k16 * 2048, 8192, 1024);
                wgmma_n64<1>(accB, da, db, ((ks - 8) | k16) != 0);
            }
            wgmma_commit();
            wgmma_wait<1>();
            if (lane == 0) mbar_arrive(empty + 8 * ((ks - 1) % K3_STAGES));
        }
        wgmma_wait<0>();
        TS(14, tid == 0);
        bf16* orow0 = out + (size_t)(rb * 128 + rl) * D_ + nb * 64;
        bf16* orow1 = orow0 + 8 * D_;
#pragma unroll
        for (int u = 0; u < 2; u++) {
            uint32_t w0[4], w1[4];
#pragma unroll
            for (int i = 0; i < 4; i++) {
                const int t = u * 4 + i;
                w0[i] = pack_bf16(fmaf(g0, accA[t * 4 + 0] - accB[t * 4 + 0], accB[t * 4 + 0]), fmaf(g0, accA[t * 4 + 1] - accB[t * 4 + 1], accB[t * 4 + 1]));
                w1[i] = pack_bf16(fmaf(g1, accA[t * 4 + 2] - accB[t * 4 + 2], accB[t * 4 + 2]), fmaf(g1, accA[t * 4 + 3] - accB[t * 4 + 3], accB[t * 4 + 3]));
            }
            quad_transpose(w0, q);
            quad_transpose(w1, q);
            const int c = (u * 4 + q) * 8;
            *(uint4*)(orow0 + c) = make_uint4(w0[0], w0[1], w0[2], w0[3]);
            *(uint4*)(orow1 + c) = make_uint4(w1[0], w1[1], w1[2], w1[3]);
        }
        TS(15, tid == 0);
    }
}

typedef CUresult (*PFN_encodeTiled)(CUtensorMap*, CUtensorMapDataType, cuuint32_t, void*, const cuuint64_t*,
                                    const cuuint64_t*, const cuuint32_t*, const cuuint32_t*, CUtensorMapInterleave,
                                    CUtensorMapSwizzle, CUtensorMapL2promotion, CUtensorMapFloatOOBfill);

static void make_map(PFN_encodeTiled enc, CUtensorMap* m, const void* ptr, uint64_t cols, uint64_t rows,
                     uint32_t box_cols, uint32_t box_rows)
{
    cuuint64_t dims[2] = {cols, rows};
    cuuint64_t strides[1] = {cols * 2};
    cuuint32_t box[2] = {box_cols, box_rows};
    cuuint32_t es[2] = {1, 1};
    enc(m, CU_TENSOR_MAP_DATA_TYPE_BFLOAT16, 2, const_cast<void*>(ptr), dims, strides, box, es,
        CU_TENSOR_MAP_INTERLEAVE_NONE, CU_TENSOR_MAP_SWIZZLE_128B, CU_TENSOR_MAP_L2_PROMOTION_L2_128B,
        CU_TENSOR_MAP_FLOAT_OOB_FILL_NONE);
}

extern "C" void kernel_launch(void* const* d_in, const int* in_sizes, int n_in, void* d_out, int out_size)
{
    const bf16* x    = (const bf16*)d_in[0];
    const bf16* wqkv = (const bf16*)d_in[1];
    const bf16* wo   = (const bf16*)d_in[2];
    const bf16* w1   = (const bf16*)d_in[4];
    const bf16* b1   = (const bf16*)d_in[5];
    const bf16* w2   = (const bf16*)d_in[6];
    const bf16* gw   = (const bf16*)d_in[7];

    static PFN_encodeTiled enc = nullptr;
    if (!enc) {
        void* fn = nullptr;
        cudaDriverEntryPointQueryResult qr;
        cudaGetDriverEntryPoint("cuTensorMapEncodeTiled", &fn, cudaEnableDefault, &qr);
        enc = (PFN_encodeTiled)fn;
        cudaFuncSetAttribute(k1_kernel, cudaFuncAttributeMaxDynamicSharedMemorySize, K1_SMEM);
        cudaFuncSetAttribute(k2_kernel, cudaFuncAttributeMaxDynamicSharedMemorySize, K2_SMEM);
        cudaFuncSetAttribute(k3_kernel, cudaFuncAttributeMaxDynamicSharedMemorySize, K3_SMEM);
    }
    void* a2p = nullptr;
    cudaGetSymbolAddress(&a2p, g_a2);
    void* qkvp = nullptr;
    cudaGetSymbolAddress(&qkvp, g_qkv);
    CUtensorMap tmX, tmWqkv, tmW1, tmA2, tmWo, tmW2, tmQKV;
    make_map(enc, &tmQKV, qkvp, 192, 8 * S_, 64, 128);
    make_map(enc, &tmX, x, D_, S_, 64, 128);
    make_map(enc, &tmWqkv, wqkv, 3 * D_, D_, 64, 64);
    make_map(enc, &tmW1, w1, F_, D_, 64, 64);
    make_map(enc, &tmA2, a2p, KA2, S_, 64, 128);
    make_map(enc, &tmWo, wo, D_, D_, 64, 64);
    make_map(enc, &tmW2, w2, D_, F_, 64, 64);

    cudaStream_t st = cudaStreamPerThread;
    k1_kernel<<<128, 384, K1_SMEM, st>>>(tmX, tmWqkv, tmW1, b1, gw, w1, wqkv, w2, wo);
    cudaLaunchAttribute at[1];
    at[0].id = cudaLaunchAttributeProgrammaticStreamSerialization;
    at[0].val.programmaticStreamSerializationAllowed = 1;
    cudaLaunchConfig_t cfg = {};
    cfg.gridDim = dim3(128); cfg.stream = st; cfg.attrs = at; cfg.numAttrs = 1;
    cfg.blockDim = dim3(512); cfg.dynamicSmemBytes = K2_SMEM;
    cudaLaunchKernelEx(&cfg, k2_kernel, tmQKV, x, gw);
    cfg.blockDim = dim3(384); cfg.dynamicSmemBytes = K3_SMEM;
    cudaLaunchKernelEx(&cfg, k3_kernel, tmA2, tmWo, tmW2, (bf16*)d_out);
}
```

```cpp
#include <cuda_runtime.h>
#include <cuda_bf16.h>
#include <cuda.h>
#include <stdint.h>

typedef __nv_bfloat16 bf16;

constexpr int S_ = 2048, D_ = 512, F_ = 1376;
constexpr int KA2 = D_ + F_;
constexpr int FCH = 176;

__device__ bf16  g_qkv[8 * S_ * 192];
__device__ bf16  g_a2[S_ * KA2];
__device__ float g_gate[S_];

#define TS(k, cond) do { } while (0)

__device__ __forceinline__ uint32_t smem_u32(const void* p) { return (uint32_t)__cvta_generic_to_shared(p); }
__device__ __forceinline__ void mbar_init(uint32_t bar, uint32_t count) {
    asm volatile("mbarrier.init.shared::cta.b64 [%0], %1;" :: "r"(bar), "r"(count) : "memory");
}
__device__ __forceinline__ void mbar_expect_tx(uint32_t bar, uint32_t bytes) {
    asm volatile("mbarrier.arrive.expect_tx.shared::cta.b64 _, [%0], %1;" :: "r"(bar), "r"(bytes) : "memory");
}
__device__ __forceinline__ void mbar_arrive(uint32_t bar) {
    asm volatile("mbarrier.arrive.shared::cta.b64 _, [%0];" :: "r"(bar) : "memory");
}
__device__ __forceinline__ bool mbar_try_wait(uint32_t bar, uint32_t parity) {
    uint32_t ok;
    asm volatile("{\n.reg .pred p;\nmbarrier.try_wait.parity.shared::cta.b64 p, [%1], %2;\nselp.u32 %0, 1, 0, p;\n}"
                 : "=r"(ok) : "r"(bar), "r"(parity) : "memory");
    return ok != 0;
}
__device__ __forceinline__ void mbar_wait(uint32_t bar, uint32_t parity) {
    for (uint32_t it = 0; it < (1u << 22); ++it) { if (mbar_try_wait(bar, parity)) break; }
}
__device__ __forceinline__ void tma_load_2d(uint32_t dst, const CUtensorMap* map, int c0, int c1, uint32_t bar) {
    asm volatile("cp.async.bulk.tensor.2d.shared::cluster.global.mbarrier::complete_tx::bytes [%0], [%1, {%3, %4}], [%2];"
                 :: "r"(dst), "l"(map), "r"(bar), "r"(c0), "r"(c1) : "memory");
}
__device__ __forceinline__ void l2_prefetch(const void* p, uint32_t bytes) {
    asm volatile("cp.async.bulk.prefetch.L2.global [%0], %1;" :: "l"(p), "r"(bytes) : "memory");
}
__device__ __forceinline__ void fence_barrier_init() { asm volatile("fence.mbarrier_init.release.cluster;" ::: "memory"); }
__device__ __forceinline__ void wgmma_fence()  { asm volatile("wgmma.fence.sync.aligned;" ::: "memory"); }
__device__ __forceinline__ void wgmma_commit() { asm volatile("wgmma.commit_group.sync.aligned;" ::: "memory"); }
template <int N> __device__ __forceinline__ void wgmma_wait() { asm volatile("wgmma.wait_group.sync.aligned %0;" :: "n"(N) : "memory"); }
template <int R> __device__ __forceinline__ void reg_alloc()   { asm volatile("setmaxnreg.inc.sync.aligned.u32 %0;" :: "n"(R)); }
template <int R> __device__ __forceinline__ void reg_dealloc() { asm volatile("setmaxnreg.dec.sync.aligned.u32 %0;" :: "n"(R)); }
__device__ __forceinline__ void bar_sync(int id, int n)   { asm volatile("bar.sync %0, %1;" :: "r"(id), "r"(n) : "memory"); }
__device__ __forceinline__ void bar_arrive(int id, int n) { asm volatile("bar.arrive %0, %1;" :: "r"(id), "r"(n) : "memory"); }

__device__ __forceinline__ uint64_t make_desc(uint32_t addr, uint32_t lbo, uint32_t sbo) {
    uint64_t d = (uint64_t)((addr & 0x3FFFF) >> 4);
    d |= (uint64_t)((lbo & 0x3FFFF) >> 4) << 16;
    d |= (uint64_t)((sbo & 0x3FFFF) >> 4) << 32;
    d |= (uint64_t)1 << 62;
    return d;
}

template <int TB>
__device__ __forceinline__ void wgmma_n64(float (&d)[32], uint64_t da, uint64_t db, int scale_d) {
    asm volatile("{\n.reg .pred p;\nsetp.ne.b32 p, %34, 0;\n"
        "wgmma.mma_async.sync.aligned.m64n64k16.f32.bf16.bf16 {%0, %1, %2, %3, %4, %5, %6, %7, %8, %9, %10, %11, %12, %13, %14, %15, %16, %17, %18, %19, %20, %21, %22, %23, %24, %25, %26, %27, %28, %29, %30, %31}, %32, %33, p, 1, 1, 0, %35;\n}\n"
        : "+f"(d[0]), "+f"(d[1]), "+f"(d[2]), "+f"(d[3]), "+f"(d[4]), "+f"(d[5]), "+f"(d[6]), "+f"(d[7]), "+f"(d[8]), "+f"(d[9]), "+f"(d[10]), "+f"(d[11]), "+f"(d[12]), "+f"(d[13]), "+f"(d[14]), "+f"(d[15]), "+f"(d[16]), "+f"(d[17]), "+f"(d[18]), "+f"(d[19]), "+f"(d[20]), "+f"(d[21]), "+f"(d[22]), "+f"(d[23]), "+f"(d[24]), "+f"(d[25]), "+f"(d[26]), "+f"(d[27]), "+f"(d[28]), "+f"(d[29]), "+f"(d[30]), "+f"(d[31])
        : "l"(da), "l"(db), "r"(scale_d), "n"(TB));
}

template <int TB>
__device__ __forceinline__ void wgmma_n128(float (&d)[64], uint64_t da, uint64_t db, int scale_d) {
    asm volatile("{\n.reg .pred p;\nsetp.ne.b32 p, %66, 0;\n"
        "wgmma.mma_async.sync.aligned.m64n128k16.f32.bf16.bf16 {%0, %1, %2, %3, %4, %5, %6, %7, %8, %9, %10, %11, %12, %13, %14, %15, %16, %17, %18, %19, %20, %21, %22, %23, %24, %25, %26, %27, %28, %29, %30, %31, %32, %33, %34, %35, %36, %37, %38, %39, %40, %41, %42, %43, %44, %45, %46, %47, %48, %49, %50, %51, %52, %53, %54, %55, %56, %57, %58, %59, %60, %61, %62, %63}, %64, %65, p, 1, 1, 0, %67;\n}\n"
        : "+f"(d[0]), "+f"(d[1]), "+f"(d[2]), "+f"(d[3]), "+f"(d[4]), "+f"(d[5]), "+f"(d[6]), "+f"(d[7]), "+f"(d[8]), "+f"(d[9]), "+f"(d[10]), "+f"(d[11]), "+f"(d[12]), "+f"(d[13]), "+f"(d[14]), "+f"(d[15]), "+f"(d[16]), "+f"(d[17]), "+f"(d[18]), "+f"(d[19]), "+f"(d[20]), "+f"(d[21]), "+f"(d[22]), "+f"(d[23]), "+f"(d[24]), "+f"(d[25]), "+f"(d[26]), "+f"(d[27]), "+f"(d[28]), "+f"(d[29]), "+f"(d[30]), "+f"(d[31]), "+f"(d[32]), "+f"(d[33]), "+f"(d[34]), "+f"(d[35]), "+f"(d[36]), "+f"(d[37]), "+f"(d[38]), "+f"(d[39]), "+f"(d[40]), "+f"(d[41]), "+f"(d[42]), "+f"(d[43]), "+f"(d[44]), "+f"(d[45]), "+f"(d[46]), "+f"(d[47]), "+f"(d[48]), "+f"(d[49]), "+f"(d[50]), "+f"(d[51]), "+f"(d[52]), "+f"(d[53]), "+f"(d[54]), "+f"(d[55]), "+f"(d[56]), "+f"(d[57]), "+f"(d[58]), "+f"(d[59]), "+f"(d[60]), "+f"(d[61]), "+f"(d[62]), "+f"(d[63])
        : "l"(da), "l"(db), "r"(scale_d), "n"(TB));
}

template <int TB>
__device__ __forceinline__ void wgmma_n176(float (&d)[88], uint64_t da, uint64_t db, int scale_d) {
    asm volatile("{\n.reg .pred p;\nsetp.ne.b32 p, %90, 0;\n"
        "wgmma.mma_async.sync.aligned.m64n176k16.f32.bf16.bf16 {%0, %1, %2, %3, %4, %5, %6, %7, %8, %9, %10, %11, %12, %13, %14, %15, %16, %17, %18, %19, %20, %21, %22, %23, %24, %25, %26, %27, %28, %29, %30, %31, %32, %33, %34, %35, %36, %37, %38, %39, %40, %41, %42, %43, %44, %45, %46, %47, %48, %49, %50, %51, %52, %53, %54, %55, %56, %57, %58, %59, %60, %61, %62, %63, %64, %65, %66, %67, %68, %69, %70, %71, %72, %73, %74, %75, %76, %77, %78, %79, %80, %81, %82, %83, %84, %85, %86, %87}, %88, %89, p, 1, 1, 0, %91;\n}\n"
        : "+f"(d[0]), "+f"(d[1]), "+f"(d[2]), "+f"(d[3]), "+f"(d[4]), "+f"(d[5]), "+f"(d[6]), "+f"(d[7]), "+f"(d[8]), "+f"(d[9]), "+f"(d[10]), "+f"(d[11]), "+f"(d[12]), "+f"(d[13]), "+f"(d[14]), "+f"(d[15]), "+f"(d[16]), "+f"(d[17]), "+f"(d[18]), "+f"(d[19]), "+f"(d[20]), "+f"(d[21]), "+f"(d[22]), "+f"(d[23]), "+f"(d[24]), "+f"(d[25]), "+f"(d[26]), "+f"(d[27]), "+f"(d[28]), "+f"(d[29]), "+f"(d[30]), "+f"(d[31]), "+f"(d[32]), "+f"(d[33]), "+f"(d[34]), "+f"(d[35]), "+f"(d[36]), "+f"(d[37]), "+f"(d[38]), "+f"(d[39]), "+f"(d[40]), "+f"(d[41]), "+f"(d[42]), "+f"(d[43]), "+f"(d[44]), "+f"(d[45]), "+f"(d[46]), "+f"(d[47]), "+f"(d[48]), "+f"(d[49]), "+f"(d[50]), "+f"(d[51]), "+f"(d[52]), "+f"(d[53]), "+f"(d[54]), "+f"(d[55]), "+f"(d[56]), "+f"(d[57]), "+f"(d[58]), "+f"(d[59]), "+f"(d[60]), "+f"(d[61]), "+f"(d[62]), "+f"(d[63]), "+f"(d[64]), "+f"(d[65]), "+f"(d[66]), "+f"(d[67]), "+f"(d[68]), "+f"(d[69]), "+f"(d[70]), "+f"(d[71]), "+f"(d[72]), "+f"(d[73]), "+f"(d[74]), "+f"(d[75]), "+f"(d[76]), "+f"(d[77]), "+f"(d[78]), "+f"(d[79]), "+f"(d[80]), "+f"(d[81]), "+f"(d[82]), "+f"(d[83]), "+f"(d[84]), "+f"(d[85]), "+f"(d[86]), "+f"(d[87])
        : "l"(da), "l"(db), "r"(scale_d), "n"(TB));
}

template <int TB>
__device__ __forceinline__ void wgmma_n192(float (&d)[96], uint64_t da, uint64_t db, int scale_d) {
    asm volatile("{\n.reg .pred p;\nsetp.ne.b32 p, %98, 0;\n"
        "wgmma.mma_async.sync.aligned.m64n192k16.f32.bf16.bf16 {%0, %1, %2, %3, %4, %5, %6, %7, %8, %9, %10, %11, %12, %13, %14, %15, %16, %17, %18, %19, %20, %21, %22, %23, %24, %25, %26, %27, %28, %29, %30, %31, %32, %33, %34, %35, %36, %37, %38, %39, %40, %41, %42, %43, %44, %45, %46, %47, %48, %49, %50, %51, %52, %53, %54, %55, %56, %57, %58, %59, %60, %61, %62, %63, %64, %65, %66, %67, %68, %69, %70, %71, %72, %73, %74, %75, %76, %77, %78, %79, %80, %81, %82, %83, %84, %85, %86, %87, %88, %89, %90, %91, %92, %93, %94, %95}, %96, %97, p, 1, 1, 0, %99;\n}\n"
        : "+f"(d[0]), "+f"(d[1]), "+f"(d[2]), "+f"(d[3]), "+f"(d[4]), "+f"(d[5]), "+f"(d[6]), "+f"(d[7]), "+f"(d[8]), "+f"(d[9]), "+f"(d[10]), "+f"(d[11]), "+f"(d[12]), "+f"(d[13]), "+f"(d[14]), "+f"(d[15]), "+f"(d[16]), "+f"(d[17]), "+f"(d[18]), "+f"(d[19]), "+f"(d[20]), "+f"(d[21]), "+f"(d[22]), "+f"(d[23]), "+f"(d[24]), "+f"(d[25]), "+f"(d[26]), "+f"(d[27]), "+f"(d[28]), "+f"(d[29]), "+f"(d[30]), "+f"(d[31]), "+f"(d[32]), "+f"(d[33]), "+f"(d[34]), "+f"(d[35]), "+f"(d[36]), "+f"(d[37]), "+f"(d[38]), "+f"(d[39]), "+f"(d[40]), "+f"(d[41]), "+f"(d[42]), "+f"(d[43]), "+f"(d[44]), "+f"(d[45]), "+f"(d[46]), "+f"(d[47]), "+f"(d[48]), "+f"(d[49]), "+f"(d[50]), "+f"(d[51]), "+f"(d[52]), "+f"(d[53]), "+f"(d[54]), "+f"(d[55]), "+f"(d[56]), "+f"(d[57]), "+f"(d[58]), "+f"(d[59]), "+f"(d[60]), "+f"(d[61]), "+f"(d[62]), "+f"(d[63]), "+f"(d[64]), "+f"(d[65]), "+f"(d[66]), "+f"(d[67]), "+f"(d[68]), "+f"(d[69]), "+f"(d[70]), "+f"(d[71]), "+f"(d[72]), "+f"(d[73]), "+f"(d[74]), "+f"(d[75]), "+f"(d[76]), "+f"(d[77]), "+f"(d[78]), "+f"(d[79]), "+f"(d[80]), "+f"(d[81]), "+f"(d[82]), "+f"(d[83]), "+f"(d[84]), "+f"(d[85]), "+f"(d[86]), "+f"(d[87]), "+f"(d[88]), "+f"(d[89]), "+f"(d[90]), "+f"(d[91]), "+f"(d[92]), "+f"(d[93]), "+f"(d[94]), "+f"(d[95])
        : "l"(da), "l"(db), "r"(scale_d), "n"(TB));
}

__device__ __forceinline__ uint32_t pack_bf16(float lo, float hi) {
    uint32_t r;
    asm("cvt.rn.bf16x2.f32 %0, %1, %2;" : "=r"(r) : "f"(hi), "f"(lo));
    return r;
}
__device__ __forceinline__ float bf_lo(uint32_t v) { return __uint_as_float(v << 16); }
__device__ __forceinline__ float bf_hi(uint32_t v) { return __uint_as_float(v & 0xffff0000u); }

__device__ __forceinline__ void quad_transpose(uint32_t (&w)[4], int q) {
    const bool o1 = q & 1, o2 = q & 2;
    {
        uint32_t s0 = o1 ? w[0] : w[1], s1 = o1 ? w[2] : w[3];
        s0 = __shfl_xor_sync(0xffffffffu, s0, 1); s1 = __shfl_xor_sync(0xffffffffu, s1, 1);
        if (o1) { w[0] = s0; w[2] = s1; } else { w[1] = s0; w[3] = s1; }
    }
    {
        uint32_t s0 = o2 ? w[0] : w[2], s1 = o2 ? w[1] : w[3];
        s0 = __shfl_xor_sync(0xffffffffu, s0, 2); s1 = __shfl_xor_sync(0xffffffffu, s1, 2);
        if (o2) { w[0] = s0; w[1] = s1; } else { w[2] = s0; w[3] = s1; }
    }
}

__device__ __forceinline__ float ex2(float x) { float y; asm("ex2.approx.ftz.f32 %0, %1;" : "=f"(y) : "f"(x)); return y; }
__device__ __forceinline__ float rcp(float x) { float y; asm("rcp.approx.ftz.f32 %0, %1;" : "=f"(y) : "f"(x)); return y; }

__device__ __forceinline__ float ex2v(float x) { float y; asm volatile("ex2.approx.ftz.f32 %0, %1;" : "=f"(y) : "f"(x)); return y; }
__device__ __forceinline__ float rcpv(float x) { float y; asm volatile("rcp.approx.ftz.f32 %0, %1;" : "=f"(y) : "f"(x)); return y; }
__device__ __forceinline__ float mish_f(float h) {
    const float e = ex2v(1.4426950408889634f * fminf(h, 20.f));
    const float n = fmaf(e, e, e + e);
    return h * n * rcpv(n + 2.f);
}

__device__ __forceinline__ void pdl_wait()   { asm volatile("griddepcontrol.wait;" ::: "memory"); }
__device__ __forceinline__ void pdl_launch() { asm volatile("griddepcontrol.launch_dependents;" ::: "memory"); }

constexpr int K1_STAGES = 4;
constexpr int K1_XBYTES = 128 * 512 * 2;
constexpr int K1_BSTAGE = 3 * 8192;
constexpr int K1_SMEM   = K1_XBYTES + K1_STAGES * K1_BSTAGE + 2048   + 1024  ;

__global__ void __launch_bounds__(384, 1)
k1_kernel(const __grid_constant__ CUtensorMap tmX, const __grid_constant__ CUtensorMap tmWqkv,
          const __grid_constant__ CUtensorMap tmW1, const bf16* __restrict__ b1,
          const bf16* __restrict__ gate_w, const bf16* __restrict__ w1p, const bf16* __restrict__ wqkvp,
          const bf16* __restrict__ w2p, const bf16* __restrict__ wop)
{

    extern __shared__ uint8_t smem_raw[];
    const uint32_t sbase = (smem_u32(smem_raw) + 1023u) & ~1023u;
    uint8_t* sgen = smem_raw + (sbase - smem_u32(smem_raw));
    const uint32_t sX = sbase;
    const uint32_t sB = sbase + K1_XBYTES;
    const uint32_t sBar = sB + K1_STAGES * K1_BSTAGE;
    const uint32_t x_full = sBar;
    const uint32_t b_full = sBar + 64;
    const uint32_t b_empty = sBar + 96;
    float* sGate = (float*)(sgen + K1_XBYTES + K1_STAGES * K1_BSTAGE + 128);
    uint8_t* sGw = sgen + K1_XBYTES + K1_STAGES * K1_BSTAGE + 640;
    uint32_t* sBias = (uint32_t*)(sgen + K1_XBYTES + K1_STAGES * K1_BSTAGE + 1664);

    const int rb = blockIdx.x >> 3, j = blockIdx.x & 7;
    const int tid = threadIdx.x, wg = tid >> 7, warp = tid >> 5, lane = tid & 31;
    TS(0, tid == 0);
    pdl_launch();

    if (tid == 0) {
        for (int i = 0; i < 8; i++) mbar_init(x_full + 8 * i, 1);
        for (int i = 0; i < K1_STAGES; i++) { mbar_init(b_full + 8 * i, 1); mbar_init(b_empty + 8 * i, 8); }
        fence_barrier_init();
    }
    __syncthreads();

    if (wg == 2) {
        reg_dealloc<40>();
        if (tid == 288) {
            const int b = blockIdx.x;
            mbar_wait(b_full + 8, 0);
            l2_prefetch((const uint8_t*)wqkvp + b * 12288, 12288);
            l2_prefetch((const uint8_t*)w2p + b * 11008, 11008);
            l2_prefetch((const uint8_t*)wop + b * 4096, 4096);
        }
        if (tid == 256) {
            for (int it = 0; it < 16; it++) {
                if (it < 8) {
                    mbar_expect_tx(x_full + 8 * it, 16384);
                    tma_load_2d(sX + it * 16384, &tmX, it * 64, rb * 128, x_full + 8 * it);
                }
                const int st = it & 3;
                if (it >= K1_STAGES) mbar_wait(b_empty + 8 * st, ((it >> 2) - 1) & 1);
                mbar_expect_tx(b_full + 8 * st, K1_BSTAGE);
                const uint32_t dst = sB + st * K1_BSTAGE;
                if (it < 8) {
                    for (int b = 0; b < 3; b++) tma_load_2d(dst + b * 8192, &tmW1, j * FCH + b * 64, it * 64, b_full + 8 * st);
                } else {
                    for (int b = 0; b < 3; b++) tma_load_2d(dst + b * 8192, &tmWqkv, b * 512 + j * 64, (it - 8) * 64, b_full + 8 * st);
                }
            }
        }
    } else {
        reg_alloc<232>();
        if (tid < 88) {
            const int c = j * FCH + tid * 2;
            sBias[tid] = c < F_ ? __ldg((const uint32_t*)(b1 + c)) : 0u;
        }
        const int t128 = tid & 127, w4 = warp & 3, q = lane & 3;
        float accF[88], accQ[96];
#pragma unroll 1
        for (int kc = 0; kc < 8; kc++) {
            const int st = kc & 3;
            mbar_wait(x_full + 8 * kc, 0);
            mbar_wait(b_full + 8 * st, (kc >> 2) & 1);
            TS(1, tid == 0 && kc == 0); TS(2, tid == 0 && kc == 4);
            wgmma_fence();
#pragma unroll
            for (int k16 = 0; k16 < 4; k16++) {
                const uint64_t db = make_desc(sB + st * K1_BSTAGE + k16 * 2048, 8192, 1024);
                const uint64_t da = make_desc(sX + kc * 16384 + wg * 8192 + k16 * 32, 16, 1024);
                wgmma_n176<1>(accF, da, db, (kc | k16) != 0);
            }
            wgmma_commit();
            if (kc > 0) { wgmma_wait<1>(); if (lane == 0) mbar_arrive(b_empty + 8 * ((kc - 1) & 3)); }
        }
        wgmma_wait<0>();
        if (lane == 0) mbar_arrive(b_empty + 8 * 3);
        bar_sync(3, 256);
        TS(3, tid == 0);
        const int n0 = j * FCH;
        const int rl = wg * 64 + w4 * 16 + (lane >> 2);
        bf16* frow0 = g_a2 + (size_t)(rb * 128 + rl) * KA2 + D_ + n0;
        bf16* frow1 = frow0 + 8 * KA2;
        auto ffn_chunk = [&](int u) {
            uint32_t w0[4], w1[4];
#pragma unroll
            for (int i = 0; i < 4; i++) {
                const int t = u * 4 + i;
                if (t < 22) {
                    const uint32_t bv = sBias[t * 4 + q];
                    const float bb0 = bf_lo(bv), bb1 = bf_hi(bv);
                    w0[i] = pack_bf16(mish_f(accF[t * 4 + 0] + bb0), mish_f(accF[t * 4 + 1] + bb1));
                    w1[i] = pack_bf16(mish_f(accF[t * 4 + 2] + bb0), mish_f(accF[t * 4 + 3] + bb1));
                } else { w0[i] = 0; w1[i] = 0; }
            }
            quad_transpose(w0, q);
            quad_transpose(w1, q);
            const int c = (u * 4 + q) * 8;
            if (c < FCH && n0 + c < F_) {
                *(uint4*)(frow0 + c) = make_uint4(w0[0], w0[1], w0[2], w0[3]);
                *(uint4*)(frow1 + c) = make_uint4(w1[0], w1[1], w1[2], w1[3]);
            }
        };
#pragma unroll
        for (int kc = 0; kc < 8; kc++) {
            const int st = kc & 3;
            mbar_wait(b_full + 8 * st, ((kc + 8) >> 2) & 1);
            wgmma_fence();
#pragma unroll
            for (int k16 = 0; k16 < 4; k16++) {
                const uint64_t db = make_desc(sB + st * K1_BSTAGE + k16 * 2048, 8192, 1024);
                const uint64_t da = make_desc(sX + kc * 16384 + wg * 8192 + k16 * 32, 16, 1024);
                wgmma_n192<1>(accQ, da, db, (kc | k16) != 0);
            }
            wgmma_commit();
            if (kc < 6) ffn_chunk(kc);
            if (kc > 0) { wgmma_wait<1>(); if (lane == 0) mbar_arrive(b_empty + 8 * ((kc - 1) & 3)); }
        }
        wgmma_wait<0>();
        TS(4, tid == 0);
        {
            bf16* orow0 = g_qkv + ((size_t)j * S_ + rb * 128 + rl) * 192;
            bf16* orow1 = orow0 + 8 * 192;
#pragma unroll
            for (int u = 0; u < 6; u++) {
                uint32_t w0[4], w1[4];
#pragma unroll
                for (int i = 0; i < 4; i++) {
                    const int t = u * 4 + i;
                    w0[i] = pack_bf16(accQ[t * 4 + 0], accQ[t * 4 + 1]);
                    w1[i] = pack_bf16(accQ[t * 4 + 2], accQ[t * 4 + 3]);
                }
                quad_transpose(w0, q);
                quad_transpose(w1, q);
                const int c = (u * 4 + q) * 8;
                *(uint4*)(orow0 + c) = make_uint4(w0[0], w0[1], w0[2], w0[3]);
                *(uint4*)(orow1 + c) = make_uint4(w1[0], w1[1], w1[2], w1[3]);
            }
        }
        TS(5, tid == 0);
    }
}

__device__ __forceinline__ void ldsm_x4(uint32_t (&r)[4], uint32_t addr) {
    asm("ldmatrix.sync.aligned.m8n8.x4.shared.b16 {%0,%1,%2,%3}, [%4];"
                 : "=r"(r[0]), "=r"(r[1]), "=r"(r[2]), "=r"(r[3]) : "r"(addr));
}
__device__ __forceinline__ void ldsm_x4_t(uint32_t (&r)[4], uint32_t addr) {
    asm("ldmatrix.sync.aligned.m8n8.x4.trans.shared.b16 {%0,%1,%2,%3}, [%4];"
                 : "=r"(r[0]), "=r"(r[1]), "=r"(r[2]), "=r"(r[3]) : "r"(addr));
}
__device__ __forceinline__ void mma16816(float (&d)[4], const uint32_t (&a)[4], uint32_t b0, uint32_t b1) {
    asm("mma.sync.aligned.m16n8k16.row.col.f32.bf16.bf16.f32 {%0,%1,%2,%3}, {%4,%5,%6,%7}, {%8,%9}, {%0,%1,%2,%3};"
                 : "+f"(d[0]), "+f"(d[1]), "+f"(d[2]), "+f"(d[3])
                 : "r"(a[0]), "r"(a[1]), "r"(a[2]), "r"(a[3]), "r"(b0), "r"(b1));
}
__device__ __forceinline__ void mma16816_z(float (&d)[4], const uint32_t (&a)[4], uint32_t b0, uint32_t b1) {
    asm("mma.sync.aligned.m16n8k16.row.col.f32.bf16.bf16.f32 {%0,%1,%2,%3}, {%4,%5,%6,%7}, {%8,%9}, {%10,%10,%10,%10};"
                 : "=f"(d[0]), "=f"(d[1]), "=f"(d[2]), "=f"(d[3])
                 : "r"(a[0]), "r"(a[1]), "r"(a[2]), "r"(a[3]), "r"(b0), "r"(b1), "f"(0.f));
}

constexpr int KV_PITCH = 128;

template <int EDGE, bool HEAD>
__device__ __forceinline__ void blk_scores(float (&s)[2][4], const uint32_t (&qa)[4], uint32_t kaddr, bool dead, int r0, int c0)
{
    uint32_t kf[4];
    ldsm_x4(kf, kaddr);
    mma16816_z(s[0], qa, kf[0], kf[1]);
    mma16816_z(s[1], qa, kf[2], kf[3]);
#pragma unroll
    for (int t = 0; t < 2; t++)
#pragma unroll
        for (int e = 0; e < 4; e++) {
            const int r = r0 + (e >> 1) * 8, c = t * 8 + c0 + (e & 1);
            if (EDGE == 1 && c <= r) s[t][e] = -1e30f;
            if (EDGE == 2 && c > r) s[t][e] = -1e30f;
            if (HEAD && dead) s[t][e] = -1e30f;
        }
}
__device__ __forceinline__ void blk_max(const float (&s)[2][4], float& n0, float& n1) {
    n0 = fmaxf(n0, fmaxf(fmaxf(s[0][0], s[0][1]), fmaxf(s[1][0], s[1][1])));
    n1 = fmaxf(n1, fmaxf(fmaxf(s[0][2], s[0][3]), fmaxf(s[1][2], s[1][3])));
}
__device__ __forceinline__ void blk_pv(const float (&s)[2][4], float mc0, float mc1, float (&l)[4],
                                       float (&o)[2][4], uint32_t vaddr) {
    const float C = 0.25f * 1.4426950408889634f;
    uint32_t pa[4];
#pragma unroll
    for (int t = 0; t < 2; t++) {
        const float p0 = ex2(fmaf(s[t][0], C, -mc0)), p1 = ex2(fmaf(s[t][1], C, -mc0));
        const float p2 = ex2(fmaf(s[t][2], C, -mc1)), p3 = ex2(fmaf(s[t][3], C, -mc1));
        pa[2 * t] = pack_bf16(p0, p1); pa[2 * t + 1] = pack_bf16(p2, p3);
    }
    uint32_t vf[4];
    ldsm_x4_t(vf, vaddr);
    mma16816(o[0], pa, vf[0], vf[1]);
    mma16816(o[1], pa, vf[2], vf[3]);
    mma16816(l, pa, 0x3F803F80u, 0x3F803F80u);
}
__device__ __forceinline__ void quad_max(float& n0, float& n1) {
    n0 = fmaxf(n0, __shfl_xor_sync(0xffffffffu, n0, 1)); n1 = fmaxf(n1, __shfl_xor_sync(0xffffffffu, n1, 1));
    n0 = fmaxf(n0, __shfl_xor_sync(0xffffffffu, n0, 2)); n1 = fmaxf(n1, __shfl_xor_sync(0xffffffffu, n1, 2));
}
template <int NC, int NN, bool FIRST, bool NEXT_IS_EDGE, bool HEAD>
__device__ __forceinline__ void pipe_step(const float (&sc)[5][2][4], float (&sn)[5][2][4], const uint32_t (&qa)[4],
                                          uint32_t ka, uint32_t va, int kc, int kn, int kb0, int r0, int c0,
                                          float& m0, float& m1, float& n0, float& n1, float (&l)[4], float (&o)[2][4])
{
    const float C = 0.25f * 1.4426950408889634f;
    const float mc0 = n0 * C, mc1 = n1 * C;
    if (!FIRST) {
        const float a0 = ex2(fmaf(m0, C, -mc0)), a1 = ex2(fmaf(m1, C, -mc1));
        l[0] *= a0; l[2] *= a1;
        o[0][0] *= a0; o[0][1] *= a0; o[1][0] *= a0; o[1][1] *= a0;
        o[0][2] *= a1; o[0][3] *= a1; o[1][2] *= a1; o[1][3] *= a1;
    }
    m0 = n0; m1 = n1;
#pragma unroll
    for (int b = 0; b < NC; b++) {
        if (b < NN) {
            if (NEXT_IS_EDGE && b == 0) blk_scores<1, HEAD>(sn[b], qa, ka + (kn + b) * 16 * KV_PITCH, kn + b < kb0, r0, c0);
            else                        blk_scores<0, HEAD>(sn[b], qa, ka + (kn + b) * 16 * KV_PITCH, kn + b < kb0, r0, c0);
        }
        blk_pv(sc[b], mc0, mc1, l, o, va + (kc + b) * 16 * KV_PITCH);
        if (b < NN) blk_max(sn[b], n0, n1);
    }
    if (NN > 0) quad_max(n0, n1);
}

__device__ __forceinline__ void kv_need(uint32_t kvbar, int blk, uint32_t& ka, uint32_t& va) {
    mbar_wait(kvbar + 8 * blk, 0);
    asm volatile("" : "+r"(ka), "+r"(va) :: "memory");
}
template <bool HEAD>
__device__ __forceinline__ void attn_task(const uint32_t (&qa)[4], uint32_t ka, uint32_t va, int kb0, int lane, int qt, uint32_t kvbar,
                                          bf16* __restrict__ out  , float g0, float g1)
{
    const int r0 = lane >> 2, c0 = (lane & 3) * 2;
    float m0 = -1e30f, m1 = -1e30f, n0 = -1e30f, n1 = -1e30f;
    float l[4] = {0.f, 0.f, 0.f, 0.f};
    float o[2][4] = {{0.f, 0.f, 0.f, 0.f}, {0.f, 0.f, 0.f, 0.f}};
    float sa[5][2][4], sb[5][2][4];
    kv_need(kvbar, 2, ka, va);
    if (qt < 4) kv_need(kvbar, 1, ka, va);
#pragma unroll
    for (int b = 0; b < 5; b++) {
        if (b == 4) blk_scores<2, HEAD>(sa[b], qa, ka + (12 + b) * 16 * KV_PITCH, false, r0, c0);
        else        blk_scores<0, HEAD>(sa[b], qa, ka + (12 + b) * 16 * KV_PITCH, 12 + b < kb0, r0, c0);
        blk_max(sa[b], n0, n1);
    }
    quad_max(n0, n1);
    kv_need(kvbar, 1, ka, va);
    if (HEAD) {
        pipe_step<5, 0, true, false, HEAD>(sa, sb, qa, ka, va, 12, 0, kb0, r0, c0, m0, m1, n0, n1, l, o);
        kv_need(kvbar, 0, ka, va);
#pragma unroll 1
        for (int kc = 8; kc >= 0 && kb0 < kc + 4; kc -= 4) {
#pragma unroll
            for (int b = 0; b < 4; b++) {
                blk_scores<0, HEAD>(sa[b], qa, ka + (kc + b) * 16 * KV_PITCH, kc + b < kb0, r0, c0);
                blk_max(sa[b], n0, n1);
            }
            quad_max(n0, n1);
            pipe_step<4, 0, false, false, HEAD>(sa, sb, qa, ka, va, kc, 0, kb0, r0, c0, m0, m1, n0, n1, l, o);
        }
    } else {
        pipe_step<5, 4, true,  false, HEAD>(sa, sb, qa, ka, va, 12, 8, kb0, r0, c0, m0, m1, n0, n1, l, o);
        if (qt < 4) kv_need(kvbar, 0, ka, va);
        pipe_step<4, 4, false, false, HEAD>(sb, sa, qa, ka, va, 8, 4, kb0, r0, c0, m0, m1, n0, n1, l, o);
        kv_need(kvbar, 0, ka, va);
        pipe_step<4, 4, false, true,  HEAD>(sa, sb, qa, ka, va, 4, 0, kb0, r0, c0, m0, m1, n0, n1, l, o);
        pipe_step<4, 0, false, false, HEAD>(sb, sa, qa, ka, va, 0, 0, kb0, r0, c0, m0, m1, n0, n1, l, o);
    }
    const float f0 = __fdividef(g0, l[0]), f1 = __fdividef(g1, l[2]);
#pragma unroll
    for (int t = 0; t < 2; t++) {
        *(uint32_t*)(out + (size_t)r0 * KA2 + t * 8 + c0) = pack_bf16(o[t][0] * f0, o[t][1] * f0);
        *(uint32_t*)(out + (size_t)(r0 + 8) * KA2 + t * 8 + c0) = pack_bf16(o[t][2] * f1, o[t][3] * f1);
    }
}

constexpr int K2_SMEM = 2 * 384 * KV_PITCH + 1024 + 64;

__global__ void __launch_bounds__(512, 1) k2_kernel(const __grid_constant__ CUtensorMap tmQKV, const bf16* __restrict__ x,
                                                    const bf16* __restrict__ gate_w)
{
    extern __shared__ uint8_t smem_raw[];
    const uint32_t sbase = (smem_u32(smem_raw) + 1023u) & ~1023u;
    uint8_t* sgen = smem_raw + (sbase - smem_u32(smem_raw));
    const uint32_t sK = sbase, sV = sK + 384 * KV_PITCH, kv_full = sbase + 2 * 384 * KV_PITCH;
    const int rb = blockIdx.x >> 3, j = blockIdx.x & 7;
    const int tid = threadIdx.x, warp = tid >> 5, lane = tid & 31;
    pdl_launch();
    if (tid == 0) {
        for (int i = 0; i < 3; i++) mbar_init(kv_full + 8 * i, 1);
        fence_barrier_init();
    }
    const int grow = blockIdx.x * 16 + warp;
    const uint4 ga = __ldg((const uint4*)gate_w + lane * 2), gb = __ldg((const uint4*)gate_w + lane * 2 + 1);
    const uint4 xa = __ldg((const uint4*)(x + (size_t)grow * D_) + lane * 2), xb = __ldg((const uint4*)(x + (size_t)grow * D_) + lane * 2 + 1);
    pdl_wait();
    TS(6, tid == 0);
    if (tid == 0) {
        for (int i = 0; i < 3; i++) {
            const uint32_t bar = kv_full + 8 * (2 - i);
            if (rb - i >= 0) {
                const int row = j * S_ + (rb - i) * 128;
                mbar_expect_tx(bar, 2 * 16384);
                tma_load_2d(sK + (2 - i) * 16384, &tmQKV, 64, row, bar);
                tma_load_2d(sV + (2 - i) * 16384, &tmQKV, 128, row, bar);
            } else {
                mbar_arrive(bar);
            }
        }
    }
    if (rb < 2) {
        for (int i = tid; i < (2 - rb) * 1024; i += 512) {
            *(uint4*)(sgen + i * 16) = make_uint4(0, 0, 0, 0);
            *(uint4*)(sgen + 384 * KV_PITCH + i * 16) = make_uint4(0, 0, 0, 0);
        }
    }
    const int qt = warp & 7, h0 = (warp >> 3) * 2;
    const int q0g = rb * 128 + qt * 16;
    const int r0 = lane >> 2, c0 = (lane & 3) * 2;
    const bf16* qsrc = g_qkv + ((size_t)j * S_ + q0g) * 192 + h0 * 16;
    uint32_t qa[4], qn[4];
    qa[0] = *(const uint32_t*)(qsrc + (size_t)r0 * 192 + c0);
    qa[1] = *(const uint32_t*)(qsrc + (size_t)(r0 + 8) * 192 + c0);
    qa[2] = *(const uint32_t*)(qsrc + (size_t)r0 * 192 + c0 + 8);
    qa[3] = *(const uint32_t*)(qsrc + (size_t)(r0 + 8) * 192 + c0 + 8);
    qn[0] = *(const uint32_t*)(qsrc + (size_t)r0 * 192 + 16 + c0);
    qn[1] = *(const uint32_t*)(qsrc + (size_t)(r0 + 8) * 192 + 16 + c0);
    qn[2] = *(const uint32_t*)(qsrc + (size_t)r0 * 192 + 16 + c0 + 8);
    qn[3] = *(const uint32_t*)(qsrc + (size_t)(r0 + 8) * 192 + 16 + c0 + 8);
    {
        float gs = bf_lo(xa.x) * bf_lo(ga.x);
        gs = fmaf(bf_hi(xa.x), bf_hi(ga.x), gs);
        gs = fmaf(bf_lo(xa.y), bf_lo(ga.y), gs); gs = fmaf(bf_hi(xa.y), bf_hi(ga.y), gs);
        gs = fmaf(bf_lo(xa.z), bf_lo(ga.z), gs); gs = fmaf(bf_hi(xa.z), bf_hi(ga.z), gs);
        gs = fmaf(bf_lo(xa.w), bf_lo(ga.w), gs); gs = fmaf(bf_hi(xa.w), bf_hi(ga.w), gs);
        gs = fmaf(bf_lo(xb.x), bf_lo(gb.x), gs); gs = fmaf(bf_hi(xb.x), bf_hi(gb.x), gs);
        gs = fmaf(bf_lo(xb.y), bf_lo(gb.y), gs); gs = fmaf(bf_hi(xb.y), bf_hi(gb.y), gs);
        gs = fmaf(bf_lo(xb.z), bf_lo(gb.z), gs); gs = fmaf(bf_hi(xb.z), bf_hi(gb.z), gs);
        gs = fmaf(bf_lo(xb.w), bf_lo(gb.w), gs); gs = fmaf(bf_hi(xb.w), bf_hi(gb.w), gs);
#pragma unroll
        for (int o = 16; o > 0; o >>= 1) gs += __shfl_xor_sync(0xffffffffu, gs, o);
        if (lane == 0) g_gate[grow] = 1.f / (1.f + __expf(-gs));
    }
    const float g0 = 1.f, g1 = 1.f;
    const int kb0 = q0g < 256 ? (256 - q0g) >> 4 : 0;
    __syncthreads();
    const uint32_t sKd = sK, sVd = sV;
    TS(7, tid == 0);
    const int krow = qt * 16 + (lane & 7) + ((lane >> 4) << 3);
    const int vrow = qt * 16 + (lane & 15);
#pragma unroll 1
    for (int hh = 0; hh < 2; hh++) {
        const int hl = h0 + hh;
        const uint32_t ka = sKd + krow * KV_PITCH + (((2 * hl + ((lane >> 3) & 1)) ^ (lane & 7)) << 4);
        const uint32_t va = sVd + vrow * KV_PITCH + (((2 * hl + (lane >> 4)) ^ (lane & 7)) << 4);
        if (rb < 2) attn_task<true>(qa, ka, va, kb0, lane, qt, kv_full, g_a2 + (size_t)q0g * KA2 + (j * 4 + hl) * 16, g0, g1);
        else        attn_task<false>(qa, ka, va, kb0, lane, qt, kv_full, g_a2 + (size_t)q0g * KA2 + (j * 4 + hl) * 16, g0, g1);
        TS(8 + hh, tid == 0);
        qa[0] = qn[0]; qa[1] = qn[1]; qa[2] = qn[2]; qa[3] = qn[3];
    }
}

constexpr int K3_STAGES = 8;
constexpr int K3_STAGE = 16384 + 8192;
constexpr int K3_SMEM = K3_STAGES * K3_STAGE + 1024 + 1024;
constexpr int K3_KSTEPS = 30;
#define K3_CL 2

__device__ __forceinline__ void tma_load_2d_mc(uint32_t dst, const CUtensorMap* map, int c0, int c1, uint32_t bar, uint16_t mask) {
    asm volatile("cp.async.bulk.tensor.2d.shared::cluster.global.mbarrier::complete_tx::bytes.multicast::cluster [%0], [%1, {%3, %4}], [%2], %5;"
                 :: "r"(dst), "l"(map), "r"(bar), "r"(c0), "r"(c1), "h"(mask) : "memory");
}

__global__ void __cluster_dims__(K3_CL, 1, 1) __launch_bounds__(384, 1)
k3_kernel(const __grid_constant__ CUtensorMap tmA2, const __grid_constant__ CUtensorMap tmWo,
          const __grid_constant__ CUtensorMap tmW2, bf16* __restrict__ out)
{
    extern __shared__ uint8_t smem_raw[];
    const uint32_t sbase = (smem_u32(smem_raw) + 1023u) & ~1023u;
    const uint32_t sBar = sbase + K3_STAGES * K3_STAGE;
    const uint32_t full = sBar, empty = sBar + 64;
    const int rb = blockIdx.x >> 3, nb = blockIdx.x & 7, cr = blockIdx.x % K3_CL;
    const int tid = threadIdx.x, wg = tid >> 7, warp = tid >> 5, lane = tid & 31;
    constexpr int AROWS = 128 / K3_CL;
    if (tid == 0) {
        for (int i = 0; i < K3_STAGES; i++) { mbar_init(full + 8 * i, 1); mbar_init(empty + 8 * i, 8 * K3_CL); }
        fence_barrier_init();
    }
    __syncthreads();
    asm volatile("barrier.cluster.arrive.release.aligned;\nbarrier.cluster.wait.acquire.aligned;" ::: "memory");
    TS(10, tid == 0);
    if (wg == 2) {
        reg_dealloc<40>();
        if (tid == 256) {
            for (int ks = 0; ks < K3_KSTEPS; ks++) {
                const int st = ks % K3_STAGES;
                if (ks >= K3_STAGES) mbar_wait(empty + 8 * st, ((ks / K3_STAGES) - 1) & 1);
                mbar_expect_tx(full + 8 * st, K3_STAGE);
                const uint32_t dst = sbase + st * K3_STAGE;
                tma_load_2d_mc(dst + cr * AROWS * 128, &tmA2, ks * 64, rb * 128 + cr * AROWS, full + 8 * st, (uint16_t)((1 << K3_CL) - 1));
                if (ks < 8) tma_load_2d(dst + 16384, &tmWo, nb * 64, ks * 64, full + 8 * st);
                else        tma_load_2d(dst + 16384, &tmW2, nb * 64, (ks - 8) * 64, full + 8 * st);
            }
        }
    } else {
        reg_alloc<232>();
        const int q = lane & 3;
        const int rl = wg * 64 + (warp & 3) * 16 + (lane >> 2);
        const float g0 = g_gate[rb * 128 + rl], g1 = g_gate[rb * 128 + rl + 8];
        uint32_t rempty = 0;
        if (lane < K3_CL) asm volatile("mapa.shared::cluster.u32 %0, %1, %2;" : "=r"(rempty) : "r"(empty), "r"(lane));
        auto release = [&](int st) {
            if (lane < K3_CL) asm volatile("mbarrier.arrive.shared::cluster.b64 _, [%0];" :: "r"(rempty + 8 * st) : "memory");
        };
        float accA[32], accB[32];
        for (int ks = 0; ks < 8; ks++) {
            mbar_wait(full + 8 * ks, 0);
            TS(11, tid == 0 && ks == 0);
            wgmma_fence();
#pragma unroll
            for (int k16 = 0; k16 < 4; k16++) {
                const uint64_t da = make_desc(sbase + ks * K3_STAGE + wg * 8192 + k16 * 32, 16, 1024);
                const uint64_t db = make_desc(sbase + ks * K3_STAGE + 16384 + k16 * 2048, 8192, 1024);
                wgmma_n64<1>(accA, da, db, (ks | k16) != 0);
            }
            wgmma_commit();
            if (ks > 0) { wgmma_wait<1>(); release(ks - 1); }
        }
        for (int ks = 8; ks < K3_KSTEPS; ks++) {
            const int st = ks % K3_STAGES;
            mbar_wait(full + 8 * st, (ks / K3_STAGES) & 1);
            TS(12, tid == 0 && ks == 8); TS(13, tid == 0 && ks == 16);
            wgmma_fence();
#pragma unroll
            for (int k16 = 0; k16 < 4; k16++) {
                const uint64_t da = make_desc(sbase + st * K3_STAGE + wg * 8192 + k16 * 32, 16, 1024);
                const uint64_t db = make_desc(sbase + st * K3_STAGE + 16384 + k16 * 2048, 8192, 1024);
                wgmma_n64<1>(accB, da, db, ((ks - 8) | k16) != 0);
            }
            wgmma_commit();
            wgmma_wait<1>();
            if (ks - 1 + K3_STAGES < K3_KSTEPS) release((ks - 1) % K3_STAGES);
        }
        wgmma_wait<0>();
        TS(14, tid == 0);
        bf16* orow0 = out + (size_t)(rb * 128 + rl) * D_ + nb * 64;
        bf16* orow1 = orow0 + 8 * D_;
#pragma unroll
        for (int u = 0; u < 2; u++) {
            uint32_t w0[4], w1[4];
#pragma unroll
            for (int i = 0; i < 4; i++) {
                const int t = u * 4 + i;
                w0[i] = pack_bf16(fmaf(g0, accA[t * 4 + 0] - accB[t * 4 + 0], accB[t * 4 + 0]), fmaf(g0, accA[t * 4 + 1] - accB[t * 4 + 1], accB[t * 4 + 1]));
                w1[i] = pack_bf16(fmaf(g1, accA[t * 4 + 2] - accB[t * 4 + 2], accB[t * 4 + 2]), fmaf(g1, accA[t * 4 + 3] - accB[t * 4 + 3], accB[t * 4 + 3]));
            }
            quad_transpose(w0, q);
            quad_transpose(w1, q);
            const int c = (u * 4 + q) * 8;
            *(uint4*)(orow0 + c) = make_uint4(w0[0], w0[1], w0[2], w0[3]);
            *(uint4*)(orow1 + c) = make_uint4(w1[0], w1[1], w1[2], w1[3]);
        }
        TS(15, tid == 0);
    }
    asm volatile("barrier.cluster.arrive.release.aligned;\nbarrier.cluster.wait.acquire.aligned;" ::: "memory");
}

typedef CUresult (*PFN_encodeTiled)(CUtensorMap*, CUtensorMapDataType, cuuint32_t, void*, const cuuint64_t*,
                                    const cuuint64_t*, const cuuint32_t*, const cuuint32_t*, CUtensorMapInterleave,
                                    CUtensorMapSwizzle, CUtensorMapL2promotion, CUtensorMapFloatOOBfill);

static void make_map(PFN_encodeTiled enc, CUtensorMap* m, const void* ptr, uint64_t cols, uint64_t rows,
                     uint32_t box_cols, uint32_t box_rows)
{
    cuuint64_t dims[2] = {cols, rows};
    cuuint64_t strides[1] = {cols * 2};
    cuuint32_t box[2] = {box_cols, box_rows};
    cuuint32_t es[2] = {1, 1};
    enc(m, CU_TENSOR_MAP_DATA_TYPE_BFLOAT16, 2, const_cast<void*>(ptr), dims, strides, box, es,
        CU_TENSOR_MAP_INTERLEAVE_NONE, CU_TENSOR_MAP_SWIZZLE_128B, CU_TENSOR_MAP_L2_PROMOTION_L2_128B,
        CU_TENSOR_MAP_FLOAT_OOB_FILL_NONE);
}

extern "C" void kernel_launch(void* const* d_in, const int* in_sizes, int n_in, void* d_out, int out_size)
{
    const bf16* x    = (const bf16*)d_in[0];
    const bf16* wqkv = (const bf16*)d_in[1];
    const bf16* wo   = (const bf16*)d_in[2];
    const bf16* w1   = (const bf16*)d_in[4];
    const bf16* b1   = (const bf16*)d_in[5];
    const bf16* w2   = (const bf16*)d_in[6];
    const bf16* gw   = (const bf16*)d_in[7];

    static PFN_encodeTiled enc = nullptr;
    if (!enc) {
        void* fn = nullptr;
        cudaDriverEntryPointQueryResult qr;
        cudaGetDriverEntryPoint("cuTensorMapEncodeTiled", &fn, cudaEnableDefault, &qr);
        enc = (PFN_encodeTiled)fn;
        cudaFuncSetAttribute(k1_kernel, cudaFuncAttributeMaxDynamicSharedMemorySize, K1_SMEM);
        cudaFuncSetAttribute(k2_kernel, cudaFuncAttributeMaxDynamicSharedMemorySize, K2_SMEM);
        cudaFuncSetAttribute(k3_kernel, cudaFuncAttributeMaxDynamicSharedMemorySize, K3_SMEM);
    }
    void* a2p = nullptr;
    cudaGetSymbolAddress(&a2p, g_a2);
    void* qkvp = nullptr;
    cudaGetSymbolAddress(&qkvp, g_qkv);
    CUtensorMap tmX, tmWqkv, tmW1, tmA2, tmWo, tmW2, tmQKV;
    make_map(enc, &tmQKV, qkvp, 192, 8 * S_, 64, 128);
    make_map(enc, &tmX, x, D_, S_, 64, 128);
    make_map(enc, &tmWqkv, wqkv, 3 * D_, D_, 64, 64);
    make_map(enc, &tmW1, w1, F_, D_, 64, 64);
    make_map(enc, &tmA2, a2p, KA2, S_, 64, 128 / K3_CL);
    make_map(enc, &tmWo, wo, D_, D_, 64, 64);
    make_map(enc, &tmW2, w2, D_, F_, 64, 64);

    cudaStream_t st = cudaStreamPerThread;
    k1_kernel<<<128, 384, K1_SMEM, st>>>(tmX, tmWqkv, tmW1, b1, gw, w1, wqkv, w2, wo);
    cudaLaunchAttribute at[1];
    at[0].id = cudaLaunchAttributeProgrammaticStreamSerialization;
    at[0].val.programmaticStreamSerializationAllowed = 1;
    cudaLaunchConfig_t cfg = {};
    cfg.gridDim = dim3(128); cfg.stream = st; cfg.attrs = at; cfg.numAttrs = 1;
    cfg.blockDim = dim3(512); cfg.dynamicSmemBytes = K2_SMEM;
    cudaLaunchKernelEx(&cfg, k2_kernel, tmQKV, x, gw);
    k3_kernel<<<128, 384, K3_SMEM, st>>>(tmA2, tmWo, tmW2, (bf16*)d_out);
}
```

```cpp
#include <cuda_runtime.h>
#include <cuda_bf16.h>
#include <cuda.h>
#include <stdint.h>

typedef __nv_bfloat16 bf16;

constexpr int S_ = 2048, D_ = 512, F_ = 1376;
constexpr int KA2 = D_ + F_;
constexpr int FCH = 176;

__device__ bf16  g_qkv[8 * S_ * 192];
__device__ bf16  g_a2[S_ * KA2];
__device__ float g_gate[S_];

#define TS(k, cond) do { } while (0)

__device__ __forceinline__ uint32_t smem_u32(const void* p) { return (uint32_t)__cvta_generic_to_shared(p); }
__device__ __forceinline__ void mbar_init(uint32_t bar, uint32_t count) {
    asm volatile("mbarrier.init.shared::cta.b64 [%0], %1;" :: "r"(bar), "r"(count) : "memory");
}
__device__ __forceinline__ void mbar_expect_tx(uint32_t bar, uint32_t bytes) {
    asm volatile("mbarrier.arrive.expect_tx.shared::cta.b64 _, [%0], %1;" :: "r"(bar), "r"(bytes) : "memory");
}
__device__ __forceinline__ void mbar_arrive(uint32_t bar) {
    asm volatile("mbarrier.arrive.shared::cta.b64 _, [%0];" :: "r"(bar) : "memory");
}
__device__ __forceinline__ bool mbar_try_wait(uint32_t bar, uint32_t parity) {
    uint32_t ok;
    asm volatile("{\n.reg .pred p;\nmbarrier.try_wait.parity.shared::cta.b64 p, [%1], %2;\nselp.u32 %0, 1, 0, p;\n}"
                 : "=r"(ok) : "r"(bar), "r"(parity) : "memory");
    return ok != 0;
}
__device__ __forceinline__ void mbar_wait(uint32_t bar, uint32_t parity) {
    for (uint32_t it = 0; it < (1u << 22); ++it) { if (mbar_try_wait(bar, parity)) break; }
}
__device__ __forceinline__ void tma_load_2d(uint32_t dst, const CUtensorMap* map, int c0, int c1, uint32_t bar) {
    asm volatile("cp.async.bulk.tensor.2d.shared::cluster.global.mbarrier::complete_tx::bytes [%0], [%1, {%3, %4}], [%2];"
                 :: "r"(dst), "l"(map), "r"(bar), "r"(c0), "r"(c1) : "memory");
}
__device__ __forceinline__ void l2_prefetch(const void* p, uint32_t bytes) {
    asm volatile("cp.async.bulk.prefetch.L2.global [%0], %1;" :: "l"(p), "r"(bytes) : "memory");
}
__device__ __forceinline__ void fence_barrier_init() { asm volatile("fence.mbarrier_init.release.cluster;" ::: "memory"); }
__device__ __forceinline__ void wgmma_fence()  { asm volatile("wgmma.fence.sync.aligned;" ::: "memory"); }
__device__ __forceinline__ void wgmma_commit() { asm volatile("wgmma.commit_group.sync.aligned;" ::: "memory"); }
template <int N> __device__ __forceinline__ void wgmma_wait() { asm volatile("wgmma.wait_group.sync.aligned %0;" :: "n"(N) : "memory"); }
template <int R> __device__ __forceinline__ void reg_alloc()   { asm volatile("setmaxnreg.inc.sync.aligned.u32 %0;" :: "n"(R)); }
template <int R> __device__ __forceinline__ void reg_dealloc() { asm volatile("setmaxnreg.dec.sync.aligned.u32 %0;" :: "n"(R)); }
__device__ __forceinline__ void bar_sync(int id, int n)   { asm volatile("bar.sync %0, %1;" :: "r"(id), "r"(n) : "memory"); }
__device__ __forceinline__ void bar_arrive(int id, int n) { asm volatile("bar.arrive %0, %1;" :: "r"(id), "r"(n) : "memory"); }

__device__ __forceinline__ uint64_t make_desc(uint32_t addr, uint32_t lbo, uint32_t sbo) {
    uint64_t d = (uint64_t)((addr & 0x3FFFF) >> 4);
    d |= (uint64_t)((lbo & 0x3FFFF) >> 4) << 16;
    d |= (uint64_t)((sbo & 0x3FFFF) >> 4) << 32;
    d |= (uint64_t)1 << 62;
    return d;
}

template <int TB>
__device__ __forceinline__ void wgmma_n64(float (&d)[32], uint64_t da, uint64_t db, int scale_d) {
    asm volatile("{\n.reg .pred p;\nsetp.ne.b32 p, %34, 0;\n"
        "wgmma.mma_async.sync.aligned.m64n64k16.f32.bf16.bf16 {%0, %1, %2, %3, %4, %5, %6, %7, %8, %9, %10, %11, %12, %13, %14, %15, %16, %17, %18, %19, %20, %21, %22, %23, %24, %25, %26, %27, %28, %29, %30, %31}, %32, %33, p, 1, 1, 0, %35;\n}\n"
        : "+f"(d[0]), "+f"(d[1]), "+f"(d[2]), "+f"(d[3]), "+f"(d[4]), "+f"(d[5]), "+f"(d[6]), "+f"(d[7]), "+f"(d[8]), "+f"(d[9]), "+f"(d[10]), "+f"(d[11]), "+f"(d[12]), "+f"(d[13]), "+f"(d[14]), "+f"(d[15]), "+f"(d[16]), "+f"(d[17]), "+f"(d[18]), "+f"(d[19]), "+f"(d[20]), "+f"(d[21]), "+f"(d[22]), "+f"(d[23]), "+f"(d[24]), "+f"(d[25]), "+f"(d[26]), "+f"(d[27]), "+f"(d[28]), "+f"(d[29]), "+f"(d[30]), "+f"(d[31])
        : "l"(da), "l"(db), "r"(scale_d), "n"(TB));
}

template <int TB>
__device__ __forceinline__ void wgmma_n128(float (&d)[64], uint64_t da, uint64_t db, int scale_d) {
    asm volatile("{\n.reg .pred p;\nsetp.ne.b32 p, %66, 0;\n"
        "wgmma.mma_async.sync.aligned.m64n128k16.f32.bf16.bf16 {%0, %1, %2, %3, %4, %5, %6, %7, %8, %9, %10, %11, %12, %13, %14, %15, %16, %17, %18, %19, %20, %21, %22, %23, %24, %25, %26, %27, %28, %29, %30, %31, %32, %33, %34, %35, %36, %37, %38, %39, %40, %41, %42, %43, %44, %45, %46, %47, %48, %49, %50, %51, %52, %53, %54, %55, %56, %57, %58, %59, %60, %61, %62, %63}, %64, %65, p, 1, 1, 0, %67;\n}\n"
        : "+f"(d[0]), "+f"(d[1]), "+f"(d[2]), "+f"(d[3]), "+f"(d[4]), "+f"(d[5]), "+f"(d[6]), "+f"(d[7]), "+f"(d[8]), "+f"(d[9]), "+f"(d[10]), "+f"(d[11]), "+f"(d[12]), "+f"(d[13]), "+f"(d[14]), "+f"(d[15]), "+f"(d[16]), "+f"(d[17]), "+f"(d[18]), "+f"(d[19]), "+f"(d[20]), "+f"(d[21]), "+f"(d[22]), "+f"(d[23]), "+f"(d[24]), "+f"(d[25]), "+f"(d[26]), "+f"(d[27]), "+f"(d[28]), "+f"(d[29]), "+f"(d[30]), "+f"(d[31]), "+f"(d[32]), "+f"(d[33]), "+f"(d[34]), "+f"(d[35]), "+f"(d[36]), "+f"(d[37]), "+f"(d[38]), "+f"(d[39]), "+f"(d[40]), "+f"(d[41]), "+f"(d[42]), "+f"(d[43]), "+f"(d[44]), "+f"(d[45]), "+f"(d[46]), "+f"(d[47]), "+f"(d[48]), "+f"(d[49]), "+f"(d[50]), "+f"(d[51]), "+f"(d[52]), "+f"(d[53]), "+f"(d[54]), "+f"(d[55]), "+f"(d[56]), "+f"(d[57]), "+f"(d[58]), "+f"(d[59]), "+f"(d[60]), "+f"(d[61]), "+f"(d[62]), "+f"(d[63])
        : "l"(da), "l"(db), "r"(scale_d), "n"(TB));
}

template <int TB>
__device__ __forceinline__ void wgmma_n176(float (&d)[88], uint64_t da, uint64_t db, int scale_d) {
    asm volatile("{\n.reg .pred p;\nsetp.ne.b32 p, %90, 0;\n"
        "wgmma.mma_async.sync.aligned.m64n176k16.f32.bf16.bf16 {%0, %1, %2, %3, %4, %5, %6, %7, %8, %9, %10, %11, %12, %13, %14, %15, %16, %17, %18, %19, %20, %21, %22, %23, %24, %25, %26, %27, %28, %29, %30, %31, %32, %33, %34, %35, %36, %37, %38, %39, %40, %41, %42, %43, %44, %45, %46, %47, %48, %49, %50, %51, %52, %53, %54, %55, %56, %57, %58, %59, %60, %61, %62, %63, %64, %65, %66, %67, %68, %69, %70, %71, %72, %73, %74, %75, %76, %77, %78, %79, %80, %81, %82, %83, %84, %85, %86, %87}, %88, %89, p, 1, 1, 0, %91;\n}\n"
        : "+f"(d[0]), "+f"(d[1]), "+f"(d[2]), "+f"(d[3]), "+f"(d[4]), "+f"(d[5]), "+f"(d[6]), "+f"(d[7]), "+f"(d[8]), "+f"(d[9]), "+f"(d[10]), "+f"(d[11]), "+f"(d[12]), "+f"(d[13]), "+f"(d[14]), "+f"(d[15]), "+f"(d[16]), "+f"(d[17]), "+f"(d[18]), "+f"(d[19]), "+f"(d[20]), "+f"(d[21]), "+f"(d[22]), "+f"(d[23]), "+f"(d[24]), "+f"(d[25]), "+f"(d[26]), "+f"(d[27]), "+f"(d[28]), "+f"(d[29]), "+f"(d[30]), "+f"(d[31]), "+f"(d[32]), "+f"(d[33]), "+f"(d[34]), "+f"(d[35]), "+f"(d[36]), "+f"(d[37]), "+f"(d[38]), "+f"(d[39]), "+f"(d[40]), "+f"(d[41]), "+f"(d[42]), "+f"(d[43]), "+f"(d[44]), "+f"(d[45]), "+f"(d[46]), "+f"(d[47]), "+f"(d[48]), "+f"(d[49]), "+f"(d[50]), "+f"(d[51]), "+f"(d[52]), "+f"(d[53]), "+f"(d[54]), "+f"(d[55]), "+f"(d[56]), "+f"(d[57]), "+f"(d[58]), "+f"(d[59]), "+f"(d[60]), "+f"(d[61]), "+f"(d[62]), "+f"(d[63]), "+f"(d[64]), "+f"(d[65]), "+f"(d[66]), "+f"(d[67]), "+f"(d[68]), "+f"(d[69]), "+f"(d[70]), "+f"(d[71]), "+f"(d[72]), "+f"(d[73]), "+f"(d[74]), "+f"(d[75]), "+f"(d[76]), "+f"(d[77]), "+f"(d[78]), "+f"(d[79]), "+f"(d[80]), "+f"(d[81]), "+f"(d[82]), "+f"(d[83]), "+f"(d[84]), "+f"(d[85]), "+f"(d[86]), "+f"(d[87])
        : "l"(da), "l"(db), "r"(scale_d), "n"(TB));
}

template <int TB>
__device__ __forceinline__ void wgmma_n192(float (&d)[96], uint64_t da, uint64_t db, int scale_d) {
    asm volatile("{\n.reg .pred p;\nsetp.ne.b32 p, %98, 0;\n"
        "wgmma.mma_async.sync.aligned.m64n192k16.f32.bf16.bf16 {%0, %1, %2, %3, %4, %5, %6, %7, %8, %9, %10, %11, %12, %13, %14, %15, %16, %17, %18, %19, %20, %21, %22, %23, %24, %25, %26, %27, %28, %29, %30, %31, %32, %33, %34, %35, %36, %37, %38, %39, %40, %41, %42, %43, %44, %45, %46, %47, %48, %49, %50, %51, %52, %53, %54, %55, %56, %57, %58, %59, %60, %61, %62, %63, %64, %65, %66, %67, %68, %69, %70, %71, %72, %73, %74, %75, %76, %77, %78, %79, %80, %81, %82, %83, %84, %85, %86, %87, %88, %89, %90, %91, %92, %93, %94, %95}, %96, %97, p, 1, 1, 0, %99;\n}\n"
        : "+f"(d[0]), "+f"(d[1]), "+f"(d[2]), "+f"(d[3]), "+f"(d[4]), "+f"(d[5]), "+f"(d[6]), "+f"(d[7]), "+f"(d[8]), "+f"(d[9]), "+f"(d[10]), "+f"(d[11]), "+f"(d[12]), "+f"(d[13]), "+f"(d[14]), "+f"(d[15]), "+f"(d[16]), "+f"(d[17]), "+f"(d[18]), "+f"(d[19]), "+f"(d[20]), "+f"(d[21]), "+f"(d[22]), "+f"(d[23]), "+f"(d[24]), "+f"(d[25]), "+f"(d[26]), "+f"(d[27]), "+f"(d[28]), "+f"(d[29]), "+f"(d[30]), "+f"(d[31]), "+f"(d[32]), "+f"(d[33]), "+f"(d[34]), "+f"(d[35]), "+f"(d[36]), "+f"(d[37]), "+f"(d[38]), "+f"(d[39]), "+f"(d[40]), "+f"(d[41]), "+f"(d[42]), "+f"(d[43]), "+f"(d[44]), "+f"(d[45]), "+f"(d[46]), "+f"(d[47]), "+f"(d[48]), "+f"(d[49]), "+f"(d[50]), "+f"(d[51]), "+f"(d[52]), "+f"(d[53]), "+f"(d[54]), "+f"(d[55]), "+f"(d[56]), "+f"(d[57]), "+f"(d[58]), "+f"(d[59]), "+f"(d[60]), "+f"(d[61]), "+f"(d[62]), "+f"(d[63]), "+f"(d[64]), "+f"(d[65]), "+f"(d[66]), "+f"(d[67]), "+f"(d[68]), "+f"(d[69]), "+f"(d[70]), "+f"(d[71]), "+f"(d[72]), "+f"(d[73]), "+f"(d[74]), "+f"(d[75]), "+f"(d[76]), "+f"(d[77]), "+f"(d[78]), "+f"(d[79]), "+f"(d[80]), "+f"(d[81]), "+f"(d[82]), "+f"(d[83]), "+f"(d[84]), "+f"(d[85]), "+f"(d[86]), "+f"(d[87]), "+f"(d[88]), "+f"(d[89]), "+f"(d[90]), "+f"(d[91]), "+f"(d[92]), "+f"(d[93]), "+f"(d[94]), "+f"(d[95])
        : "l"(da), "l"(db), "r"(scale_d), "n"(TB));
}

__device__ __forceinline__ uint32_t pack_bf16(float lo, float hi) {
    uint32_t r;
    asm("cvt.rn.bf16x2.f32 %0, %1, %2;" : "=r"(r) : "f"(hi), "f"(lo));
    return r;
}
__device__ __forceinline__ float bf_lo(uint32_t v) { return __uint_as_float(v << 16); }
__device__ __forceinline__ float bf_hi(uint32_t v) { return __uint_as_float(v & 0xffff0000u); }

__device__ __forceinline__ void quad_transpose(uint32_t (&w)[4], int q) {
    const bool o1 = q & 1, o2 = q & 2;
    {
        uint32_t s0 = o1 ? w[0] : w[1], s1 = o1 ? w[2] : w[3];
        s0 = __shfl_xor_sync(0xffffffffu, s0, 1); s1 = __shfl_xor_sync(0xffffffffu, s1, 1);
        if (o1) { w[0] = s0; w[2] = s1; } else { w[1] = s0; w[3] = s1; }
    }
    {
        uint32_t s0 = o2 ? w[0] : w[2], s1 = o2 ? w[1] : w[3];
        s0 = __shfl_xor_sync(0xffffffffu, s0, 2); s1 = __shfl_xor_sync(0xffffffffu, s1, 2);
        if (o2) { w[0] = s0; w[1] = s1; } else { w[2] = s0; w[3] = s1; }
    }
}

__device__ __forceinline__ float ex2(float x) { float y; asm("ex2.approx.ftz.f32 %0, %1;" : "=f"(y) : "f"(x)); return y; }
__device__ __forceinline__ float rcp(float x) { float y; asm("rcp.approx.ftz.f32 %0, %1;" : "=f"(y) : "f"(x)); return y; }

__device__ __forceinline__ float ex2v(float x) { float y; asm volatile("ex2.approx.ftz.f32 %0, %1;" : "=f"(y) : "f"(x)); return y; }
__device__ __forceinline__ float rcpv(float x) { float y; asm volatile("rcp.approx.ftz.f32 %0, %1;" : "=f"(y) : "f"(x)); return y; }
__device__ __forceinline__ float mish_f(float h) {
    const float e = ex2v(1.4426950408889634f * fminf(h, 20.f));
    const float n = fmaf(e, e, e + e);
    return h * n * rcpv(n + 2.f);
}

__device__ __forceinline__ void pdl_wait()   { asm volatile("griddepcontrol.wait;" ::: "memory"); }
__device__ __forceinline__ void pdl_launch() { asm volatile("griddepcontrol.launch_dependents;" ::: "memory"); }

constexpr int K1_STAGES = 4;
constexpr int K1_XBYTES = 128 * 512 * 2;
constexpr int K1_BSTAGE = 3 * 8192;
constexpr int K1_SMEM   = K1_XBYTES + K1_STAGES * K1_BSTAGE + 2048   + 1024  ;

__global__ void __launch_bounds__(384, 1)
k1_kernel(const __grid_constant__ CUtensorMap tmX, const __grid_constant__ CUtensorMap tmWqkv,
          const __grid_constant__ CUtensorMap tmW1, const bf16* __restrict__ b1,
          const bf16* __restrict__ wqkvp, const bf16* __restrict__ w2p, const bf16* __restrict__ wop)
{
    extern __shared__ uint8_t smem_raw[];
    const uint32_t sbase = (smem_u32(smem_raw) + 1023u) & ~1023u;
    uint8_t* sgen = smem_raw + (sbase - smem_u32(smem_raw));
    const uint32_t sX = sbase;
    const uint32_t sB = sbase + K1_XBYTES;
    const uint32_t sBar = sB + K1_STAGES * K1_BSTAGE;
    const uint32_t x_full = sBar;
    const uint32_t b_full = sBar + 64;
    const uint32_t b_empty = sBar + 96;
    uint32_t* sBias = (uint32_t*)(sgen + K1_XBYTES + K1_STAGES * K1_BSTAGE + 1664);

    const int rb = blockIdx.x >> 3, j = blockIdx.x & 7;
    const int tid = threadIdx.x, wg = tid >> 7, warp = tid >> 5, lane = tid & 31;
    TS(0, tid == 0);
    pdl_launch();

    if (tid == 0) {
        for (int i = 0; i < 8; i++) mbar_init(x_full + 8 * i, 1);
        for (int i = 0; i < K1_STAGES; i++) { mbar_init(b_full + 8 * i, 1); mbar_init(b_empty + 8 * i, 8); }
        fence_barrier_init();
    }
    __syncthreads();

    if (wg == 2) {
        reg_dealloc<40>();
        if (tid == 288) {
            const int b = blockIdx.x;
            mbar_wait(b_full + 8, 0);
            l2_prefetch((const uint8_t*)wqkvp + b * 12288, 12288);
            l2_prefetch((const uint8_t*)w2p + b * 11008, 11008);
            l2_prefetch((const uint8_t*)wop + b * 4096, 4096);
        }
        if (tid == 256) {
            for (int it = 0; it < 16; it++) {
                if (it < 8) {
                    mbar_expect_tx(x_full + 8 * it, 16384);
                    tma_load_2d(sX + it * 16384, &tmX, it * 64, rb * 128, x_full + 8 * it);
                }
                const int st = it & 3;
                if (it >= K1_STAGES) mbar_wait(b_empty + 8 * st, ((it >> 2) - 1) & 1);
                mbar_expect_tx(b_full + 8 * st, K1_BSTAGE);
                const uint32_t dst = sB + st * K1_BSTAGE;
                if (it < 8) {
                    for (int b = 0; b < 3; b++) tma_load_2d(dst + b * 8192, &tmW1, j * FCH + b * 64, it * 64, b_full + 8 * st);
                } else {
                    for (int b = 0; b < 3; b++) tma_load_2d(dst + b * 8192, &tmWqkv, b * 512 + j * 64, (it - 8) * 64, b_full + 8 * st);
                }
            }
        }
    } else {
        reg_alloc<232>();
        if (tid < 88) {
            const int c = j * FCH + tid * 2;
            sBias[tid] = c < F_ ? __ldg((const uint32_t*)(b1 + c)) : 0u;
        }
        const int t128 = tid & 127, w4 = warp & 3, q = lane & 3;
        float accF[88], accQ[96];
#pragma unroll 1
        for (int kc = 0; kc < 8; kc++) {
            const int st = kc & 3;
            mbar_wait(x_full + 8 * kc, 0);
            mbar_wait(b_full + 8 * st, (kc >> 2) & 1);
            TS(1, tid == 0 && kc == 0); TS(2, tid == 0 && kc == 4);
            wgmma_fence();
#pragma unroll
            for (int k16 = 0; k16 < 4; k16++) {
                const uint64_t db = make_desc(sB + st * K1_BSTAGE + k16 * 2048, 8192, 1024);
                const uint64_t da = make_desc(sX + kc * 16384 + wg * 8192 + k16 * 32, 16, 1024);
                wgmma_n176<1>(accF, da, db, (kc | k16) != 0);
            }
            wgmma_commit();
            if (kc > 0) { wgmma_wait<1>(); if (lane == 0) mbar_arrive(b_empty + 8 * ((kc - 1) & 3)); }
        }
        wgmma_wait<0>();
        if (lane == 0) mbar_arrive(b_empty + 8 * 3);
        bar_sync(3, 256);
        TS(3, tid == 0);
        const int n0 = j * FCH;
        const int rl = wg * 64 + w4 * 16 + (lane >> 2);
        bf16* frow0 = g_a2 + (size_t)(rb * 128 + rl) * KA2 + D_ + n0;
        bf16* frow1 = frow0 + 8 * KA2;
        auto ffn_chunk = [&](int u) {
            uint32_t w0[4], w1[4];
#pragma unroll
            for (int i = 0; i < 4; i++) {
                const int t = u * 4 + i;
                if (t < 22) {
                    const uint32_t bv = sBias[t * 4 + q];
                    const float bb0 = bf_lo(bv), bb1 = bf_hi(bv);
                    w0[i] = pack_bf16(mish_f(accF[t * 4 + 0] + bb0), mish_f(accF[t * 4 + 1] + bb1));
                    w1[i] = pack_bf16(mish_f(accF[t * 4 + 2] + bb0), mish_f(accF[t * 4 + 3] + bb1));
                } else { w0[i] = 0; w1[i] = 0; }
            }
            quad_transpose(w0, q);
            quad_transpose(w1, q);
            const int c = (u * 4 + q) * 8;
            if (c < FCH && n0 + c < F_) {
                *(uint4*)(frow0 + c) = make_uint4(w0[0], w0[1], w0[2], w0[3]);
                *(uint4*)(frow1 + c) = make_uint4(w1[0], w1[1], w1[2], w1[3]);
            }
        };
#pragma unroll
        for (int kc = 0; kc < 8; kc++) {
            const int st = kc & 3;
            mbar_wait(b_full + 8 * st, ((kc + 8) >> 2) & 1);
            wgmma_fence();
#pragma unroll
            for (int k16 = 0; k16 < 4; k16++) {
                const uint64_t db = make_desc(sB + st * K1_BSTAGE + k16 * 2048, 8192, 1024);
                const uint64_t da = make_desc(sX + kc * 16384 + wg * 8192 + k16 * 32, 16, 1024);
                wgmma_n192<1>(accQ, da, db, (kc | k16) != 0);
            }
            wgmma_commit();
            if (kc < 6) ffn_chunk(kc);
            if (kc > 0) { wgmma_wait<1>(); if (lane == 0) mbar_arrive(b_empty + 8 * ((kc - 1) & 3)); }
        }
        wgmma_wait<0>();
        TS(4, tid == 0);
        {
            bf16* orow0 = g_qkv + ((size_t)j * S_ + rb * 128 + rl) * 192;
            bf16* orow1 = orow0 + 8 * 192;
#pragma unroll
            for (int u = 0; u < 6; u++) {
                uint32_t w0[4], w1[4];
#pragma unroll
                for (int i = 0; i < 4; i++) {
                    const int t = u * 4 + i;
                    w0[i] = pack_bf16(accQ[t * 4 + 0], accQ[t * 4 + 1]);
                    w1[i] = pack_bf16(accQ[t * 4 + 2], accQ[t * 4 + 3]);
                }
                quad_transpose(w0, q);
                quad_transpose(w1, q);
                const int c = (u * 4 + q) * 8;
                *(uint4*)(orow0 + c) = make_uint4(w0[0], w0[1], w0[2], w0[3]);
                *(uint4*)(orow1 + c) = make_uint4(w1[0], w1[1], w1[2], w1[3]);
            }
        }
        TS(5, tid == 0);
    }
}

__device__ __forceinline__ void ldsm_x4(uint32_t (&r)[4], uint32_t addr) {
    asm("ldmatrix.sync.aligned.m8n8.x4.shared.b16 {%0,%1,%2,%3}, [%4];"
                 : "=r"(r[0]), "=r"(r[1]), "=r"(r[2]), "=r"(r[3]) : "r"(addr));
}
__device__ __forceinline__ void ldsm_x4_t(uint32_t (&r)[4], uint32_t addr) {
    asm("ldmatrix.sync.aligned.m8n8.x4.trans.shared.b16 {%0,%1,%2,%3}, [%4];"
                 : "=r"(r[0]), "=r"(r[1]), "=r"(r[2]), "=r"(r[3]) : "r"(addr));
}
__device__ __forceinline__ void mma16816(float (&d)[4], const uint32_t (&a)[4], uint32_t b0, uint32_t b1) {
    asm("mma.sync.aligned.m16n8k16.row.col.f32.bf16.bf16.f32 {%0,%1,%2,%3}, {%4,%5,%6,%7}, {%8,%9}, {%0,%1,%2,%3};"
                 : "+f"(d[0]), "+f"(d[1]), "+f"(d[2]), "+f"(d[3])
                 : "r"(a[0]), "r"(a[1]), "r"(a[2]), "r"(a[3]), "r"(b0), "r"(b1));
}
__device__ __forceinline__ void mma16816_z(float (&d)[4], const uint32_t (&a)[4], uint32_t b0, uint32_t b1) {
    asm("mma.sync.aligned.m16n8k16.row.col.f32.bf16.bf16.f32 {%0,%1,%2,%3}, {%4,%5,%6,%7}, {%8,%9}, {%10,%10,%10,%10};"
                 : "=f"(d[0]), "=f"(d[1]), "=f"(d[2]), "=f"(d[3])
                 : "r"(a[0]), "r"(a[1]), "r"(a[2]), "r"(a[3]), "r"(b0), "r"(b1), "f"(0.f));
}

constexpr int KV_PITCH = 128;

template <int EDGE, bool HEAD>
__device__ __forceinline__ void blk_scores(float (&s)[2][4], const uint32_t (&qa)[4], uint32_t kaddr, bool dead, int r0, int c0)
{
    uint32_t kf[4];
    ldsm_x4(kf, kaddr);
    mma16816_z(s[0], qa, kf[0], kf[1]);
    mma16816_z(s[1], qa, kf[2], kf[3]);
#pragma unroll
    for (int t = 0; t < 2; t++)
#pragma unroll
        for (int e = 0; e < 4; e++) {
            const int r = r0 + (e >> 1) * 8, c = t * 8 + c0 + (e & 1);
            if (EDGE == 1 && c <= r) s[t][e] = -1e30f;
            if (EDGE == 2 && c > r) s[t][e] = -1e30f;
            if (HEAD && dead) s[t][e] = -1e30f;
        }
}
__device__ __forceinline__ void blk_max(const float (&s)[2][4], float& n0, float& n1) {
    n0 = fmaxf(n0, fmaxf(fmaxf(s[0][0], s[0][1]), fmaxf(s[1][0], s[1][1])));
    n1 = fmaxf(n1, fmaxf(fmaxf(s[0][2], s[0][3]), fmaxf(s[1][2], s[1][3])));
}
__device__ __forceinline__ void blk_pv(const float (&s)[2][4], float mc0, float mc1, float (&l)[4],
                                       float (&o)[2][4], uint32_t vaddr) {
    const float C = 0.25f * 1.4426950408889634f;
    uint32_t pa[4];
#pragma unroll
    for (int t = 0; t < 2; t++) {
        const float p0 = ex2(fmaf(s[t][0], C, -mc0)), p1 = ex2(fmaf(s[t][1], C, -mc0));
        const float p2 = ex2(fmaf(s[t][2], C, -mc1)), p3 = ex2(fmaf(s[t][3], C, -mc1));
        pa[2 * t] = pack_bf16(p0, p1); pa[2 * t + 1] = pack_bf16(p2, p3);
    }
    uint32_t vf[4];
    ldsm_x4_t(vf, vaddr);
    mma16816(o[0], pa, vf[0], vf[1]);
    mma16816(o[1], pa, vf[2], vf[3]);
    mma16816(l, pa, 0x3F803F80u, 0x3F803F80u);
}
__device__ __forceinline__ void quad_max(float& n0, float& n1) {
    n0 = fmaxf(n0, __shfl_xor_sync(0xffffffffu, n0, 1)); n1 = fmaxf(n1, __shfl_xor_sync(0xffffffffu, n1, 1));
    n0 = fmaxf(n0, __shfl_xor_sync(0xffffffffu, n0, 2)); n1 = fmaxf(n1, __shfl_xor_sync(0xffffffffu, n1, 2));
}
template <int NC, int NN, bool FIRST, bool NEXT_IS_EDGE, bool HEAD>
__device__ __forceinline__ void pipe_step(const float (&sc)[5][2][4], float (&sn)[5][2][4], const uint32_t (&qa)[4],
                                          uint32_t ka, uint32_t va, int kc, int kn, int kb0, int r0, int c0,
                                          float& m0, float& m1, float& n0, float& n1, float (&l)[4], float (&o)[2][4])
{
    const float C = 0.25f * 1.4426950408889634f;
    const float mc0 = n0 * C, mc1 = n1 * C;
    if (!FIRST) {
        const float a0 = ex2(fmaf(m0, C, -mc0)), a1 = ex2(fmaf(m1, C, -mc1));
        l[0] *= a0; l[2] *= a1;
        o[0][0] *= a0; o[0][1] *= a0; o[1][0] *= a0; o[1][1] *= a0;
        o[0][2] *= a1; o[0][3] *= a1; o[1][2] *= a1; o[1][3] *= a1;
    }
    m0 = n0; m1 = n1;
#pragma unroll
    for (int b = 0; b < NC; b++) {
        if (b < NN) {
            if (NEXT_IS_EDGE && b == 0) blk_scores<1, HEAD>(sn[b], qa, ka + (kn + b) * 16 * KV_PITCH, kn + b < kb0, r0, c0);
            else                        blk_scores<0, HEAD>(sn[b], qa, ka + (kn + b) * 16 * KV_PITCH, kn + b < kb0, r0, c0);
        }
        blk_pv(sc[b], mc0, mc1, l, o, va + (kc + b) * 16 * KV_PITCH);
        if (b < NN) blk_max(sn[b], n0, n1);
    }
    if (NN > 0) quad_max(n0, n1);
}

__device__ __forceinline__ void kv_need(uint32_t kvbar, int blk, uint32_t& ka, uint32_t& va) {
    mbar_wait(kvbar + 8 * blk, 0);
    asm volatile("" : "+r"(ka), "+r"(va) :: "memory");
}
template <bool HEAD>
__device__ __forceinline__ void attn_task(const uint32_t (&qa)[4], uint32_t ka, uint32_t va, int kb0, int lane, int qt, uint32_t kvbar,
                                          bf16* __restrict__ out  , float g0, float g1)
{
    const int r0 = lane >> 2, c0 = (lane & 3) * 2;
    float m0 = -1e30f, m1 = -1e30f, n0 = -1e30f, n1 = -1e30f;
    float l[4] = {0.f, 0.f, 0.f, 0.f};
    float o[2][4] = {{0.f, 0.f, 0.f, 0.f}, {0.f, 0.f, 0.f, 0.f}};
    float sa[5][2][4], sb[5][2][4];
    kv_need(kvbar, 2, ka, va);
    if (qt < 4) kv_need(kvbar, 1, ka, va);
#pragma unroll
    for (int b = 0; b < 5; b++) {
        if (b == 4) blk_scores<2, HEAD>(sa[b], qa, ka + (12 + b) * 16 * KV_PITCH, false, r0, c0);
        else        blk_scores<0, HEAD>(sa[b], qa, ka + (12 + b) * 16 * KV_PITCH, 12 + b < kb0, r0, c0);
        blk_max(sa[b], n0, n1);
    }
    quad_max(n0, n1);
    kv_need(kvbar, 1, ka, va);
    if (HEAD) {
        pipe_step<5, 0, true, false, HEAD>(sa, sb, qa, ka, va, 12, 0, kb0, r0, c0, m0, m1, n0, n1, l, o);
        kv_need(kvbar, 0, ka, va);
#pragma unroll 1
        for (int kc = 8; kc >= 0 && kb0 < kc + 4; kc -= 4) {
#pragma unroll
            for (int b = 0; b < 4; b++) {
                blk_scores<0, HEAD>(sa[b], qa, ka + (kc + b) * 16 * KV_PITCH, kc + b < kb0, r0, c0);
                blk_max(sa[b], n0, n1);
            }
            quad_max(n0, n1);
            pipe_step<4, 0, false, false, HEAD>(sa, sb, qa, ka, va, kc, 0, kb0, r0, c0, m0, m1, n0, n1, l, o);
        }
    } else {
        pipe_step<5, 4, true,  false, HEAD>(sa, sb, qa, ka, va, 12, 8, kb0, r0, c0, m0, m1, n0, n1, l, o);
        if (qt < 4) kv_need(kvbar, 0, ka, va);
        pipe_step<4, 4, false, false, HEAD>(sb, sa, qa, ka, va, 8, 4, kb0, r0, c0, m0, m1, n0, n1, l, o);
        kv_need(kvbar, 0, ka, va);
        pipe_step<4, 4, false, true,  HEAD>(sa, sb, qa, ka, va, 4, 0, kb0, r0, c0, m0, m1, n0, n1, l, o);
        pipe_step<4, 0, false, false, HEAD>(sb, sa, qa, ka, va, 0, 0, kb0, r0, c0, m0, m1, n0, n1, l, o);
    }
    const float f0 = __fdividef(g0, l[0]), f1 = __fdividef(g1, l[2]);
#pragma unroll
    for (int t = 0; t < 2; t++) {
        *(uint32_t*)(out + (size_t)r0 * KA2 + t * 8 + c0) = pack_bf16(o[t][0] * f0, o[t][1] * f0);
        *(uint32_t*)(out + (size_t)(r0 + 8) * KA2 + t * 8 + c0) = pack_bf16(o[t][2] * f1, o[t][3] * f1);
    }
}

constexpr int K2_SMEM = 2 * 384 * KV_PITCH + 1024 + 64;

__global__ void __launch_bounds__(512, 1) k2_kernel(const __grid_constant__ CUtensorMap tmQKV, const bf16* __restrict__ x,
                                                    const bf16* __restrict__ gate_w)
{
    extern __shared__ uint8_t smem_raw[];
    const uint32_t sbase = (smem_u32(smem_raw) + 1023u) & ~1023u;
    uint8_t* sgen = smem_raw + (sbase - smem_u32(smem_raw));
    const uint32_t sK = sbase, sV = sK + 384 * KV_PITCH, kv_full = sbase + 2 * 384 * KV_PITCH;
    const int rb = blockIdx.x >> 3, j = blockIdx.x & 7;
    const int tid = threadIdx.x, warp = tid >> 5, lane = tid & 31;
    pdl_launch();
    if (tid == 0) {
        for (int i = 0; i < 3; i++) mbar_init(kv_full + 8 * i, 1);
        fence_barrier_init();
    }
    const int grow = blockIdx.x * 16 + warp;
    const uint4 ga = __ldg((const uint4*)gate_w + lane * 2), gb = __ldg((const uint4*)gate_w + lane * 2 + 1);
    const uint4 xa = __ldg((const uint4*)(x + (size_t)grow * D_) + lane * 2), xb = __ldg((const uint4*)(x + (size_t)grow * D_) + lane * 2 + 1);
    pdl_wait();
    TS(6, tid == 0);
    if (tid == 0) {
        for (int i = 0; i < 3; i++) {
            const uint32_t bar = kv_full + 8 * (2 - i);
            if (rb - i >= 0) {
                const int row = j * S_ + (rb - i) * 128;
                mbar_expect_tx(bar, 2 * 16384);
                tma_load_2d(sK + (2 - i) * 16384, &tmQKV, 64, row, bar);
                tma_load_2d(sV + (2 - i) * 16384, &tmQKV, 128, row, bar);
            } else {
                mbar_arrive(bar);
            }
        }
    }
    if (rb < 2) {
        for (int i = tid; i < (2 - rb) * 1024; i += 512) {
            *(uint4*)(sgen + i * 16) = make_uint4(0, 0, 0, 0);
            *(uint4*)(sgen + 384 * KV_PITCH + i * 16) = make_uint4(0, 0, 0, 0);
        }
    }
    const int qt = warp & 7, h0 = (warp >> 3) * 2;
    const int q0g = rb * 128 + qt * 16;
    const int r0 = lane >> 2, c0 = (lane & 3) * 2;
    const bf16* qsrc = g_qkv + ((size_t)j * S_ + q0g) * 192 + h0 * 16;
    uint32_t qa[4], qn[4];
    qa[0] = *(const uint32_t*)(qsrc + (size_t)r0 * 192 + c0);
    qa[1] = *(const uint32_t*)(qsrc + (size_t)(r0 + 8) * 192 + c0);
    qa[2] = *(const uint32_t*)(qsrc + (size_t)r0 * 192 + c0 + 8);
    qa[3] = *(const uint32_t*)(qsrc + (size_t)(r0 + 8) * 192 + c0 + 8);
    qn[0] = *(const uint32_t*)(qsrc + (size_t)r0 * 192 + 16 + c0);
    qn[1] = *(const uint32_t*)(qsrc + (size_t)(r0 + 8) * 192 + 16 + c0);
    qn[2] = *(const uint32_t*)(qsrc + (size_t)r0 * 192 + 16 + c0 + 8);
    qn[3] = *(const uint32_t*)(qsrc + (size_t)(r0 + 8) * 192 + 16 + c0 + 8);
    {
        float gs = bf_lo(xa.x) * bf_lo(ga.x);
        gs = fmaf(bf_hi(xa.x), bf_hi(ga.x), gs);
        gs = fmaf(bf_lo(xa.y), bf_lo(ga.y), gs); gs = fmaf(bf_hi(xa.y), bf_hi(ga.y), gs);
        gs = fmaf(bf_lo(xa.z), bf_lo(ga.z), gs); gs = fmaf(bf_hi(xa.z), bf_hi(ga.z), gs);
        gs = fmaf(bf_lo(xa.w), bf_lo(ga.w), gs); gs = fmaf(bf_hi(xa.w), bf_hi(ga.w), gs);
        gs = fmaf(bf_lo(xb.x), bf_lo(gb.x), gs); gs = fmaf(bf_hi(xb.x), bf_hi(gb.x), gs);
        gs = fmaf(bf_lo(xb.y), bf_lo(gb.y), gs); gs = fmaf(bf_hi(xb.y), bf_hi(gb.y), gs);
        gs = fmaf(bf_lo(xb.z), bf_lo(gb.z), gs); gs = fmaf(bf_hi(xb.z), bf_hi(gb.z), gs);
        gs = fmaf(bf_lo(xb.w), bf_lo(gb.w), gs); gs = fmaf(bf_hi(xb.w), bf_hi(gb.w), gs);
#pragma unroll
        for (int o = 16; o > 0; o >>= 1) gs += __shfl_xor_sync(0xffffffffu, gs, o);
        if (lane == 0) g_gate[grow] = 1.f / (1.f + __expf(-gs));
    }
    const float g0 = 1.f, g1 = 1.f;
    const int kb0 = q0g < 256 ? (256 - q0g) >> 4 : 0;
    __syncthreads();
    const uint32_t sKd = sK, sVd = sV;
    TS(7, tid == 0);
    const int krow = qt * 16 + (lane & 7) + ((lane >> 4) << 3);
    const int vrow = qt * 16 + (lane & 15);
#pragma unroll 1
    for (int hh = 0; hh < 2; hh++) {
        const int hl = h0 + hh;
        const uint32_t ka = sKd + krow * KV_PITCH + (((2 * hl + ((lane >> 3) & 1)) ^ (lane & 7)) << 4);
        const uint32_t va = sVd + vrow * KV_PITCH + (((2 * hl + (lane >> 4)) ^ (lane & 7)) << 4);
        if (rb < 2) attn_task<true>(qa, ka, va, kb0, lane, qt, kv_full, g_a2 + (size_t)q0g * KA2 + (j * 4 + hl) * 16, g0, g1);
        else        attn_task<false>(qa, ka, va, kb0, lane, qt, kv_full, g_a2 + (size_t)q0g * KA2 + (j * 4 + hl) * 16, g0, g1);
        TS(8 + hh, tid == 0);
        qa[0] = qn[0]; qa[1] = qn[1]; qa[2] = qn[2]; qa[3] = qn[3];
    }
}

constexpr int K3_STAGES = 8;
constexpr int K3_STAGE = 16384 + 8192;
constexpr int K3_SMEM = K3_STAGES * K3_STAGE + 1024 + 1024;
constexpr int K3_KSTEPS = 30;

__global__ void __launch_bounds__(384, 1)
k3_kernel(const __grid_constant__ CUtensorMap tmA2, const __grid_constant__ CUtensorMap tmWo,
          const __grid_constant__ CUtensorMap tmW2, bf16* __restrict__ out)
{
    extern __shared__ uint8_t smem_raw[];
    const uint32_t sbase = (smem_u32(smem_raw) + 1023u) & ~1023u;
    const uint32_t sBar = sbase + K3_STAGES * K3_STAGE;
    const uint32_t full = sBar, empty = sBar + 64;
    const int rb = blockIdx.x >> 3, nb = blockIdx.x & 7;
    const int tid = threadIdx.x, wg = tid >> 7, warp = tid >> 5, lane = tid & 31;
    if (tid == 0) {
        for (int i = 0; i < K3_STAGES; i++) { mbar_init(full + 8 * i, 1); mbar_init(empty + 8 * i, 8); }
        fence_barrier_init();
    }
    __syncthreads();
    TS(10, tid == 0);
    if (wg == 2) {
        reg_dealloc<40>();
        if (warp == 8) {
            if (lane == 0) {
                for (int ks = 0; ks < K3_KSTEPS; ks++) {
                    const int st = ks % K3_STAGES;
                    if (ks >= K3_STAGES) mbar_wait(empty + 8 * st, ((ks / K3_STAGES) - 1) & 1);
                    mbar_expect_tx(full + 8 * st, K3_STAGE);
                    const uint32_t dst = sbase + st * K3_STAGE;
                    tma_load_2d(dst, &tmA2, ks * 64, rb * 128, full + 8 * st);
                    if (ks < 8) tma_load_2d(dst + 16384, &tmWo, nb * 64, ks * 64, full + 8 * st);
                    else        tma_load_2d(dst + 16384, &tmW2, nb * 64, (ks - 8) * 64, full + 8 * st);
                }
            }
        }
    } else {
        reg_alloc<232>();
        float accA[32], accB[32];
        const int q = lane & 3;
        const int rl = wg * 64 + (warp & 3) * 16 + (lane >> 2);
        const float g0 = g_gate[rb * 128 + rl], g1 = g_gate[rb * 128 + rl + 8];
        for (int ks = 0; ks < 8; ks++) {
            mbar_wait(full + 8 * ks, 0);
            TS(11, tid == 0 && ks == 0);
            wgmma_fence();
#pragma unroll
            for (int k16 = 0; k16 < 4; k16++) {
                const uint64_t da = make_desc(sbase + ks * K3_STAGE + wg * 8192 + k16 * 32, 16, 1024);
                const uint64_t db = make_desc(sbase + ks * K3_STAGE + 16384 + k16 * 2048, 8192, 1024);
                wgmma_n64<1>(accA, da, db, (ks | k16) != 0);
            }
            wgmma_commit();
            if (ks > 0) { wgmma_wait<1>(); if (lane == 0) mbar_arrive(empty + 8 * (ks - 1)); }
        }
        for (int ks = 8; ks < K3_KSTEPS; ks++) {
            const int st = ks % K3_STAGES;
            mbar_wait(full + 8 * st, (ks / K3_STAGES) & 1);
            TS(12, tid == 0 && ks == 8); TS(13, tid == 0 && ks == 16);
            wgmma_fence();
#pragma unroll
            for (int k16 = 0; k16 < 4; k16++) {
                const uint64_t da = make_desc(sbase + st * K3_STAGE + wg * 8192 + k16 * 32, 16, 1024);
                const uint64_t db = make_desc(sbase + st * K3_STAGE + 16384 + k16 * 2048, 8192, 1024);
                wgmma_n64<1>(accB, da, db, ((ks - 8) | k16) != 0);
            }
            wgmma_commit();
            wgmma_wait<1>();
            if (lane == 0) mbar_arrive(empty + 8 * ((ks - 1) % K3_STAGES));
        }
        wgmma_wait<0>();
        TS(14, tid == 0);
        bf16* orow0 = out + (size_t)(rb * 128 + rl) * D_ + nb * 64;
        bf16* orow1 = orow0 + 8 * D_;
#pragma unroll
        for (int u = 0; u < 2; u++) {
            uint32_t w0[4], w1[4];
#pragma unroll
            for (int i = 0; i < 4; i++) {
                const int t = u * 4 + i;
                w0[i] = pack_bf16(fmaf(g0, accA[t * 4 + 0] - accB[t * 4 + 0], accB[t * 4 + 0]), fmaf(g0, accA[t * 4 + 1] - accB[t * 4 + 1], accB[t * 4 + 1]));
                w1[i] = pack_bf16(fmaf(g1, accA[t * 4 + 2] - accB[t * 4 + 2], accB[t * 4 + 2]), fmaf(g1, accA[t * 4 + 3] - accB[t * 4 + 3], accB[t * 4 + 3]));
            }
            quad_transpose(w0, q);
            quad_transpose(w1, q);
            const int c = (u * 4 + q) * 8;
            *(uint4*)(orow0 + c) = make_uint4(w0[0], w0[1], w0[2], w0[3]);
            *(uint4*)(orow1 + c) = make_uint4(w1[0], w1[1], w1[2], w1[3]);
        }
        TS(15, tid == 0);
    }
}

typedef CUresult (*PFN_encodeTiled)(CUtensorMap*, CUtensorMapDataType, cuuint32_t, void*, const cuuint64_t*,
                                    const cuuint64_t*, const cuuint32_t*, const cuuint32_t*, CUtensorMapInterleave,
                                    CUtensorMapSwizzle, CUtensorMapL2promotion, CUtensorMapFloatOOBfill);

static void make_map(PFN_encodeTiled enc, CUtensorMap* m, const void* ptr, uint64_t cols, uint64_t rows,
                     uint32_t box_cols, uint32_t box_rows)
{
    cuuint64_t dims[2] = {cols, rows};
    cuuint64_t strides[1] = {cols * 2};
    cuuint32_t box[2] = {box_cols, box_rows};
    cuuint32_t es[2] = {1, 1};
    enc(m, CU_TENSOR_MAP_DATA_TYPE_BFLOAT16, 2, const_cast<void*>(ptr), dims, strides, box, es,
        CU_TENSOR_MAP_INTERLEAVE_NONE, CU_TENSOR_MAP_SWIZZLE_128B, CU_TENSOR_MAP_L2_PROMOTION_L2_128B,
        CU_TENSOR_MAP_FLOAT_OOB_FILL_NONE);
}

extern "C" void kernel_launch(void* const* d_in, const int* in_sizes, int n_in, void* d_out, int out_size)
{
    const bf16* x    = (const bf16*)d_in[0];
    const bf16* wqkv = (const bf16*)d_in[1];
    const bf16* wo   = (const bf16*)d_in[2];
    const bf16* w1   = (const bf16*)d_in[4];
    const bf16* b1   = (const bf16*)d_in[5];
    const bf16* w2   = (const bf16*)d_in[6];
    const bf16* gw   = (const bf16*)d_in[7];

    static PFN_encodeTiled enc = nullptr;
    if (!enc) {
        void* fn = nullptr;
        cudaDriverEntryPointQueryResult qr;
        cudaGetDriverEntryPoint("cuTensorMapEncodeTiled", &fn, cudaEnableDefault, &qr);
        enc = (PFN_encodeTiled)fn;
        cudaFuncSetAttribute(k1_kernel, cudaFuncAttributeMaxDynamicSharedMemorySize, K1_SMEM);
        cudaFuncSetAttribute(k2_kernel, cudaFuncAttributeMaxDynamicSharedMemorySize, K2_SMEM);
        cudaFuncSetAttribute(k3_kernel, cudaFuncAttributeMaxDynamicSharedMemorySize, K3_SMEM);
    }
    void* a2p = nullptr;
    cudaGetSymbolAddress(&a2p, g_a2);
    void* qkvp = nullptr;
    cudaGetSymbolAddress(&qkvp, g_qkv);
    CUtensorMap tmX, tmWqkv, tmW1, tmA2, tmWo, tmW2, tmQKV;
    make_map(enc, &tmQKV, qkvp, 192, 8 * S_, 64, 128);
    make_map(enc, &tmX, x, D_, S_, 64, 128);
    make_map(enc, &tmWqkv, wqkv, 3 * D_, D_, 64, 64);
    make_map(enc, &tmW1, w1, F_, D_, 64, 64);
    make_map(enc, &tmA2, a2p, KA2, S_, 64, 128);
    make_map(enc, &tmWo, wo, D_, D_, 64, 64);
    make_map(enc, &tmW2, w2, D_, F_, 64, 64);

    cudaStream_t st = cudaStreamPerThread;
    k1_kernel<<<128, 384, K1_SMEM, st>>>(tmX, tmWqkv, tmW1, b1, wqkv, w2, wo);
    cudaLaunchAttribute at[1];
    at[0].id = cudaLaunchAttributeProgrammaticStreamSerialization;
    at[0].val.programmaticStreamSerializationAllowed = 1;
    cudaLaunchConfig_t cfg = {};
    cfg.gridDim = dim3(128); cfg.stream = st; cfg.attrs = at; cfg.numAttrs = 1;
    cfg.blockDim = dim3(512); cfg.dynamicSmemBytes = K2_SMEM;
    cudaLaunchKernelEx(&cfg, k2_kernel, tmQKV, x, gw);
    k3_kernel<<<128, 384, K3_SMEM, st>>>(tmA2, tmWo, tmW2, (bf16*)d_out);
}
```

```cpp
#include <cuda_runtime.h>
#include <cuda_bf16.h>
#include <cuda.h>
#include <stdint.h>

typedef __nv_bfloat16 bf16;

constexpr int S_ = 2048, D_ = 512, F_ = 1376;
constexpr int KA2 = D_ + F_;
constexpr int FCH = 176;

__device__ bf16  g_qkv[8 * S_ * 192];
__device__ bf16  g_a2[S_ * KA2];
__device__ float g_gate[S_];

#define TS(k, cond) do { } while (0)

__device__ __forceinline__ uint32_t smem_u32(const void* p) { return (uint32_t)__cvta_generic_to_shared(p); }
__device__ __forceinline__ void mbar_init(uint32_t bar, uint32_t count) {
    asm volatile("mbarrier.init.shared::cta.b64 [%0], %1;" :: "r"(bar), "r"(count) : "memory");
}
__device__ __forceinline__ void mbar_expect_tx(uint32_t bar, uint32_t bytes) {
    asm volatile("mbarrier.arrive.expect_tx.shared::cta.b64 _, [%0], %1;" :: "r"(bar), "r"(bytes) : "memory");
}
__device__ __forceinline__ void mbar_arrive(uint32_t bar) {
    asm volatile("mbarrier.arrive.shared::cta.b64 _, [%0];" :: "r"(bar) : "memory");
}
__device__ __forceinline__ bool mbar_try_wait(uint32_t bar, uint32_t parity) {
    uint32_t ok;
    asm volatile("{\n.reg .pred p;\nmbarrier.try_wait.parity.shared::cta.b64 p, [%1], %2;\nselp.u32 %0, 1, 0, p;\n}"
                 : "=r"(ok) : "r"(bar), "r"(parity) : "memory");
    return ok != 0;
}
__device__ __forceinline__ void mbar_wait(uint32_t bar, uint32_t parity) {
    for (uint32_t it = 0; it < (1u << 22); ++it) { if (mbar_try_wait(bar, parity)) break; }
}
__device__ __forceinline__ void tma_load_2d(uint32_t dst, const CUtensorMap* map, int c0, int c1, uint32_t bar) {
    asm volatile("cp.async.bulk.tensor.2d.shared::cluster.global.mbarrier::complete_tx::bytes [%0], [%1, {%3, %4}], [%2];"
                 :: "r"(dst), "l"(map), "r"(bar), "r"(c0), "r"(c1) : "memory");
}
__device__ __forceinline__ void l2_prefetch(const void* p, uint32_t bytes) {
    asm volatile("cp.async.bulk.prefetch.L2.global [%0], %1;" :: "l"(p), "r"(bytes) : "memory");
}
__device__ __forceinline__ void fence_barrier_init() { asm volatile("fence.mbarrier_init.release.cluster;" ::: "memory"); }
__device__ __forceinline__ void wgmma_fence()  { asm volatile("wgmma.fence.sync.aligned;" ::: "memory"); }
__device__ __forceinline__ void wgmma_commit() { asm volatile("wgmma.commit_group.sync.aligned;" ::: "memory"); }
template <int N> __device__ __forceinline__ void wgmma_wait() { asm volatile("wgmma.wait_group.sync.aligned %0;" :: "n"(N) : "memory"); }
template <int R> __device__ __forceinline__ void reg_alloc()   { asm volatile("setmaxnreg.inc.sync.aligned.u32 %0;" :: "n"(R)); }
template <int R> __device__ __forceinline__ void reg_dealloc() { asm volatile("setmaxnreg.dec.sync.aligned.u32 %0;" :: "n"(R)); }
__device__ __forceinline__ void bar_sync(int id, int n)   { asm volatile("bar.sync %0, %1;" :: "r"(id), "r"(n) : "memory"); }
__device__ __forceinline__ void bar_arrive(int id, int n) { asm volatile("bar.arrive %0, %1;" :: "r"(id), "r"(n) : "memory"); }

__device__ __forceinline__ uint64_t make_desc(uint32_t addr, uint32_t lbo, uint32_t sbo) {
    uint64_t d = (uint64_t)((addr & 0x3FFFF) >> 4);
    d |= (uint64_t)((lbo & 0x3FFFF) >> 4) << 16;
    d |= (uint64_t)((sbo & 0x3FFFF) >> 4) << 32;
    d |= (uint64_t)1 << 62;
    return d;
}

template <int TB>
__device__ __forceinline__ void wgmma_n64(float (&d)[32], uint64_t da, uint64_t db, int scale_d) {
    asm volatile("{\n.reg .pred p;\nsetp.ne.b32 p, %34, 0;\n"
        "wgmma.mma_async.sync.aligned.m64n64k16.f32.bf16.bf16 {%0, %1, %2, %3, %4, %5, %6, %7, %8, %9, %10, %11, %12, %13, %14, %15, %16, %17, %18, %19, %20, %21, %22, %23, %24, %25, %26, %27, %28, %29, %30, %31}, %32, %33, p, 1, 1, 0, %35;\n}\n"
        : "+f"(d[0]), "+f"(d[1]), "+f"(d[2]), "+f"(d[3]), "+f"(d[4]), "+f"(d[5]), "+f"(d[6]), "+f"(d[7]), "+f"(d[8]), "+f"(d[9]), "+f"(d[10]), "+f"(d[11]), "+f"(d[12]), "+f"(d[13]), "+f"(d[14]), "+f"(d[15]), "+f"(d[16]), "+f"(d[17]), "+f"(d[18]), "+f"(d[19]), "+f"(d[20]), "+f"(d[21]), "+f"(d[22]), "+f"(d[23]), "+f"(d[24]), "+f"(d[25]), "+f"(d[26]), "+f"(d[27]), "+f"(d[28]), "+f"(d[29]), "+f"(d[30]), "+f"(d[31])
        : "l"(da), "l"(db), "r"(scale_d), "n"(TB));
}

template <int TB>
__device__ __forceinline__ void wgmma_n128(float (&d)[64], uint64_t da, uint64_t db, int scale_d) {
    asm volatile("{\n.reg .pred p;\nsetp.ne.b32 p, %66, 0;\n"
        "wgmma.mma_async.sync.aligned.m64n128k16.f32.bf16.bf16 {%0, %1, %2, %3, %4, %5, %6, %7, %8, %9, %10, %11, %12, %13, %14, %15, %16, %17, %18, %19, %20, %21, %22, %23, %24, %25, %26, %27, %28, %29, %30, %31, %32, %33, %34, %35, %36, %37, %38, %39, %40, %41, %42, %43, %44, %45, %46, %47, %48, %49, %50, %51, %52, %53, %54, %55, %56, %57, %58, %59, %60, %61, %62, %63}, %64, %65, p, 1, 1, 0, %67;\n}\n"
        : "+f"(d[0]), "+f"(d[1]), "+f"(d[2]), "+f"(d[3]), "+f"(d[4]), "+f"(d[5]), "+f"(d[6]), "+f"(d[7]), "+f"(d[8]), "+f"(d[9]), "+f"(d[10]), "+f"(d[11]), "+f"(d[12]), "+f"(d[13]), "+f"(d[14]), "+f"(d[15]), "+f"(d[16]), "+f"(d[17]), "+f"(d[18]), "+f"(d[19]), "+f"(d[20]), "+f"(d[21]), "+f"(d[22]), "+f"(d[23]), "+f"(d[24]), "+f"(d[25]), "+f"(d[26]), "+f"(d[27]), "+f"(d[28]), "+f"(d[29]), "+f"(d[30]), "+f"(d[31]), "+f"(d[32]), "+f"(d[33]), "+f"(d[34]), "+f"(d[35]), "+f"(d[36]), "+f"(d[37]), "+f"(d[38]), "+f"(d[39]), "+f"(d[40]), "+f"(d[41]), "+f"(d[42]), "+f"(d[43]), "+f"(d[44]), "+f"(d[45]), "+f"(d[46]), "+f"(d[47]), "+f"(d[48]), "+f"(d[49]), "+f"(d[50]), "+f"(d[51]), "+f"(d[52]), "+f"(d[53]), "+f"(d[54]), "+f"(d[55]), "+f"(d[56]), "+f"(d[57]), "+f"(d[58]), "+f"(d[59]), "+f"(d[60]), "+f"(d[61]), "+f"(d[62]), "+f"(d[63])
        : "l"(da), "l"(db), "r"(scale_d), "n"(TB));
}

template <int TB>
__device__ __forceinline__ void wgmma_n176(float (&d)[88], uint64_t da, uint64_t db, int scale_d) {
    asm volatile("{\n.reg .pred p;\nsetp.ne.b32 p, %90, 0;\n"
        "wgmma.mma_async.sync.aligned.m64n176k16.f32.bf16.bf16 {%0, %1, %2, %3, %4, %5, %6, %7, %8, %9, %10, %11, %12, %13, %14, %15, %16, %17, %18, %19, %20, %21, %22, %23, %24, %25, %26, %27, %28, %29, %30, %31, %32, %33, %34, %35, %36, %37, %38, %39, %40, %41, %42, %43, %44, %45, %46, %47, %48, %49, %50, %51, %52, %53, %54, %55, %56, %57, %58, %59, %60, %61, %62, %63, %64, %65, %66, %67, %68, %69, %70, %71, %72, %73, %74, %75, %76, %77, %78, %79, %80, %81, %82, %83, %84, %85, %86, %87}, %88, %89, p, 1, 1, 0, %91;\n}\n"
        : "+f"(d[0]), "+f"(d[1]), "+f"(d[2]), "+f"(d[3]), "+f"(d[4]), "+f"(d[5]), "+f"(d[6]), "+f"(d[7]), "+f"(d[8]), "+f"(d[9]), "+f"(d[10]), "+f"(d[11]), "+f"(d[12]), "+f"(d[13]), "+f"(d[14]), "+f"(d[15]), "+f"(d[16]), "+f"(d[17]), "+f"(d[18]), "+f"(d[19]), "+f"(d[20]), "+f"(d[21]), "+f"(d[22]), "+f"(d[23]), "+f"(d[24]), "+f"(d[25]), "+f"(d[26]), "+f"(d[27]), "+f"(d[28]), "+f"(d[29]), "+f"(d[30]), "+f"(d[31]), "+f"(d[32]), "+f"(d[33]), "+f"(d[34]), "+f"(d[35]), "+f"(d[36]), "+f"(d[37]), "+f"(d[38]), "+f"(d[39]), "+f"(d[40]), "+f"(d[41]), "+f"(d[42]), "+f"(d[43]), "+f"(d[44]), "+f"(d[45]), "+f"(d[46]), "+f"(d[47]), "+f"(d[48]), "+f"(d[49]), "+f"(d[50]), "+f"(d[51]), "+f"(d[52]), "+f"(d[53]), "+f"(d[54]), "+f"(d[55]), "+f"(d[56]), "+f"(d[57]), "+f"(d[58]), "+f"(d[59]), "+f"(d[60]), "+f"(d[61]), "+f"(d[62]), "+f"(d[63]), "+f"(d[64]), "+f"(d[65]), "+f"(d[66]), "+f"(d[67]), "+f"(d[68]), "+f"(d[69]), "+f"(d[70]), "+f"(d[71]), "+f"(d[72]), "+f"(d[73]), "+f"(d[74]), "+f"(d[75]), "+f"(d[76]), "+f"(d[77]), "+f"(d[78]), "+f"(d[79]), "+f"(d[80]), "+f"(d[81]), "+f"(d[82]), "+f"(d[83]), "+f"(d[84]), "+f"(d[85]), "+f"(d[86]), "+f"(d[87])
        : "l"(da), "l"(db), "r"(scale_d), "n"(TB));
}

template <int TB>
__device__ __forceinline__ void wgmma_n192(float (&d)[96], uint64_t da, uint64_t db, int scale_d) {
    asm volatile("{\n.reg .pred p;\nsetp.ne.b32 p, %98, 0;\n"
        "wgmma.mma_async.sync.aligned.m64n192k16.f32.bf16.bf16 {%0, %1, %2, %3, %4, %5, %6, %7, %8, %9, %10, %11, %12, %13, %14, %15, %16, %17, %18, %19, %20, %21, %22, %23, %24, %25, %26, %27, %28, %29, %30, %31, %32, %33, %34, %35, %36, %37, %38, %39, %40, %41, %42, %43, %44, %45, %46, %47, %48, %49, %50, %51, %52, %53, %54, %55, %56, %57, %58, %59, %60, %61, %62, %63, %64, %65, %66, %67, %68, %69, %70, %71, %72, %73, %74, %75, %76, %77, %78, %79, %80, %81, %82, %83, %84, %85, %86, %87, %88, %89, %90, %91, %92, %93, %94, %95}, %96, %97, p, 1, 1, 0, %99;\n}\n"
        : "+f"(d[0]), "+f"(d[1]), "+f"(d[2]), "+f"(d[3]), "+f"(d[4]), "+f"(d[5]), "+f"(d[6]), "+f"(d[7]), "+f"(d[8]), "+f"(d[9]), "+f"(d[10]), "+f"(d[11]), "+f"(d[12]), "+f"(d[13]), "+f"(d[14]), "+f"(d[15]), "+f"(d[16]), "+f"(d[17]), "+f"(d[18]), "+f"(d[19]), "+f"(d[20]), "+f"(d[21]), "+f"(d[22]), "+f"(d[23]), "+f"(d[24]), "+f"(d[25]), "+f"(d[26]), "+f"(d[27]), "+f"(d[28]), "+f"(d[29]), "+f"(d[30]), "+f"(d[31]), "+f"(d[32]), "+f"(d[33]), "+f"(d[34]), "+f"(d[35]), "+f"(d[36]), "+f"(d[37]), "+f"(d[38]), "+f"(d[39]), "+f"(d[40]), "+f"(d[41]), "+f"(d[42]), "+f"(d[43]), "+f"(d[44]), "+f"(d[45]), "+f"(d[46]), "+f"(d[47]), "+f"(d[48]), "+f"(d[49]), "+f"(d[50]), "+f"(d[51]), "+f"(d[52]), "+f"(d[53]), "+f"(d[54]), "+f"(d[55]), "+f"(d[56]), "+f"(d[57]), "+f"(d[58]), "+f"(d[59]), "+f"(d[60]), "+f"(d[61]), "+f"(d[62]), "+f"(d[63]), "+f"(d[64]), "+f"(d[65]), "+f"(d[66]), "+f"(d[67]), "+f"(d[68]), "+f"(d[69]), "+f"(d[70]), "+f"(d[71]), "+f"(d[72]), "+f"(d[73]), "+f"(d[74]), "+f"(d[75]), "+f"(d[76]), "+f"(d[77]), "+f"(d[78]), "+f"(d[79]), "+f"(d[80]), "+f"(d[81]), "+f"(d[82]), "+f"(d[83]), "+f"(d[84]), "+f"(d[85]), "+f"(d[86]), "+f"(d[87]), "+f"(d[88]), "+f"(d[89]), "+f"(d[90]), "+f"(d[91]), "+f"(d[92]), "+f"(d[93]), "+f"(d[94]), "+f"(d[95])
        : "l"(da), "l"(db), "r"(scale_d), "n"(TB));
}

__device__ __forceinline__ uint32_t pack_bf16(float lo, float hi) {
    uint32_t r;
    asm("cvt.rn.bf16x2.f32 %0, %1, %2;" : "=r"(r) : "f"(hi), "f"(lo));
    return r;
}
__device__ __forceinline__ float bf_lo(uint32_t v) { return __uint_as_float(v << 16); }
__device__ __forceinline__ float bf_hi(uint32_t v) { return __uint_as_float(v & 0xffff0000u); }

__device__ __forceinline__ void quad_transpose(uint32_t (&w)[4], int q) {
    const bool o1 = q & 1, o2 = q & 2;
    {
        uint32_t s0 = o1 ? w[0] : w[1], s1 = o1 ? w[2] : w[3];
        s0 = __shfl_xor_sync(0xffffffffu, s0, 1); s1 = __shfl_xor_sync(0xffffffffu, s1, 1);
        if (o1) { w[0] = s0; w[2] = s1; } else { w[1] = s0; w[3] = s1; }
    }
    {
        uint32_t s0 = o2 ? w[0] : w[2], s1 = o2 ? w[1] : w[3];
        s0 = __shfl_xor_sync(0xffffffffu, s0, 2); s1 = __shfl_xor_sync(0xffffffffu, s1, 2);
        if (o2) { w[0] = s0; w[1] = s1; } else { w[2] = s0; w[3] = s1; }
    }
}

__device__ __forceinline__ float ex2(float x) { float y; asm("ex2.approx.ftz.f32 %0, %1;" : "=f"(y) : "f"(x)); return y; }
__device__ __forceinline__ float rcp(float x) { float y; asm("rcp.approx.ftz.f32 %0, %1;" : "=f"(y) : "f"(x)); return y; }

__device__ __forceinline__ float ex2v(float x) { float y; asm volatile("ex2.approx.ftz.f32 %0, %1;" : "=f"(y) : "f"(x)); return y; }
__device__ __forceinline__ float rcpv(float x) { float y; asm volatile("rcp.approx.ftz.f32 %0, %1;" : "=f"(y) : "f"(x)); return y; }
__device__ __forceinline__ float mish_f(float h) {
    const float e = ex2v(1.4426950408889634f * fminf(h, 20.f));
    const float n = fmaf(e, e, e + e);
    return h * n * rcpv(n + 2.f);
}

__device__ __forceinline__ void pdl_wait()   { asm volatile("griddepcontrol.wait;" ::: "memory"); }
__device__ __forceinline__ void pdl_launch() { asm volatile("griddepcontrol.launch_dependents;" ::: "memory"); }

constexpr int K1_STAGES = 4;
constexpr int K1_XBYTES = 128 * 512 * 2;
constexpr int K1_BSTAGE = 3 * 8192;
constexpr int K1_SMEM   = K1_XBYTES + K1_STAGES * K1_BSTAGE + 2048   + 1024  ;

__global__ void __launch_bounds__(384, 1)
k1_kernel(const __grid_constant__ CUtensorMap tmX, const __grid_constant__ CUtensorMap tmWqkv,
          const __grid_constant__ CUtensorMap tmW1, const bf16* __restrict__ b1,
          const bf16* __restrict__ gate_w, const bf16* __restrict__ w1p, const bf16* __restrict__ wqkvp,
          const bf16* __restrict__ w2p, const bf16* __restrict__ wop)
{

    extern __shared__ uint8_t smem_raw[];
    const uint32_t sbase = (smem_u32(smem_raw) + 1023u) & ~1023u;
    uint8_t* sgen = smem_raw + (sbase - smem_u32(smem_raw));
    const uint32_t sX = sbase;
    const uint32_t sB = sbase + K1_XBYTES;
    const uint32_t sBar = sB + K1_STAGES * K1_BSTAGE;
    const uint32_t x_full = sBar;
    const uint32_t b_full = sBar + 64;
    const uint32_t b_empty = sBar + 96;
    float* sGate = (float*)(sgen + K1_XBYTES + K1_STAGES * K1_BSTAGE + 128);
    uint8_t* sGw = sgen + K1_XBYTES + K1_STAGES * K1_BSTAGE + 640;
    uint32_t* sBias = (uint32_t*)(sgen + K1_XBYTES + K1_STAGES * K1_BSTAGE + 1664);

    const int rb = blockIdx.x >> 3, j = blockIdx.x & 7;
    const int tid = threadIdx.x, wg = tid >> 7, warp = tid >> 5, lane = tid & 31;
    TS(0, tid == 0);
    pdl_launch();

    if (tid == 0) {
        for (int i = 0; i < 8; i++) mbar_init(x_full + 8 * i, 1);
        for (int i = 0; i < K1_STAGES; i++) { mbar_init(b_full + 8 * i, 1); mbar_init(b_empty + 8 * i, 8); }
        fence_barrier_init();
    }
    __syncthreads();

    if (wg == 2) {
        reg_dealloc<40>();
        if (tid == 288) {
            const int b = blockIdx.x;
            mbar_wait(b_full + 8, 0);
            l2_prefetch((const uint8_t*)wqkvp + b * 12288, 12288);
            l2_prefetch((const uint8_t*)w2p + b * 11008, 11008);
            l2_prefetch((const uint8_t*)wop + b * 4096, 4096);
        }
        if (tid == 256) {
            for (int it = 0; it < 16; it++) {
                if (it < 8) {
                    mbar_expect_tx(x_full + 8 * it, 16384);
                    tma_load_2d(sX + it * 16384, &tmX, it * 64, rb * 128, x_full + 8 * it);
                }
                const int st = it & 3;
                if (it >= K1_STAGES) mbar_wait(b_empty + 8 * st, ((it >> 2) - 1) & 1);
                mbar_expect_tx(b_full + 8 * st, K1_BSTAGE);
                const uint32_t dst = sB + st * K1_BSTAGE;
                if (it < 8) {
                    for (int b = 0; b < 3; b++) tma_load_2d(dst + b * 8192, &tmW1, j * FCH + b * 64, it * 64, b_full + 8 * st);
                } else {
                    for (int b = 0; b < 3; b++) tma_load_2d(dst + b * 8192, &tmWqkv, b * 512 + j * 64, (it - 8) * 64, b_full + 8 * st);
                }
            }
        }
    } else {
        reg_alloc<232>();
        if (tid < 64) ((uint4*)sGw)[tid] = __ldg((const uint4*)gate_w + tid);
        else if (tid < 64 + 88) {
            const int c = j * FCH + (tid - 64) * 2;
            sBias[tid - 64] = c < F_ ? __ldg((const uint32_t*)(b1 + c)) : 0u;
        }
        bar_sync(3, 256);
        const int t128 = tid & 127, w4 = warp & 3, q = lane & 3;
        float accF[88], accQ[96];
        float gs = 0.f;
        const int grow = wg * 64 + (t128 >> 1), ghalf = t128 & 1;
#pragma unroll
        for (int kc = 0; kc < 8; kc++) {
            const int st = kc & 3;
            mbar_wait(x_full + 8 * kc, 0);
            mbar_wait(b_full + 8 * st, (kc >> 2) & 1);
            TS(1, tid == 0 && kc == 0); TS(2, tid == 0 && kc == 4);
            wgmma_fence();
#pragma unroll
            for (int k16 = 0; k16 < 4; k16++) {
                const uint64_t db = make_desc(sB + st * K1_BSTAGE + k16 * 2048, 8192, 1024);
                const uint64_t da = make_desc(sX + kc * 16384 + wg * 8192 + k16 * 32, 16, 1024);
                wgmma_n176<1>(accF, da, db, (kc | k16) != 0);
            }
            wgmma_commit();
#pragma unroll
            for (int c = 0; c < 4; c++) {
                const int cc = ghalf * 4 + c;
                const uint4 xv = *(const uint4*)(sgen + kc * 16384 + grow * 128 + ((cc ^ (grow & 7)) << 4));
                const uint4 gv = *(const uint4*)(sGw + kc * 128 + cc * 16);
                gs = fmaf(bf_lo(xv.x), bf_lo(gv.x), gs); gs = fmaf(bf_hi(xv.x), bf_hi(gv.x), gs);
                gs = fmaf(bf_lo(xv.y), bf_lo(gv.y), gs); gs = fmaf(bf_hi(xv.y), bf_hi(gv.y), gs);
                gs = fmaf(bf_lo(xv.z), bf_lo(gv.z), gs); gs = fmaf(bf_hi(xv.z), bf_hi(gv.z), gs);
                gs = fmaf(bf_lo(xv.w), bf_lo(gv.w), gs); gs = fmaf(bf_hi(xv.w), bf_hi(gv.w), gs);
            }
            if (kc > 0) { wgmma_wait<1>(); if (lane == 0) mbar_arrive(b_empty + 8 * ((kc - 1) & 3)); }
        }
        gs += __shfl_xor_sync(0xffffffffu, gs, 1);
        {
            const float g = 1.f / (1.f + __expf(-gs));
            if (ghalf == 0) {
                sGate[grow] = g;
                if (j == 0) g_gate[rb * 128 + grow] = g;
            }
        }
        wgmma_wait<0>();
        if (lane == 0) mbar_arrive(b_empty + 8 * 3);
        bar_sync(1 + wg, 128);
        TS(3, tid == 0);
        const int n0 = j * FCH;
        const int rl = wg * 64 + w4 * 16 + (lane >> 2);
        const float om0 = 1.f - sGate[rl], om1 = 1.f - sGate[rl + 8];
        bf16* frow0 = g_a2 + (size_t)(rb * 128 + rl) * KA2 + D_ + n0;
        bf16* frow1 = frow0 + 8 * KA2;
        auto ffn_chunk = [&](int u) {
            uint32_t w0[4], w1[4];
#pragma unroll
            for (int i = 0; i < 4; i++) {
                const int t = u * 4 + i;
                if (t < 22) {
                    const uint32_t bv = sBias[t * 4 + q];
                    const float bb0 = bf_lo(bv), bb1 = bf_hi(bv);
                    w0[i] = pack_bf16(mish_f(accF[t * 4 + 0] + bb0) * om0, mish_f(accF[t * 4 + 1] + bb1) * om0);
                    w1[i] = pack_bf16(mish_f(accF[t * 4 + 2] + bb0) * om1, mish_f(accF[t * 4 + 3] + bb1) * om1);
                } else { w0[i] = 0; w1[i] = 0; }
            }
            quad_transpose(w0, q);
            quad_transpose(w1, q);
            const int c = (u * 4 + q) * 8;
            if (c < FCH && n0 + c < F_) {
                *(uint4*)(frow0 + c) = make_uint4(w0[0], w0[1], w0[2], w0[3]);
                *(uint4*)(frow1 + c) = make_uint4(w1[0], w1[1], w1[2], w1[3]);
            }
        };
#pragma unroll
        for (int kc = 0; kc < 8; kc++) {
            const int st = kc & 3;
            mbar_wait(b_full + 8 * st, ((kc + 8) >> 2) & 1);
            wgmma_fence();
#pragma unroll
            for (int k16 = 0; k16 < 4; k16++) {
                const uint64_t db = make_desc(sB + st * K1_BSTAGE + k16 * 2048, 8192, 1024);
                const uint64_t da = make_desc(sX + kc * 16384 + wg * 8192 + k16 * 32, 16, 1024);
                wgmma_n192<1>(accQ, da, db, (kc | k16) != 0);
            }
            wgmma_commit();
            if (kc < 6) ffn_chunk(kc);
            if (kc > 0) { wgmma_wait<1>(); if (lane == 0) mbar_arrive(b_empty + 8 * ((kc - 1) & 3)); }
        }
        wgmma_wait<0>();
        TS(4, tid == 0);
        {
            bf16* orow0 = g_qkv + ((size_t)j * S_ + rb * 128 + rl) * 192;
            bf16* orow1 = orow0 + 8 * 192;
#pragma unroll
            for (int u = 0; u < 6; u++) {
                uint32_t w0[4], w1[4];
#pragma unroll
                for (int i = 0; i < 4; i++) {
                    const int t = u * 4 + i;
                    w0[i] = pack_bf16(accQ[t * 4 + 0], accQ[t * 4 + 1]);
                    w1[i] = pack_bf16(accQ[t * 4 + 2], accQ[t * 4 + 3]);
                }
                quad_transpose(w0, q);
                quad_transpose(w1, q);
                const int c = (u * 4 + q) * 8;
                *(uint4*)(orow0 + c) = make_uint4(w0[0], w0[1], w0[2], w0[3]);
                *(uint4*)(orow1 + c) = make_uint4(w1[0], w1[1], w1[2], w1[3]);
            }
        }
        TS(5, tid == 0);
    }
}

__device__ __forceinline__ void ldsm_x4(uint32_t (&r)[4], uint32_t addr) {
    asm("ldmatrix.sync.aligned.m8n8.x4.shared.b16 {%0,%1,%2,%3}, [%4];"
                 : "=r"(r[0]), "=r"(r[1]), "=r"(r[2]), "=r"(r[3]) : "r"(addr));
}
__device__ __forceinline__ void ldsm_x4_t(uint32_t (&r)[4], uint32_t addr) {
    asm("ldmatrix.sync.aligned.m8n8.x4.trans.shared.b16 {%0,%1,%2,%3}, [%4];"
                 : "=r"(r[0]), "=r"(r[1]), "=r"(r[2]), "=r"(r[3]) : "r"(addr));
}
__device__ __forceinline__ void mma16816(float (&d)[4], const uint32_t (&a)[4], uint32_t b0, uint32_t b1) {
    asm("mma.sync.aligned.m16n8k16.row.col.f32.bf16.bf16.f32 {%0,%1,%2,%3}, {%4,%5,%6,%7}, {%8,%9}, {%0,%1,%2,%3};"
                 : "+f"(d[0]), "+f"(d[1]), "+f"(d[2]), "+f"(d[3])
                 : "r"(a[0]), "r"(a[1]), "r"(a[2]), "r"(a[3]), "r"(b0), "r"(b1));
}
__device__ __forceinline__ void mma16816_z(float (&d)[4], const uint32_t (&a)[4], uint32_t b0, uint32_t b1) {
    asm("mma.sync.aligned.m16n8k16.row.col.f32.bf16.bf16.f32 {%0,%1,%2,%3}, {%4,%5,%6,%7}, {%8,%9}, {%10,%10,%10,%10};"
                 : "=f"(d[0]), "=f"(d[1]), "=f"(d[2]), "=f"(d[3])
                 : "r"(a[0]), "r"(a[1]), "r"(a[2]), "r"(a[3]), "r"(b0), "r"(b1), "f"(0.f));
}

constexpr int KV_PITCH = 128;

template <int EDGE, bool HEAD>
__device__ __forceinline__ void blk_scores(float (&s)[2][4], const uint32_t (&qa)[4], uint32_t kaddr, bool dead, int r0, int c0)
{
    uint32_t kf[4];
    ldsm_x4(kf, kaddr);
    mma16816_z(s[0], qa, kf[0], kf[1]);
    mma16816_z(s[1], qa, kf[2], kf[3]);
#pragma unroll
    for (int t = 0; t < 2; t++)
#pragma unroll
        for (int e = 0; e < 4; e++) {
            const int r = r0 + (e >> 1) * 8, c = t * 8 + c0 + (e & 1);
            if (EDGE == 1 && c <= r) s[t][e] = -1e30f;
            if (EDGE == 2 && c > r) s[t][e] = -1e30f;
            if (HEAD && dead) s[t][e] = -1e30f;
        }
}
__device__ __forceinline__ void blk_max(const float (&s)[2][4], float& n0, float& n1) {
    n0 = fmaxf(n0, fmaxf(fmaxf(s[0][0], s[0][1]), fmaxf(s[1][0], s[1][1])));
    n1 = fmaxf(n1, fmaxf(fmaxf(s[0][2], s[0][3]), fmaxf(s[1][2], s[1][3])));
}
__device__ __forceinline__ void blk_pv(const float (&s)[2][4], float mc0, float mc1, float (&l)[4],
                                       float (&o)[2][4], uint32_t vaddr) {
    const float C = 0.25f * 1.4426950408889634f;
    uint32_t pa[4];
#pragma unroll
    for (int t = 0; t < 2; t++) {
        const float p0 = ex2(fmaf(s[t][0], C, -mc0)), p1 = ex2(fmaf(s[t][1], C, -mc0));
        const float p2 = ex2(fmaf(s[t][2], C, -mc1)), p3 = ex2(fmaf(s[t][3], C, -mc1));
        pa[2 * t] = pack_bf16(p0, p1); pa[2 * t + 1] = pack_bf16(p2, p3);
    }
    uint32_t vf[4];
    ldsm_x4_t(vf, vaddr);
    mma16816(o[0], pa, vf[0], vf[1]);
    mma16816(o[1], pa, vf[2], vf[3]);
    mma16816(l, pa, 0x3F803F80u, 0x3F803F80u);
}
__device__ __forceinline__ void quad_max(float& n0, float& n1) {
    n0 = fmaxf(n0, __shfl_xor_sync(0xffffffffu, n0, 1)); n1 = fmaxf(n1, __shfl_xor_sync(0xffffffffu, n1, 1));
    n0 = fmaxf(n0, __shfl_xor_sync(0xffffffffu, n0, 2)); n1 = fmaxf(n1, __shfl_xor_sync(0xffffffffu, n1, 2));
}
template <int NC, int NN, bool FIRST, bool NEXT_IS_EDGE, bool HEAD>
__device__ __forceinline__ void pipe_step(const float (&sc)[5][2][4], float (&sn)[5][2][4], const uint32_t (&qa)[4],
                                          uint32_t ka, uint32_t va, int kc, int kn, int kb0, int r0, int c0,
                                          float& m0, float& m1, float& n0, float& n1, float (&l)[4], float (&o)[2][4])
{
    const float C = 0.25f * 1.4426950408889634f;
    const float mc0 = n0 * C, mc1 = n1 * C;
    if (!FIRST) {
        const float a0 = ex2(fmaf(m0, C, -mc0)), a1 = ex2(fmaf(m1, C, -mc1));
        l[0] *= a0; l[2] *= a1;
        o[0][0] *= a0; o[0][1] *= a0; o[1][0] *= a0; o[1][1] *= a0;
        o[0][2] *= a1; o[0][3] *= a1; o[1][2] *= a1; o[1][3] *= a1;
    }
    m0 = n0; m1 = n1;
#pragma unroll
    for (int b = 0; b < NC; b++) {
        if (b < NN) {
            if (NEXT_IS_EDGE && b == 0) blk_scores<1, HEAD>(sn[b], qa, ka + (kn + b) * 16 * KV_PITCH, kn + b < kb0, r0, c0);
            else                        blk_scores<0, HEAD>(sn[b], qa, ka + (kn + b) * 16 * KV_PITCH, kn + b < kb0, r0, c0);
        }
        blk_pv(sc[b], mc0, mc1, l, o, va + (kc + b) * 16 * KV_PITCH);
        if (b < NN) blk_max(sn[b], n0, n1);
    }
    if (NN > 0) quad_max(n0, n1);
}

__device__ __forceinline__ void kv_need(uint32_t kvbar, int blk, uint32_t& ka, uint32_t& va) {
    mbar_wait(kvbar + 8 * blk, 0);
    asm volatile("" : "+r"(ka), "+r"(va) :: "memory");
}
template <bool HEAD>
__device__ __forceinline__ void attn_task(const uint32_t (&qa)[4], uint32_t ka, uint32_t va, int kb0, int lane, int qt, uint32_t kvbar,
                                          bf16* __restrict__ out  , float g0, float g1)
{
    const int r0 = lane >> 2, c0 = (lane & 3) * 2;
    float m0 = -1e30f, m1 = -1e30f, n0 = -1e30f, n1 = -1e30f;
    float l[4] = {0.f, 0.f, 0.f, 0.f};
    float o[2][4] = {{0.f, 0.f, 0.f, 0.f}, {0.f, 0.f, 0.f, 0.f}};
    float sa[5][2][4], sb[5][2][4];
    kv_need(kvbar, 2, ka, va);
    if (qt < 4) kv_need(kvbar, 1, ka, va);
#pragma unroll
    for (int b = 0; b < 5; b++) {
        if (b == 4) blk_scores<2, HEAD>(sa[b], qa, ka + (12 + b) * 16 * KV_PITCH, false, r0, c0);
        else        blk_scores<0, HEAD>(sa[b], qa, ka + (12 + b) * 16 * KV_PITCH, 12 + b < kb0, r0, c0);
        blk_max(sa[b], n0, n1);
    }
    quad_max(n0, n1);
    kv_need(kvbar, 1, ka, va);
    if (HEAD) {
        pipe_step<5, 0, true, false, HEAD>(sa, sb, qa, ka, va, 12, 0, kb0, r0, c0, m0, m1, n0, n1, l, o);
        kv_need(kvbar, 0, ka, va);
#pragma unroll 1
        for (int kc = 8; kc >= 0 && kb0 < kc + 4; kc -= 4) {
#pragma unroll
            for (int b = 0; b < 4; b++) {
                blk_scores<0, HEAD>(sa[b], qa, ka + (kc + b) * 16 * KV_PITCH, kc + b < kb0, r0, c0);
                blk_max(sa[b], n0, n1);
            }
            quad_max(n0, n1);
            pipe_step<4, 0, false, false, HEAD>(sa, sb, qa, ka, va, kc, 0, kb0, r0, c0, m0, m1, n0, n1, l, o);
        }
    } else {
        pipe_step<5, 4, true,  false, HEAD>(sa, sb, qa, ka, va, 12, 8, kb0, r0, c0, m0, m1, n0, n1, l, o);
        if (qt < 4) kv_need(kvbar, 0, ka, va);
        pipe_step<4, 4, false, false, HEAD>(sb, sa, qa, ka, va, 8, 4, kb0, r0, c0, m0, m1, n0, n1, l, o);
        kv_need(kvbar, 0, ka, va);
        pipe_step<4, 4, false, true,  HEAD>(sa, sb, qa, ka, va, 4, 0, kb0, r0, c0, m0, m1, n0, n1, l, o);
        pipe_step<4, 0, false, false, HEAD>(sb, sa, qa, ka, va, 0, 0, kb0, r0, c0, m0, m1, n0, n1, l, o);
    }
    const float f0 = __fdividef(g0, l[0]), f1 = __fdividef(g1, l[2]);
#pragma unroll
    for (int t = 0; t < 2; t++) {
        *(uint32_t*)(out + (size_t)r0 * KA2 + t * 8 + c0) = pack_bf16(o[t][0] * f0, o[t][1] * f0);
        *(uint32_t*)(out + (size_t)(r0 + 8) * KA2 + t * 8 + c0) = pack_bf16(o[t][2] * f1, o[t][3] * f1);
    }
}

constexpr int K2_SMEM = 2 * 384 * KV_PITCH + 1024 + 64;

__global__ void __launch_bounds__(512, 1) k2_kernel(const __grid_constant__ CUtensorMap tmQKV)
{
    extern __shared__ uint8_t smem_raw[];
    const uint32_t sbase = (smem_u32(smem_raw) + 1023u) & ~1023u;
    uint8_t* sgen = smem_raw + (sbase - smem_u32(smem_raw));
    const uint32_t sK = sbase, sV = sK + 384 * KV_PITCH, kv_full = sbase + 2 * 384 * KV_PITCH;
    const int rb = blockIdx.x >> 3, j = blockIdx.x & 7;
    const int tid = threadIdx.x, warp = tid >> 5, lane = tid & 31;
    if (tid == 0) {
        for (int i = 0; i < 3; i++) mbar_init(kv_full + 8 * i, 1);
        fence_barrier_init();
    }
    pdl_wait();
    pdl_launch();
    TS(6, tid == 0);
    if (tid == 0) {
        for (int i = 0; i < 3; i++) {
            const uint32_t bar = kv_full + 8 * (2 - i);
            if (rb - i >= 0) {
                const int row = j * S_ + (rb - i) * 128;
                mbar_expect_tx(bar, 2 * 16384);
                tma_load_2d(sK + (2 - i) * 16384, &tmQKV, 64, row, bar);
                tma_load_2d(sV + (2 - i) * 16384, &tmQKV, 128, row, bar);
            } else {
                mbar_arrive(bar);
            }
        }
    }
    if (rb < 2) {
        for (int i = tid; i < (2 - rb) * 1024; i += 512) {
            *(uint4*)(sgen + i * 16) = make_uint4(0, 0, 0, 0);
            *(uint4*)(sgen + 384 * KV_PITCH + i * 16) = make_uint4(0, 0, 0, 0);
        }
    }
    const int qt = warp & 7, h0 = (warp >> 3) * 2;
    const int q0g = rb * 128 + qt * 16;
    const int r0 = lane >> 2, c0 = (lane & 3) * 2;
    const bf16* qsrc = g_qkv + ((size_t)j * S_ + q0g) * 192 + h0 * 16;
    uint32_t qa[4], qn[4];
    qa[0] = *(const uint32_t*)(qsrc + (size_t)r0 * 192 + c0);
    qa[1] = *(const uint32_t*)(qsrc + (size_t)(r0 + 8) * 192 + c0);
    qa[2] = *(const uint32_t*)(qsrc + (size_t)r0 * 192 + c0 + 8);
    qa[3] = *(const uint32_t*)(qsrc + (size_t)(r0 + 8) * 192 + c0 + 8);
    qn[0] = *(const uint32_t*)(qsrc + (size_t)r0 * 192 + 16 + c0);
    qn[1] = *(const uint32_t*)(qsrc + (size_t)(r0 + 8) * 192 + 16 + c0);
    qn[2] = *(const uint32_t*)(qsrc + (size_t)r0 * 192 + 16 + c0 + 8);
    qn[3] = *(const uint32_t*)(qsrc + (size_t)(r0 + 8) * 192 + 16 + c0 + 8);
    const float g0 = g_gate[q0g + r0], g1 = g_gate[q0g + r0 + 8];
    const int kb0 = q0g < 256 ? (256 - q0g) >> 4 : 0;
    __syncthreads();
    const uint32_t sKd = sK, sVd = sV;
    TS(7, tid == 0);
    const int krow = qt * 16 + (lane & 7) + ((lane >> 4) << 3);
    const int vrow = qt * 16 + (lane & 15);
#pragma unroll 1
    for (int hh = 0; hh < 2; hh++) {
        const int hl = h0 + hh;
        const uint32_t ka = sKd + krow * KV_PITCH + (((2 * hl + ((lane >> 3) & 1)) ^ (lane & 7)) << 4);
        const uint32_t va = sVd + vrow * KV_PITCH + (((2 * hl + (lane >> 4)) ^ (lane & 7)) << 4);
        if (rb < 2) attn_task<true>(qa, ka, va, kb0, lane, qt, kv_full, g_a2 + (size_t)q0g * KA2 + (j * 4 + hl) * 16, g0, g1);
        else        attn_task<false>(qa, ka, va, kb0, lane, qt, kv_full, g_a2 + (size_t)q0g * KA2 + (j * 4 + hl) * 16, g0, g1);
        TS(8 + hh, tid == 0);
        qa[0] = qn[0]; qa[1] = qn[1]; qa[2] = qn[2]; qa[3] = qn[3];
    }
}

constexpr int K3_STAGES = 8;
constexpr int K3_STAGE = 16384 + 8192;
constexpr int K3_SMEM = K3_STAGES * K3_STAGE + 1024 + 1024;
constexpr int K3_KSTEPS = 30;

__global__ void __launch_bounds__(384, 1)
k3_kernel(const __grid_constant__ CUtensorMap tmA2, const __grid_constant__ CUtensorMap tmWo,
          const __grid_constant__ CUtensorMap tmW2, bf16* __restrict__ out)
{
    extern __shared__ uint8_t smem_raw[];
    const uint32_t sbase = (smem_u32(smem_raw) + 1023u) & ~1023u;
    const uint32_t sBar = sbase + K3_STAGES * K3_STAGE;
    const uint32_t full = sBar, empty = sBar + 64;
    const int rb = blockIdx.x >> 3, nb = blockIdx.x & 7;
    const int tid = threadIdx.x, wg = tid >> 7, warp = tid >> 5, lane = tid & 31;
    if (tid == 0) {
        for (int i = 0; i < K3_STAGES; i++) { mbar_init(full + 8 * i, 1); mbar_init(empty + 8 * i, 8); }
        fence_barrier_init();
    }
    __syncthreads();
    TS(10, tid == 0);
    if (wg == 2) {
        reg_dealloc<40>();
        if (tid == 256) {
            for (int ks = 0; ks < K3_KSTEPS; ks++) {
                const int st = ks % K3_STAGES;
                if (ks >= K3_STAGES) mbar_wait(empty + 8 * st, ((ks / K3_STAGES) - 1) & 1);
                mbar_expect_tx(full + 8 * st, K3_STAGE);
                const uint32_t dst = sbase + st * K3_STAGE;
                if (ks < 22) {
                    tma_load_2d(dst, &tmA2, D_ + ks * 64, rb * 128, full + 8 * st);
                    tma_load_2d(dst + 16384, &tmW2, nb * 64, ks * 64, full + 8 * st);
                } else {
                    if (ks == 22) pdl_wait();
                    tma_load_2d(dst, &tmA2, (ks - 22) * 64, rb * 128, full + 8 * st);
                    tma_load_2d(dst + 16384, &tmWo, nb * 64, (ks - 22) * 64, full + 8 * st);
                }
            }
        }
    } else {
        reg_alloc<232>();
        float acc[32];
        for (int ks = 0; ks < K3_KSTEPS; ks++) {
            const int st = ks % K3_STAGES;
            mbar_wait(full + 8 * st, (ks / K3_STAGES) & 1);
            TS(11, tid == 0 && ks == 0); TS(12, tid == 0 && ks == 8); TS(13, tid == 0 && ks == 16);
            wgmma_fence();
#pragma unroll
            for (int k16 = 0; k16 < 4; k16++) {
                const uint64_t da = make_desc(sbase + st * K3_STAGE + wg * 8192 + k16 * 32, 16, 1024);
                const uint64_t db = make_desc(sbase + st * K3_STAGE + 16384 + k16 * 2048, 8192, 1024);
                wgmma_n64<1>(acc, da, db, (ks | k16) != 0);
            }
            wgmma_commit();
            if (ks > 0) { wgmma_wait<1>(); if (lane == 0) mbar_arrive(empty + 8 * ((ks - 1) % K3_STAGES)); }
        }
        wgmma_wait<0>();
        TS(14, tid == 0);
        const int q = lane & 3;
        const int r = rb * 128 + wg * 64 + (warp & 3) * 16 + (lane >> 2);
        bf16* orow0 = out + (size_t)r * D_ + nb * 64;
        bf16* orow1 = orow0 + 8 * D_;
#pragma unroll
        for (int u = 0; u < 2; u++) {
            uint32_t w0[4], w1[4];
#pragma unroll
            for (int i = 0; i < 4; i++) {
                const int t = u * 4 + i;
                w0[i] = pack_bf16(acc[t * 4 + 0], acc[t * 4 + 1]);
                w1[i] = pack_bf16(acc[t * 4 + 2], acc[t * 4 + 3]);
            }
            quad_transpose(w0, q);
            quad_transpose(w1, q);
            const int c = (u * 4 + q) * 8;
            *(uint4*)(orow0 + c) = make_uint4(w0[0], w0[1], w0[2], w0[3]);
            *(uint4*)(orow1 + c) = make_uint4(w1[0], w1[1], w1[2], w1[3]);
        }
        TS(15, tid == 0);
    }
}

typedef CUresult (*PFN_encodeTiled)(CUtensorMap*, CUtensorMapDataType, cuuint32_t, void*, const cuuint64_t*,
                                    const cuuint64_t*, const cuuint32_t*, const cuuint32_t*, CUtensorMapInterleave,
                                    CUtensorMapSwizzle, CUtensorMapL2promotion, CUtensorMapFloatOOBfill);

static void make_map(PFN_encodeTiled enc, CUtensorMap* m, const void* ptr, uint64_t cols, uint64_t rows,
                     uint32_t box_cols, uint32_t box_rows)
{
    cuuint64_t dims[2] = {cols, rows};
    cuuint64_t strides[1] = {cols * 2};
    cuuint32_t box[2] = {box_cols, box_rows};
    cuuint32_t es[2] = {1, 1};
    enc(m, CU_TENSOR_MAP_DATA_TYPE_BFLOAT16, 2, const_cast<void*>(ptr), dims, strides, box, es,
        CU_TENSOR_MAP_INTERLEAVE_NONE, CU_TENSOR_MAP_SWIZZLE_128B, CU_TENSOR_MAP_L2_PROMOTION_L2_128B,
        CU_TENSOR_MAP_FLOAT_OOB_FILL_NONE);
}

extern "C" void kernel_launch(void* const* d_in, const int* in_sizes, int n_in, void* d_out, int out_size)
{
    const bf16* x    = (const bf16*)d_in[0];
    const bf16* wqkv = (const bf16*)d_in[1];
    const bf16* wo   = (const bf16*)d_in[2];
    const bf16* w1   = (const bf16*)d_in[4];
    const bf16* b1   = (const bf16*)d_in[5];
    const bf16* w2   = (const bf16*)d_in[6];
    const bf16* gw   = (const bf16*)d_in[7];

    static PFN_encodeTiled enc = nullptr;
    if (!enc) {
        void* fn = nullptr;
        cudaDriverEntryPointQueryResult qr;
        cudaGetDriverEntryPoint("cuTensorMapEncodeTiled", &fn, cudaEnableDefault, &qr);
        enc = (PFN_encodeTiled)fn;
        cudaFuncSetAttribute(k1_kernel, cudaFuncAttributeMaxDynamicSharedMemorySize, K1_SMEM);
        cudaFuncSetAttribute(k2_kernel, cudaFuncAttributeMaxDynamicSharedMemorySize, K2_SMEM);
        cudaFuncSetAttribute(k3_kernel, cudaFuncAttributeMaxDynamicSharedMemorySize, K3_SMEM);
    }
    void* a2p = nullptr;
    cudaGetSymbolAddress(&a2p, g_a2);
    void* qkvp = nullptr;
    cudaGetSymbolAddress(&qkvp, g_qkv);
    CUtensorMap tmX, tmWqkv, tmW1, tmA2, tmWo, tmW2, tmQKV;
    make_map(enc, &tmQKV, qkvp, 192, 8 * S_, 64, 128);
    make_map(enc, &tmX, x, D_, S_, 64, 128);
    make_map(enc, &tmWqkv, wqkv, 3 * D_, D_, 64, 64);
    make_map(enc, &tmW1, w1, F_, D_, 64, 64);
    make_map(enc, &tmA2, a2p, KA2, S_, 64, 128);
    make_map(enc, &tmWo, wo, D_, D_, 64, 64);
    make_map(enc, &tmW2, w2, D_, F_, 64, 64);

    cudaStream_t st = cudaStreamPerThread;
    k1_kernel<<<128, 384, K1_SMEM, st>>>(tmX, tmWqkv, tmW1, b1, gw, w1, wqkv, w2, wo);
    cudaLaunchAttribute at[1];
    at[0].id = cudaLaunchAttributeProgrammaticStreamSerialization;
    at[0].val.programmaticStreamSerializationAllowed = 1;
    cudaLaunchConfig_t cfg = {};
    cfg.gridDim = dim3(128); cfg.stream = st; cfg.attrs = at; cfg.numAttrs = 1;
    cfg.blockDim = dim3(512); cfg.dynamicSmemBytes = K2_SMEM;
    cudaLaunchKernelEx(&cfg, k2_kernel, tmQKV);
    cfg.blockDim = dim3(384); cfg.dynamicSmemBytes = K3_SMEM;
    cudaLaunchKernelEx(&cfg, k3_kernel, tmA2, tmWo, tmW2, (bf16*)d_out);
}
```

```cpp
#include <cuda_runtime.h>
#include <cuda_bf16.h>
#include <cuda.h>
#include <stdint.h>

typedef __nv_bfloat16 bf16;

constexpr int S_ = 2048, D_ = 512, F_ = 1376;
constexpr int KA2 = D_ + F_;
constexpr int FCH = 176;

__device__ bf16  g_qkv[8 * S_ * 192];
__device__ bf16  g_a2[S_ * KA2];
__device__ float g_gate[S_];

#define TS(k, cond) do { } while (0)

__device__ __forceinline__ uint32_t smem_u32(const void* p) { return (uint32_t)__cvta_generic_to_shared(p); }
__device__ __forceinline__ void mbar_init(uint32_t bar, uint32_t count) {
    asm volatile("mbarrier.init.shared::cta.b64 [%0], %1;" :: "r"(bar), "r"(count) : "memory");
}
__device__ __forceinline__ void mbar_expect_tx(uint32_t bar, uint32_t bytes) {
    asm volatile("mbarrier.arrive.expect_tx.shared::cta.b64 _, [%0], %1;" :: "r"(bar), "r"(bytes) : "memory");
}
__device__ __forceinline__ void mbar_arrive(uint32_t bar) {
    asm volatile("mbarrier.arrive.shared::cta.b64 _, [%0];" :: "r"(bar) : "memory");
}
__device__ __forceinline__ bool mbar_try_wait(uint32_t bar, uint32_t parity) {
    uint32_t ok;
    asm volatile("{\n.reg .pred p;\nmbarrier.try_wait.parity.shared::cta.b64 p, [%1], %2;\nselp.u32 %0, 1, 0, p;\n}"
                 : "=r"(ok) : "r"(bar), "r"(parity) : "memory");
    return ok != 0;
}
__device__ __forceinline__ void mbar_wait(uint32_t bar, uint32_t parity) {
    for (uint32_t it = 0; it < (1u << 22); ++it) { if (mbar_try_wait(bar, parity)) break; }
}
__device__ __forceinline__ void tma_load_2d(uint32_t dst, const CUtensorMap* map, int c0, int c1, uint32_t bar) {
    asm volatile("cp.async.bulk.tensor.2d.shared::cluster.global.mbarrier::complete_tx::bytes [%0], [%1, {%3, %4}], [%2];"
                 :: "r"(dst), "l"(map), "r"(bar), "r"(c0), "r"(c1) : "memory");
}
__device__ __forceinline__ void l2_prefetch(const void* p, uint32_t bytes) {
    asm volatile("cp.async.bulk.prefetch.L2.global [%0], %1;" :: "l"(p), "r"(bytes) : "memory");
}
__device__ __forceinline__ void fence_barrier_init() { asm volatile("fence.mbarrier_init.release.cluster;" ::: "memory"); }
__device__ __forceinline__ void wgmma_fence()  { asm volatile("wgmma.fence.sync.aligned;" ::: "memory"); }
__device__ __forceinline__ void wgmma_commit() { asm volatile("wgmma.commit_group.sync.aligned;" ::: "memory"); }
template <int N> __device__ __forceinline__ void wgmma_wait() { asm volatile("wgmma.wait_group.sync.aligned %0;" :: "n"(N) : "memory"); }
template <int R> __device__ __forceinline__ void reg_alloc()   { asm volatile("setmaxnreg.inc.sync.aligned.u32 %0;" :: "n"(R)); }
template <int R> __device__ __forceinline__ void reg_dealloc() { asm volatile("setmaxnreg.dec.sync.aligned.u32 %0;" :: "n"(R)); }
__device__ __forceinline__ void bar_sync(int id, int n)   { asm volatile("bar.sync %0, %1;" :: "r"(id), "r"(n) : "memory"); }
__device__ __forceinline__ void bar_arrive(int id, int n) { asm volatile("bar.arrive %0, %1;" :: "r"(id), "r"(n) : "memory"); }

__device__ __forceinline__ uint64_t make_desc(uint32_t addr, uint32_t lbo, uint32_t sbo) {
    uint64_t d = (uint64_t)((addr & 0x3FFFF) >> 4);
    d |= (uint64_t)((lbo & 0x3FFFF) >> 4) << 16;
    d |= (uint64_t)((sbo & 0x3FFFF) >> 4) << 32;
    d |= (uint64_t)1 << 62;
    return d;
}

template <int TB>
__device__ __forceinline__ void wgmma_n64(float (&d)[32], uint64_t da, uint64_t db, int scale_d) {
    asm volatile("{\n.reg .pred p;\nsetp.ne.b32 p, %34, 0;\n"
        "wgmma.mma_async.sync.aligned.m64n64k16.f32.bf16.bf16 {%0, %1, %2, %3, %4, %5, %6, %7, %8, %9, %10, %11, %12, %13, %14, %15, %16, %17, %18, %19, %20, %21, %22, %23, %24, %25, %26, %27, %28, %29, %30, %31}, %32, %33, p, 1, 1, 0, %35;\n}\n"
        : "+f"(d[0]), "+f"(d[1]), "+f"(d[2]), "+f"(d[3]), "+f"(d[4]), "+f"(d[5]), "+f"(d[6]), "+f"(d[7]), "+f"(d[8]), "+f"(d[9]), "+f"(d[10]), "+f"(d[11]), "+f"(d[12]), "+f"(d[13]), "+f"(d[14]), "+f"(d[15]), "+f"(d[16]), "+f"(d[17]), "+f"(d[18]), "+f"(d[19]), "+f"(d[20]), "+f"(d[21]), "+f"(d[22]), "+f"(d[23]), "+f"(d[24]), "+f"(d[25]), "+f"(d[26]), "+f"(d[27]), "+f"(d[28]), "+f"(d[29]), "+f"(d[30]), "+f"(d[31])
        : "l"(da), "l"(db), "r"(scale_d), "n"(TB));
}

template <int TB>
__device__ __forceinline__ void wgmma_n128(float (&d)[64], uint64_t da, uint64_t db, int scale_d) {
    asm volatile("{\n.reg .pred p;\nsetp.ne.b32 p, %66, 0;\n"
        "wgmma.mma_async.sync.aligned.m64n128k16.f32.bf16.bf16 {%0, %1, %2, %3, %4, %5, %6, %7, %8, %9, %10, %11, %12, %13, %14, %15, %16, %17, %18, %19, %20, %21, %22, %23, %24, %25, %26, %27, %28, %29, %30, %31, %32, %33, %34, %35, %36, %37, %38, %39, %40, %41, %42, %43, %44, %45, %46, %47, %48, %49, %50, %51, %52, %53, %54, %55, %56, %57, %58, %59, %60, %61, %62, %63}, %64, %65, p, 1, 1, 0, %67;\n}\n"
        : "+f"(d[0]), "+f"(d[1]), "+f"(d[2]), "+f"(d[3]), "+f"(d[4]), "+f"(d[5]), "+f"(d[6]), "+f"(d[7]), "+f"(d[8]), "+f"(d[9]), "+f"(d[10]), "+f"(d[11]), "+f"(d[12]), "+f"(d[13]), "+f"(d[14]), "+f"(d[15]), "+f"(d[16]), "+f"(d[17]), "+f"(d[18]), "+f"(d[19]), "+f"(d[20]), "+f"(d[21]), "+f"(d[22]), "+f"(d[23]), "+f"(d[24]), "+f"(d[25]), "+f"(d[26]), "+f"(d[27]), "+f"(d[28]), "+f"(d[29]), "+f"(d[30]), "+f"(d[31]), "+f"(d[32]), "+f"(d[33]), "+f"(d[34]), "+f"(d[35]), "+f"(d[36]), "+f"(d[37]), "+f"(d[38]), "+f"(d[39]), "+f"(d[40]), "+f"(d[41]), "+f"(d[42]), "+f"(d[43]), "+f"(d[44]), "+f"(d[45]), "+f"(d[46]), "+f"(d[47]), "+f"(d[48]), "+f"(d[49]), "+f"(d[50]), "+f"(d[51]), "+f"(d[52]), "+f"(d[53]), "+f"(d[54]), "+f"(d[55]), "+f"(d[56]), "+f"(d[57]), "+f"(d[58]), "+f"(d[59]), "+f"(d[60]), "+f"(d[61]), "+f"(d[62]), "+f"(d[63])
        : "l"(da), "l"(db), "r"(scale_d), "n"(TB));
}

template <int TB>
__device__ __forceinline__ void wgmma_n176(float (&d)[88], uint64_t da, uint64_t db, int scale_d) {
    asm volatile("{\n.reg .pred p;\nsetp.ne.b32 p, %90, 0;\n"
        "wgmma.mma_async.sync.aligned.m64n176k16.f32.bf16.bf16 {%0, %1, %2, %3, %4, %5, %6, %7, %8, %9, %10, %11, %12, %13, %14, %15, %16, %17, %18, %19, %20, %21, %22, %23, %24, %25, %26, %27, %28, %29, %30, %31, %32, %33, %34, %35, %36, %37, %38, %39, %40, %41, %42, %43, %44, %45, %46, %47, %48, %49, %50, %51, %52, %53, %54, %55, %56, %57, %58, %59, %60, %61, %62, %63, %64, %65, %66, %67, %68, %69, %70, %71, %72, %73, %74, %75, %76, %77, %78, %79, %80, %81, %82, %83, %84, %85, %86, %87}, %88, %89, p, 1, 1, 0, %91;\n}\n"
        : "+f"(d[0]), "+f"(d[1]), "+f"(d[2]), "+f"(d[3]), "+f"(d[4]), "+f"(d[5]), "+f"(d[6]), "+f"(d[7]), "+f"(d[8]), "+f"(d[9]), "+f"(d[10]), "+f"(d[11]), "+f"(d[12]), "+f"(d[13]), "+f"(d[14]), "+f"(d[15]), "+f"(d[16]), "+f"(d[17]), "+f"(d[18]), "+f"(d[19]), "+f"(d[20]), "+f"(d[21]), "+f"(d[22]), "+f"(d[23]), "+f"(d[24]), "+f"(d[25]), "+f"(d[26]), "+f"(d[27]), "+f"(d[28]), "+f"(d[29]), "+f"(d[30]), "+f"(d[31]), "+f"(d[32]), "+f"(d[33]), "+f"(d[34]), "+f"(d[35]), "+f"(d[36]), "+f"(d[37]), "+f"(d[38]), "+f"(d[39]), "+f"(d[40]), "+f"(d[41]), "+f"(d[42]), "+f"(d[43]), "+f"(d[44]), "+f"(d[45]), "+f"(d[46]), "+f"(d[47]), "+f"(d[48]), "+f"(d[49]), "+f"(d[50]), "+f"(d[51]), "+f"(d[52]), "+f"(d[53]), "+f"(d[54]), "+f"(d[55]), "+f"(d[56]), "+f"(d[57]), "+f"(d[58]), "+f"(d[59]), "+f"(d[60]), "+f"(d[61]), "+f"(d[62]), "+f"(d[63]), "+f"(d[64]), "+f"(d[65]), "+f"(d[66]), "+f"(d[67]), "+f"(d[68]), "+f"(d[69]), "+f"(d[70]), "+f"(d[71]), "+f"(d[72]), "+f"(d[73]), "+f"(d[74]), "+f"(d[75]), "+f"(d[76]), "+f"(d[77]), "+f"(d[78]), "+f"(d[79]), "+f"(d[80]), "+f"(d[81]), "+f"(d[82]), "+f"(d[83]), "+f"(d[84]), "+f"(d[85]), "+f"(d[86]), "+f"(d[87])
        : "l"(da), "l"(db), "r"(scale_d), "n"(TB));
}

template <int TB>
__device__ __forceinline__ void wgmma_n192(float (&d)[96], uint64_t da, uint64_t db, int scale_d) {
    asm volatile("{\n.reg .pred p;\nsetp.ne.b32 p, %98, 0;\n"
        "wgmma.mma_async.sync.aligned.m64n192k16.f32.bf16.bf16 {%0, %1, %2, %3, %4, %5, %6, %7, %8, %9, %10, %11, %12, %13, %14, %15, %16, %17, %18, %19, %20, %21, %22, %23, %24, %25, %26, %27, %28, %29, %30, %31, %32, %33, %34, %35, %36, %37, %38, %39, %40, %41, %42, %43, %44, %45, %46, %47, %48, %49, %50, %51, %52, %53, %54, %55, %56, %57, %58, %59, %60, %61, %62, %63, %64, %65, %66, %67, %68, %69, %70, %71, %72, %73, %74, %75, %76, %77, %78, %79, %80, %81, %82, %83, %84, %85, %86, %87, %88, %89, %90, %91, %92, %93, %94, %95}, %96, %97, p, 1, 1, 0, %99;\n}\n"
        : "+f"(d[0]), "+f"(d[1]), "+f"(d[2]), "+f"(d[3]), "+f"(d[4]), "+f"(d[5]), "+f"(d[6]), "+f"(d[7]), "+f"(d[8]), "+f"(d[9]), "+f"(d[10]), "+f"(d[11]), "+f"(d[12]), "+f"(d[13]), "+f"(d[14]), "+f"(d[15]), "+f"(d[16]), "+f"(d[17]), "+f"(d[18]), "+f"(d[19]), "+f"(d[20]), "+f"(d[21]), "+f"(d[22]), "+f"(d[23]), "+f"(d[24]), "+f"(d[25]), "+f"(d[26]), "+f"(d[27]), "+f"(d[28]), "+f"(d[29]), "+f"(d[30]), "+f"(d[31]), "+f"(d[32]), "+f"(d[33]), "+f"(d[34]), "+f"(d[35]), "+f"(d[36]), "+f"(d[37]), "+f"(d[38]), "+f"(d[39]), "+f"(d[40]), "+f"(d[41]), "+f"(d[42]), "+f"(d[43]), "+f"(d[44]), "+f"(d[45]), "+f"(d[46]), "+f"(d[47]), "+f"(d[48]), "+f"(d[49]), "+f"(d[50]), "+f"(d[51]), "+f"(d[52]), "+f"(d[53]), "+f"(d[54]), "+f"(d[55]), "+f"(d[56]), "+f"(d[57]), "+f"(d[58]), "+f"(d[59]), "+f"(d[60]), "+f"(d[61]), "+f"(d[62]), "+f"(d[63]), "+f"(d[64]), "+f"(d[65]), "+f"(d[66]), "+f"(d[67]), "+f"(d[68]), "+f"(d[69]), "+f"(d[70]), "+f"(d[71]), "+f"(d[72]), "+f"(d[73]), "+f"(d[74]), "+f"(d[75]), "+f"(d[76]), "+f"(d[77]), "+f"(d[78]), "+f"(d[79]), "+f"(d[80]), "+f"(d[81]), "+f"(d[82]), "+f"(d[83]), "+f"(d[84]), "+f"(d[85]), "+f"(d[86]), "+f"(d[87]), "+f"(d[88]), "+f"(d[89]), "+f"(d[90]), "+f"(d[91]), "+f"(d[92]), "+f"(d[93]), "+f"(d[94]), "+f"(d[95])
        : "l"(da), "l"(db), "r"(scale_d), "n"(TB));
}

__device__ __forceinline__ uint32_t pack_bf16(float lo, float hi) {
    uint32_t r;
    asm("cvt.rn.bf16x2.f32 %0, %1, %2;" : "=r"(r) : "f"(hi), "f"(lo));
    return r;
}
__device__ __forceinline__ float bf_lo(uint32_t v) { return __uint_as_float(v << 16); }
__device__ __forceinline__ float bf_hi(uint32_t v) { return __uint_as_float(v & 0xffff0000u); }

__device__ __forceinline__ void quad_transpose(uint32_t (&w)[4], int q) {
    const bool o1 = q & 1, o2 = q & 2;
    {
        uint32_t s0 = o1 ? w[0] : w[1], s1 = o1 ? w[2] : w[3];
        s0 = __shfl_xor_sync(0xffffffffu, s0, 1); s1 = __shfl_xor_sync(0xffffffffu, s1, 1);
        if (o1) { w[0] = s0; w[2] = s1; } else { w[1] = s0; w[3] = s1; }
    }
    {
        uint32_t s0 = o2 ? w[0] : w[2], s1 = o2 ? w[1] : w[3];
        s0 = __shfl_xor_sync(0xffffffffu, s0, 2); s1 = __shfl_xor_sync(0xffffffffu, s1, 2);
        if (o2) { w[0] = s0; w[1] = s1; } else { w[2] = s0; w[3] = s1; }
    }
}

__device__ __forceinline__ float ex2(float x) { float y; asm("ex2.approx.ftz.f32 %0, %1;" : "=f"(y) : "f"(x)); return y; }
__device__ __forceinline__ float rcp(float x) { float y; asm("rcp.approx.ftz.f32 %0, %1;" : "=f"(y) : "f"(x)); return y; }

__device__ __forceinline__ float ex2v(float x) { float y; asm volatile("ex2.approx.ftz.f32 %0, %1;" : "=f"(y) : "f"(x)); return y; }
__device__ __forceinline__ float rcpv(float x) { float y; asm volatile("rcp.approx.ftz.f32 %0, %1;" : "=f"(y) : "f"(x)); return y; }
__device__ __forceinline__ float mish_f(float h) {
    const float e = ex2v(1.4426950408889634f * fminf(h, 20.f));
    const float n = fmaf(e, e, e + e);
    return h * n * rcpv(n + 2.f);
}

__device__ __forceinline__ void pdl_wait()   { asm volatile("griddepcontrol.wait;" ::: "memory"); }
__device__ __forceinline__ void pdl_launch() { asm volatile("griddepcontrol.launch_dependents;" ::: "memory"); }

constexpr int K1_STAGES = 4;
constexpr int K1_XBYTES = 128 * 512 * 2;
constexpr int K1_BSTAGE = 3 * 8192;
constexpr int K1_SMEM   = K1_XBYTES + K1_STAGES * K1_BSTAGE + 2048   + 1024  ;

__global__ void __launch_bounds__(384, 1)
k1_kernel(const __grid_constant__ CUtensorMap tmX, const __grid_constant__ CUtensorMap tmWqkv,
          const __grid_constant__ CUtensorMap tmW1, const bf16* __restrict__ b1,
          const bf16* __restrict__ gate_w, const bf16* __restrict__ w1p, const bf16* __restrict__ wqkvp,
          const bf16* __restrict__ w2p, const bf16* __restrict__ wop)
{

    extern __shared__ uint8_t smem_raw[];
    const uint32_t sbase = (smem_u32(smem_raw) + 1023u) & ~1023u;
    uint8_t* sgen = smem_raw + (sbase - smem_u32(smem_raw));
    const uint32_t sX = sbase;
    const uint32_t sB = sbase + K1_XBYTES;
    const uint32_t sBar = sB + K1_STAGES * K1_BSTAGE;
    const uint32_t x_full = sBar;
    const uint32_t b_full = sBar + 64;
    const uint32_t b_empty = sBar + 96;
    float* sGate = (float*)(sgen + K1_XBYTES + K1_STAGES * K1_BSTAGE + 128);
    uint8_t* sGw = sgen + K1_XBYTES + K1_STAGES * K1_BSTAGE + 640;
    uint32_t* sBias = (uint32_t*)(sgen + K1_XBYTES + K1_STAGES * K1_BSTAGE + 1664);

    const int rb = blockIdx.x >> 3, j = blockIdx.x & 7;
    const int tid = threadIdx.x, wg = tid >> 7, warp = tid >> 5, lane = tid & 31;
    TS(0, tid == 0);
    pdl_launch();

    if (tid == 0) {
        for (int i = 0; i < 8; i++) mbar_init(x_full + 8 * i, 1);
        for (int i = 0; i < K1_STAGES; i++) { mbar_init(b_full + 8 * i, 1); mbar_init(b_empty + 8 * i, 8); }
        fence_barrier_init();
    }
    __syncthreads();

    if (wg == 2) {
        reg_dealloc<40>();
        if (tid == 288) {
            const int b = blockIdx.x;
            mbar_wait(b_full + 8, 0);
            l2_prefetch((const uint8_t*)wqkvp + b * 12288, 12288);
            l2_prefetch((const uint8_t*)w2p + b * 11008, 11008);
            l2_prefetch((const uint8_t*)wop + b * 4096, 4096);
        }
        if (tid == 256) {
            for (int it = 0; it < 16; it++) {
                if (it < 8) {
                    mbar_expect_tx(x_full + 8 * it, 16384);
                    tma_load_2d(sX + it * 16384, &tmX, it * 64, rb * 128, x_full + 8 * it);
                }
                const int st = it & 3;
                if (it >= K1_STAGES) mbar_wait(b_empty + 8 * st, ((it >> 2) - 1) & 1);
                mbar_expect_tx(b_full + 8 * st, K1_BSTAGE);
                const uint32_t dst = sB + st * K1_BSTAGE;
                if (it < 8) {
                    for (int b = 0; b < 3; b++) tma_load_2d(dst + b * 8192, &tmW1, j * FCH + b * 64, it * 64, b_full + 8 * st);
                } else {
                    for (int b = 0; b < 3; b++) tma_load_2d(dst + b * 8192, &tmWqkv, b * 512 + j * 64, (it - 8) * 64, b_full + 8 * st);
                }
            }
        }
    } else {
        reg_alloc<232>();
        if (tid < 64) ((uint4*)sGw)[tid] = __ldg((const uint4*)gate_w + tid);
        else if (tid < 64 + 88) {
            const int c = j * FCH + (tid - 64) * 2;
            sBias[tid - 64] = c < F_ ? __ldg((const uint32_t*)(b1 + c)) : 0u;
        }
        bar_sync(3, 256);
        const int t128 = tid & 127, w4 = warp & 3, q = lane & 3;
        float accF[88], accQ[96];
        float gs = 0.f;
        const int grow = wg * 64 + (t128 >> 1), ghalf = t128 & 1;
#pragma unroll
        for (int kc = 0; kc < 8; kc++) {
            const int st = kc & 3;
            mbar_wait(x_full + 8 * kc, 0);
            mbar_wait(b_full + 8 * st, (kc >> 2) & 1);
            TS(1, tid == 0 && kc == 0); TS(2, tid == 0 && kc == 4);
            wgmma_fence();
#pragma unroll
            for (int k16 = 0; k16 < 4; k16++) {
                const uint64_t db = make_desc(sB + st * K1_BSTAGE + k16 * 2048, 8192, 1024);
                const uint64_t da = make_desc(sX + kc * 16384 + wg * 8192 + k16 * 32, 16, 1024);
                wgmma_n176<1>(accF, da, db, (kc | k16) != 0);
            }
            wgmma_commit();
#pragma unroll
            for (int c = 0; c < 4; c++) {
                const int cc = ghalf * 4 + c;
                const uint4 xv = *(const uint4*)(sgen + kc * 16384 + grow * 128 + ((cc ^ (grow & 7)) << 4));
                const uint4 gv = *(const uint4*)(sGw + kc * 128 + cc * 16);
                gs = fmaf(bf_lo(xv.x), bf_lo(gv.x), gs); gs = fmaf(bf_hi(xv.x), bf_hi(gv.x), gs);
                gs = fmaf(bf_lo(xv.y), bf_lo(gv.y), gs); gs = fmaf(bf_hi(xv.y), bf_hi(gv.y), gs);
                gs = fmaf(bf_lo(xv.z), bf_lo(gv.z), gs); gs = fmaf(bf_hi(xv.z), bf_hi(gv.z), gs);
                gs = fmaf(bf_lo(xv.w), bf_lo(gv.w), gs); gs = fmaf(bf_hi(xv.w), bf_hi(gv.w), gs);
            }
            if (kc > 0) { wgmma_wait<1>(); if (lane == 0) mbar_arrive(b_empty + 8 * ((kc - 1) & 3)); }
        }
        gs += __shfl_xor_sync(0xffffffffu, gs, 1);
        {
            const float g = 1.f / (1.f + __expf(-gs));
            if (ghalf == 0) {
                sGate[grow] = g;
                if (j == 0) g_gate[rb * 128 + grow] = g;
            }
        }
        wgmma_wait<0>();
        if (lane == 0) mbar_arrive(b_empty + 8 * 3);
        bar_sync(1 + wg, 128);
        TS(3, tid == 0);
        const int n0 = j * FCH;
        const int rl = wg * 64 + w4 * 16 + (lane >> 2);
        const float om0 = 1.f - sGate[rl], om1 = 1.f - sGate[rl + 8];
        bf16* frow0 = g_a2 + (size_t)(rb * 128 + rl) * KA2 + D_ + n0;
        bf16* frow1 = frow0 + 8 * KA2;
        auto ffn_chunk = [&](int u) {
            uint32_t w0[4], w1[4];
#pragma unroll
            for (int i = 0; i < 4; i++) {
                const int t = u * 4 + i;
                if (t < 22) {
                    const uint32_t bv = sBias[t * 4 + q];
                    const float bb0 = bf_lo(bv), bb1 = bf_hi(bv);
                    w0[i] = pack_bf16(mish_f(accF[t * 4 + 0] + bb0) * om0, mish_f(accF[t * 4 + 1] + bb1) * om0);
                    w1[i] = pack_bf16(mish_f(accF[t * 4 + 2] + bb0) * om1, mish_f(accF[t * 4 + 3] + bb1) * om1);
                } else { w0[i] = 0; w1[i] = 0; }
            }
            quad_transpose(w0, q);
            quad_transpose(w1, q);
            const int c = (u * 4 + q) * 8;
            if (c < FCH && n0 + c < F_) {
                *(uint4*)(frow0 + c) = make_uint4(w0[0], w0[1], w0[2], w0[3]);
                *(uint4*)(frow1 + c) = make_uint4(w1[0], w1[1], w1[2], w1[3]);
            }
        };
#pragma unroll
        for (int kc = 0; kc < 8; kc++) {
            const int st = kc & 3;
            mbar_wait(b_full + 8 * st, ((kc + 8) >> 2) & 1);
            wgmma_fence();
#pragma unroll
            for (int k16 = 0; k16 < 4; k16++) {
                const uint64_t db = make_desc(sB + st * K1_BSTAGE + k16 * 2048, 8192, 1024);
                const uint64_t da = make_desc(sX + kc * 16384 + wg * 8192 + k16 * 32, 16, 1024);
                wgmma_n192<1>(accQ, da, db, (kc | k16) != 0);
            }
            wgmma_commit();
            if (kc < 6) ffn_chunk(kc);
            if (kc > 0) { wgmma_wait<1>(); if (lane == 0) mbar_arrive(b_empty + 8 * ((kc - 1) & 3)); }
        }
        wgmma_wait<0>();
        TS(4, tid == 0);
        {
            bf16* orow0 = g_qkv + ((size_t)j * S_ + rb * 128 + rl) * 192;
            bf16* orow1 = orow0 + 8 * 192;
#pragma unroll
            for (int u = 0; u < 6; u++) {
                uint32_t w0[4], w1[4];
#pragma unroll
                for (int i = 0; i < 4; i++) {
                    const int t = u * 4 + i;
                    w0[i] = pack_bf16(accQ[t * 4 + 0], accQ[t * 4 + 1]);
                    w1[i] = pack_bf16(accQ[t * 4 + 2], accQ[t * 4 + 3]);
                }
                quad_transpose(w0, q);
                quad_transpose(w1, q);
                const int c = (u * 4 + q) * 8;
                *(uint4*)(orow0 + c) = make_uint4(w0[0], w0[1], w0[2], w0[3]);
                *(uint4*)(orow1 + c) = make_uint4(w1[0], w1[1], w1[2], w1[3]);
            }
        }
        TS(5, tid == 0);
    }
}

__device__ __forceinline__ void ldsm_x4(uint32_t (&r)[4], uint32_t addr) {
    asm("ldmatrix.sync.aligned.m8n8.x4.shared.b16 {%0,%1,%2,%3}, [%4];"
                 : "=r"(r[0]), "=r"(r[1]), "=r"(r[2]), "=r"(r[3]) : "r"(addr));
}
__device__ __forceinline__ void ldsm_x4_t(uint32_t (&r)[4], uint32_t addr) {
    asm("ldmatrix.sync.aligned.m8n8.x4.trans.shared.b16 {%0,%1,%2,%3}, [%4];"
                 : "=r"(r[0]), "=r"(r[1]), "=r"(r[2]), "=r"(r[3]) : "r"(addr));
}
__device__ __forceinline__ void mma16816(float (&d)[4], const uint32_t (&a)[4], uint32_t b0, uint32_t b1) {
    asm("mma.sync.aligned.m16n8k16.row.col.f32.bf16.bf16.f32 {%0,%1,%2,%3}, {%4,%5,%6,%7}, {%8,%9}, {%0,%1,%2,%3};"
                 : "+f"(d[0]), "+f"(d[1]), "+f"(d[2]), "+f"(d[3])
                 : "r"(a[0]), "r"(a[1]), "r"(a[2]), "r"(a[3]), "r"(b0), "r"(b1));
}
__device__ __forceinline__ void mma16816_z(float (&d)[4], const uint32_t (&a)[4], uint32_t b0, uint32_t b1) {
    asm("mma.sync.aligned.m16n8k16.row.col.f32.bf16.bf16.f32 {%0,%1,%2,%3}, {%4,%5,%6,%7}, {%8,%9}, {%10,%10,%10,%10};"
                 : "=f"(d[0]), "=f"(d[1]), "=f"(d[2]), "=f"(d[3])
                 : "r"(a[0]), "r"(a[1]), "r"(a[2]), "r"(a[3]), "r"(b0), "r"(b1), "f"(0.f));
}

constexpr int KV_PITCH = 128;

template <int EDGE, bool HEAD>
__device__ __forceinline__ void blk_scores(float (&s)[2][4], const uint32_t (&qa)[4], uint32_t kaddr, bool dead, int r0, int c0)
{
    uint32_t kf[4];
    ldsm_x4(kf, kaddr);
    mma16816_z(s[0], qa, kf[0], kf[1]);
    mma16816_z(s[1], qa, kf[2], kf[3]);
#pragma unroll
    for (int t = 0; t < 2; t++)
#pragma unroll
        for (int e = 0; e < 4; e++) {
            const int r = r0 + (e >> 1) * 8, c = t * 8 + c0 + (e & 1);
            if (EDGE == 1 && c <= r) s[t][e] = -1e30f;
            if (EDGE == 2 && c > r) s[t][e] = -1e30f;
            if (HEAD && dead) s[t][e] = -1e30f;
        }
}
__device__ __forceinline__ void blk_max(const float (&s)[2][4], float& n0, float& n1) {
    n0 = fmaxf(n0, fmaxf(fmaxf(s[0][0], s[0][1]), fmaxf(s[1][0], s[1][1])));
    n1 = fmaxf(n1, fmaxf(fmaxf(s[0][2], s[0][3]), fmaxf(s[1][2], s[1][3])));
}
__device__ __forceinline__ void blk_pv(const float (&s)[2][4], float mc0, float mc1, float (&l)[4],
                                       float (&o)[2][4], uint32_t vaddr) {
    const float C = 0.25f * 1.4426950408889634f;
    uint32_t pa[4];
#pragma unroll
    for (int t = 0; t < 2; t++) {
        const float p0 = ex2(fmaf(s[t][0], C, -mc0)), p1 = ex2(fmaf(s[t][1], C, -mc0));
        const float p2 = ex2(fmaf(s[t][2], C, -mc1)), p3 = ex2(fmaf(s[t][3], C, -mc1));
        pa[2 * t] = pack_bf16(p0, p1); pa[2 * t + 1] = pack_bf16(p2, p3);
    }
    uint32_t vf[4];
    ldsm_x4_t(vf, vaddr);
    mma16816(o[0], pa, vf[0], vf[1]);
    mma16816(o[1], pa, vf[2], vf[3]);
    mma16816(l, pa, 0x3F803F80u, 0x3F803F80u);
}
__device__ __forceinline__ void quad_max(float& n0, float& n1) {
    n0 = fmaxf(n0, __shfl_xor_sync(0xffffffffu, n0, 1)); n1 = fmaxf(n1, __shfl_xor_sync(0xffffffffu, n1, 1));
    n0 = fmaxf(n0, __shfl_xor_sync(0xffffffffu, n0, 2)); n1 = fmaxf(n1, __shfl_xor_sync(0xffffffffu, n1, 2));
}
template <int NC, int NN, bool FIRST, bool NEXT_IS_EDGE, bool HEAD>
__device__ __forceinline__ void pipe_step(const float (&sc)[5][2][4], float (&sn)[5][2][4], const uint32_t (&qa)[4],
                                          uint32_t ka, uint32_t va, int kc, int kn, int kb0, int r0, int c0,
                                          float& m0, float& m1, float& n0, float& n1, float (&l)[4], float (&o)[2][4])
{
    const float C = 0.25f * 1.4426950408889634f;
    const float mc0 = n0 * C, mc1 = n1 * C;
    if (!FIRST) {
        const float a0 = ex2(fmaf(m0, C, -mc0)), a1 = ex2(fmaf(m1, C, -mc1));
        l[0] *= a0; l[2] *= a1;
        o[0][0] *= a0; o[0][1] *= a0; o[1][0] *= a0; o[1][1] *= a0;
        o[0][2] *= a1; o[0][3] *= a1; o[1][2] *= a1; o[1][3] *= a1;
    }
    m0 = n0; m1 = n1;
#pragma unroll
    for (int b = 0; b < NC; b++) {
        if (b < NN) {
            if (NEXT_IS_EDGE && b == 0) blk_scores<1, HEAD>(sn[b], qa, ka + (kn + b) * 16 * KV_PITCH, kn + b < kb0, r0, c0);
            else                        blk_scores<0, HEAD>(sn[b], qa, ka + (kn + b) * 16 * KV_PITCH, kn + b < kb0, r0, c0);
        }
        blk_pv(sc[b], mc0, mc1, l, o, va + (kc + b) * 16 * KV_PITCH);
        if (b < NN) blk_max(sn[b], n0, n1);
    }
    if (NN > 0) quad_max(n0, n1);
}

__device__ __forceinline__ void kv_need(uint32_t kvbar, int blk, uint32_t& ka, uint32_t& va) {
    mbar_wait(kvbar + 8 * blk, 0);
    asm volatile("" : "+r"(ka), "+r"(va) :: "memory");
}
template <bool HEAD>
__device__ __forceinline__ void attn_task(const uint32_t (&qa)[4], uint32_t ka, uint32_t va, int kb0, int lane, int qt, uint32_t kvbar,
                                          bf16* __restrict__ out  , float g0, float g1)
{
    const int r0 = lane >> 2, c0 = (lane & 3) * 2;
    float m0 = -1e30f, m1 = -1e30f, n0 = -1e30f, n1 = -1e30f;
    float l[4] = {0.f, 0.f, 0.f, 0.f};
    float o[2][4] = {{0.f, 0.f, 0.f, 0.f}, {0.f, 0.f, 0.f, 0.f}};
    float sa[5][2][4], sb[5][2][4];
    kv_need(kvbar, 2, ka, va);
    if (qt < 4) kv_need(kvbar, 1, ka, va);
#pragma unroll
    for (int b = 0; b < 5; b++) {
        if (b == 4) blk_scores<2, HEAD>(sa[b], qa, ka + (12 + b) * 16 * KV_PITCH, false, r0, c0);
        else        blk_scores<0, HEAD>(sa[b], qa, ka + (12 + b) * 16 * KV_PITCH, 12 + b < kb0, r0, c0);
        blk_max(sa[b], n0, n1);
    }
    quad_max(n0, n1);
    kv_need(kvbar, 1, ka, va);
    if (HEAD) {
        pipe_step<5, 0, true, false, HEAD>(sa, sb, qa, ka, va, 12, 0, kb0, r0, c0, m0, m1, n0, n1, l, o);
        kv_need(kvbar, 0, ka, va);
#pragma unroll 1
        for (int kc = 8; kc >= 0 && kb0 < kc + 4; kc -= 4) {
#pragma unroll
            for (int b = 0; b < 4; b++) {
                blk_scores<0, HEAD>(sa[b], qa, ka + (kc + b) * 16 * KV_PITCH, kc + b < kb0, r0, c0);
                blk_max(sa[b], n0, n1);
            }
            quad_max(n0, n1);
            pipe_step<4, 0, false, false, HEAD>(sa, sb, qa, ka, va, kc, 0, kb0, r0, c0, m0, m1, n0, n1, l, o);
        }
    } else {
        pipe_step<5, 4, true,  false, HEAD>(sa, sb, qa, ka, va, 12, 8, kb0, r0, c0, m0, m1, n0, n1, l, o);
        if (qt < 4) kv_need(kvbar, 0, ka, va);
        pipe_step<4, 4, false, false, HEAD>(sb, sa, qa, ka, va, 8, 4, kb0, r0, c0, m0, m1, n0, n1, l, o);
        kv_need(kvbar, 0, ka, va);
        pipe_step<4, 4, false, true,  HEAD>(sa, sb, qa, ka, va, 4, 0, kb0, r0, c0, m0, m1, n0, n1, l, o);
        pipe_step<4, 0, false, false, HEAD>(sb, sa, qa, ka, va, 0, 0, kb0, r0, c0, m0, m1, n0, n1, l, o);
    }
    const float f0 = __fdividef(g0, l[0]), f1 = __fdividef(g1, l[2]);
#pragma unroll
    for (int t = 0; t < 2; t++) {
        *(uint32_t*)(out + (size_t)r0 * KA2 + t * 8 + c0) = pack_bf16(o[t][0] * f0, o[t][1] * f0);
        *(uint32_t*)(out + (size_t)(r0 + 8) * KA2 + t * 8 + c0) = pack_bf16(o[t][2] * f1, o[t][3] * f1);
    }
}

__device__ unsigned int g_epoch;
__device__ unsigned int g_done;
__device__ unsigned int g_flag_att[128];

constexpr int G_STAGES = 5;
constexpr int G_STAGE = 16384 + 8192;
constexpr int G_KSTEPS = 30;
constexpr int K23_OFF_KV = G_STAGES * G_STAGE;
constexpr int K23_OFF_BAR = K23_OFF_KV + 2 * 384 * KV_PITCH;
constexpr int K23_SMEM = K23_OFF_BAR + 256 + 1024;

__global__ void __launch_bounds__(512, 1)
k23_kernel(const __grid_constant__ CUtensorMap tmQKV, const __grid_constant__ CUtensorMap tmA2,
           const __grid_constant__ CUtensorMap tmWo, const __grid_constant__ CUtensorMap tmW2, bf16* __restrict__ out)
{
    extern __shared__ uint8_t smem_raw[];
    const uint32_t sbase = (smem_u32(smem_raw) + 1023u) & ~1023u;
    uint8_t* sgen = smem_raw + (sbase - smem_u32(smem_raw));
    const uint32_t sK = sbase + K23_OFF_KV, sV = sK + 384 * KV_PITCH;
    const uint32_t sBar = sbase + K23_OFF_BAR;
    const uint32_t full = sBar, empty = sBar + 64, kv_full = sBar + 128;
    const int rb = blockIdx.x >> 3, j = blockIdx.x & 7;
    const int tid = threadIdx.x, wg = tid >> 7, warp = tid >> 5, lane = tid & 31;

    auto gload = [&](int ks) {
        const int st = ks % G_STAGES;
        mbar_expect_tx(full + 8 * st, G_STAGE);
        const uint32_t dst = sbase + st * G_STAGE;
        if (ks < 22) {
            tma_load_2d(dst, &tmA2, D_ + ks * 64, rb * 128, full + 8 * st);
            tma_load_2d(dst + 16384, &tmW2, j * 64, ks * 64, full + 8 * st);
        } else {
            tma_load_2d(dst, &tmA2, (ks - 22) * 64, rb * 128, full + 8 * st);
            tma_load_2d(dst + 16384, &tmWo, j * 64, (ks - 22) * 64, full + 8 * st);
        }
    };

    if (tid == 0) {
        for (int i = 0; i < 3; i++) mbar_init(kv_full + 8 * i, 1);
        for (int i = 0; i < G_STAGES; i++) { mbar_init(full + 8 * i, 1); mbar_init(empty + 8 * i, 8); }
        fence_barrier_init();
    }
    pdl_wait();
    TS(6, tid == 0);
    const unsigned int ep = *(volatile unsigned int*)&g_epoch + 1;
    if (tid == 0) {
        for (int i = 0; i < 3; i++) {
            const uint32_t bar = kv_full + 8 * (2 - i);
            if (rb - i >= 0) {
                const int row = j * S_ + (rb - i) * 128;
                mbar_expect_tx(bar, 2 * 16384);
                tma_load_2d(sK + (2 - i) * 16384, &tmQKV, 64, row, bar);
                tma_load_2d(sV + (2 - i) * 16384, &tmQKV, 128, row, bar);
            } else {
                mbar_arrive(bar);
            }
        }
        for (int ks = 0; ks < G_STAGES; ks++) gload(ks);
    }
    if (rb < 2) {
        for (int i = tid; i < (2 - rb) * 1024; i += 512) {
            *(uint4*)(sgen + K23_OFF_KV + i * 16) = make_uint4(0, 0, 0, 0);
            *(uint4*)(sgen + K23_OFF_KV + 384 * KV_PITCH + i * 16) = make_uint4(0, 0, 0, 0);
        }
    }
    {
        const int qt = warp & 7, h0 = (warp >> 3) * 2;
        const int q0g = rb * 128 + qt * 16;
        const int r0 = lane >> 2, c0 = (lane & 3) * 2;
        const bf16* qsrc = g_qkv + ((size_t)j * S_ + q0g) * 192 + h0 * 16;
        uint32_t qa[4], qn[4];
        qa[0] = *(const uint32_t*)(qsrc + (size_t)r0 * 192 + c0);
        qa[1] = *(const uint32_t*)(qsrc + (size_t)(r0 + 8) * 192 + c0);
        qa[2] = *(const uint32_t*)(qsrc + (size_t)r0 * 192 + c0 + 8);
        qa[3] = *(const uint32_t*)(qsrc + (size_t)(r0 + 8) * 192 + c0 + 8);
        qn[0] = *(const uint32_t*)(qsrc + (size_t)r0 * 192 + 16 + c0);
        qn[1] = *(const uint32_t*)(qsrc + (size_t)(r0 + 8) * 192 + 16 + c0);
        qn[2] = *(const uint32_t*)(qsrc + (size_t)r0 * 192 + 16 + c0 + 8);
        qn[3] = *(const uint32_t*)(qsrc + (size_t)(r0 + 8) * 192 + 16 + c0 + 8);
        const float g0 = g_gate[q0g + r0], g1 = g_gate[q0g + r0 + 8];
        const int kb0 = q0g < 256 ? (256 - q0g) >> 4 : 0;
        __syncthreads();
        TS(7, tid == 0);
        const int krow = qt * 16 + (lane & 7) + ((lane >> 4) << 3);
        const int vrow = qt * 16 + (lane & 15);
#pragma unroll 1
        for (int hh = 0; hh < 2; hh++) {
            const int hl = h0 + hh;
            const uint32_t ka = sK + krow * KV_PITCH + (((2 * hl + ((lane >> 3) & 1)) ^ (lane & 7)) << 4);
            const uint32_t va = sV + vrow * KV_PITCH + (((2 * hl + (lane >> 4)) ^ (lane & 7)) << 4);
            if (rb < 2) attn_task<true>(qa, ka, va, kb0, lane, qt, kv_full, g_a2 + (size_t)q0g * KA2 + (j * 4 + hl) * 16, g0, g1);
            else        attn_task<false>(qa, ka, va, kb0, lane, qt, kv_full, g_a2 + (size_t)q0g * KA2 + (j * 4 + hl) * 16, g0, g1);
            TS(8 + hh, tid == 0);
            qa[0] = qn[0]; qa[1] = qn[1]; qa[2] = qn[2]; qa[3] = qn[3];
        }
    }
    __syncthreads();
    if (wg >= 2) {
        if (tid == 288) {
            __threadfence();
            asm volatile("st.release.gpu.global.u32 [%0], %1;" :: "l"(&g_flag_att[blockIdx.x]), "r"(ep) : "memory");
        }
        if (tid == 256) {
            for (int ks = G_STAGES; ks < G_KSTEPS; ks++) {
                mbar_wait(empty + 8 * (ks % G_STAGES), ((ks / G_STAGES) - 1) & 1);
                if (ks == 22) {
                    for (int i = 0; i < 8; i++) {
                        for (uint32_t it = 0; it < (1u << 22); ++it) {
                            unsigned int x;
                            asm volatile("ld.acquire.gpu.global.u32 %0, [%1];" : "=r"(x) : "l"(&g_flag_att[rb * 8 + i]) : "memory");
                            if (x == ep) break;
                        }
                    }
                    asm volatile("fence.proxy.async;" ::: "memory");
                }
                gload(ks);
            }
        }
    } else {
        TS(10, tid == 0);
        float acc[32];
        for (int ks = 0; ks < G_KSTEPS; ks++) {
            const int st = ks % G_STAGES;
            mbar_wait(full + 8 * st, (ks / G_STAGES) & 1);
            TS(11, tid == 0 && ks == 0); TS(12, tid == 0 && ks == 8); TS(13, tid == 0 && ks == 22);
            wgmma_fence();
#pragma unroll
            for (int k16 = 0; k16 < 4; k16++) {
                const uint64_t da = make_desc(sbase + st * G_STAGE + wg * 8192 + k16 * 32, 16, 1024);
                const uint64_t db = make_desc(sbase + st * G_STAGE + 16384 + k16 * 2048, 8192, 1024);
                wgmma_n64<1>(acc, da, db, (ks | k16) != 0);
            }
            wgmma_commit();
            if (ks > 0) { wgmma_wait<1>(); if (lane == 0) mbar_arrive(empty + 8 * ((ks - 1) % G_STAGES)); }
        }
        wgmma_wait<0>();
        TS(14, tid == 0);
        const int q = lane & 3;
        const int r = rb * 128 + wg * 64 + (warp & 3) * 16 + (lane >> 2);
        bf16* orow0 = out + (size_t)r * D_ + j * 64;
        bf16* orow1 = orow0 + 8 * D_;
#pragma unroll
        for (int u = 0; u < 2; u++) {
            uint32_t w0[4], w1[4];
#pragma unroll
            for (int i = 0; i < 4; i++) {
                const int t = u * 4 + i;
                w0[i] = pack_bf16(acc[t * 4 + 0], acc[t * 4 + 1]);
                w1[i] = pack_bf16(acc[t * 4 + 2], acc[t * 4 + 3]);
            }
            quad_transpose(w0, q);
            quad_transpose(w1, q);
            const int c = (u * 4 + q) * 8;
            *(uint4*)(orow0 + c) = make_uint4(w0[0], w0[1], w0[2], w0[3]);
            *(uint4*)(orow1 + c) = make_uint4(w1[0], w1[1], w1[2], w1[3]);
        }
        TS(15, tid == 0);
        if (tid == 0) {
            __threadfence();
            if (atomicAdd(&g_done, 1u) == gridDim.x - 1) {
                g_done = 0;
                __threadfence();
                atomicAdd(&g_epoch, 1u);
            }
        }
    }
}

typedef CUresult (*PFN_encodeTiled)(CUtensorMap*, CUtensorMapDataType, cuuint32_t, void*, const cuuint64_t*,
                                    const cuuint64_t*, const cuuint32_t*, const cuuint32_t*, CUtensorMapInterleave,
                                    CUtensorMapSwizzle, CUtensorMapL2promotion, CUtensorMapFloatOOBfill);

static void make_map(PFN_encodeTiled enc, CUtensorMap* m, const void* ptr, uint64_t cols, uint64_t rows,
                     uint32_t box_cols, uint32_t box_rows)
{
    cuuint64_t dims[2] = {cols, rows};
    cuuint64_t strides[1] = {cols * 2};
    cuuint32_t box[2] = {box_cols, box_rows};
    cuuint32_t es[2] = {1, 1};
    enc(m, CU_TENSOR_MAP_DATA_TYPE_BFLOAT16, 2, const_cast<void*>(ptr), dims, strides, box, es,
        CU_TENSOR_MAP_INTERLEAVE_NONE, CU_TENSOR_MAP_SWIZZLE_128B, CU_TENSOR_MAP_L2_PROMOTION_L2_128B,
        CU_TENSOR_MAP_FLOAT_OOB_FILL_NONE);
}

extern "C" void kernel_launch(void* const* d_in, const int* in_sizes, int n_in, void* d_out, int out_size)
{
    const bf16* x    = (const bf16*)d_in[0];
    const bf16* wqkv = (const bf16*)d_in[1];
    const bf16* wo   = (const bf16*)d_in[2];
    const bf16* w1   = (const bf16*)d_in[4];
    const bf16* b1   = (const bf16*)d_in[5];
    const bf16* w2   = (const bf16*)d_in[6];
    const bf16* gw   = (const bf16*)d_in[7];

    static PFN_encodeTiled enc = nullptr;
    if (!enc) {
        void* fn = nullptr;
        cudaDriverEntryPointQueryResult qr;
        cudaGetDriverEntryPoint("cuTensorMapEncodeTiled", &fn, cudaEnableDefault, &qr);
        enc = (PFN_encodeTiled)fn;
        cudaFuncSetAttribute(k1_kernel, cudaFuncAttributeMaxDynamicSharedMemorySize, K1_SMEM);
        cudaFuncSetAttribute(k23_kernel, cudaFuncAttributeMaxDynamicSharedMemorySize, K23_SMEM);
    }
    void* a2p = nullptr;
    cudaGetSymbolAddress(&a2p, g_a2);
    void* qkvp = nullptr;
    cudaGetSymbolAddress(&qkvp, g_qkv);
    CUtensorMap tmX, tmWqkv, tmW1, tmA2, tmWo, tmW2, tmQKV;
    make_map(enc, &tmQKV, qkvp, 192, 8 * S_, 64, 128);
    make_map(enc, &tmX, x, D_, S_, 64, 128);
    make_map(enc, &tmWqkv, wqkv, 3 * D_, D_, 64, 64);
    make_map(enc, &tmW1, w1, F_, D_, 64, 64);
    make_map(enc, &tmA2, a2p, KA2, S_, 64, 128);
    make_map(enc, &tmWo, wo, D_, D_, 64, 64);
    make_map(enc, &tmW2, w2, D_, F_, 64, 64);

    cudaStream_t st = cudaStreamPerThread;
    k1_kernel<<<128, 384, K1_SMEM, st>>>(tmX, tmWqkv, tmW1, b1, gw, w1, wqkv, w2, wo);
    cudaLaunchAttribute at[1];
    at[0].id = cudaLaunchAttributeProgrammaticStreamSerialization;
    at[0].val.programmaticStreamSerializationAllowed = 1;
    cudaLaunchConfig_t cfg = {};
    cfg.gridDim = dim3(128); cfg.stream = st; cfg.attrs = at; cfg.numAttrs = 1;
    cfg.blockDim = dim3(512); cfg.dynamicSmemBytes = K23_SMEM;
    cudaLaunchKernelEx(&cfg, k23_kernel, tmQKV, tmA2, tmWo, tmW2, (bf16*)d_out);
}
```

```cpp
#include <cuda_runtime.h>
#include <cuda_bf16.h>
#include <cuda.h>
#include <stdint.h>

typedef __nv_bfloat16 bf16;

constexpr int S_ = 2048, D_ = 512, F_ = 1376;
constexpr int KA2 = D_ + F_;
constexpr int FCH = 176;

__device__ bf16  g_qkv[8 * S_ * 192];
__device__ bf16  g_a2[S_ * KA2];
__device__ float g_gate[S_];

#define TS(k, cond) do { } while (0)

__device__ __forceinline__ uint32_t smem_u32(const void* p) { return (uint32_t)__cvta_generic_to_shared(p); }
__device__ __forceinline__ void mbar_init(uint32_t bar, uint32_t count) {
    asm volatile("mbarrier.init.shared::cta.b64 [%0], %1;" :: "r"(bar), "r"(count) : "memory");
}
__device__ __forceinline__ void mbar_expect_tx(uint32_t bar, uint32_t bytes) {
    asm volatile("mbarrier.arrive.expect_tx.shared::cta.b64 _, [%0], %1;" :: "r"(bar), "r"(bytes) : "memory");
}
__device__ __forceinline__ void mbar_arrive(uint32_t bar) {
    asm volatile("mbarrier.arrive.shared::cta.b64 _, [%0];" :: "r"(bar) : "memory");
}
__device__ __forceinline__ bool mbar_try_wait(uint32_t bar, uint32_t parity) {
    uint32_t ok;
    asm volatile("{\n.reg .pred p;\nmbarrier.try_wait.parity.shared::cta.b64 p, [%1], %2;\nselp.u32 %0, 1, 0, p;\n}"
                 : "=r"(ok) : "r"(bar), "r"(parity) : "memory");
    return ok != 0;
}
__device__ __forceinline__ void mbar_wait(uint32_t bar, uint32_t parity) {
    for (uint32_t it = 0; it < (1u << 22); ++it) { if (mbar_try_wait(bar, parity)) break; }
}
__device__ __forceinline__ void tma_load_2d(uint32_t dst, const CUtensorMap* map, int c0, int c1, uint32_t bar) {
    asm volatile("cp.async.bulk.tensor.2d.shared::cluster.global.mbarrier::complete_tx::bytes [%0], [%1, {%3, %4}], [%2];"
                 :: "r"(dst), "l"(map), "r"(bar), "r"(c0), "r"(c1) : "memory");
}
__device__ __forceinline__ void l2_prefetch(const void* p, uint32_t bytes) {
    asm volatile("cp.async.bulk.prefetch.L2.global [%0], %1;" :: "l"(p), "r"(bytes) : "memory");
}
__device__ __forceinline__ void fence_barrier_init() { asm volatile("fence.mbarrier_init.release.cluster;" ::: "memory"); }
__device__ __forceinline__ void wgmma_fence()  { asm volatile("wgmma.fence.sync.aligned;" ::: "memory"); }
__device__ __forceinline__ void wgmma_commit() { asm volatile("wgmma.commit_group.sync.aligned;" ::: "memory"); }
template <int N> __device__ __forceinline__ void wgmma_wait() { asm volatile("wgmma.wait_group.sync.aligned %0;" :: "n"(N) : "memory"); }
template <int R> __device__ __forceinline__ void reg_alloc()   { asm volatile("setmaxnreg.inc.sync.aligned.u32 %0;" :: "n"(R)); }
template <int R> __device__ __forceinline__ void reg_dealloc() { asm volatile("setmaxnreg.dec.sync.aligned.u32 %0;" :: "n"(R)); }
__device__ __forceinline__ void bar_sync(int id, int n)   { asm volatile("bar.sync %0, %1;" :: "r"(id), "r"(n) : "memory"); }
__device__ __forceinline__ void bar_arrive(int id, int n) { asm volatile("bar.arrive %0, %1;" :: "r"(id), "r"(n) : "memory"); }

__device__ __forceinline__ uint64_t make_desc(uint32_t addr, uint32_t lbo, uint32_t sbo) {
    uint64_t d = (uint64_t)((addr & 0x3FFFF) >> 4);
    d |= (uint64_t)((lbo & 0x3FFFF) >> 4) << 16;
    d |= (uint64_t)((sbo & 0x3FFFF) >> 4) << 32;
    d |= (uint64_t)1 << 62;
    return d;
}

template <int TB>
__device__ __forceinline__ void wgmma_n64(float (&d)[32], uint64_t da, uint64_t db, int scale_d) {
    asm volatile("{\n.reg .pred p;\nsetp.ne.b32 p, %34, 0;\n"
        "wgmma.mma_async.sync.aligned.m64n64k16.f32.bf16.bf16 {%0, %1, %2, %3, %4, %5, %6, %7, %8, %9, %10, %11, %12, %13, %14, %15, %16, %17, %18, %19, %20, %21, %22, %23, %24, %25, %26, %27, %28, %29, %30, %31}, %32, %33, p, 1, 1, 0, %35;\n}\n"
        : "+f"(d[0]), "+f"(d[1]), "+f"(d[2]), "+f"(d[3]), "+f"(d[4]), "+f"(d[5]), "+f"(d[6]), "+f"(d[7]), "+f"(d[8]), "+f"(d[9]), "+f"(d[10]), "+f"(d[11]), "+f"(d[12]), "+f"(d[13]), "+f"(d[14]), "+f"(d[15]), "+f"(d[16]), "+f"(d[17]), "+f"(d[18]), "+f"(d[19]), "+f"(d[20]), "+f"(d[21]), "+f"(d[22]), "+f"(d[23]), "+f"(d[24]), "+f"(d[25]), "+f"(d[26]), "+f"(d[27]), "+f"(d[28]), "+f"(d[29]), "+f"(d[30]), "+f"(d[31])
        : "l"(da), "l"(db), "r"(scale_d), "n"(TB));
}

template <int TB>
__device__ __forceinline__ void wgmma_n128(float (&d)[64], uint64_t da, uint64_t db, int scale_d) {
    asm volatile("{\n.reg .pred p;\nsetp.ne.b32 p, %66, 0;\n"
        "wgmma.mma_async.sync.aligned.m64n128k16.f32.bf16.bf16 {%0, %1, %2, %3, %4, %5, %6, %7, %8, %9, %10, %11, %12, %13, %14, %15, %16, %17, %18, %19, %20, %21, %22, %23, %24, %25, %26, %27, %28, %29, %30, %31, %32, %33, %34, %35, %36, %37, %38, %39, %40, %41, %42, %43, %44, %45, %46, %47, %48, %49, %50, %51, %52, %53, %54, %55, %56, %57, %58, %59, %60, %61, %62, %63}, %64, %65, p, 1, 1, 0, %67;\n}\n"
        : "+f"(d[0]), "+f"(d[1]), "+f"(d[2]), "+f"(d[3]), "+f"(d[4]), "+f"(d[5]), "+f"(d[6]), "+f"(d[7]), "+f"(d[8]), "+f"(d[9]), "+f"(d[10]), "+f"(d[11]), "+f"(d[12]), "+f"(d[13]), "+f"(d[14]), "+f"(d[15]), "+f"(d[16]), "+f"(d[17]), "+f"(d[18]), "+f"(d[19]), "+f"(d[20]), "+f"(d[21]), "+f"(d[22]), "+f"(d[23]), "+f"(d[24]), "+f"(d[25]), "+f"(d[26]), "+f"(d[27]), "+f"(d[28]), "+f"(d[29]), "+f"(d[30]), "+f"(d[31]), "+f"(d[32]), "+f"(d[33]), "+f"(d[34]), "+f"(d[35]), "+f"(d[36]), "+f"(d[37]), "+f"(d[38]), "+f"(d[39]), "+f"(d[40]), "+f"(d[41]), "+f"(d[42]), "+f"(d[43]), "+f"(d[44]), "+f"(d[45]), "+f"(d[46]), "+f"(d[47]), "+f"(d[48]), "+f"(d[49]), "+f"(d[50]), "+f"(d[51]), "+f"(d[52]), "+f"(d[53]), "+f"(d[54]), "+f"(d[55]), "+f"(d[56]), "+f"(d[57]), "+f"(d[58]), "+f"(d[59]), "+f"(d[60]), "+f"(d[61]), "+f"(d[62]), "+f"(d[63])
        : "l"(da), "l"(db), "r"(scale_d), "n"(TB));
}

template <int TB>
__device__ __forceinline__ void wgmma_n176(float (&d)[88], uint64_t da, uint64_t db, int scale_d) {
    asm volatile("{\n.reg .pred p;\nsetp.ne.b32 p, %90, 0;\n"
        "wgmma.mma_async.sync.aligned.m64n176k16.f32.bf16.bf16 {%0, %1, %2, %3, %4, %5, %6, %7, %8, %9, %10, %11, %12, %13, %14, %15, %16, %17, %18, %19, %20, %21, %22, %23, %24, %25, %26, %27, %28, %29, %30, %31, %32, %33, %34, %35, %36, %37, %38, %39, %40, %41, %42, %43, %44, %45, %46, %47, %48, %49, %50, %51, %52, %53, %54, %55, %56, %57, %58, %59, %60, %61, %62, %63, %64, %65, %66, %67, %68, %69, %70, %71, %72, %73, %74, %75, %76, %77, %78, %79, %80, %81, %82, %83, %84, %85, %86, %87}, %88, %89, p, 1, 1, 0, %91;\n}\n"
        : "+f"(d[0]), "+f"(d[1]), "+f"(d[2]), "+f"(d[3]), "+f"(d[4]), "+f"(d[5]), "+f"(d[6]), "+f"(d[7]), "+f"(d[8]), "+f"(d[9]), "+f"(d[10]), "+f"(d[11]), "+f"(d[12]), "+f"(d[13]), "+f"(d[14]), "+f"(d[15]), "+f"(d[16]), "+f"(d[17]), "+f"(d[18]), "+f"(d[19]), "+f"(d[20]), "+f"(d[21]), "+f"(d[22]), "+f"(d[23]), "+f"(d[24]), "+f"(d[25]), "+f"(d[26]), "+f"(d[27]), "+f"(d[28]), "+f"(d[29]), "+f"(d[30]), "+f"(d[31]), "+f"(d[32]), "+f"(d[33]), "+f"(d[34]), "+f"(d[35]), "+f"(d[36]), "+f"(d[37]), "+f"(d[38]), "+f"(d[39]), "+f"(d[40]), "+f"(d[41]), "+f"(d[42]), "+f"(d[43]), "+f"(d[44]), "+f"(d[45]), "+f"(d[46]), "+f"(d[47]), "+f"(d[48]), "+f"(d[49]), "+f"(d[50]), "+f"(d[51]), "+f"(d[52]), "+f"(d[53]), "+f"(d[54]), "+f"(d[55]), "+f"(d[56]), "+f"(d[57]), "+f"(d[58]), "+f"(d[59]), "+f"(d[60]), "+f"(d[61]), "+f"(d[62]), "+f"(d[63]), "+f"(d[64]), "+f"(d[65]), "+f"(d[66]), "+f"(d[67]), "+f"(d[68]), "+f"(d[69]), "+f"(d[70]), "+f"(d[71]), "+f"(d[72]), "+f"(d[73]), "+f"(d[74]), "+f"(d[75]), "+f"(d[76]), "+f"(d[77]), "+f"(d[78]), "+f"(d[79]), "+f"(d[80]), "+f"(d[81]), "+f"(d[82]), "+f"(d[83]), "+f"(d[84]), "+f"(d[85]), "+f"(d[86]), "+f"(d[87])
        : "l"(da), "l"(db), "r"(scale_d), "n"(TB));
}

template <int TB>
__device__ __forceinline__ void wgmma_n192(float (&d)[96], uint64_t da, uint64_t db, int scale_d) {
    asm volatile("{\n.reg .pred p;\nsetp.ne.b32 p, %98, 0;\n"
        "wgmma.mma_async.sync.aligned.m64n192k16.f32.bf16.bf16 {%0, %1, %2, %3, %4, %5, %6, %7, %8, %9, %10, %11, %12, %13, %14, %15, %16, %17, %18, %19, %20, %21, %22, %23, %24, %25, %26, %27, %28, %29, %30, %31, %32, %33, %34, %35, %36, %37, %38, %39, %40, %41, %42, %43, %44, %45, %46, %47, %48, %49, %50, %51, %52, %53, %54, %55, %56, %57, %58, %59, %60, %61, %62, %63, %64, %65, %66, %67, %68, %69, %70, %71, %72, %73, %74, %75, %76, %77, %78, %79, %80, %81, %82, %83, %84, %85, %86, %87, %88, %89, %90, %91, %92, %93, %94, %95}, %96, %97, p, 1, 1, 0, %99;\n}\n"
        : "+f"(d[0]), "+f"(d[1]), "+f"(d[2]), "+f"(d[3]), "+f"(d[4]), "+f"(d[5]), "+f"(d[6]), "+f"(d[7]), "+f"(d[8]), "+f"(d[9]), "+f"(d[10]), "+f"(d[11]), "+f"(d[12]), "+f"(d[13]), "+f"(d[14]), "+f"(d[15]), "+f"(d[16]), "+f"(d[17]), "+f"(d[18]), "+f"(d[19]), "+f"(d[20]), "+f"(d[21]), "+f"(d[22]), "+f"(d[23]), "+f"(d[24]), "+f"(d[25]), "+f"(d[26]), "+f"(d[27]), "+f"(d[28]), "+f"(d[29]), "+f"(d[30]), "+f"(d[31]), "+f"(d[32]), "+f"(d[33]), "+f"(d[34]), "+f"(d[35]), "+f"(d[36]), "+f"(d[37]), "+f"(d[38]), "+f"(d[39]), "+f"(d[40]), "+f"(d[41]), "+f"(d[42]), "+f"(d[43]), "+f"(d[44]), "+f"(d[45]), "+f"(d[46]), "+f"(d[47]), "+f"(d[48]), "+f"(d[49]), "+f"(d[50]), "+f"(d[51]), "+f"(d[52]), "+f"(d[53]), "+f"(d[54]), "+f"(d[55]), "+f"(d[56]), "+f"(d[57]), "+f"(d[58]), "+f"(d[59]), "+f"(d[60]), "+f"(d[61]), "+f"(d[62]), "+f"(d[63]), "+f"(d[64]), "+f"(d[65]), "+f"(d[66]), "+f"(d[67]), "+f"(d[68]), "+f"(d[69]), "+f"(d[70]), "+f"(d[71]), "+f"(d[72]), "+f"(d[73]), "+f"(d[74]), "+f"(d[75]), "+f"(d[76]), "+f"(d[77]), "+f"(d[78]), "+f"(d[79]), "+f"(d[80]), "+f"(d[81]), "+f"(d[82]), "+f"(d[83]), "+f"(d[84]), "+f"(d[85]), "+f"(d[86]), "+f"(d[87]), "+f"(d[88]), "+f"(d[89]), "+f"(d[90]), "+f"(d[91]), "+f"(d[92]), "+f"(d[93]), "+f"(d[94]), "+f"(d[95])
        : "l"(da), "l"(db), "r"(scale_d), "n"(TB));
}

__device__ __forceinline__ uint32_t pack_bf16(float lo, float hi) {
    uint32_t r;
    asm("cvt.rn.bf16x2.f32 %0, %1, %2;" : "=r"(r) : "f"(hi), "f"(lo));
    return r;
}
__device__ __forceinline__ float bf_lo(uint32_t v) { return __uint_as_float(v << 16); }
__device__ __forceinline__ float bf_hi(uint32_t v) { return __uint_as_float(v & 0xffff0000u); }

__device__ __forceinline__ void quad_transpose(uint32_t (&w)[4], int q) {
    const bool o1 = q & 1, o2 = q & 2;
    {
        uint32_t s0 = o1 ? w[0] : w[1], s1 = o1 ? w[2] : w[3];
        s0 = __shfl_xor_sync(0xffffffffu, s0, 1); s1 = __shfl_xor_sync(0xffffffffu, s1, 1);
        if (o1) { w[0] = s0; w[2] = s1; } else { w[1] = s0; w[3] = s1; }
    }
    {
        uint32_t s0 = o2 ? w[0] : w[2], s1 = o2 ? w[1] : w[3];
        s0 = __shfl_xor_sync(0xffffffffu, s0, 2); s1 = __shfl_xor_sync(0xffffffffu, s1, 2);
        if (o2) { w[0] = s0; w[1] = s1; } else { w[2] = s0; w[3] = s1; }
    }
}

__device__ __forceinline__ float ex2(float x) { float y; asm("ex2.approx.ftz.f32 %0, %1;" : "=f"(y) : "f"(x)); return y; }
__device__ __forceinline__ float rcp(float x) { float y; asm("rcp.approx.ftz.f32 %0, %1;" : "=f"(y) : "f"(x)); return y; }

__device__ __forceinline__ float ex2v(float x) { float y; asm volatile("ex2.approx.ftz.f32 %0, %1;" : "=f"(y) : "f"(x)); return y; }
__device__ __forceinline__ float rcpv(float x) { float y; asm volatile("rcp.approx.ftz.f32 %0, %1;" : "=f"(y) : "f"(x)); return y; }
__device__ __forceinline__ float mish_f(float h) {
    const float e = ex2v(1.4426950408889634f * fminf(h, 20.f));
    const float n = fmaf(e, e, e + e);
    return h * n * rcpv(n + 2.f);
}

__device__ __forceinline__ void pdl_wait()   { asm volatile("griddepcontrol.wait;" ::: "memory"); }
__device__ __forceinline__ void pdl_launch() { asm volatile("griddepcontrol.launch_dependents;" ::: "memory"); }

constexpr int K1_STAGES = 4;
constexpr int K1_XBYTES = 128 * 512 * 2;
constexpr int K1_BSTAGE = 3 * 8192;
constexpr int K1_SMEM   = K1_XBYTES + K1_STAGES * K1_BSTAGE + 2048   + 1024  ;

__global__ void __launch_bounds__(384, 1)
k1_kernel(const __grid_constant__ CUtensorMap tmX, const __grid_constant__ CUtensorMap tmWqkv,
          const __grid_constant__ CUtensorMap tmW1, const bf16* __restrict__ b1,
          const bf16* __restrict__ gate_w, const bf16* __restrict__ w1p, const bf16* __restrict__ wqkvp,
          const bf16* __restrict__ w2p, const bf16* __restrict__ wop)
{

    extern __shared__ uint8_t smem_raw[];
    const uint32_t sbase = (smem_u32(smem_raw) + 1023u) & ~1023u;
    uint8_t* sgen = smem_raw + (sbase - smem_u32(smem_raw));
    const uint32_t sX = sbase;
    const uint32_t sB = sbase + K1_XBYTES;
    const uint32_t sBar = sB + K1_STAGES * K1_BSTAGE;
    const uint32_t x_full = sBar;
    const uint32_t b_full = sBar + 64;
    const uint32_t b_empty = sBar + 96;
    float* sGate = (float*)(sgen + K1_XBYTES + K1_STAGES * K1_BSTAGE + 128);
    uint8_t* sGw = sgen + K1_XBYTES + K1_STAGES * K1_BSTAGE + 640;
    uint32_t* sBias = (uint32_t*)(sgen + K1_XBYTES + K1_STAGES * K1_BSTAGE + 1664);

    const int rb = blockIdx.x >> 3, j = blockIdx.x & 7;
    const int tid = threadIdx.x, wg = tid >> 7, warp = tid >> 5, lane = tid & 31;
    TS(0, tid == 0);
    pdl_launch();

    if (tid == 0) {
        for (int i = 0; i < 8; i++) mbar_init(x_full + 8 * i, 1);
        for (int i = 0; i < K1_STAGES; i++) { mbar_init(b_full + 8 * i, 1); mbar_init(b_empty + 8 * i, 8); }
        fence_barrier_init();
    }
    __syncthreads();

    if (wg == 2) {
        reg_dealloc<40>();
        if (tid == 288) {
            const int b = blockIdx.x;
            mbar_wait(b_full + 8, 0);
            l2_prefetch((const uint8_t*)wqkvp + b * 12288, 12288);
            l2_prefetch((const uint8_t*)w2p + b * 11008, 11008);
            l2_prefetch((const uint8_t*)wop + b * 4096, 4096);
        }
        if (tid == 256) {
            for (int it = 0; it < 16; it++) {
                if (it < 8) {
                    mbar_expect_tx(x_full + 8 * it, 16384);
                    tma_load_2d(sX + it * 16384, &tmX, it * 64, rb * 128, x_full + 8 * it);
                }
                const int st = it & 3;
                if (it >= K1_STAGES) mbar_wait(b_empty + 8 * st, ((it >> 2) - 1) & 1);
                mbar_expect_tx(b_full + 8 * st, K1_BSTAGE);
                const uint32_t dst = sB + st * K1_BSTAGE;
                if (it < 8) {
                    for (int b = 0; b < 3; b++) tma_load_2d(dst + b * 8192, &tmW1, j * FCH + b * 64, it * 64, b_full + 8 * st);
                } else {
                    for (int b = 0; b < 3; b++) tma_load_2d(dst + b * 8192, &tmWqkv, b * 512 + j * 64, (it - 8) * 64, b_full + 8 * st);
                }
            }
        }
    } else {
        reg_alloc<232>();
        if (tid < 64) ((uint4*)sGw)[tid] = __ldg((const uint4*)gate_w + tid);
        else if (tid < 64 + 88) {
            const int c = j * FCH + (tid - 64) * 2;
            sBias[tid - 64] = c < F_ ? __ldg((const uint32_t*)(b1 + c)) : 0u;
        }
        bar_sync(3, 256);
        const int t128 = tid & 127, w4 = warp & 3, q = lane & 3;
        float accF[88], accQ[96];
        float gs = 0.f;
        const int grow = wg * 64 + (t128 >> 1), ghalf = t128 & 1;
#pragma unroll
        for (int kc = 0; kc < 8; kc++) {
            const int st = kc & 3;
            mbar_wait(x_full + 8 * kc, 0);
            mbar_wait(b_full + 8 * st, (kc >> 2) & 1);
            TS(1, tid == 0 && kc == 0); TS(2, tid == 0 && kc == 4);
            wgmma_fence();
#pragma unroll
            for (int k16 = 0; k16 < 4; k16++) {
                const uint64_t db = make_desc(sB + st * K1_BSTAGE + k16 * 2048, 8192, 1024);
                const uint64_t da = make_desc(sX + kc * 16384 + wg * 8192 + k16 * 32, 16, 1024);
                wgmma_n176<1>(accF, da, db, (kc | k16) != 0);
            }
            wgmma_commit();
#pragma unroll
            for (int c = 0; c < 4; c++) {
                const int cc = ghalf * 4 + c;
                const uint4 xv = *(const uint4*)(sgen + kc * 16384 + grow * 128 + ((cc ^ (grow & 7)) << 4));
                const uint4 gv = *(const uint4*)(sGw + kc * 128 + cc * 16);
                gs = fmaf(bf_lo(xv.x), bf_lo(gv.x), gs); gs = fmaf(bf_hi(xv.x), bf_hi(gv.x), gs);
                gs = fmaf(bf_lo(xv.y), bf_lo(gv.y), gs); gs = fmaf(bf_hi(xv.y), bf_hi(gv.y), gs);
                gs = fmaf(bf_lo(xv.z), bf_lo(gv.z), gs); gs = fmaf(bf_hi(xv.z), bf_hi(gv.z), gs);
                gs = fmaf(bf_lo(xv.w), bf_lo(gv.w), gs); gs = fmaf(bf_hi(xv.w), bf_hi(gv.w), gs);
            }
            if (kc > 0) { wgmma_wait<1>(); if (lane == 0) mbar_arrive(b_empty + 8 * ((kc - 1) & 3)); }
        }
        gs += __shfl_xor_sync(0xffffffffu, gs, 1);
        {
            const float g = 1.f / (1.f + __expf(-gs));
            if (ghalf == 0) {
                sGate[grow] = g;
                if (j == 0) g_gate[rb * 128 + grow] = g;
            }
        }
        wgmma_wait<0>();
        if (lane == 0) mbar_arrive(b_empty + 8 * 3);
        bar_sync(1 + wg, 128);
        TS(3, tid == 0);
        const int n0 = j * FCH;
        const int rl = wg * 64 + w4 * 16 + (lane >> 2);
        const float om0 = 1.f - sGate[rl], om1 = 1.f - sGate[rl + 8];
        bf16* frow0 = g_a2 + (size_t)(rb * 128 + rl) * KA2 + D_ + n0;
        bf16* frow1 = frow0 + 8 * KA2;
        auto ffn_chunk = [&](int u) {
            uint32_t w0[4], w1[4];
#pragma unroll
            for (int i = 0; i < 4; i++) {
                const int t = u * 4 + i;
                if (t < 22) {
                    const uint32_t bv = sBias[t * 4 + q];
                    const float bb0 = bf_lo(bv), bb1 = bf_hi(bv);
                    w0[i] = pack_bf16(mish_f(accF[t * 4 + 0] + bb0) * om0, mish_f(accF[t * 4 + 1] + bb1) * om0);
                    w1[i] = pack_bf16(mish_f(accF[t * 4 + 2] + bb0) * om1, mish_f(accF[t * 4 + 3] + bb1) * om1);
                } else { w0[i] = 0; w1[i] = 0; }
            }
            quad_transpose(w0, q);
            quad_transpose(w1, q);
            const int c = (u * 4 + q) * 8;
            if (c < FCH && n0 + c < F_) {
                *(uint4*)(frow0 + c) = make_uint4(w0[0], w0[1], w0[2], w0[3]);
                *(uint4*)(frow1 + c) = make_uint4(w1[0], w1[1], w1[2], w1[3]);
            }
        };
#pragma unroll
        for (int kc = 0; kc < 8; kc++) {
            const int st = kc & 3;
            mbar_wait(b_full + 8 * st, ((kc + 8) >> 2) & 1);
            wgmma_fence();
#pragma unroll
            for (int k16 = 0; k16 < 4; k16++) {
                const uint64_t db = make_desc(sB + st * K1_BSTAGE + k16 * 2048, 8192, 1024);
                const uint64_t da = make_desc(sX + kc * 16384 + wg * 8192 + k16 * 32, 16, 1024);
                wgmma_n192<1>(accQ, da, db, (kc | k16) != 0);
            }
            wgmma_commit();
            if (kc < 6) ffn_chunk(kc);
            if (kc > 0) { wgmma_wait<1>(); if (lane == 0) mbar_arrive(b_empty + 8 * ((kc - 1) & 3)); }
        }
        wgmma_wait<0>();
        TS(4, tid == 0);
        {
            bf16* orow0 = g_qkv + ((size_t)j * S_ + rb * 128 + rl) * 192;
            bf16* orow1 = orow0 + 8 * 192;
#pragma unroll
            for (int u = 0; u < 6; u++) {
                uint32_t w0[4], w1[4];
#pragma unroll
                for (int i = 0; i < 4; i++) {
                    const int t = u * 4 + i;
                    w0[i] = pack_bf16(accQ[t * 4 + 0], accQ[t * 4 + 1]);
                    w1[i] = pack_bf16(accQ[t * 4 + 2], accQ[t * 4 + 3]);
                }
                quad_transpose(w0, q);
                quad_transpose(w1, q);
                const int c = (u * 4 + q) * 8;
                *(uint4*)(orow0 + c) = make_uint4(w0[0], w0[1], w0[2], w0[3]);
                *(uint4*)(orow1 + c) = make_uint4(w1[0], w1[1], w1[2], w1[3]);
            }
        }
        TS(5, tid == 0);
    }
}

__device__ __forceinline__ void ldsm_x4(uint32_t (&r)[4], uint32_t addr) {
    asm("ldmatrix.sync.aligned.m8n8.x4.shared.b16 {%0,%1,%2,%3}, [%4];"
                 : "=r"(r[0]), "=r"(r[1]), "=r"(r[2]), "=r"(r[3]) : "r"(addr));
}
__device__ __forceinline__ void ldsm_x4_t(uint32_t (&r)[4], uint32_t addr) {
    asm("ldmatrix.sync.aligned.m8n8.x4.trans.shared.b16 {%0,%1,%2,%3}, [%4];"
                 : "=r"(r[0]), "=r"(r[1]), "=r"(r[2]), "=r"(r[3]) : "r"(addr));
}
__device__ __forceinline__ void mma16816(float (&d)[4], const uint32_t (&a)[4], uint32_t b0, uint32_t b1) {
    asm("mma.sync.aligned.m16n8k16.row.col.f32.bf16.bf16.f32 {%0,%1,%2,%3}, {%4,%5,%6,%7}, {%8,%9}, {%0,%1,%2,%3};"
                 : "+f"(d[0]), "+f"(d[1]), "+f"(d[2]), "+f"(d[3])
                 : "r"(a[0]), "r"(a[1]), "r"(a[2]), "r"(a[3]), "r"(b0), "r"(b1));
}
__device__ __forceinline__ void mma16816_z(float (&d)[4], const uint32_t (&a)[4], uint32_t b0, uint32_t b1) {
    asm("mma.sync.aligned.m16n8k16.row.col.f32.bf16.bf16.f32 {%0,%1,%2,%3}, {%4,%5,%6,%7}, {%8,%9}, {%10,%10,%10,%10};"
                 : "=f"(d[0]), "=f"(d[1]), "=f"(d[2]), "=f"(d[3])
                 : "r"(a[0]), "r"(a[1]), "r"(a[2]), "r"(a[3]), "r"(b0), "r"(b1), "f"(0.f));
}

constexpr int KV_PITCH = 128;

template <int EDGE, bool HEAD>
__device__ __forceinline__ void blk_scores(float (&s)[2][4], const uint32_t (&qa)[4], uint32_t kaddr, bool dead, int r0, int c0)
{
    uint32_t kf[4];
    ldsm_x4(kf, kaddr);
    mma16816_z(s[0], qa, kf[0], kf[1]);
    mma16816_z(s[1], qa, kf[2], kf[3]);
#pragma unroll
    for (int t = 0; t < 2; t++)
#pragma unroll
        for (int e = 0; e < 4; e++) {
            const int r = r0 + (e >> 1) * 8, c = t * 8 + c0 + (e & 1);
            if (EDGE == 1 && c <= r) s[t][e] = -1e30f;
            if (EDGE == 2 && c > r) s[t][e] = -1e30f;
            if (HEAD && dead) s[t][e] = -1e30f;
        }
}
__device__ __forceinline__ void blk_max(const float (&s)[2][4], float& n0, float& n1) {
    n0 = fmaxf(n0, fmaxf(fmaxf(s[0][0], s[0][1]), fmaxf(s[1][0], s[1][1])));
    n1 = fmaxf(n1, fmaxf(fmaxf(s[0][2], s[0][3]), fmaxf(s[1][2], s[1][3])));
}
__device__ __forceinline__ void blk_pv(const float (&s)[2][4], float mc0, float mc1, float (&l)[4],
                                       float (&o)[2][4], uint32_t vaddr) {
    const float C = 0.25f * 1.4426950408889634f;
    uint32_t pa[4];
#pragma unroll
    for (int t = 0; t < 2; t++) {
        const float p0 = ex2(fmaf(s[t][0], C, -mc0)), p1 = ex2(fmaf(s[t][1], C, -mc0));
        const float p2 = ex2(fmaf(s[t][2], C, -mc1)), p3 = ex2(fmaf(s[t][3], C, -mc1));
        pa[2 * t] = pack_bf16(p0, p1); pa[2 * t + 1] = pack_bf16(p2, p3);
    }
    uint32_t vf[4];
    ldsm_x4_t(vf, vaddr);
    mma16816(o[0], pa, vf[0], vf[1]);
    mma16816(o[1], pa, vf[2], vf[3]);
    mma16816(l, pa, 0x3F803F80u, 0x3F803F80u);
}
__device__ __forceinline__ void quad_max(float& n0, float& n1) {
    n0 = fmaxf(n0, __shfl_xor_sync(0xffffffffu, n0, 1)); n1 = fmaxf(n1, __shfl_xor_sync(0xffffffffu, n1, 1));
    n0 = fmaxf(n0, __shfl_xor_sync(0xffffffffu, n0, 2)); n1 = fmaxf(n1, __shfl_xor_sync(0xffffffffu, n1, 2));
}
template <int NC, int NN, bool FIRST, bool NEXT_IS_EDGE, bool HEAD>
__device__ __forceinline__ void pipe_step(const float (&sc)[5][2][4], float (&sn)[5][2][4], const uint32_t (&qa)[4],
                                          uint32_t ka, uint32_t va, int kc, int kn, int kb0, int r0, int c0,
                                          float& m0, float& m1, float& n0, float& n1, float (&l)[4], float (&o)[2][4])
{
    const float C = 0.25f * 1.4426950408889634f;
    const float mc0 = n0 * C, mc1 = n1 * C;
    if (!FIRST) {
        const float a0 = ex2(fmaf(m0, C, -mc0)), a1 = ex2(fmaf(m1, C, -mc1));
        l[0] *= a0; l[2] *= a1;
        o[0][0] *= a0; o[0][1] *= a0; o[1][0] *= a0; o[1][1] *= a0;
        o[0][2] *= a1; o[0][3] *= a1; o[1][2] *= a1; o[1][3] *= a1;
    }
    m0 = n0; m1 = n1;
#pragma unroll
    for (int b = 0; b < NC; b++) {
        if (b < NN) {
            if (NEXT_IS_EDGE && b == 0) blk_scores<1, HEAD>(sn[b], qa, ka + (kn + b) * 16 * KV_PITCH, kn + b < kb0, r0, c0);
            else                        blk_scores<0, HEAD>(sn[b], qa, ka + (kn + b) * 16 * KV_PITCH, kn + b < kb0, r0, c0);
        }
        blk_pv(sc[b], mc0, mc1, l, o, va + (kc + b) * 16 * KV_PITCH);
        if (b < NN) blk_max(sn[b], n0, n1);
    }
    if (NN > 0) quad_max(n0, n1);
}

__device__ __forceinline__ void kv_need(uint32_t kvbar, int blk, uint32_t& ka, uint32_t& va) {
    mbar_wait(kvbar + 8 * blk, 0);
    asm volatile("" : "+r"(ka), "+r"(va) :: "memory");
}
template <bool HEAD>
__device__ __forceinline__ void attn_task(const uint32_t (&qa)[4], uint32_t ka, uint32_t va, int kb0, int lane, int qt, uint32_t kvbar,
                                          bf16* __restrict__ out  , float g0, float g1)
{
    const int r0 = lane >> 2, c0 = (lane & 3) * 2;
    float m0 = -1e30f, m1 = -1e30f, n0 = -1e30f, n1 = -1e30f;
    float l[4] = {0.f, 0.f, 0.f, 0.f};
    float o[2][4] = {{0.f, 0.f, 0.f, 0.f}, {0.f, 0.f, 0.f, 0.f}};
    float sa[5][2][4], sb[5][2][4];
    kv_need(kvbar, 2, ka, va);
    if (qt < 4) kv_need(kvbar, 1, ka, va);
#pragma unroll
    for (int b = 0; b < 5; b++) {
        if (b == 4) blk_scores<2, HEAD>(sa[b], qa, ka + (12 + b) * 16 * KV_PITCH, false, r0, c0);
        else        blk_scores<0, HEAD>(sa[b], qa, ka + (12 + b) * 16 * KV_PITCH, 12 + b < kb0, r0, c0);
        blk_max(sa[b], n0, n1);
    }
    quad_max(n0, n1);
    kv_need(kvbar, 1, ka, va);
    if (HEAD) {
        pipe_step<5, 0, true, false, HEAD>(sa, sb, qa, ka, va, 12, 0, kb0, r0, c0, m0, m1, n0, n1, l, o);
        kv_need(kvbar, 0, ka, va);
#pragma unroll 1
        for (int kc = 8; kc >= 0 && kb0 < kc + 4; kc -= 4) {
#pragma unroll
            for (int b = 0; b < 4; b++) {
                blk_scores<0, HEAD>(sa[b], qa, ka + (kc + b) * 16 * KV_PITCH, kc + b < kb0, r0, c0);
                blk_max(sa[b], n0, n1);
            }
            quad_max(n0, n1);
            pipe_step<4, 0, false, false, HEAD>(sa, sb, qa, ka, va, kc, 0, kb0, r0, c0, m0, m1, n0, n1, l, o);
        }
    } else {
        pipe_step<5, 4, true,  false, HEAD>(sa, sb, qa, ka, va, 12, 8, kb0, r0, c0, m0, m1, n0, n1, l, o);
        if (qt < 4) kv_need(kvbar, 0, ka, va);
        pipe_step<4, 4, false, false, HEAD>(sb, sa, qa, ka, va, 8, 4, kb0, r0, c0, m0, m1, n0, n1, l, o);
        kv_need(kvbar, 0, ka, va);
        pipe_step<4, 4, false, true,  HEAD>(sa, sb, qa, ka, va, 4, 0, kb0, r0, c0, m0, m1, n0, n1, l, o);
        pipe_step<4, 0, false, false, HEAD>(sb, sa, qa, ka, va, 0, 0, kb0, r0, c0, m0, m1, n0, n1, l, o);
    }
    const float f0 = __fdividef(g0, l[0]), f1 = __fdividef(g1, l[2]);
#pragma unroll
    for (int t = 0; t < 2; t++) {
        *(uint32_t*)(out + (size_t)r0 * KA2 + t * 8 + c0) = pack_bf16(o[t][0] * f0, o[t][1] * f0);
        *(uint32_t*)(out + (size_t)(r0 + 8) * KA2 + t * 8 + c0) = pack_bf16(o[t][2] * f1, o[t][3] * f1);
    }
}

__device__ unsigned int g_epoch;
__device__ unsigned int g_done;
__device__ unsigned int g_flag_att[128];

constexpr int G_STAGES = 9;
constexpr int G_PRE = 5;
constexpr int G_STAGE = 16384 + 8192;
constexpr int G_KSTEPS = 30;
constexpr int K23_OFF_KV = G_PRE * G_STAGE;
constexpr int K23_OFF_BAR = K23_OFF_KV + 2 * 384 * KV_PITCH;
constexpr int K23_SMEM = K23_OFF_BAR + 256 + 1024;

__global__ void __launch_bounds__(512, 1)
k23_kernel(const __grid_constant__ CUtensorMap tmQKV, const __grid_constant__ CUtensorMap tmA2,
           const __grid_constant__ CUtensorMap tmWo, const __grid_constant__ CUtensorMap tmW2, bf16* __restrict__ out)
{
    extern __shared__ uint8_t smem_raw[];
    const uint32_t sbase = (smem_u32(smem_raw) + 1023u) & ~1023u;
    uint8_t* sgen = smem_raw + (sbase - smem_u32(smem_raw));
    const uint32_t sK = sbase + K23_OFF_KV, sV = sK + 384 * KV_PITCH;
    const uint32_t sBar = sbase + K23_OFF_BAR;
    const uint32_t full = sBar, empty = sBar + 80, kv_full = sBar + 160;
    const int rb = blockIdx.x >> 3, j = blockIdx.x & 7;
    const int tid = threadIdx.x, wg = tid >> 7, warp = tid >> 5, lane = tid & 31;

    auto gload = [&](int ks) {
        const int st = ks % G_STAGES;
        mbar_expect_tx(full + 8 * st, G_STAGE);
        const uint32_t dst = sbase + st * G_STAGE;
        if (ks < 22) {
            tma_load_2d(dst, &tmA2, D_ + ks * 64, rb * 128, full + 8 * st);
            tma_load_2d(dst + 16384, &tmW2, j * 64, ks * 64, full + 8 * st);
        } else {
            tma_load_2d(dst, &tmA2, (ks - 22) * 64, rb * 128, full + 8 * st);
            tma_load_2d(dst + 16384, &tmWo, j * 64, (ks - 22) * 64, full + 8 * st);
        }
    };

    if (tid == 0) {
        for (int i = 0; i < 3; i++) mbar_init(kv_full + 8 * i, 1);
        for (int i = 0; i < G_STAGES; i++) { mbar_init(full + 8 * i, 1); mbar_init(empty + 8 * i, 8); }
        fence_barrier_init();
    }
    pdl_wait();
    TS(6, tid == 0);
    const unsigned int ep = *(volatile unsigned int*)&g_epoch + 1;
    if (tid == 0) {
        for (int i = 0; i < 3; i++) {
            const uint32_t bar = kv_full + 8 * (2 - i);
            if (rb - i >= 0) {
                const int row = j * S_ + (rb - i) * 128;
                mbar_expect_tx(bar, 2 * 16384);
                tma_load_2d(sK + (2 - i) * 16384, &tmQKV, 64, row, bar);
                tma_load_2d(sV + (2 - i) * 16384, &tmQKV, 128, row, bar);
            } else {
                mbar_arrive(bar);
            }
        }
        for (int ks = 0; ks < G_PRE; ks++) gload(ks);
    }
    if (rb < 2) {
        for (int i = tid; i < (2 - rb) * 1024; i += 512) {
            *(uint4*)(sgen + K23_OFF_KV + i * 16) = make_uint4(0, 0, 0, 0);
            *(uint4*)(sgen + K23_OFF_KV + 384 * KV_PITCH + i * 16) = make_uint4(0, 0, 0, 0);
        }
    }
    {
        const int qt = warp & 7, h0 = (warp >> 3) * 2;
        const int q0g = rb * 128 + qt * 16;
        const int r0 = lane >> 2, c0 = (lane & 3) * 2;
        const bf16* qsrc = g_qkv + ((size_t)j * S_ + q0g) * 192 + h0 * 16;
        uint32_t qa[4], qn[4];
        qa[0] = *(const uint32_t*)(qsrc + (size_t)r0 * 192 + c0);
        qa[1] = *(const uint32_t*)(qsrc + (size_t)(r0 + 8) * 192 + c0);
        qa[2] = *(const uint32_t*)(qsrc + (size_t)r0 * 192 + c0 + 8);
        qa[3] = *(const uint32_t*)(qsrc + (size_t)(r0 + 8) * 192 + c0 + 8);
        qn[0] = *(const uint32_t*)(qsrc + (size_t)r0 * 192 + 16 + c0);
        qn[1] = *(const uint32_t*)(qsrc + (size_t)(r0 + 8) * 192 + 16 + c0);
        qn[2] = *(const uint32_t*)(qsrc + (size_t)r0 * 192 + 16 + c0 + 8);
        qn[3] = *(const uint32_t*)(qsrc + (size_t)(r0 + 8) * 192 + 16 + c0 + 8);
        const float g0 = g_gate[q0g + r0], g1 = g_gate[q0g + r0 + 8];
        const int kb0 = q0g < 256 ? (256 - q0g) >> 4 : 0;
        __syncthreads();
        TS(7, tid == 0);
        const int krow = qt * 16 + (lane & 7) + ((lane >> 4) << 3);
        const int vrow = qt * 16 + (lane & 15);
#pragma unroll 1
        for (int hh = 0; hh < 2; hh++) {
            const int hl = h0 + hh;
            const uint32_t ka = sK + krow * KV_PITCH + (((2 * hl + ((lane >> 3) & 1)) ^ (lane & 7)) << 4);
            const uint32_t va = sV + vrow * KV_PITCH + (((2 * hl + (lane >> 4)) ^ (lane & 7)) << 4);
            if (rb < 2) attn_task<true>(qa, ka, va, kb0, lane, qt, kv_full, g_a2 + (size_t)q0g * KA2 + (j * 4 + hl) * 16, g0, g1);
            else        attn_task<false>(qa, ka, va, kb0, lane, qt, kv_full, g_a2 + (size_t)q0g * KA2 + (j * 4 + hl) * 16, g0, g1);
            TS(8 + hh, tid == 0);
            qa[0] = qn[0]; qa[1] = qn[1]; qa[2] = qn[2]; qa[3] = qn[3];
        }
    }
    __syncthreads();
    if (wg >= 2) {
        if (tid == 288) {
            __threadfence();
            asm volatile("st.release.gpu.global.u32 [%0], %1;" :: "l"(&g_flag_att[blockIdx.x]), "r"(ep) : "memory");
        }
        if (tid == 256) {
            asm volatile("fence.proxy.async;" ::: "memory");
            for (int ks = G_PRE; ks < G_KSTEPS; ks++) {
                if (ks >= G_STAGES) mbar_wait(empty + 8 * (ks % G_STAGES), ((ks / G_STAGES) - 1) & 1);
                if (ks == 22) {
                    for (int i = 0; i < 8; i++) {
                        for (uint32_t it = 0; it < (1u << 22); ++it) {
                            unsigned int x;
                            asm volatile("ld.acquire.gpu.global.u32 %0, [%1];" : "=r"(x) : "l"(&g_flag_att[rb * 8 + i]) : "memory");
                            if (x == ep) break;
                        }
                    }
                    asm volatile("fence.proxy.async;" ::: "memory");
                }
                gload(ks);
            }
        }
    } else {
        TS(10, tid == 0);
        float acc[32];
        for (int ks = 0; ks < G_KSTEPS; ks++) {
            const int st = ks % G_STAGES;
            mbar_wait(full + 8 * st, (ks / G_STAGES) & 1);
            TS(11, tid == 0 && ks == 0); TS(12, tid == 0 && ks == 8); TS(13, tid == 0 && ks == 22);
            wgmma_fence();
#pragma unroll
            for (int k16 = 0; k16 < 4; k16++) {
                const uint64_t da = make_desc(sbase + st * G_STAGE + wg * 8192 + k16 * 32, 16, 1024);
                const uint64_t db = make_desc(sbase + st * G_STAGE + 16384 + k16 * 2048, 8192, 1024);
                wgmma_n64<1>(acc, da, db, (ks | k16) != 0);
            }
            wgmma_commit();
            if (ks > 0) { wgmma_wait<1>(); if (lane == 0) mbar_arrive(empty + 8 * ((ks - 1) % G_STAGES)); }
        }
        wgmma_wait<0>();
        TS(14, tid == 0);
        const int q = lane & 3;
        const int r = rb * 128 + wg * 64 + (warp & 3) * 16 + (lane >> 2);
        bf16* orow0 = out + (size_t)r * D_ + j * 64;
        bf16* orow1 = orow0 + 8 * D_;
#pragma unroll
        for (int u = 0; u < 2; u++) {
            uint32_t w0[4], w1[4];
#pragma unroll
            for (int i = 0; i < 4; i++) {
                const int t = u * 4 + i;
                w0[i] = pack_bf16(acc[t * 4 + 0], acc[t * 4 + 1]);
                w1[i] = pack_bf16(acc[t * 4 + 2], acc[t * 4 + 3]);
            }
            quad_transpose(w0, q);
            quad_transpose(w1, q);
            const int c = (u * 4 + q) * 8;
            *(uint4*)(orow0 + c) = make_uint4(w0[0], w0[1], w0[2], w0[3]);
            *(uint4*)(orow1 + c) = make_uint4(w1[0], w1[1], w1[2], w1[3]);
        }
        TS(15, tid == 0);
        if (tid == 0) {
            __threadfence();
            if (atomicAdd(&g_done, 1u) == gridDim.x - 1) {
                g_done = 0;
                __threadfence();
                atomicAdd(&g_epoch, 1u);
            }
        }
    }
}

typedef CUresult (*PFN_encodeTiled)(CUtensorMap*, CUtensorMapDataType, cuuint32_t, void*, const cuuint64_t*,
                                    const cuuint64_t*, const cuuint32_t*, const cuuint32_t*, CUtensorMapInterleave,
                                    CUtensorMapSwizzle, CUtensorMapL2promotion, CUtensorMapFloatOOBfill);

static void make_map(PFN_encodeTiled enc, CUtensorMap* m, const void* ptr, uint64_t cols, uint64_t rows,
                     uint32_t box_cols, uint32_t box_rows)
{
    cuuint64_t dims[2] = {cols, rows};
    cuuint64_t strides[1] = {cols * 2};
    cuuint32_t box[2] = {box_cols, box_rows};
    cuuint32_t es[2] = {1, 1};
    enc(m, CU_TENSOR_MAP_DATA_TYPE_BFLOAT16, 2, const_cast<void*>(ptr), dims, strides, box, es,
        CU_TENSOR_MAP_INTERLEAVE_NONE, CU_TENSOR_MAP_SWIZZLE_128B, CU_TENSOR_MAP_L2_PROMOTION_L2_128B,
        CU_TENSOR_MAP_FLOAT_OOB_FILL_NONE);
}

extern "C" void kernel_launch(void* const* d_in, const int* in_sizes, int n_in, void* d_out, int out_size)
{
    const bf16* x    = (const bf16*)d_in[0];
    const bf16* wqkv = (const bf16*)d_in[1];
    const bf16* wo   = (const bf16*)d_in[2];
    const bf16* w1   = (const bf16*)d_in[4];
    const bf16* b1   = (const bf16*)d_in[5];
    const bf16* w2   = (const bf16*)d_in[6];
    const bf16* gw   = (const bf16*)d_in[7];

    static PFN_encodeTiled enc = nullptr;
    if (!enc) {
        void* fn = nullptr;
        cudaDriverEntryPointQueryResult qr;
        cudaGetDriverEntryPoint("cuTensorMapEncodeTiled", &fn, cudaEnableDefault, &qr);
        enc = (PFN_encodeTiled)fn;
        cudaFuncSetAttribute(k1_kernel, cudaFuncAttributeMaxDynamicSharedMemorySize, K1_SMEM);
        cudaFuncSetAttribute(k23_kernel, cudaFuncAttributeMaxDynamicSharedMemorySize, K23_SMEM);
    }
    void* a2p = nullptr;
    cudaGetSymbolAddress(&a2p, g_a2);
    void* qkvp = nullptr;
    cudaGetSymbolAddress(&qkvp, g_qkv);
    CUtensorMap tmX, tmWqkv, tmW1, tmA2, tmWo, tmW2, tmQKV;
    make_map(enc, &tmQKV, qkvp, 192, 8 * S_, 64, 128);
    make_map(enc, &tmX, x, D_, S_, 64, 128);
    make_map(enc, &tmWqkv, wqkv, 3 * D_, D_, 64, 64);
    make_map(enc, &tmW1, w1, F_, D_, 64, 64);
    make_map(enc, &tmA2, a2p, KA2, S_, 64, 128);
    make_map(enc, &tmWo, wo, D_, D_, 64, 64);
    make_map(enc, &tmW2, w2, D_, F_, 64, 64);

    cudaStream_t st = cudaStreamPerThread;
    k1_kernel<<<128, 384, K1_SMEM, st>>>(tmX, tmWqkv, tmW1, b1, gw, w1, wqkv, w2, wo);
    cudaLaunchAttribute at[1];
    at[0].id = cudaLaunchAttributeProgrammaticStreamSerialization;
    at[0].val.programmaticStreamSerializationAllowed = 1;
    cudaLaunchConfig_t cfg = {};
    cfg.gridDim = dim3(128); cfg.stream = st; cfg.attrs = at; cfg.numAttrs = 1;
    cfg.blockDim = dim3(512); cfg.dynamicSmemBytes = K23_SMEM;
    k23_kernel<<<128, 512, K23_SMEM, st>>>(tmQKV, tmA2, tmWo, tmW2, (bf16*)d_out);
}
```

```cpp
#include <cuda_runtime.h>
#include <cuda_bf16.h>
#include <cuda.h>
#include <stdint.h>

typedef __nv_bfloat16 bf16;

constexpr int S_ = 2048, D_ = 512, F_ = 1376;
constexpr int KA2 = D_ + F_;
constexpr int FCH = 176;

__device__ bf16  g_qkv[8 * S_ * 192];
__device__ bf16  g_a2[S_ * KA2];
__device__ float g_gate[S_];

#define TS(k, cond) do { } while (0)

__device__ __forceinline__ uint32_t smem_u32(const void* p) { return (uint32_t)__cvta_generic_to_shared(p); }
__device__ __forceinline__ void mbar_init(uint32_t bar, uint32_t count) {
    asm volatile("mbarrier.init.shared::cta.b64 [%0], %1;" :: "r"(bar), "r"(count) : "memory");
}
__device__ __forceinline__ void mbar_expect_tx(uint32_t bar, uint32_t bytes) {
    asm volatile("mbarrier.arrive.expect_tx.shared::cta.b64 _, [%0], %1;" :: "r"(bar), "r"(bytes) : "memory");
}
__device__ __forceinline__ void mbar_arrive(uint32_t bar) {
    asm volatile("mbarrier.arrive.shared::cta.b64 _, [%0];" :: "r"(bar) : "memory");
}
__device__ __forceinline__ bool mbar_try_wait(uint32_t bar, uint32_t parity) {
    uint32_t ok;
    asm volatile("{\n.reg .pred p;\nmbarrier.try_wait.parity.shared::cta.b64 p, [%1], %2;\nselp.u32 %0, 1, 0, p;\n}"
                 : "=r"(ok) : "r"(bar), "r"(parity) : "memory");
    return ok != 0;
}
__device__ __forceinline__ void mbar_wait(uint32_t bar, uint32_t parity) {
    for (uint32_t it = 0; it < (1u << 22); ++it) { if (mbar_try_wait(bar, parity)) break; }
}
__device__ __forceinline__ void tma_load_2d(uint32_t dst, const CUtensorMap* map, int c0, int c1, uint32_t bar) {
    asm volatile("cp.async.bulk.tensor.2d.shared::cluster.global.mbarrier::complete_tx::bytes [%0], [%1, {%3, %4}], [%2];"
                 :: "r"(dst), "l"(map), "r"(bar), "r"(c0), "r"(c1) : "memory");
}
__device__ __forceinline__ void l2_prefetch(const void* p, uint32_t bytes) {
    asm volatile("cp.async.bulk.prefetch.L2.global [%0], %1;" :: "l"(p), "r"(bytes) : "memory");
}
__device__ __forceinline__ void fence_barrier_init() { asm volatile("fence.mbarrier_init.release.cluster;" ::: "memory"); }
__device__ __forceinline__ void wgmma_fence()  { asm volatile("wgmma.fence.sync.aligned;" ::: "memory"); }
__device__ __forceinline__ void wgmma_commit() { asm volatile("wgmma.commit_group.sync.aligned;" ::: "memory"); }
template <int N> __device__ __forceinline__ void wgmma_wait() { asm volatile("wgmma.wait_group.sync.aligned %0;" :: "n"(N) : "memory"); }
template <int R> __device__ __forceinline__ void reg_alloc()   { asm volatile("setmaxnreg.inc.sync.aligned.u32 %0;" :: "n"(R)); }
template <int R> __device__ __forceinline__ void reg_dealloc() { asm volatile("setmaxnreg.dec.sync.aligned.u32 %0;" :: "n"(R)); }
__device__ __forceinline__ void bar_sync(int id, int n)   { asm volatile("bar.sync %0, %1;" :: "r"(id), "r"(n) : "memory"); }
__device__ __forceinline__ void bar_arrive(int id, int n) { asm volatile("bar.arrive %0, %1;" :: "r"(id), "r"(n) : "memory"); }

__device__ __forceinline__ uint64_t make_desc(uint32_t addr, uint32_t lbo, uint32_t sbo) {
    uint64_t d = (uint64_t)((addr & 0x3FFFF) >> 4);
    d |= (uint64_t)((lbo & 0x3FFFF) >> 4) << 16;
    d |= (uint64_t)((sbo & 0x3FFFF) >> 4) << 32;
    d |= (uint64_t)1 << 62;
    return d;
}

template <int TB>
__device__ __forceinline__ void wgmma_n64(float (&d)[32], uint64_t da, uint64_t db, int scale_d) {
    asm volatile("{\n.reg .pred p;\nsetp.ne.b32 p, %34, 0;\n"
        "wgmma.mma_async.sync.aligned.m64n64k16.f32.bf16.bf16 {%0, %1, %2, %3, %4, %5, %6, %7, %8, %9, %10, %11, %12, %13, %14, %15, %16, %17, %18, %19, %20, %21, %22, %23, %24, %25, %26, %27, %28, %29, %30, %31}, %32, %33, p, 1, 1, 0, %35;\n}\n"
        : "+f"(d[0]), "+f"(d[1]), "+f"(d[2]), "+f"(d[3]), "+f"(d[4]), "+f"(d[5]), "+f"(d[6]), "+f"(d[7]), "+f"(d[8]), "+f"(d[9]), "+f"(d[10]), "+f"(d[11]), "+f"(d[12]), "+f"(d[13]), "+f"(d[14]), "+f"(d[15]), "+f"(d[16]), "+f"(d[17]), "+f"(d[18]), "+f"(d[19]), "+f"(d[20]), "+f"(d[21]), "+f"(d[22]), "+f"(d[23]), "+f"(d[24]), "+f"(d[25]), "+f"(d[26]), "+f"(d[27]), "+f"(d[28]), "+f"(d[29]), "+f"(d[30]), "+f"(d[31])
        : "l"(da), "l"(db), "r"(scale_d), "n"(TB));
}

template <int TB>
__device__ __forceinline__ void wgmma_n128(float (&d)[64], uint64_t da, uint64_t db, int scale_d) {
    asm volatile("{\n.reg .pred p;\nsetp.ne.b32 p, %66, 0;\n"
        "wgmma.mma_async.sync.aligned.m64n128k16.f32.bf16.bf16 {%0, %1, %2, %3, %4, %5, %6, %7, %8, %9, %10, %11, %12, %13, %14, %15, %16, %17, %18, %19, %20, %21, %22, %23, %24, %25, %26, %27, %28, %29, %30, %31, %32, %33, %34, %35, %36, %37, %38, %39, %40, %41, %42, %43, %44, %45, %46, %47, %48, %49, %50, %51, %52, %53, %54, %55, %56, %57, %58, %59, %60, %61, %62, %63}, %64, %65, p, 1, 1, 0, %67;\n}\n"
        : "+f"(d[0]), "+f"(d[1]), "+f"(d[2]), "+f"(d[3]), "+f"(d[4]), "+f"(d[5]), "+f"(d[6]), "+f"(d[7]), "+f"(d[8]), "+f"(d[9]), "+f"(d[10]), "+f"(d[11]), "+f"(d[12]), "+f"(d[13]), "+f"(d[14]), "+f"(d[15]), "+f"(d[16]), "+f"(d[17]), "+f"(d[18]), "+f"(d[19]), "+f"(d[20]), "+f"(d[21]), "+f"(d[22]), "+f"(d[23]), "+f"(d[24]), "+f"(d[25]), "+f"(d[26]), "+f"(d[27]), "+f"(d[28]), "+f"(d[29]), "+f"(d[30]), "+f"(d[31]), "+f"(d[32]), "+f"(d[33]), "+f"(d[34]), "+f"(d[35]), "+f"(d[36]), "+f"(d[37]), "+f"(d[38]), "+f"(d[39]), "+f"(d[40]), "+f"(d[41]), "+f"(d[42]), "+f"(d[43]), "+f"(d[44]), "+f"(d[45]), "+f"(d[46]), "+f"(d[47]), "+f"(d[48]), "+f"(d[49]), "+f"(d[50]), "+f"(d[51]), "+f"(d[52]), "+f"(d[53]), "+f"(d[54]), "+f"(d[55]), "+f"(d[56]), "+f"(d[57]), "+f"(d[58]), "+f"(d[59]), "+f"(d[60]), "+f"(d[61]), "+f"(d[62]), "+f"(d[63])
        : "l"(da), "l"(db), "r"(scale_d), "n"(TB));
}

template <int TB>
__device__ __forceinline__ void wgmma_n176(float (&d)[88], uint64_t da, uint64_t db, int scale_d) {
    asm volatile("{\n.reg .pred p;\nsetp.ne.b32 p, %90, 0;\n"
        "wgmma.mma_async.sync.aligned.m64n176k16.f32.bf16.bf16 {%0, %1, %2, %3, %4, %5, %6, %7, %8, %9, %10, %11, %12, %13, %14, %15, %16, %17, %18, %19, %20, %21, %22, %23, %24, %25, %26, %27, %28, %29, %30, %31, %32, %33, %34, %35, %36, %37, %38, %39, %40, %41, %42, %43, %44, %45, %46, %47, %48, %49, %50, %51, %52, %53, %54, %55, %56, %57, %58, %59, %60, %61, %62, %63, %64, %65, %66, %67, %68, %69, %70, %71, %72, %73, %74, %75, %76, %77, %78, %79, %80, %81, %82, %83, %84, %85, %86, %87}, %88, %89, p, 1, 1, 0, %91;\n}\n"
        : "+f"(d[0]), "+f"(d[1]), "+f"(d[2]), "+f"(d[3]), "+f"(d[4]), "+f"(d[5]), "+f"(d[6]), "+f"(d[7]), "+f"(d[8]), "+f"(d[9]), "+f"(d[10]), "+f"(d[11]), "+f"(d[12]), "+f"(d[13]), "+f"(d[14]), "+f"(d[15]), "+f"(d[16]), "+f"(d[17]), "+f"(d[18]), "+f"(d[19]), "+f"(d[20]), "+f"(d[21]), "+f"(d[22]), "+f"(d[23]), "+f"(d[24]), "+f"(d[25]), "+f"(d[26]), "+f"(d[27]), "+f"(d[28]), "+f"(d[29]), "+f"(d[30]), "+f"(d[31]), "+f"(d[32]), "+f"(d[33]), "+f"(d[34]), "+f"(d[35]), "+f"(d[36]), "+f"(d[37]), "+f"(d[38]), "+f"(d[39]), "+f"(d[40]), "+f"(d[41]), "+f"(d[42]), "+f"(d[43]), "+f"(d[44]), "+f"(d[45]), "+f"(d[46]), "+f"(d[47]), "+f"(d[48]), "+f"(d[49]), "+f"(d[50]), "+f"(d[51]), "+f"(d[52]), "+f"(d[53]), "+f"(d[54]), "+f"(d[55]), "+f"(d[56]), "+f"(d[57]), "+f"(d[58]), "+f"(d[59]), "+f"(d[60]), "+f"(d[61]), "+f"(d[62]), "+f"(d[63]), "+f"(d[64]), "+f"(d[65]), "+f"(d[66]), "+f"(d[67]), "+f"(d[68]), "+f"(d[69]), "+f"(d[70]), "+f"(d[71]), "+f"(d[72]), "+f"(d[73]), "+f"(d[74]), "+f"(d[75]), "+f"(d[76]), "+f"(d[77]), "+f"(d[78]), "+f"(d[79]), "+f"(d[80]), "+f"(d[81]), "+f"(d[82]), "+f"(d[83]), "+f"(d[84]), "+f"(d[85]), "+f"(d[86]), "+f"(d[87])
        : "l"(da), "l"(db), "r"(scale_d), "n"(TB));
}

template <int TB>
__device__ __forceinline__ void wgmma_n192(float (&d)[96], uint64_t da, uint64_t db, int scale_d) {
    asm volatile("{\n.reg .pred p;\nsetp.ne.b32 p, %98, 0;\n"
        "wgmma.mma_async.sync.aligned.m64n192k16.f32.bf16.bf16 {%0, %1, %2, %3, %4, %5, %6, %7, %8, %9, %10, %11, %12, %13, %14, %15, %16, %17, %18, %19, %20, %21, %22, %23, %24, %25, %26, %27, %28, %29, %30, %31, %32, %33, %34, %35, %36, %37, %38, %39, %40, %41, %42, %43, %44, %45, %46, %47, %48, %49, %50, %51, %52, %53, %54, %55, %56, %57, %58, %59, %60, %61, %62, %63, %64, %65, %66, %67, %68, %69, %70, %71, %72, %73, %74, %75, %76, %77, %78, %79, %80, %81, %82, %83, %84, %85, %86, %87, %88, %89, %90, %91, %92, %93, %94, %95}, %96, %97, p, 1, 1, 0, %99;\n}\n"
        : "+f"(d[0]), "+f"(d[1]), "+f"(d[2]), "+f"(d[3]), "+f"(d[4]), "+f"(d[5]), "+f"(d[6]), "+f"(d[7]), "+f"(d[8]), "+f"(d[9]), "+f"(d[10]), "+f"(d[11]), "+f"(d[12]), "+f"(d[13]), "+f"(d[14]), "+f"(d[15]), "+f"(d[16]), "+f"(d[17]), "+f"(d[18]), "+f"(d[19]), "+f"(d[20]), "+f"(d[21]), "+f"(d[22]), "+f"(d[23]), "+f"(d[24]), "+f"(d[25]), "+f"(d[26]), "+f"(d[27]), "+f"(d[28]), "+f"(d[29]), "+f"(d[30]), "+f"(d[31]), "+f"(d[32]), "+f"(d[33]), "+f"(d[34]), "+f"(d[35]), "+f"(d[36]), "+f"(d[37]), "+f"(d[38]), "+f"(d[39]), "+f"(d[40]), "+f"(d[41]), "+f"(d[42]), "+f"(d[43]), "+f"(d[44]), "+f"(d[45]), "+f"(d[46]), "+f"(d[47]), "+f"(d[48]), "+f"(d[49]), "+f"(d[50]), "+f"(d[51]), "+f"(d[52]), "+f"(d[53]), "+f"(d[54]), "+f"(d[55]), "+f"(d[56]), "+f"(d[57]), "+f"(d[58]), "+f"(d[59]), "+f"(d[60]), "+f"(d[61]), "+f"(d[62]), "+f"(d[63]), "+f"(d[64]), "+f"(d[65]), "+f"(d[66]), "+f"(d[67]), "+f"(d[68]), "+f"(d[69]), "+f"(d[70]), "+f"(d[71]), "+f"(d[72]), "+f"(d[73]), "+f"(d[74]), "+f"(d[75]), "+f"(d[76]), "+f"(d[77]), "+f"(d[78]), "+f"(d[79]), "+f"(d[80]), "+f"(d[81]), "+f"(d[82]), "+f"(d[83]), "+f"(d[84]), "+f"(d[85]), "+f"(d[86]), "+f"(d[87]), "+f"(d[88]), "+f"(d[89]), "+f"(d[90]), "+f"(d[91]), "+f"(d[92]), "+f"(d[93]), "+f"(d[94]), "+f"(d[95])
        : "l"(da), "l"(db), "r"(scale_d), "n"(TB));
}

__device__ __forceinline__ uint32_t pack_bf16(float lo, float hi) {
    uint32_t r;
    asm("cvt.rn.bf16x2.f32 %0, %1, %2;" : "=r"(r) : "f"(hi), "f"(lo));
    return r;
}
__device__ __forceinline__ float bf_lo(uint32_t v) { return __uint_as_float(v << 16); }
__device__ __forceinline__ float bf_hi(uint32_t v) { return __uint_as_float(v & 0xffff0000u); }

__device__ __forceinline__ void quad_transpose(uint32_t (&w)[4], int q) {
    const bool o1 = q & 1, o2 = q & 2;
    {
        uint32_t s0 = o1 ? w[0] : w[1], s1 = o1 ? w[2] : w[3];
        s0 = __shfl_xor_sync(0xffffffffu, s0, 1); s1 = __shfl_xor_sync(0xffffffffu, s1, 1);
        if (o1) { w[0] = s0; w[2] = s1; } else { w[1] = s0; w[3] = s1; }
    }
    {
        uint32_t s0 = o2 ? w[0] : w[2], s1 = o2 ? w[1] : w[3];
        s0 = __shfl_xor_sync(0xffffffffu, s0, 2); s1 = __shfl_xor_sync(0xffffffffu, s1, 2);
        if (o2) { w[0] = s0; w[1] = s1; } else { w[2] = s0; w[3] = s1; }
    }
}

__device__ __forceinline__ float ex2(float x) { float y; asm("ex2.approx.ftz.f32 %0, %1;" : "=f"(y) : "f"(x)); return y; }
__device__ __forceinline__ float rcp(float x) { float y; asm("rcp.approx.ftz.f32 %0, %1;" : "=f"(y) : "f"(x)); return y; }

__device__ __forceinline__ float ex2v(float x) { float y; asm volatile("ex2.approx.ftz.f32 %0, %1;" : "=f"(y) : "f"(x)); return y; }
__device__ __forceinline__ float rcpv(float x) { float y; asm volatile("rcp.approx.ftz.f32 %0, %1;" : "=f"(y) : "f"(x)); return y; }
__device__ __forceinline__ float mish_f(float h) {
    const float e = ex2v(1.4426950408889634f * fminf(h, 20.f));
    const float n = fmaf(e, e, e + e);
    return h * n * rcpv(n + 2.f);
}

__device__ __forceinline__ void pdl_wait()   { asm volatile("griddepcontrol.wait;" ::: "memory"); }
__device__ __forceinline__ void pdl_launch() { asm volatile("griddepcontrol.launch_dependents;" ::: "memory"); }

constexpr int K1_STAGES = 4;
constexpr int K1_XBYTES = 128 * 512 * 2;
constexpr int K1_BSTAGE = 3 * 8192;
constexpr int K1_SMEM   = K1_XBYTES + K1_STAGES * K1_BSTAGE + 2048   + 1024  ;

__global__ void __launch_bounds__(384, 1)
k1_kernel(const __grid_constant__ CUtensorMap tmX, const __grid_constant__ CUtensorMap tmWqkv,
          const __grid_constant__ CUtensorMap tmW1, const bf16* __restrict__ b1,
          const bf16* __restrict__ gate_w, const bf16* __restrict__ w1p, const bf16* __restrict__ wqkvp,
          const bf16* __restrict__ w2p, const bf16* __restrict__ wop)
{

    extern __shared__ uint8_t smem_raw[];
    const uint32_t sbase = (smem_u32(smem_raw) + 1023u) & ~1023u;
    uint8_t* sgen = smem_raw + (sbase - smem_u32(smem_raw));
    const uint32_t sX = sbase;
    const uint32_t sB = sbase + K1_XBYTES;
    const uint32_t sBar = sB + K1_STAGES * K1_BSTAGE;
    const uint32_t x_full = sBar;
    const uint32_t b_full = sBar + 64;
    const uint32_t b_empty = sBar + 96;
    float* sGate = (float*)(sgen + K1_XBYTES + K1_STAGES * K1_BSTAGE + 128);
    uint8_t* sGw = sgen + K1_XBYTES + K1_STAGES * K1_BSTAGE + 640;
    uint32_t* sBias = (uint32_t*)(sgen + K1_XBYTES + K1_STAGES * K1_BSTAGE + 1664);

    const int rb = blockIdx.x >> 3, j = blockIdx.x & 7;
    const int tid = threadIdx.x, wg = tid >> 7, warp = tid >> 5, lane = tid & 31;
    TS(0, tid == 0);
    pdl_launch();

    if (tid == 0) {
        for (int i = 0; i < 8; i++) mbar_init(x_full + 8 * i, 1);
        for (int i = 0; i < K1_STAGES; i++) { mbar_init(b_full + 8 * i, 1); mbar_init(b_empty + 8 * i, 8); }
        fence_barrier_init();
    }
    __syncthreads();

    if (wg == 2) {
        reg_dealloc<40>();
        if (tid == 288) {
            const int b = blockIdx.x;
            mbar_wait(b_full + 8, 0);
            l2_prefetch((const uint8_t*)wqkvp + b * 12288, 12288);
            l2_prefetch((const uint8_t*)w2p + b * 11008, 11008);
            l2_prefetch((const uint8_t*)wop + b * 4096, 4096);
        }
        if (tid == 256) {
            for (int it = 0; it < 16; it++) {
                if (it < 8) {
                    mbar_expect_tx(x_full + 8 * it, 16384);
                    tma_load_2d(sX + it * 16384, &tmX, it * 64, rb * 128, x_full + 8 * it);
                }
                const int st = it & 3;
                if (it >= K1_STAGES) mbar_wait(b_empty + 8 * st, ((it >> 2) - 1) & 1);
                mbar_expect_tx(b_full + 8 * st, K1_BSTAGE);
                const uint32_t dst = sB + st * K1_BSTAGE;
                if (it < 8) {
                    for (int b = 0; b < 3; b++) tma_load_2d(dst + b * 8192, &tmW1, j * FCH + b * 64, it * 64, b_full + 8 * st);
                } else {
                    for (int b = 0; b < 3; b++) tma_load_2d(dst + b * 8192, &tmWqkv, b * 512 + j * 64, (it - 8) * 64, b_full + 8 * st);
                }
            }
        }
    } else {
        reg_alloc<232>();
        if (tid < 64) ((uint4*)sGw)[tid] = __ldg((const uint4*)gate_w + tid);
        else if (tid < 64 + 88) {
            const int c = j * FCH + (tid - 64) * 2;
            sBias[tid - 64] = c < F_ ? __ldg((const uint32_t*)(b1 + c)) : 0u;
        }
        bar_sync(3, 256);
        const int t128 = tid & 127, w4 = warp & 3, q = lane & 3;
        float accF[88], accQ[96];
        float gs = 0.f;
        const int grow = wg * 64 + (t128 >> 1), ghalf = t128 & 1;
#pragma unroll
        for (int kc = 0; kc < 8; kc++) {
            const int st = kc & 3;
            mbar_wait(x_full + 8 * kc, 0);
            mbar_wait(b_full + 8 * st, (kc >> 2) & 1);
            TS(1, tid == 0 && kc == 0); TS(2, tid == 0 && kc == 4);
            wgmma_fence();
#pragma unroll
            for (int k16 = 0; k16 < 4; k16++) {
                const uint64_t db = make_desc(sB + st * K1_BSTAGE + k16 * 2048, 8192, 1024);
                const uint64_t da = make_desc(sX + kc * 16384 + wg * 8192 + k16 * 32, 16, 1024);
                wgmma_n176<1>(accF, da, db, (kc | k16) != 0);
            }
            wgmma_commit();
#pragma unroll
            for (int c = 0; c < 4; c++) {
                const int cc = ghalf * 4 + c;
                const uint4 xv = *(const uint4*)(sgen + kc * 16384 + grow * 128 + ((cc ^ (grow & 7)) << 4));
                const uint4 gv = *(const uint4*)(sGw + kc * 128 + cc * 16);
                gs = fmaf(bf_lo(xv.x), bf_lo(gv.x), gs); gs = fmaf(bf_hi(xv.x), bf_hi(gv.x), gs);
                gs = fmaf(bf_lo(xv.y), bf_lo(gv.y), gs); gs = fmaf(bf_hi(xv.y), bf_hi(gv.y), gs);
                gs = fmaf(bf_lo(xv.z), bf_lo(gv.z), gs); gs = fmaf(bf_hi(xv.z), bf_hi(gv.z), gs);
                gs = fmaf(bf_lo(xv.w), bf_lo(gv.w), gs); gs = fmaf(bf_hi(xv.w), bf_hi(gv.w), gs);
            }
            if (kc > 0) { wgmma_wait<1>(); if (lane == 0) mbar_arrive(b_empty + 8 * ((kc - 1) & 3)); }
        }
        gs += __shfl_xor_sync(0xffffffffu, gs, 1);
        {
            const float g = 1.f / (1.f + __expf(-gs));
            if (ghalf == 0) {
                sGate[grow] = g;
                if (j == 0) g_gate[rb * 128 + grow] = g;
            }
        }
        wgmma_wait<0>();
        if (lane == 0) mbar_arrive(b_empty + 8 * 3);
        bar_sync(1 + wg, 128);
        TS(3, tid == 0);
        const int n0 = j * FCH;
        const int rl = wg * 64 + w4 * 16 + (lane >> 2);
        const float om0 = 1.f - sGate[rl], om1 = 1.f - sGate[rl + 8];
        bf16* frow0 = g_a2 + (size_t)(rb * 128 + rl) * KA2 + D_ + n0;
        bf16* frow1 = frow0 + 8 * KA2;
        auto ffn_chunk = [&](int u) {
            uint32_t w0[4], w1[4];
#pragma unroll
            for (int i = 0; i < 4; i++) {
                const int t = u * 4 + i;
                if (t < 22) {
                    const uint32_t bv = sBias[t * 4 + q];
                    const float bb0 = bf_lo(bv), bb1 = bf_hi(bv);
                    w0[i] = pack_bf16(mish_f(accF[t * 4 + 0] + bb0) * om0, mish_f(accF[t * 4 + 1] + bb1) * om0);
                    w1[i] = pack_bf16(mish_f(accF[t * 4 + 2] + bb0) * om1, mish_f(accF[t * 4 + 3] + bb1) * om1);
                } else { w0[i] = 0; w1[i] = 0; }
            }
            quad_transpose(w0, q);
            quad_transpose(w1, q);
            const int c = (u * 4 + q) * 8;
            if (c < FCH && n0 + c < F_) {
                *(uint4*)(frow0 + c) = make_uint4(w0[0], w0[1], w0[2], w0[3]);
                *(uint4*)(frow1 + c) = make_uint4(w1[0], w1[1], w1[2], w1[3]);
            }
        };
#pragma unroll
        for (int kc = 0; kc < 8; kc++) {
            const int st = kc & 3;
            mbar_wait(b_full + 8 * st, ((kc + 8) >> 2) & 1);
            wgmma_fence();
#pragma unroll
            for (int k16 = 0; k16 < 4; k16++) {
                const uint64_t db = make_desc(sB + st * K1_BSTAGE + k16 * 2048, 8192, 1024);
                const uint64_t da = make_desc(sX + kc * 16384 + wg * 8192 + k16 * 32, 16, 1024);
                wgmma_n192<1>(accQ, da, db, (kc | k16) != 0);
            }
            wgmma_commit();
            if (kc < 6) ffn_chunk(kc);
            if (kc > 0) { wgmma_wait<1>(); if (lane == 0) mbar_arrive(b_empty + 8 * ((kc - 1) & 3)); }
        }
        wgmma_wait<0>();
        TS(4, tid == 0);
        {
            bf16* orow0 = g_qkv + ((size_t)j * S_ + rb * 128 + rl) * 192;
            bf16* orow1 = orow0 + 8 * 192;
#pragma unroll
            for (int u = 0; u < 6; u++) {
                uint32_t w0[4], w1[4];
#pragma unroll
                for (int i = 0; i < 4; i++) {
                    const int t = u * 4 + i;
                    w0[i] = pack_bf16(accQ[t * 4 + 0], accQ[t * 4 + 1]);
                    w1[i] = pack_bf16(accQ[t * 4 + 2], accQ[t * 4 + 3]);
                }
                quad_transpose(w0, q);
                quad_transpose(w1, q);
                const int c = (u * 4 + q) * 8;
                *(uint4*)(orow0 + c) = make_uint4(w0[0], w0[1], w0[2], w0[3]);
                *(uint4*)(orow1 + c) = make_uint4(w1[0], w1[1], w1[2], w1[3]);
            }
        }
        TS(5, tid == 0);
    }
}

__device__ __forceinline__ void ldsm_x4(uint32_t (&r)[4], uint32_t addr) {
    asm("ldmatrix.sync.aligned.m8n8.x4.shared.b16 {%0,%1,%2,%3}, [%4];"
                 : "=r"(r[0]), "=r"(r[1]), "=r"(r[2]), "=r"(r[3]) : "r"(addr));
}
__device__ __forceinline__ void ldsm_x4_t(uint32_t (&r)[4], uint32_t addr) {
    asm("ldmatrix.sync.aligned.m8n8.x4.trans.shared.b16 {%0,%1,%2,%3}, [%4];"
                 : "=r"(r[0]), "=r"(r[1]), "=r"(r[2]), "=r"(r[3]) : "r"(addr));
}
__device__ __forceinline__ void mma16816(float (&d)[4], const uint32_t (&a)[4], uint32_t b0, uint32_t b1) {
    asm("mma.sync.aligned.m16n8k16.row.col.f32.bf16.bf16.f32 {%0,%1,%2,%3}, {%4,%5,%6,%7}, {%8,%9}, {%0,%1,%2,%3};"
                 : "+f"(d[0]), "+f"(d[1]), "+f"(d[2]), "+f"(d[3])
                 : "r"(a[0]), "r"(a[1]), "r"(a[2]), "r"(a[3]), "r"(b0), "r"(b1));
}
__device__ __forceinline__ void mma16816_z(float (&d)[4], const uint32_t (&a)[4], uint32_t b0, uint32_t b1) {
    asm("mma.sync.aligned.m16n8k16.row.col.f32.bf16.bf16.f32 {%0,%1,%2,%3}, {%4,%5,%6,%7}, {%8,%9}, {%10,%10,%10,%10};"
                 : "=f"(d[0]), "=f"(d[1]), "=f"(d[2]), "=f"(d[3])
                 : "r"(a[0]), "r"(a[1]), "r"(a[2]), "r"(a[3]), "r"(b0), "r"(b1), "f"(0.f));
}

constexpr int KV_PITCH = 128;

template <int EDGE, bool HEAD>
__device__ __forceinline__ void blk_scores(float (&s)[2][4], const uint32_t (&qa)[4], uint32_t kaddr, bool dead, int r0, int c0)
{
    uint32_t kf[4];
    ldsm_x4(kf, kaddr);
    mma16816_z(s[0], qa, kf[0], kf[1]);
    mma16816_z(s[1], qa, kf[2], kf[3]);
#pragma unroll
    for (int t = 0; t < 2; t++)
#pragma unroll
        for (int e = 0; e < 4; e++) {
            const int r = r0 + (e >> 1) * 8, c = t * 8 + c0 + (e & 1);
            if (EDGE == 1 && c <= r) s[t][e] = -1e30f;
            if (EDGE == 2 && c > r) s[t][e] = -1e30f;
            if (HEAD && dead) s[t][e] = -1e30f;
        }
}
__device__ __forceinline__ void blk_max(const float (&s)[2][4], float& n0, float& n1) {
    n0 = fmaxf(n0, fmaxf(fmaxf(s[0][0], s[0][1]), fmaxf(s[1][0], s[1][1])));
    n1 = fmaxf(n1, fmaxf(fmaxf(s[0][2], s[0][3]), fmaxf(s[1][2], s[1][3])));
}
__device__ __forceinline__ void blk_pv(const float (&s)[2][4], float mc0, float mc1, float (&l)[4],
                                       float (&o)[2][4], uint32_t vaddr) {
    const float C = 0.25f * 1.4426950408889634f;
    uint32_t pa[4];
#pragma unroll
    for (int t = 0; t < 2; t++) {
        const float p0 = ex2(fmaf(s[t][0], C, -mc0)), p1 = ex2(fmaf(s[t][1], C, -mc0));
        const float p2 = ex2(fmaf(s[t][2], C, -mc1)), p3 = ex2(fmaf(s[t][3], C, -mc1));
        pa[2 * t] = pack_bf16(p0, p1); pa[2 * t + 1] = pack_bf16(p2, p3);
    }
    uint32_t vf[4];
    ldsm_x4_t(vf, vaddr);
    mma16816(o[0], pa, vf[0], vf[1]);
    mma16816(o[1], pa, vf[2], vf[3]);
    mma16816(l, pa, 0x3F803F80u, 0x3F803F80u);
}
__device__ __forceinline__ void quad_max(float& n0, float& n1) {
    n0 = fmaxf(n0, __shfl_xor_sync(0xffffffffu, n0, 1)); n1 = fmaxf(n1, __shfl_xor_sync(0xffffffffu, n1, 1));
    n0 = fmaxf(n0, __shfl_xor_sync(0xffffffffu, n0, 2)); n1 = fmaxf(n1, __shfl_xor_sync(0xffffffffu, n1, 2));
}
template <int NC, int NN, bool FIRST, bool NEXT_IS_EDGE, bool HEAD>
__device__ __forceinline__ void pipe_step(const float (&sc)[5][2][4], float (&sn)[5][2][4], const uint32_t (&qa)[4],
                                          uint32_t ka, uint32_t va, int kc, int kn, int kb0, int r0, int c0,
                                          float& m0, float& m1, float& n0, float& n1, float (&l)[4], float (&o)[2][4])
{
    const float C = 0.25f * 1.4426950408889634f;
    const float mc0 = n0 * C, mc1 = n1 * C;
    if (!FIRST) {
        const float a0 = ex2(fmaf(m0, C, -mc0)), a1 = ex2(fmaf(m1, C, -mc1));
        l[0] *= a0; l[2] *= a1;
        o[0][0] *= a0; o[0][1] *= a0; o[1][0] *= a0; o[1][1] *= a0;
        o[0][2] *= a1; o[0][3] *= a1; o[1][2] *= a1; o[1][3] *= a1;
    }
    m0 = n0; m1 = n1;
#pragma unroll
    for (int b = 0; b < NC; b++) {
        if (b < NN) {
            if (NEXT_IS_EDGE && b == 0) blk_scores<1, HEAD>(sn[b], qa, ka + (kn + b) * 16 * KV_PITCH, kn + b < kb0, r0, c0);
            else                        blk_scores<0, HEAD>(sn[b], qa, ka + (kn + b) * 16 * KV_PITCH, kn + b < kb0, r0, c0);
        }
        blk_pv(sc[b], mc0, mc1, l, o, va + (kc + b) * 16 * KV_PITCH);
        if (b < NN) blk_max(sn[b], n0, n1);
    }
    if (NN > 0) quad_max(n0, n1);
}

__device__ __forceinline__ void kv_need(uint32_t kvbar, int blk, uint32_t& ka, uint32_t& va) {
    mbar_wait(kvbar + 8 * blk, 0);
    asm volatile("" : "+r"(ka), "+r"(va) :: "memory");
}
template <bool HEAD>
__device__ __forceinline__ void attn_task(const uint32_t (&qa)[4], uint32_t ka, uint32_t va, int kb0, int lane, int qt, uint32_t kvbar,
                                          bf16* __restrict__ out  , float g0, float g1)
{
    const int r0 = lane >> 2, c0 = (lane & 3) * 2;
    float m0 = -1e30f, m1 = -1e30f, n0 = -1e30f, n1 = -1e30f;
    float l[4] = {0.f, 0.f, 0.f, 0.f};
    float o[2][4] = {{0.f, 0.f, 0.f, 0.f}, {0.f, 0.f, 0.f, 0.f}};
    float sa[5][2][4], sb[5][2][4];
    kv_need(kvbar, 2, ka, va);
    if (qt < 4) kv_need(kvbar, 1, ka, va);
#pragma unroll
    for (int b = 0; b < 5; b++) {
        if (b == 4) blk_scores<2, HEAD>(sa[b], qa, ka + (12 + b) * 16 * KV_PITCH, false, r0, c0);
        else        blk_scores<0, HEAD>(sa[b], qa, ka + (12 + b) * 16 * KV_PITCH, 12 + b < kb0, r0, c0);
        blk_max(sa[b], n0, n1);
    }
    quad_max(n0, n1);
    kv_need(kvbar, 1, ka, va);
    if (HEAD) {
        pipe_step<5, 0, true, false, HEAD>(sa, sb, qa, ka, va, 12, 0, kb0, r0, c0, m0, m1, n0, n1, l, o);
        kv_need(kvbar, 0, ka, va);
#pragma unroll 1
        for (int kc = 8; kc >= 0 && kb0 < kc + 4; kc -= 4) {
#pragma unroll
            for (int b = 0; b < 4; b++) {
                blk_scores<0, HEAD>(sa[b], qa, ka + (kc + b) * 16 * KV_PITCH, kc + b < kb0, r0, c0);
                blk_max(sa[b], n0, n1);
            }
            quad_max(n0, n1);
            pipe_step<4, 0, false, false, HEAD>(sa, sb, qa, ka, va, kc, 0, kb0, r0, c0, m0, m1, n0, n1, l, o);
        }
    } else {
        pipe_step<5, 4, true,  false, HEAD>(sa, sb, qa, ka, va, 12, 8, kb0, r0, c0, m0, m1, n0, n1, l, o);
        if (qt < 4) kv_need(kvbar, 0, ka, va);
        pipe_step<4, 4, false, false, HEAD>(sb, sa, qa, ka, va, 8, 4, kb0, r0, c0, m0, m1, n0, n1, l, o);
        kv_need(kvbar, 0, ka, va);
        pipe_step<4, 4, false, true,  HEAD>(sa, sb, qa, ka, va, 4, 0, kb0, r0, c0, m0, m1, n0, n1, l, o);
        pipe_step<4, 0, false, false, HEAD>(sb, sa, qa, ka, va, 0, 0, kb0, r0, c0, m0, m1, n0, n1, l, o);
    }
    const float f0 = __fdividef(g0, l[0]), f1 = __fdividef(g1, l[2]);
#pragma unroll
    for (int t = 0; t < 2; t++) {
        *(uint32_t*)(out + (size_t)r0 * KA2 + t * 8 + c0) = pack_bf16(o[t][0] * f0, o[t][1] * f0);
        *(uint32_t*)(out + (size_t)(r0 + 8) * KA2 + t * 8 + c0) = pack_bf16(o[t][2] * f1, o[t][3] * f1);
    }
}

__device__ unsigned int g_epoch;
__device__ unsigned int g_done;
__device__ unsigned int g_flag_att[128];

constexpr int G_STAGES = 9;
constexpr int G_PRE = 5;
constexpr int G_STAGE = 16384 + 8192;
constexpr int G_KSTEPS = 30;
constexpr int K23_OFF_KV = G_PRE * G_STAGE;
constexpr int K23_OFF_BAR = K23_OFF_KV + 2 * 384 * KV_PITCH;
constexpr int K23_SMEM = K23_OFF_BAR + 256 + 1024;

__global__ void __launch_bounds__(512, 1)
k23_kernel(const __grid_constant__ CUtensorMap tmQKV, const __grid_constant__ CUtensorMap tmA2,
           const __grid_constant__ CUtensorMap tmWo, const __grid_constant__ CUtensorMap tmW2, bf16* __restrict__ out)
{
    extern __shared__ uint8_t smem_raw[];
    const uint32_t sbase = (smem_u32(smem_raw) + 1023u) & ~1023u;
    uint8_t* sgen = smem_raw + (sbase - smem_u32(smem_raw));
    const uint32_t sK = sbase + K23_OFF_KV, sV = sK + 384 * KV_PITCH;
    const uint32_t sBar = sbase + K23_OFF_BAR;
    const uint32_t full = sBar, empty = sBar + 80, kv_full = sBar + 160;
    const int rb = blockIdx.x >> 3, j = blockIdx.x & 7;
    const int tid = threadIdx.x, wg = tid >> 7, warp = tid >> 5, lane = tid & 31;

    auto gload = [&](int ks) {
        const int st = ks % G_STAGES;
        mbar_expect_tx(full + 8 * st, G_STAGE);
        const uint32_t dst = sbase + st * G_STAGE;
        if (ks < 22) {
            tma_load_2d(dst, &tmA2, D_ + ks * 64, rb * 128, full + 8 * st);
            tma_load_2d(dst + 16384, &tmW2, j * 64, ks * 64, full + 8 * st);
        } else {
            tma_load_2d(dst, &tmA2, (ks - 22) * 64, rb * 128, full + 8 * st);
            tma_load_2d(dst + 16384, &tmWo, j * 64, (ks - 22) * 64, full + 8 * st);
        }
    };

    if (tid == 0) {
        for (int i = 0; i < 3; i++) mbar_init(kv_full + 8 * i, 1);
        for (int i = 0; i < G_STAGES; i++) { mbar_init(full + 8 * i, 1); mbar_init(empty + 8 * i, 8); }
        fence_barrier_init();
    }
    pdl_wait();
    TS(6, tid == 0);
    const unsigned int ep = *(volatile unsigned int*)&g_epoch + 1;
    if (tid == 0) {
        for (int i = 0; i < 3; i++) {
            const uint32_t bar = kv_full + 8 * (2 - i);
            if (rb - i >= 0) {
                const int row = j * S_ + (rb - i) * 128;
                mbar_expect_tx(bar, 2 * 16384);
                tma_load_2d(sK + (2 - i) * 16384, &tmQKV, 64, row, bar);
                tma_load_2d(sV + (2 - i) * 16384, &tmQKV, 128, row, bar);
            } else {
                mbar_arrive(bar);
            }
        }
        for (int ks = 0; ks < G_PRE; ks++) gload(ks);
    }
    if (rb < 2) {
        for (int i = tid; i < (2 - rb) * 1024; i += 512) {
            *(uint4*)(sgen + K23_OFF_KV + i * 16) = make_uint4(0, 0, 0, 0);
            *(uint4*)(sgen + K23_OFF_KV + 384 * KV_PITCH + i * 16) = make_uint4(0, 0, 0, 0);
        }
    }
    {
        const int qt = warp & 7, h0 = (warp >> 3) * 2;
        const int q0g = rb * 128 + qt * 16;
        const int r0 = lane >> 2, c0 = (lane & 3) * 2;
        const bf16* qsrc = g_qkv + ((size_t)j * S_ + q0g) * 192 + h0 * 16;
        uint32_t qa[4], qn[4];
        qa[0] = *(const uint32_t*)(qsrc + (size_t)r0 * 192 + c0);
        qa[1] = *(const uint32_t*)(qsrc + (size_t)(r0 + 8) * 192 + c0);
        qa[2] = *(const uint32_t*)(qsrc + (size_t)r0 * 192 + c0 + 8);
        qa[3] = *(const uint32_t*)(qsrc + (size_t)(r0 + 8) * 192 + c0 + 8);
        qn[0] = *(const uint32_t*)(qsrc + (size_t)r0 * 192 + 16 + c0);
        qn[1] = *(const uint32_t*)(qsrc + (size_t)(r0 + 8) * 192 + 16 + c0);
        qn[2] = *(const uint32_t*)(qsrc + (size_t)r0 * 192 + 16 + c0 + 8);
        qn[3] = *(const uint32_t*)(qsrc + (size_t)(r0 + 8) * 192 + 16 + c0 + 8);
        const float g0 = g_gate[q0g + r0], g1 = g_gate[q0g + r0 + 8];
        const int kb0 = q0g < 256 ? (256 - q0g) >> 4 : 0;
        __syncthreads();
        TS(7, tid == 0);
        const int krow = qt * 16 + (lane & 7) + ((lane >> 4) << 3);
        const int vrow = qt * 16 + (lane & 15);
#pragma unroll 1
        for (int hh = 0; hh < 2; hh++) {
            const int hl = h0 + hh;
            const uint32_t ka = sK + krow * KV_PITCH + (((2 * hl + ((lane >> 3) & 1)) ^ (lane & 7)) << 4);
            const uint32_t va = sV + vrow * KV_PITCH + (((2 * hl + (lane >> 4)) ^ (lane & 7)) << 4);
            if (rb < 2) attn_task<true>(qa, ka, va, kb0, lane, qt, kv_full, g_a2 + (size_t)q0g * KA2 + (j * 4 + hl) * 16, g0, g1);
            else        attn_task<false>(qa, ka, va, kb0, lane, qt, kv_full, g_a2 + (size_t)q0g * KA2 + (j * 4 + hl) * 16, g0, g1);
            TS(8 + hh, tid == 0);
            qa[0] = qn[0]; qa[1] = qn[1]; qa[2] = qn[2]; qa[3] = qn[3];
        }
    }
    __syncthreads();
    if (wg >= 2) {
        if (tid == 288) {
            __threadfence();
            asm volatile("st.release.gpu.global.u32 [%0], %1;" :: "l"(&g_flag_att[blockIdx.x]), "r"(ep) : "memory");
        }
        if (tid == 256) {
            asm volatile("fence.proxy.async;" ::: "memory");
            for (int ks = G_PRE; ks < G_KSTEPS; ks++) {
                if (ks >= G_STAGES) mbar_wait(empty + 8 * (ks % G_STAGES), ((ks / G_STAGES) - 1) & 1);
                if (ks == 22) {
                    for (int i = 0; i < 8; i++) {
                        for (uint32_t it = 0; it < (1u << 22); ++it) {
                            unsigned int x;
                            asm volatile("ld.acquire.gpu.global.u32 %0, [%1];" : "=r"(x) : "l"(&g_flag_att[rb * 8 + i]) : "memory");
                            if (x == ep) break;
                        }
                    }
                    asm volatile("fence.proxy.async;" ::: "memory");
                }
                gload(ks);
            }
        }
    } else {
        TS(10, tid == 0);
        float acc[32];
        const uint32_t abase = __shfl_sync(0xffffffffu, sbase + wg * 8192, 0);
        const uint32_t bbase = __shfl_sync(0xffffffffu, sbase + 16384, 0);
        for (int ks = 0; ks < G_KSTEPS; ks++) {
            const int st = ks % G_STAGES;
            mbar_wait(full + 8 * st, (ks / G_STAGES) & 1);
            TS(11, tid == 0 && ks == 0); TS(12, tid == 0 && ks == 8); TS(13, tid == 0 && ks == 22);
            wgmma_fence();
#pragma unroll
            for (int k16 = 0; k16 < 4; k16++) {
                const uint64_t da = make_desc(abase + st * G_STAGE + k16 * 32, 16, 1024);
                const uint64_t db = make_desc(bbase + st * G_STAGE + k16 * 2048, 8192, 1024);
                wgmma_n64<1>(acc, da, db, (ks | k16) != 0);
            }
            wgmma_commit();
            if (ks > 0) { wgmma_wait<1>(); if (lane == 0) mbar_arrive(empty + 8 * ((ks - 1) % G_STAGES)); }
        }
        wgmma_wait<0>();
        TS(14, tid == 0);
        const int q = lane & 3;
        const int r = rb * 128 + wg * 64 + (warp & 3) * 16 + (lane >> 2);
        bf16* orow0 = out + (size_t)r * D_ + j * 64;
        bf16* orow1 = orow0 + 8 * D_;
#pragma unroll
        for (int u = 0; u < 2; u++) {
            uint32_t w0[4], w1[4];
#pragma unroll
            for (int i = 0; i < 4; i++) {
                const int t = u * 4 + i;
                w0[i] = pack_bf16(acc[t * 4 + 0], acc[t * 4 + 1]);
                w1[i] = pack_bf16(acc[t * 4 + 2], acc[t * 4 + 3]);
            }
            quad_transpose(w0, q);
            quad_transpose(w1, q);
            const int c = (u * 4 + q) * 8;
            *(uint4*)(orow0 + c) = make_uint4(w0[0], w0[1], w0[2], w0[3]);
            *(uint4*)(orow1 + c) = make_uint4(w1[0], w1[1], w1[2], w1[3]);
        }
        TS(15, tid == 0);
        if (tid == 0) {
            __threadfence();
            if (atomicAdd(&g_done, 1u) == gridDim.x - 1) {
                g_done = 0;
                __threadfence();
                atomicAdd(&g_epoch, 1u);
            }
        }
    }
}

typedef CUresult (*PFN_encodeTiled)(CUtensorMap*, CUtensorMapDataType, cuuint32_t, void*, const cuuint64_t*,
                                    const cuuint64_t*, const cuuint32_t*, const cuuint32_t*, CUtensorMapInterleave,
                                    CUtensorMapSwizzle, CUtensorMapL2promotion, CUtensorMapFloatOOBfill);

static void make_map(PFN_encodeTiled enc, CUtensorMap* m, const void* ptr, uint64_t cols, uint64_t rows,
                     uint32_t box_cols, uint32_t box_rows)
{
    cuuint64_t dims[2] = {cols, rows};
    cuuint64_t strides[1] = {cols * 2};
    cuuint32_t box[2] = {box_cols, box_rows};
    cuuint32_t es[2] = {1, 1};
    enc(m, CU_TENSOR_MAP_DATA_TYPE_BFLOAT16, 2, const_cast<void*>(ptr), dims, strides, box, es,
        CU_TENSOR_MAP_INTERLEAVE_NONE, CU_TENSOR_MAP_SWIZZLE_128B, CU_TENSOR_MAP_L2_PROMOTION_L2_128B,
        CU_TENSOR_MAP_FLOAT_OOB_FILL_NONE);
}

extern "C" void kernel_launch(void* const* d_in, const int* in_sizes, int n_in, void* d_out, int out_size)
{
    const bf16* x    = (const bf16*)d_in[0];
    const bf16* wqkv = (const bf16*)d_in[1];
    const bf16* wo   = (const bf16*)d_in[2];
    const bf16* w1   = (const bf16*)d_in[4];
    const bf16* b1   = (const bf16*)d_in[5];
    const bf16* w2   = (const bf16*)d_in[6];
    const bf16* gw   = (const bf16*)d_in[7];

    static PFN_encodeTiled enc = nullptr;
    if (!enc) {
        void* fn = nullptr;
        cudaDriverEntryPointQueryResult qr;
        cudaGetDriverEntryPoint("cuTensorMapEncodeTiled", &fn, cudaEnableDefault, &qr);
        enc = (PFN_encodeTiled)fn;
        cudaFuncSetAttribute(k1_kernel, cudaFuncAttributeMaxDynamicSharedMemorySize, K1_SMEM);
        cudaFuncSetAttribute(k23_kernel, cudaFuncAttributeMaxDynamicSharedMemorySize, K23_SMEM);
    }
    void* a2p = nullptr;
    cudaGetSymbolAddress(&a2p, g_a2);
    void* qkvp = nullptr;
    cudaGetSymbolAddress(&qkvp, g_qkv);
    CUtensorMap tmX, tmWqkv, tmW1, tmA2, tmWo, tmW2, tmQKV;
    make_map(enc, &tmQKV, qkvp, 192, 8 * S_, 64, 128);
    make_map(enc, &tmX, x, D_, S_, 64, 128);
    make_map(enc, &tmWqkv, wqkv, 3 * D_, D_, 64, 64);
    make_map(enc, &tmW1, w1, F_, D_, 64, 64);
    make_map(enc, &tmA2, a2p, KA2, S_, 64, 128);
    make_map(enc, &tmWo, wo, D_, D_, 64, 64);
    make_map(enc, &tmW2, w2, D_, F_, 64, 64);

    cudaStream_t st = cudaStreamPerThread;
    k1_kernel<<<128, 384, K1_SMEM, st>>>(tmX, tmWqkv, tmW1, b1, gw, w1, wqkv, w2, wo);
    cudaLaunchAttribute at[1];
    at[0].id = cudaLaunchAttributeProgrammaticStreamSerialization;
    at[0].val.programmaticStreamSerializationAllowed = 1;
    cudaLaunchConfig_t cfg = {};
    cfg.gridDim = dim3(128); cfg.stream = st; cfg.attrs = at; cfg.numAttrs = 1;
    cfg.blockDim = dim3(512); cfg.dynamicSmemBytes = K23_SMEM;
    k23_kernel<<<128, 512, K23_SMEM, st>>>(tmQKV, tmA2, tmWo, tmW2, (bf16*)d_out);
}
```

```cpp
#include <cuda_runtime.h>
#include <cuda_bf16.h>
#include <cuda.h>
#include <stdint.h>

typedef __nv_bfloat16 bf16;

constexpr int S_ = 2048, D_ = 512, F_ = 1376;
constexpr int KA2 = D_ + F_;
constexpr int FCH = 176;

__device__ bf16  g_qkv[8 * S_ * 192];
__device__ bf16  g_a2[S_ * KA2];
__device__ float g_gate[S_];

#define TS(k, cond) do { } while (0)

__device__ __forceinline__ uint32_t smem_u32(const void* p) { return (uint32_t)__cvta_generic_to_shared(p); }
__device__ __forceinline__ void mbar_init(uint32_t bar, uint32_t count) {
    asm volatile("mbarrier.init.shared::cta.b64 [%0], %1;" :: "r"(bar), "r"(count) : "memory");
}
__device__ __forceinline__ void mbar_expect_tx(uint32_t bar, uint32_t bytes) {
    asm volatile("mbarrier.arrive.expect_tx.shared::cta.b64 _, [%0], %1;" :: "r"(bar), "r"(bytes) : "memory");
}
__device__ __forceinline__ void mbar_arrive(uint32_t bar) {
    asm volatile("mbarrier.arrive.shared::cta.b64 _, [%0];" :: "r"(bar) : "memory");
}
__device__ __forceinline__ bool mbar_try_wait(uint32_t bar, uint32_t parity) {
    uint32_t ok;
    asm volatile("{\n.reg .pred p;\nmbarrier.try_wait.parity.shared::cta.b64 p, [%1], %2;\nselp.u32 %0, 1, 0, p;\n}"
                 : "=r"(ok) : "r"(bar), "r"(parity) : "memory");
    return ok != 0;
}
__device__ __forceinline__ void mbar_wait(uint32_t bar, uint32_t parity) {
    for (uint32_t it = 0; it < (1u << 22); ++it) { if (mbar_try_wait(bar, parity)) break; }
}
__device__ __forceinline__ void tma_load_2d(uint32_t dst, const CUtensorMap* map, int c0, int c1, uint32_t bar) {
    asm volatile("cp.async.bulk.tensor.2d.shared::cluster.global.mbarrier::complete_tx::bytes [%0], [%1, {%3, %4}], [%2];"
                 :: "r"(dst), "l"(map), "r"(bar), "r"(c0), "r"(c1) : "memory");
}
__device__ __forceinline__ void l2_prefetch(const void* p, uint32_t bytes) {
    asm volatile("cp.async.bulk.prefetch.L2.global [%0], %1;" :: "l"(p), "r"(bytes) : "memory");
}
__device__ __forceinline__ void fence_barrier_init() { asm volatile("fence.mbarrier_init.release.cluster;" ::: "memory"); }
__device__ __forceinline__ void wgmma_fence()  { asm volatile("wgmma.fence.sync.aligned;" ::: "memory"); }
__device__ __forceinline__ void wgmma_commit() { asm volatile("wgmma.commit_group.sync.aligned;" ::: "memory"); }
template <int N> __device__ __forceinline__ void wgmma_wait() { asm volatile("wgmma.wait_group.sync.aligned %0;" :: "n"(N) : "memory"); }
template <int R> __device__ __forceinline__ void reg_alloc()   { asm volatile("setmaxnreg.inc.sync.aligned.u32 %0;" :: "n"(R)); }
template <int R> __device__ __forceinline__ void reg_dealloc() { asm volatile("setmaxnreg.dec.sync.aligned.u32 %0;" :: "n"(R)); }
__device__ __forceinline__ void bar_sync(int id, int n)   { asm volatile("bar.sync %0, %1;" :: "r"(id), "r"(n) : "memory"); }
__device__ __forceinline__ void bar_arrive(int id, int n) { asm volatile("bar.arrive %0, %1;" :: "r"(id), "r"(n) : "memory"); }

__device__ __forceinline__ uint64_t make_desc(uint32_t addr, uint32_t lbo, uint32_t sbo) {
    uint64_t d = (uint64_t)((addr & 0x3FFFF) >> 4);
    d |= (uint64_t)((lbo & 0x3FFFF) >> 4) << 16;
    d |= (uint64_t)((sbo & 0x3FFFF) >> 4) << 32;
    d |= (uint64_t)1 << 62;
    return d;
}

template <int V> struct IC { static constexpr int value = V; };

template <int TB>
__device__ __forceinline__ void wgmma_n64(float (&d)[32], uint64_t da, uint64_t db, int scale_d) {
    asm volatile("{\n.reg .pred p;\nsetp.ne.b32 p, %34, 0;\n"
        "wgmma.mma_async.sync.aligned.m64n64k16.f32.bf16.bf16 {%0, %1, %2, %3, %4, %5, %6, %7, %8, %9, %10, %11, %12, %13, %14, %15, %16, %17, %18, %19, %20, %21, %22, %23, %24, %25, %26, %27, %28, %29, %30, %31}, %32, %33, p, 1, 1, 0, %35;\n}\n"
        : "+f"(d[0]), "+f"(d[1]), "+f"(d[2]), "+f"(d[3]), "+f"(d[4]), "+f"(d[5]), "+f"(d[6]), "+f"(d[7]), "+f"(d[8]), "+f"(d[9]), "+f"(d[10]), "+f"(d[11]), "+f"(d[12]), "+f"(d[13]), "+f"(d[14]), "+f"(d[15]), "+f"(d[16]), "+f"(d[17]), "+f"(d[18]), "+f"(d[19]), "+f"(d[20]), "+f"(d[21]), "+f"(d[22]), "+f"(d[23]), "+f"(d[24]), "+f"(d[25]), "+f"(d[26]), "+f"(d[27]), "+f"(d[28]), "+f"(d[29]), "+f"(d[30]), "+f"(d[31])
        : "l"(da), "l"(db), "r"(scale_d), "n"(TB));
}

template <int TB>
__device__ __forceinline__ void wgmma_n128(float (&d)[64], uint64_t da, uint64_t db, int scale_d) {
    asm volatile("{\n.reg .pred p;\nsetp.ne.b32 p, %66, 0;\n"
        "wgmma.mma_async.sync.aligned.m64n128k16.f32.bf16.bf16 {%0, %1, %2, %3, %4, %5, %6, %7, %8, %9, %10, %11, %12, %13, %14, %15, %16, %17, %18, %19, %20, %21, %22, %23, %24, %25, %26, %27, %28, %29, %30, %31, %32, %33, %34, %35, %36, %37, %38, %39, %40, %41, %42, %43, %44, %45, %46, %47, %48, %49, %50, %51, %52, %53, %54, %55, %56, %57, %58, %59, %60, %61, %62, %63}, %64, %65, p, 1, 1, 0, %67;\n}\n"
        : "+f"(d[0]), "+f"(d[1]), "+f"(d[2]), "+f"(d[3]), "+f"(d[4]), "+f"(d[5]), "+f"(d[6]), "+f"(d[7]), "+f"(d[8]), "+f"(d[9]), "+f"(d[10]), "+f"(d[11]), "+f"(d[12]), "+f"(d[13]), "+f"(d[14]), "+f"(d[15]), "+f"(d[16]), "+f"(d[17]), "+f"(d[18]), "+f"(d[19]), "+f"(d[20]), "+f"(d[21]), "+f"(d[22]), "+f"(d[23]), "+f"(d[24]), "+f"(d[25]), "+f"(d[26]), "+f"(d[27]), "+f"(d[28]), "+f"(d[29]), "+f"(d[30]), "+f"(d[31]), "+f"(d[32]), "+f"(d[33]), "+f"(d[34]), "+f"(d[35]), "+f"(d[36]), "+f"(d[37]), "+f"(d[38]), "+f"(d[39]), "+f"(d[40]), "+f"(d[41]), "+f"(d[42]), "+f"(d[43]), "+f"(d[44]), "+f"(d[45]), "+f"(d[46]), "+f"(d[47]), "+f"(d[48]), "+f"(d[49]), "+f"(d[50]), "+f"(d[51]), "+f"(d[52]), "+f"(d[53]), "+f"(d[54]), "+f"(d[55]), "+f"(d[56]), "+f"(d[57]), "+f"(d[58]), "+f"(d[59]), "+f"(d[60]), "+f"(d[61]), "+f"(d[62]), "+f"(d[63])
        : "l"(da), "l"(db), "r"(scale_d), "n"(TB));
}

template <int TB>
__device__ __forceinline__ void wgmma_n176(float (&d)[88], uint64_t da, uint64_t db, int scale_d) {
    asm volatile("{\n.reg .pred p;\nsetp.ne.b32 p, %90, 0;\n"
        "wgmma.mma_async.sync.aligned.m64n176k16.f32.bf16.bf16 {%0, %1, %2, %3, %4, %5, %6, %7, %8, %9, %10, %11, %12, %13, %14, %15, %16, %17, %18, %19, %20, %21, %22, %23, %24, %25, %26, %27, %28, %29, %30, %31, %32, %33, %34, %35, %36, %37, %38, %39, %40, %41, %42, %43, %44, %45, %46, %47, %48, %49, %50, %51, %52, %53, %54, %55, %56, %57, %58, %59, %60, %61, %62, %63, %64, %65, %66, %67, %68, %69, %70, %71, %72, %73, %74, %75, %76, %77, %78, %79, %80, %81, %82, %83, %84, %85, %86, %87}, %88, %89, p, 1, 1, 0, %91;\n}\n"
        : "+f"(d[0]), "+f"(d[1]), "+f"(d[2]), "+f"(d[3]), "+f"(d[4]), "+f"(d[5]), "+f"(d[6]), "+f"(d[7]), "+f"(d[8]), "+f"(d[9]), "+f"(d[10]), "+f"(d[11]), "+f"(d[12]), "+f"(d[13]), "+f"(d[14]), "+f"(d[15]), "+f"(d[16]), "+f"(d[17]), "+f"(d[18]), "+f"(d[19]), "+f"(d[20]), "+f"(d[21]), "+f"(d[22]), "+f"(d[23]), "+f"(d[24]), "+f"(d[25]), "+f"(d[26]), "+f"(d[27]), "+f"(d[28]), "+f"(d[29]), "+f"(d[30]), "+f"(d[31]), "+f"(d[32]), "+f"(d[33]), "+f"(d[34]), "+f"(d[35]), "+f"(d[36]), "+f"(d[37]), "+f"(d[38]), "+f"(d[39]), "+f"(d[40]), "+f"(d[41]), "+f"(d[42]), "+f"(d[43]), "+f"(d[44]), "+f"(d[45]), "+f"(d[46]), "+f"(d[47]), "+f"(d[48]), "+f"(d[49]), "+f"(d[50]), "+f"(d[51]), "+f"(d[52]), "+f"(d[53]), "+f"(d[54]), "+f"(d[55]), "+f"(d[56]), "+f"(d[57]), "+f"(d[58]), "+f"(d[59]), "+f"(d[60]), "+f"(d[61]), "+f"(d[62]), "+f"(d[63]), "+f"(d[64]), "+f"(d[65]), "+f"(d[66]), "+f"(d[67]), "+f"(d[68]), "+f"(d[69]), "+f"(d[70]), "+f"(d[71]), "+f"(d[72]), "+f"(d[73]), "+f"(d[74]), "+f"(d[75]), "+f"(d[76]), "+f"(d[77]), "+f"(d[78]), "+f"(d[79]), "+f"(d[80]), "+f"(d[81]), "+f"(d[82]), "+f"(d[83]), "+f"(d[84]), "+f"(d[85]), "+f"(d[86]), "+f"(d[87])
        : "l"(da), "l"(db), "r"(scale_d), "n"(TB));
}

template <int TB>
__device__ __forceinline__ void wgmma_n192(float (&d)[96], uint64_t da, uint64_t db, int scale_d) {
    asm volatile("{\n.reg .pred p;\nsetp.ne.b32 p, %98, 0;\n"
        "wgmma.mma_async.sync.aligned.m64n192k16.f32.bf16.bf16 {%0, %1, %2, %3, %4, %5, %6, %7, %8, %9, %10, %11, %12, %13, %14, %15, %16, %17, %18, %19, %20, %21, %22, %23, %24, %25, %26, %27, %28, %29, %30, %31, %32, %33, %34, %35, %36, %37, %38, %39, %40, %41, %42, %43, %44, %45, %46, %47, %48, %49, %50, %51, %52, %53, %54, %55, %56, %57, %58, %59, %60, %61, %62, %63, %64, %65, %66, %67, %68, %69, %70, %71, %72, %73, %74, %75, %76, %77, %78, %79, %80, %81, %82, %83, %84, %85, %86, %87, %88, %89, %90, %91, %92, %93, %94, %95}, %96, %97, p, 1, 1, 0, %99;\n}\n"
        : "+f"(d[0]), "+f"(d[1]), "+f"(d[2]), "+f"(d[3]), "+f"(d[4]), "+f"(d[5]), "+f"(d[6]), "+f"(d[7]), "+f"(d[8]), "+f"(d[9]), "+f"(d[10]), "+f"(d[11]), "+f"(d[12]), "+f"(d[13]), "+f"(d[14]), "+f"(d[15]), "+f"(d[16]), "+f"(d[17]), "+f"(d[18]), "+f"(d[19]), "+f"(d[20]), "+f"(d[21]), "+f"(d[22]), "+f"(d[23]), "+f"(d[24]), "+f"(d[25]), "+f"(d[26]), "+f"(d[27]), "+f"(d[28]), "+f"(d[29]), "+f"(d[30]), "+f"(d[31]), "+f"(d[32]), "+f"(d[33]), "+f"(d[34]), "+f"(d[35]), "+f"(d[36]), "+f"(d[37]), "+f"(d[38]), "+f"(d[39]), "+f"(d[40]), "+f"(d[41]), "+f"(d[42]), "+f"(d[43]), "+f"(d[44]), "+f"(d[45]), "+f"(d[46]), "+f"(d[47]), "+f"(d[48]), "+f"(d[49]), "+f"(d[50]), "+f"(d[51]), "+f"(d[52]), "+f"(d[53]), "+f"(d[54]), "+f"(d[55]), "+f"(d[56]), "+f"(d[57]), "+f"(d[58]), "+f"(d[59]), "+f"(d[60]), "+f"(d[61]), "+f"(d[62]), "+f"(d[63]), "+f"(d[64]), "+f"(d[65]), "+f"(d[66]), "+f"(d[67]), "+f"(d[68]), "+f"(d[69]), "+f"(d[70]), "+f"(d[71]), "+f"(d[72]), "+f"(d[73]), "+f"(d[74]), "+f"(d[75]), "+f"(d[76]), "+f"(d[77]), "+f"(d[78]), "+f"(d[79]), "+f"(d[80]), "+f"(d[81]), "+f"(d[82]), "+f"(d[83]), "+f"(d[84]), "+f"(d[85]), "+f"(d[86]), "+f"(d[87]), "+f"(d[88]), "+f"(d[89]), "+f"(d[90]), "+f"(d[91]), "+f"(d[92]), "+f"(d[93]), "+f"(d[94]), "+f"(d[95])
        : "l"(da), "l"(db), "r"(scale_d), "n"(TB));
}

__device__ __forceinline__ uint32_t pack_bf16(float lo, float hi) {
    uint32_t r;
    asm("cvt.rn.bf16x2.f32 %0, %1, %2;" : "=r"(r) : "f"(hi), "f"(lo));
    return r;
}
__device__ __forceinline__ float bf_lo(uint32_t v) { return __uint_as_float(v << 16); }
__device__ __forceinline__ float bf_hi(uint32_t v) { return __uint_as_float(v & 0xffff0000u); }

__device__ __forceinline__ void quad_transpose(uint32_t (&w)[4], int q) {
    const bool o1 = q & 1, o2 = q & 2;
    {
        uint32_t s0 = o1 ? w[0] : w[1], s1 = o1 ? w[2] : w[3];
        s0 = __shfl_xor_sync(0xffffffffu, s0, 1); s1 = __shfl_xor_sync(0xffffffffu, s1, 1);
        if (o1) { w[0] = s0; w[2] = s1; } else { w[1] = s0; w[3] = s1; }
    }
    {
        uint32_t s0 = o2 ? w[0] : w[2], s1 = o2 ? w[1] : w[3];
        s0 = __shfl_xor_sync(0xffffffffu, s0, 2); s1 = __shfl_xor_sync(0xffffffffu, s1, 2);
        if (o2) { w[0] = s0; w[1] = s1; } else { w[2] = s0; w[3] = s1; }
    }
}

__device__ __forceinline__ float ex2(float x) { float y; asm("ex2.approx.ftz.f32 %0, %1;" : "=f"(y) : "f"(x)); return y; }
__device__ __forceinline__ float rcp(float x) { float y; asm("rcp.approx.ftz.f32 %0, %1;" : "=f"(y) : "f"(x)); return y; }

__device__ __forceinline__ float ex2v(float x) { float y; asm volatile("ex2.approx.ftz.f32 %0, %1;" : "=f"(y) : "f"(x)); return y; }
__device__ __forceinline__ float rcpv(float x) { float y; asm volatile("rcp.approx.ftz.f32 %0, %1;" : "=f"(y) : "f"(x)); return y; }
__device__ __forceinline__ float mish_f(float h) {
    const float e = ex2v(1.4426950408889634f * fminf(h, 20.f));
    const float n = fmaf(e, e, e + e);
    return h * n * rcpv(n + 2.f);
}

__device__ __forceinline__ void pdl_wait()   { asm volatile("griddepcontrol.wait;" ::: "memory"); }
__device__ __forceinline__ void pdl_launch() { asm volatile("griddepcontrol.launch_dependents;" ::: "memory"); }

constexpr int K1_STAGES = 4;
constexpr int K1_XBYTES = 128 * 512 * 2;
constexpr int K1_BSTAGE = 3 * 8192;
constexpr int K1_SMEM   = K1_XBYTES + K1_STAGES * K1_BSTAGE + 2048   + 1024  ;

__global__ void __launch_bounds__(384, 1)
k1_kernel(const __grid_constant__ CUtensorMap tmX, const __grid_constant__ CUtensorMap tmWqkv,
          const __grid_constant__ CUtensorMap tmW1, const bf16* __restrict__ b1,
          const bf16* __restrict__ gate_w, const bf16* __restrict__ w1p, const bf16* __restrict__ wqkvp,
          const bf16* __restrict__ w2p, const bf16* __restrict__ wop)
{

    extern __shared__ uint8_t smem_raw[];
    const uint32_t sbase = (smem_u32(smem_raw) + 1023u) & ~1023u;
    uint8_t* sgen = smem_raw + (sbase - smem_u32(smem_raw));
    const uint32_t sX = sbase;
    const uint32_t sB = sbase + K1_XBYTES;
    const uint32_t sBar = sB + K1_STAGES * K1_BSTAGE;
    const uint32_t x_full = sBar;
    const uint32_t b_full = sBar + 64;
    const uint32_t b_empty = sBar + 96;
    float* sGate = (float*)(sgen + K1_XBYTES + K1_STAGES * K1_BSTAGE + 128);
    uint8_t* sGw = sgen + K1_XBYTES + K1_STAGES * K1_BSTAGE + 640;
    uint32_t* sBias = (uint32_t*)(sgen + K1_XBYTES + K1_STAGES * K1_BSTAGE + 1664);

    const int rb = blockIdx.x >> 3, j = blockIdx.x & 7;
    const int tid = threadIdx.x, wg = tid >> 7, warp = tid >> 5, lane = tid & 31;
    TS(0, tid == 0);
    pdl_launch();

    if (tid == 0) {
        for (int i = 0; i < 8; i++) mbar_init(x_full + 8 * i, 1);
        for (int i = 0; i < K1_STAGES; i++) { mbar_init(b_full + 8 * i, 1); mbar_init(b_empty + 8 * i, 8); }
        fence_barrier_init();
    }
    __syncthreads();

    if (wg == 2) {
        reg_dealloc<40>();
        if (tid == 288) {
            const int b = blockIdx.x;
            mbar_wait(b_full + 8, 0);
            l2_prefetch((const uint8_t*)wqkvp + b * 12288, 12288);
            l2_prefetch((const uint8_t*)w2p + b * 11008, 11008);
            l2_prefetch((const uint8_t*)wop + b * 4096, 4096);
        }
        if (tid == 256) {
            for (int it = 0; it < 16; it++) {
                if (it < 8) {
                    mbar_expect_tx(x_full + 8 * it, 16384);
                    tma_load_2d(sX + it * 16384, &tmX, it * 64, rb * 128, x_full + 8 * it);
                }
                const int st = it & 3;
                if (it >= K1_STAGES) mbar_wait(b_empty + 8 * st, ((it >> 2) - 1) & 1);
                mbar_expect_tx(b_full + 8 * st, K1_BSTAGE);
                const uint32_t dst = sB + st * K1_BSTAGE;
                if (it < 8) {
                    for (int b = 0; b < 3; b++) tma_load_2d(dst + b * 8192, &tmW1, j * FCH + b * 64, it * 64, b_full + 8 * st);
                } else {
                    for (int b = 0; b < 3; b++) tma_load_2d(dst + b * 8192, &tmWqkv, b * 512 + j * 64, (it - 8) * 64, b_full + 8 * st);
                }
            }
        }
    } else {
        reg_alloc<232>();
        if (tid < 64) ((uint4*)sGw)[tid] = __ldg((const uint4*)gate_w + tid);
        else if (tid < 64 + 88) {
            const int c = j * FCH + (tid - 64) * 2;
            sBias[tid - 64] = c < F_ ? __ldg((const uint32_t*)(b1 + c)) : 0u;
        }
        bar_sync(3, 256);
        const int t128 = tid & 127, w4 = warp & 3, q = lane & 3;
        float accF[88], accQ[96];
        float gs = 0.f;
        const int grow = wg * 64 + (t128 >> 1), ghalf = t128 & 1;
#pragma unroll
        for (int kc = 0; kc < 8; kc++) {
            const int st = kc & 3;
            mbar_wait(x_full + 8 * kc, 0);
            mbar_wait(b_full + 8 * st, (kc >> 2) & 1);
            TS(1, tid == 0 && kc == 0); TS(2, tid == 0 && kc == 4);
            wgmma_fence();
#pragma unroll
            for (int k16 = 0; k16 < 4; k16++) {
                const uint64_t db = make_desc(sB + st * K1_BSTAGE + k16 * 2048, 8192, 1024);
                const uint64_t da = make_desc(sX + kc * 16384 + wg * 8192 + k16 * 32, 16, 1024);
                wgmma_n176<1>(accF, da, db, (kc | k16) != 0);
            }
            wgmma_commit();
#pragma unroll
            for (int c = 0; c < 4; c++) {
                const int cc = ghalf * 4 + c;
                const uint4 xv = *(const uint4*)(sgen + kc * 16384 + grow * 128 + ((cc ^ (grow & 7)) << 4));
                const uint4 gv = *(const uint4*)(sGw + kc * 128 + cc * 16);
                gs = fmaf(bf_lo(xv.x), bf_lo(gv.x), gs); gs = fmaf(bf_hi(xv.x), bf_hi(gv.x), gs);
                gs = fmaf(bf_lo(xv.y), bf_lo(gv.y), gs); gs = fmaf(bf_hi(xv.y), bf_hi(gv.y), gs);
                gs = fmaf(bf_lo(xv.z), bf_lo(gv.z), gs); gs = fmaf(bf_hi(xv.z), bf_hi(gv.z), gs);
                gs = fmaf(bf_lo(xv.w), bf_lo(gv.w), gs); gs = fmaf(bf_hi(xv.w), bf_hi(gv.w), gs);
            }
            if (kc > 0) { wgmma_wait<1>(); if (lane == 0) mbar_arrive(b_empty + 8 * ((kc - 1) & 3)); }
        }
        gs += __shfl_xor_sync(0xffffffffu, gs, 1);
        {
            const float g = 1.f / (1.f + __expf(-gs));
            if (ghalf == 0) {
                sGate[grow] = g;
                if (j == 0) g_gate[rb * 128 + grow] = g;
            }
        }
        wgmma_wait<0>();
        if (lane == 0) mbar_arrive(b_empty + 8 * 3);
        bar_sync(1 + wg, 128);
        TS(3, tid == 0);
        const int n0 = j * FCH;
        const int rl = wg * 64 + w4 * 16 + (lane >> 2);
        const float om0 = 1.f - sGate[rl], om1 = 1.f - sGate[rl + 8];
        bf16* frow0 = g_a2 + (size_t)(rb * 128 + rl) * KA2 + D_ + n0;
        bf16* frow1 = frow0 + 8 * KA2;
        auto ffn_chunk = [&](int u) {
            uint32_t w0[4], w1[4];
#pragma unroll
            for (int i = 0; i < 4; i++) {
                const int t = u * 4 + i;
                if (t < 22) {
                    const uint32_t bv = sBias[t * 4 + q];
                    const float bb0 = bf_lo(bv), bb1 = bf_hi(bv);
                    w0[i] = pack_bf16(mish_f(accF[t * 4 + 0] + bb0) * om0, mish_f(accF[t * 4 + 1] + bb1) * om0);
                    w1[i] = pack_bf16(mish_f(accF[t * 4 + 2] + bb0) * om1, mish_f(accF[t * 4 + 3] + bb1) * om1);
                } else { w0[i] = 0; w1[i] = 0; }
            }
            quad_transpose(w0, q);
            quad_transpose(w1, q);
            const int c = (u * 4 + q) * 8;
            if (c < FCH && n0 + c < F_) {
                *(uint4*)(frow0 + c) = make_uint4(w0[0], w0[1], w0[2], w0[3]);
                *(uint4*)(frow1 + c) = make_uint4(w1[0], w1[1], w1[2], w1[3]);
            }
        };
#pragma unroll
        for (int kc = 0; kc < 8; kc++) {
            const int st = kc & 3;
            mbar_wait(b_full + 8 * st, ((kc + 8) >> 2) & 1);
            wgmma_fence();
#pragma unroll
            for (int k16 = 0; k16 < 4; k16++) {
                const uint64_t db = make_desc(sB + st * K1_BSTAGE + k16 * 2048, 8192, 1024);
                const uint64_t da = make_desc(sX + kc * 16384 + wg * 8192 + k16 * 32, 16, 1024);
                wgmma_n192<1>(accQ, da, db, (kc | k16) != 0);
            }
            wgmma_commit();
            if (kc < 6) ffn_chunk(kc);
            if (kc > 0) { wgmma_wait<1>(); if (lane == 0) mbar_arrive(b_empty + 8 * ((kc - 1) & 3)); }
        }
        wgmma_wait<0>();
        TS(4, tid == 0);
        {
            bf16* orow0 = g_qkv + ((size_t)j * S_ + rb * 128 + rl) * 192;
            bf16* orow1 = orow0 + 8 * 192;
#pragma unroll
            for (int u = 0; u < 6; u++) {
                uint32_t w0[4], w1[4];
#pragma unroll
                for (int i = 0; i < 4; i++) {
                    const int t = u * 4 + i;
                    w0[i] = pack_bf16(accQ[t * 4 + 0], accQ[t * 4 + 1]);
                    w1[i] = pack_bf16(accQ[t * 4 + 2], accQ[t * 4 + 3]);
                }
                quad_transpose(w0, q);
                quad_transpose(w1, q);
                const int c = (u * 4 + q) * 8;
                *(uint4*)(orow0 + c) = make_uint4(w0[0], w0[1], w0[2], w0[3]);
                *(uint4*)(orow1 + c) = make_uint4(w1[0], w1[1], w1[2], w1[3]);
            }
        }
        TS(5, tid == 0);
    }
}

__device__ __forceinline__ void ldsm_x4(uint32_t (&r)[4], uint32_t addr) {
    asm("ldmatrix.sync.aligned.m8n8.x4.shared.b16 {%0,%1,%2,%3}, [%4];"
                 : "=r"(r[0]), "=r"(r[1]), "=r"(r[2]), "=r"(r[3]) : "r"(addr));
}
__device__ __forceinline__ void ldsm_x4_t(uint32_t (&r)[4], uint32_t addr) {
    asm("ldmatrix.sync.aligned.m8n8.x4.trans.shared.b16 {%0,%1,%2,%3}, [%4];"
                 : "=r"(r[0]), "=r"(r[1]), "=r"(r[2]), "=r"(r[3]) : "r"(addr));
}
__device__ __forceinline__ void mma16816(float (&d)[4], const uint32_t (&a)[4], uint32_t b0, uint32_t b1) {
    asm("mma.sync.aligned.m16n8k16.row.col.f32.bf16.bf16.f32 {%0,%1,%2,%3}, {%4,%5,%6,%7}, {%8,%9}, {%0,%1,%2,%3};"
                 : "+f"(d[0]), "+f"(d[1]), "+f"(d[2]), "+f"(d[3])
                 : "r"(a[0]), "r"(a[1]), "r"(a[2]), "r"(a[3]), "r"(b0), "r"(b1));
}
__device__ __forceinline__ void mma16816_z(float (&d)[4], const uint32_t (&a)[4], uint32_t b0, uint32_t b1) {
    asm("mma.sync.aligned.m16n8k16.row.col.f32.bf16.bf16.f32 {%0,%1,%2,%3}, {%4,%5,%6,%7}, {%8,%9}, {%10,%10,%10,%10};"
                 : "=f"(d[0]), "=f"(d[1]), "=f"(d[2]), "=f"(d[3])
                 : "r"(a[0]), "r"(a[1]), "r"(a[2]), "r"(a[3]), "r"(b0), "r"(b1), "f"(0.f));
}

constexpr int KV_PITCH = 128;

template <int EDGE, bool HEAD>
__device__ __forceinline__ void blk_scores(float (&s)[2][4], const uint32_t (&qa)[4], uint32_t kaddr, bool dead, int r0, int c0)
{
    uint32_t kf[4];
    ldsm_x4(kf, kaddr);
    mma16816_z(s[0], qa, kf[0], kf[1]);
    mma16816_z(s[1], qa, kf[2], kf[3]);
#pragma unroll
    for (int t = 0; t < 2; t++)
#pragma unroll
        for (int e = 0; e < 4; e++) {
            const int r = r0 + (e >> 1) * 8, c = t * 8 + c0 + (e & 1);
            if (EDGE == 1 && c <= r) s[t][e] = -1e30f;
            if (EDGE == 2 && c > r) s[t][e] = -1e30f;
            if (HEAD && dead) s[t][e] = -1e30f;
        }
}
__device__ __forceinline__ void blk_max(const float (&s)[2][4], float& n0, float& n1) {
    n0 = fmaxf(n0, fmaxf(fmaxf(s[0][0], s[0][1]), fmaxf(s[1][0], s[1][1])));
    n1 = fmaxf(n1, fmaxf(fmaxf(s[0][2], s[0][3]), fmaxf(s[1][2], s[1][3])));
}
__device__ __forceinline__ void blk_pv(const float (&s)[2][4], float mc0, float mc1, float (&l)[4],
                                       float (&o)[2][4], uint32_t vaddr) {
    const float C = 0.25f * 1.4426950408889634f;
    uint32_t pa[4];
#pragma unroll
    for (int t = 0; t < 2; t++) {
        const float p0 = ex2(fmaf(s[t][0], C, -mc0)), p1 = ex2(fmaf(s[t][1], C, -mc0));
        const float p2 = ex2(fmaf(s[t][2], C, -mc1)), p3 = ex2(fmaf(s[t][3], C, -mc1));
        pa[2 * t] = pack_bf16(p0, p1); pa[2 * t + 1] = pack_bf16(p2, p3);
    }
    uint32_t vf[4];
    ldsm_x4_t(vf, vaddr);
    mma16816(o[0], pa, vf[0], vf[1]);
    mma16816(o[1], pa, vf[2], vf[3]);
    mma16816(l, pa, 0x3F803F80u, 0x3F803F80u);
}
__device__ __forceinline__ void quad_max(float& n0, float& n1) {
    n0 = fmaxf(n0, __shfl_xor_sync(0xffffffffu, n0, 1)); n1 = fmaxf(n1, __shfl_xor_sync(0xffffffffu, n1, 1));
    n0 = fmaxf(n0, __shfl_xor_sync(0xffffffffu, n0, 2)); n1 = fmaxf(n1, __shfl_xor_sync(0xffffffffu, n1, 2));
}
template <int NC, int NN, bool FIRST, bool NEXT_IS_EDGE, bool HEAD>
__device__ __forceinline__ void pipe_step(const float (&sc)[5][2][4], float (&sn)[5][2][4], const uint32_t (&qa)[4],
                                          uint32_t ka, uint32_t va, int kc, int kn, int kb0, int r0, int c0,
                                          float& m0, float& m1, float& n0, float& n1, float (&l)[4], float (&o)[2][4])
{
    const float C = 0.25f * 1.4426950408889634f;
    const float mc0 = n0 * C, mc1 = n1 * C;
    if (!FIRST) {
        const float a0 = ex2(fmaf(m0, C, -mc0)), a1 = ex2(fmaf(m1, C, -mc1));
        l[0] *= a0; l[2] *= a1;
        o[0][0] *= a0; o[0][1] *= a0; o[1][0] *= a0; o[1][1] *= a0;
        o[0][2] *= a1; o[0][3] *= a1; o[1][2] *= a1; o[1][3] *= a1;
    }
    m0 = n0; m1 = n1;
#pragma unroll
    for (int b = 0; b < NC; b++) {
        if (b < NN) {
            if (NEXT_IS_EDGE && b == 0) blk_scores<1, HEAD>(sn[b], qa, ka + (kn + b) * 16 * KV_PITCH, kn + b < kb0, r0, c0);
            else                        blk_scores<0, HEAD>(sn[b], qa, ka + (kn + b) * 16 * KV_PITCH, kn + b < kb0, r0, c0);
        }
        blk_pv(sc[b], mc0, mc1, l, o, va + (kc + b) * 16 * KV_PITCH);
        if (b < NN) blk_max(sn[b], n0, n1);
    }
    if (NN > 0) quad_max(n0, n1);
}

__device__ __forceinline__ void kv_need(uint32_t kvbar, int blk, uint32_t& ka, uint32_t& va) {
    mbar_wait(kvbar + 8 * blk, 0);
    asm volatile("" : "+r"(ka), "+r"(va) :: "memory");
}
template <bool HEAD>
__device__ __forceinline__ void attn_task(const uint32_t (&qa)[4], uint32_t ka, uint32_t va, int kb0, int lane, int qt, uint32_t kvbar,
                                          bf16* __restrict__ out  , float g0, float g1)
{
    const int r0 = lane >> 2, c0 = (lane & 3) * 2;
    float m0 = -1e30f, m1 = -1e30f, n0 = -1e30f, n1 = -1e30f;
    float l[4] = {0.f, 0.f, 0.f, 0.f};
    float o[2][4] = {{0.f, 0.f, 0.f, 0.f}, {0.f, 0.f, 0.f, 0.f}};
    float sa[5][2][4], sb[5][2][4];
    kv_need(kvbar, 2, ka, va);
    if (qt < 4) kv_need(kvbar, 1, ka, va);
#pragma unroll
    for (int b = 0; b < 5; b++) {
        if (b == 4) blk_scores<2, HEAD>(sa[b], qa, ka + (12 + b) * 16 * KV_PITCH, false, r0, c0);
        else        blk_scores<0, HEAD>(sa[b], qa, ka + (12 + b) * 16 * KV_PITCH, 12 + b < kb0, r0, c0);
        blk_max(sa[b], n0, n1);
    }
    quad_max(n0, n1);
    kv_need(kvbar, 1, ka, va);
    if (HEAD) {
        pipe_step<5, 0, true, false, HEAD>(sa, sb, qa, ka, va, 12, 0, kb0, r0, c0, m0, m1, n0, n1, l, o);
        kv_need(kvbar, 0, ka, va);
#pragma unroll 1
        for (int kc = 8; kc >= 0 && kb0 < kc + 4; kc -= 4) {
#pragma unroll
            for (int b = 0; b < 4; b++) {
                blk_scores<0, HEAD>(sa[b], qa, ka + (kc + b) * 16 * KV_PITCH, kc + b < kb0, r0, c0);
                blk_max(sa[b], n0, n1);
            }
            quad_max(n0, n1);
            pipe_step<4, 0, false, false, HEAD>(sa, sb, qa, ka, va, kc, 0, kb0, r0, c0, m0, m1, n0, n1, l, o);
        }
    } else {
        pipe_step<5, 4, true,  false, HEAD>(sa, sb, qa, ka, va, 12, 8, kb0, r0, c0, m0, m1, n0, n1, l, o);
        if (qt < 4) kv_need(kvbar, 0, ka, va);
        pipe_step<4, 4, false, false, HEAD>(sb, sa, qa, ka, va, 8, 4, kb0, r0, c0, m0, m1, n0, n1, l, o);
        kv_need(kvbar, 0, ka, va);
        pipe_step<4, 4, false, true,  HEAD>(sa, sb, qa, ka, va, 4, 0, kb0, r0, c0, m0, m1, n0, n1, l, o);
        pipe_step<4, 0, false, false, HEAD>(sb, sa, qa, ka, va, 0, 0, kb0, r0, c0, m0, m1, n0, n1, l, o);
    }
    const float f0 = __fdividef(g0, l[0]), f1 = __fdividef(g1, l[2]);
#pragma unroll
    for (int t = 0; t < 2; t++) {
        *(uint32_t*)(out + (size_t)r0 * KA2 + t * 8 + c0) = pack_bf16(o[t][0] * f0, o[t][1] * f0);
        *(uint32_t*)(out + (size_t)(r0 + 8) * KA2 + t * 8 + c0) = pack_bf16(o[t][2] * f1, o[t][3] * f1);
    }
}

constexpr int K2_SMEM = 2 * 384 * KV_PITCH + 1024 + 64;

__global__ void __launch_bounds__(512, 1) k2_kernel(const __grid_constant__ CUtensorMap tmQKV)
{
    extern __shared__ uint8_t smem_raw[];
    const uint32_t sbase = (smem_u32(smem_raw) + 1023u) & ~1023u;
    uint8_t* sgen = smem_raw + (sbase - smem_u32(smem_raw));
    const uint32_t sK = sbase, sV = sK + 384 * KV_PITCH, kv_full = sbase + 2 * 384 * KV_PITCH;
    const int rb = blockIdx.x >> 3, j = blockIdx.x & 7;
    const int tid = threadIdx.x, warp = tid >> 5, lane = tid & 31;
    pdl_launch();
    if (tid == 0) {
        for (int i = 0; i < 3; i++) mbar_init(kv_full + 8 * i, 1);
        fence_barrier_init();
    }
    pdl_wait();
    TS(6, tid == 0);
    if (tid == 0) {
        for (int i = 0; i < 3; i++) {
            const uint32_t bar = kv_full + 8 * (2 - i);
            if (rb - i >= 0) {
                const int row = j * S_ + (rb - i) * 128;
                mbar_expect_tx(bar, 2 * 16384);
                tma_load_2d(sK + (2 - i) * 16384, &tmQKV, 64, row, bar);
                tma_load_2d(sV + (2 - i) * 16384, &tmQKV, 128, row, bar);
            } else {
                mbar_arrive(bar);
            }
        }
    }
    if (rb < 2) {
        for (int i = tid; i < (2 - rb) * 1024; i += 512) {
            *(uint4*)(sgen + i * 16) = make_uint4(0, 0, 0, 0);
            *(uint4*)(sgen + 384 * KV_PITCH + i * 16) = make_uint4(0, 0, 0, 0);
        }
    }
    const int qt = warp & 7, h0 = (warp >> 3) * 2;
    const int q0g = rb * 128 + qt * 16;
    const int r0 = lane >> 2, c0 = (lane & 3) * 2;
    const bf16* qsrc = g_qkv + ((size_t)j * S_ + q0g) * 192 + h0 * 16;
    uint32_t qa[4], qn[4];
    qa[0] = *(const uint32_t*)(qsrc + (size_t)r0 * 192 + c0);
    qa[1] = *(const uint32_t*)(qsrc + (size_t)(r0 + 8) * 192 + c0);
    qa[2] = *(const uint32_t*)(qsrc + (size_t)r0 * 192 + c0 + 8);
    qa[3] = *(const uint32_t*)(qsrc + (size_t)(r0 + 8) * 192 + c0 + 8);
    qn[0] = *(const uint32_t*)(qsrc + (size_t)r0 * 192 + 16 + c0);
    qn[1] = *(const uint32_t*)(qsrc + (size_t)(r0 + 8) * 192 + 16 + c0);
    qn[2] = *(const uint32_t*)(qsrc + (size_t)r0 * 192 + 16 + c0 + 8);
    qn[3] = *(const uint32_t*)(qsrc + (size_t)(r0 + 8) * 192 + 16 + c0 + 8);
    const float g0 = g_gate[q0g + r0], g1 = g_gate[q0g + r0 + 8];
    const int kb0 = q0g < 256 ? (256 - q0g) >> 4 : 0;
    __syncthreads();
    const uint32_t sKd = sK, sVd = sV;
    TS(7, tid == 0);
    const int krow = qt * 16 + (lane & 7) + ((lane >> 4) << 3);
    const int vrow = qt * 16 + (lane & 15);
#pragma unroll 1
    for (int hh = 0; hh < 2; hh++) {
        const int hl = h0 + hh;
        const uint32_t ka = sKd + krow * KV_PITCH + (((2 * hl + ((lane >> 3) & 1)) ^ (lane & 7)) << 4);
        const uint32_t va = sVd + vrow * KV_PITCH + (((2 * hl + (lane >> 4)) ^ (lane & 7)) << 4);
        if (rb < 2) attn_task<true>(qa, ka, va, kb0, lane, qt, kv_full, g_a2 + (size_t)q0g * KA2 + (j * 4 + hl) * 16, g0, g1);
        else        attn_task<false>(qa, ka, va, kb0, lane, qt, kv_full, g_a2 + (size_t)q0g * KA2 + (j * 4 + hl) * 16, g0, g1);
        TS(8 + hh, tid == 0);
        qa[0] = qn[0]; qa[1] = qn[1]; qa[2] = qn[2]; qa[3] = qn[3];
    }
}

constexpr int K3_STAGES = 8;
constexpr int K3_STAGE = 16384 + 8192;
constexpr int K3_SMEM = K3_STAGES * K3_STAGE + 1024 + 1024;
constexpr int K3_KSTEPS = 30;

__global__ void __launch_bounds__(384, 1)
k3_kernel(const __grid_constant__ CUtensorMap tmA2, const __grid_constant__ CUtensorMap tmWo,
          const __grid_constant__ CUtensorMap tmW2, bf16* __restrict__ out)
{
    extern __shared__ uint8_t smem_raw[];
    const uint32_t sbase = (smem_u32(smem_raw) + 1023u) & ~1023u;
    const uint32_t sBar = sbase + K3_STAGES * K3_STAGE;
    const uint32_t full = sBar, empty = sBar + 64;
    const int rb = blockIdx.x >> 3, nb = blockIdx.x & 7;
    const int tid = threadIdx.x, wg = tid >> 7, warp = tid >> 5, lane = tid & 31;
    if (tid == 0) {
        for (int i = 0; i < K3_STAGES; i++) { mbar_init(full + 8 * i, 1); mbar_init(empty + 8 * i, 8); }
        fence_barrier_init();
    }
    __syncthreads();
    pdl_wait();
    TS(10, tid == 0);
    if (wg == 2) {
        reg_dealloc<40>();
        if (tid == 256) {
            for (int ks = 0; ks < K3_KSTEPS; ks++) {
                const int st = ks % K3_STAGES;
                if (ks >= K3_STAGES) mbar_wait(empty + 8 * st, ((ks / K3_STAGES) - 1) & 1);
                mbar_expect_tx(full + 8 * st, K3_STAGE);
                const uint32_t dst = sbase + st * K3_STAGE;
                tma_load_2d(dst, &tmA2, ks * 64, rb * 128, full + 8 * st);
                if (ks < 8) tma_load_2d(dst + 16384, &tmWo, nb * 64, ks * 64, full + 8 * st);
                else        tma_load_2d(dst + 16384, &tmW2, nb * 64, (ks - 8) * 64, full + 8 * st);
            }
        }
    } else {
        reg_alloc<232>();
        float acc[32];
        auto mainloop = [&](auto WGC) {
            constexpr int WG = decltype(WGC)::value;
            const uint64_t da0 = make_desc(sbase + WG * 8192, 16, 1024);
            const uint64_t db0 = make_desc(sbase + 16384, 8192, 1024);
            for (int ks = 0; ks < K3_KSTEPS; ks++) {
                const int st = ks % K3_STAGES;
                mbar_wait(full + 8 * st, (ks / K3_STAGES) & 1);
                TS(11, tid == 0 && ks == 0); TS(12, tid == 0 && ks == 8); TS(13, tid == 0 && ks == 16);
                wgmma_fence();
                const uint32_t so = (uint32_t)(st * K3_STAGE) >> 4;
#pragma unroll
                for (int k16 = 0; k16 < 4; k16++)
                    wgmma_n64<1>(acc, da0 + so + k16 * 2, db0 + so + k16 * 128, (ks | k16) != 0);
                wgmma_commit();
                if (ks > 0) { wgmma_wait<1>(); if (lane == 0) mbar_arrive(empty + 8 * ((ks - 1) % K3_STAGES)); }
            }
        };
        if (wg == 0) mainloop(IC<0>{}); else mainloop(IC<1>{});
        wgmma_wait<0>();
        TS(14, tid == 0);
        const int q = lane & 3;
        const int r = rb * 128 + wg * 64 + (warp & 3) * 16 + (lane >> 2);
        bf16* orow0 = out + (size_t)r * D_ + nb * 64;
        bf16* orow1 = orow0 + 8 * D_;
#pragma unroll
        for (int u = 0; u < 2; u++) {
            uint32_t w0[4], w1[4];
#pragma unroll
            for (int i = 0; i < 4; i++) {
                const int t = u * 4 + i;
                w0[i] = pack_bf16(acc[t * 4 + 0], acc[t * 4 + 1]);
                w1[i] = pack_bf16(acc[t * 4 + 2], acc[t * 4 + 3]);
            }
            quad_transpose(w0, q);
            quad_transpose(w1, q);
            const int c = (u * 4 + q) * 8;
            *(uint4*)(orow0 + c) = make_uint4(w0[0], w0[1], w0[2], w0[3]);
            *(uint4*)(orow1 + c) = make_uint4(w1[0], w1[1], w1[2], w1[3]);
        }
        TS(15, tid == 0);
    }
}

typedef CUresult (*PFN_encodeTiled)(CUtensorMap*, CUtensorMapDataType, cuuint32_t, void*, const cuuint64_t*,
                                    const cuuint64_t*, const cuuint32_t*, const cuuint32_t*, CUtensorMapInterleave,
                                    CUtensorMapSwizzle, CUtensorMapL2promotion, CUtensorMapFloatOOBfill);

static void make_map(PFN_encodeTiled enc, CUtensorMap* m, const void* ptr, uint64_t cols, uint64_t rows,
                     uint32_t box_cols, uint32_t box_rows)
{
    cuuint64_t dims[2] = {cols, rows};
    cuuint64_t strides[1] = {cols * 2};
    cuuint32_t box[2] = {box_cols, box_rows};
    cuuint32_t es[2] = {1, 1};
    enc(m, CU_TENSOR_MAP_DATA_TYPE_BFLOAT16, 2, const_cast<void*>(ptr), dims, strides, box, es,
        CU_TENSOR_MAP_INTERLEAVE_NONE, CU_TENSOR_MAP_SWIZZLE_128B, CU_TENSOR_MAP_L2_PROMOTION_L2_128B,
        CU_TENSOR_MAP_FLOAT_OOB_FILL_NONE);
}

extern "C" void kernel_launch(void* const* d_in, const int* in_sizes, int n_in, void* d_out, int out_size)
{
    const bf16* x    = (const bf16*)d_in[0];
    const bf16* wqkv = (const bf16*)d_in[1];
    const bf16* wo   = (const bf16*)d_in[2];
    const bf16* w1   = (const bf16*)d_in[4];
    const bf16* b1   = (const bf16*)d_in[5];
    const bf16* w2   = (const bf16*)d_in[6];
    const bf16* gw   = (const bf16*)d_in[7];

    static PFN_encodeTiled enc = nullptr;
    if (!enc) {
        void* fn = nullptr;
        cudaDriverEntryPointQueryResult qr;
        cudaGetDriverEntryPoint("cuTensorMapEncodeTiled", &fn, cudaEnableDefault, &qr);
        enc = (PFN_encodeTiled)fn;
        cudaFuncSetAttribute(k1_kernel, cudaFuncAttributeMaxDynamicSharedMemorySize, K1_SMEM);
        cudaFuncSetAttribute(k2_kernel, cudaFuncAttributeMaxDynamicSharedMemorySize, K2_SMEM);
        cudaFuncSetAttribute(k3_kernel, cudaFuncAttributeMaxDynamicSharedMemorySize, K3_SMEM);
    }
    void* a2p = nullptr;
    cudaGetSymbolAddress(&a2p, g_a2);
    void* qkvp = nullptr;
    cudaGetSymbolAddress(&qkvp, g_qkv);
    CUtensorMap tmX, tmWqkv, tmW1, tmA2, tmWo, tmW2, tmQKV;
    make_map(enc, &tmQKV, qkvp, 192, 8 * S_, 64, 128);
    make_map(enc, &tmX, x, D_, S_, 64, 128);
    make_map(enc, &tmWqkv, wqkv, 3 * D_, D_, 64, 64);
    make_map(enc, &tmW1, w1, F_, D_, 64, 64);
    make_map(enc, &tmA2, a2p, KA2, S_, 64, 128);
    make_map(enc, &tmWo, wo, D_, D_, 64, 64);
    make_map(enc, &tmW2, w2, D_, F_, 64, 64);

    cudaStream_t st = cudaStreamPerThread;
    k1_kernel<<<128, 384, K1_SMEM, st>>>(tmX, tmWqkv, tmW1, b1, gw, w1, wqkv, w2, wo);
    cudaLaunchAttribute at[1];
    at[0].id = cudaLaunchAttributeProgrammaticStreamSerialization;
    at[0].val.programmaticStreamSerializationAllowed = 1;
    cudaLaunchConfig_t cfg = {};
    cfg.gridDim = dim3(128); cfg.stream = st; cfg.attrs = at; cfg.numAttrs = 1;
    cfg.blockDim = dim3(512); cfg.dynamicSmemBytes = K2_SMEM;
    cudaLaunchKernelEx(&cfg, k2_kernel, tmQKV);
    k3_kernel<<<128, 384, K3_SMEM, st>>>(tmA2, tmWo, tmW2, (bf16*)d_out);
}
```

```cpp
#include <cuda_runtime.h>
#include <cuda_bf16.h>
#include <cuda.h>
#include <stdint.h>

typedef __nv_bfloat16 bf16;

constexpr int S_ = 2048, D_ = 512, F_ = 1376;
constexpr int KA2 = D_ + F_;
constexpr int FCH = 176;

__device__ bf16  g_qkv[8 * S_ * 192];
__device__ bf16  g_a2[S_ * KA2];
__device__ float g_gate[S_];

#define TS(k, cond) do { } while (0)

__device__ __forceinline__ uint32_t smem_u32(const void* p) { return (uint32_t)__cvta_generic_to_shared(p); }
__device__ __forceinline__ void mbar_init(uint32_t bar, uint32_t count) {
    asm volatile("mbarrier.init.shared::cta.b64 [%0], %1;" :: "r"(bar), "r"(count) : "memory");
}
__device__ __forceinline__ void mbar_expect_tx(uint32_t bar, uint32_t bytes) {
    asm volatile("mbarrier.arrive.expect_tx.shared::cta.b64 _, [%0], %1;" :: "r"(bar), "r"(bytes) : "memory");
}
__device__ __forceinline__ void mbar_arrive(uint32_t bar) {
    asm volatile("mbarrier.arrive.shared::cta.b64 _, [%0];" :: "r"(bar) : "memory");
}
__device__ __forceinline__ bool mbar_try_wait(uint32_t bar, uint32_t parity) {
    uint32_t ok;
    asm volatile("{\n.reg .pred p;\nmbarrier.try_wait.parity.shared::cta.b64 p, [%1], %2;\nselp.u32 %0, 1, 0, p;\n}"
                 : "=r"(ok) : "r"(bar), "r"(parity) : "memory");
    return ok != 0;
}
__device__ __forceinline__ void mbar_wait(uint32_t bar, uint32_t parity) {
    for (uint32_t it = 0; it < (1u << 22); ++it) { if (mbar_try_wait(bar, parity)) break; }
}
__device__ __forceinline__ void tma_load_2d(uint32_t dst, const CUtensorMap* map, int c0, int c1, uint32_t bar) {
    asm volatile("cp.async.bulk.tensor.2d.shared::cluster.global.mbarrier::complete_tx::bytes [%0], [%1, {%3, %4}], [%2];"
                 :: "r"(dst), "l"(map), "r"(bar), "r"(c0), "r"(c1) : "memory");
}
__device__ __forceinline__ void l2_prefetch(const void* p, uint32_t bytes) {
    asm volatile("cp.async.bulk.prefetch.L2.global [%0], %1;" :: "l"(p), "r"(bytes) : "memory");
}
__device__ __forceinline__ void fence_barrier_init() { asm volatile("fence.mbarrier_init.release.cluster;" ::: "memory"); }
__device__ __forceinline__ void wgmma_fence()  { asm volatile("wgmma.fence.sync.aligned;" ::: "memory"); }
__device__ __forceinline__ void wgmma_commit() { asm volatile("wgmma.commit_group.sync.aligned;" ::: "memory"); }
template <int N> __device__ __forceinline__ void wgmma_wait() { asm volatile("wgmma.wait_group.sync.aligned %0;" :: "n"(N) : "memory"); }
template <int R> __device__ __forceinline__ void reg_alloc()   { asm volatile("setmaxnreg.inc.sync.aligned.u32 %0;" :: "n"(R)); }
template <int R> __device__ __forceinline__ void reg_dealloc() { asm volatile("setmaxnreg.dec.sync.aligned.u32 %0;" :: "n"(R)); }
__device__ __forceinline__ void bar_sync(int id, int n)   { asm volatile("bar.sync %0, %1;" :: "r"(id), "r"(n) : "memory"); }
__device__ __forceinline__ void bar_arrive(int id, int n) { asm volatile("bar.arrive %0, %1;" :: "r"(id), "r"(n) : "memory"); }

__device__ __forceinline__ uint64_t make_desc(uint32_t addr, uint32_t lbo, uint32_t sbo) {
    uint64_t d = (uint64_t)((addr & 0x3FFFF) >> 4);
    d |= (uint64_t)((lbo & 0x3FFFF) >> 4) << 16;
    d |= (uint64_t)((sbo & 0x3FFFF) >> 4) << 32;
    d |= (uint64_t)1 << 62;
    return d;
}

template <int TB>
__device__ __forceinline__ void wgmma_n64(float (&d)[32], uint64_t da, uint64_t db, int scale_d) {
    asm volatile("{\n.reg .pred p;\nsetp.ne.b32 p, %34, 0;\n"
        "wgmma.mma_async.sync.aligned.m64n64k16.f32.bf16.bf16 {%0, %1, %2, %3, %4, %5, %6, %7, %8, %9, %10, %11, %12, %13, %14, %15, %16, %17, %18, %19, %20, %21, %22, %23, %24, %25, %26, %27, %28, %29, %30, %31}, %32, %33, p, 1, 1, 0, %35;\n}\n"
        : "+f"(d[0]), "+f"(d[1]), "+f"(d[2]), "+f"(d[3]), "+f"(d[4]), "+f"(d[5]), "+f"(d[6]), "+f"(d[7]), "+f"(d[8]), "+f"(d[9]), "+f"(d[10]), "+f"(d[11]), "+f"(d[12]), "+f"(d[13]), "+f"(d[14]), "+f"(d[15]), "+f"(d[16]), "+f"(d[17]), "+f"(d[18]), "+f"(d[19]), "+f"(d[20]), "+f"(d[21]), "+f"(d[22]), "+f"(d[23]), "+f"(d[24]), "+f"(d[25]), "+f"(d[26]), "+f"(d[27]), "+f"(d[28]), "+f"(d[29]), "+f"(d[30]), "+f"(d[31])
        : "l"(da), "l"(db), "r"(scale_d), "n"(TB));
}

template <int TB>
__device__ __forceinline__ void wgmma_n128(float (&d)[64], uint64_t da, uint64_t db, int scale_d) {
    asm volatile("{\n.reg .pred p;\nsetp.ne.b32 p, %66, 0;\n"
        "wgmma.mma_async.sync.aligned.m64n128k16.f32.bf16.bf16 {%0, %1, %2, %3, %4, %5, %6, %7, %8, %9, %10, %11, %12, %13, %14, %15, %16, %17, %18, %19, %20, %21, %22, %23, %24, %25, %26, %27, %28, %29, %30, %31, %32, %33, %34, %35, %36, %37, %38, %39, %40, %41, %42, %43, %44, %45, %46, %47, %48, %49, %50, %51, %52, %53, %54, %55, %56, %57, %58, %59, %60, %61, %62, %63}, %64, %65, p, 1, 1, 0, %67;\n}\n"
        : "+f"(d[0]), "+f"(d[1]), "+f"(d[2]), "+f"(d[3]), "+f"(d[4]), "+f"(d[5]), "+f"(d[6]), "+f"(d[7]), "+f"(d[8]), "+f"(d[9]), "+f"(d[10]), "+f"(d[11]), "+f"(d[12]), "+f"(d[13]), "+f"(d[14]), "+f"(d[15]), "+f"(d[16]), "+f"(d[17]), "+f"(d[18]), "+f"(d[19]), "+f"(d[20]), "+f"(d[21]), "+f"(d[22]), "+f"(d[23]), "+f"(d[24]), "+f"(d[25]), "+f"(d[26]), "+f"(d[27]), "+f"(d[28]), "+f"(d[29]), "+f"(d[30]), "+f"(d[31]), "+f"(d[32]), "+f"(d[33]), "+f"(d[34]), "+f"(d[35]), "+f"(d[36]), "+f"(d[37]), "+f"(d[38]), "+f"(d[39]), "+f"(d[40]), "+f"(d[41]), "+f"(d[42]), "+f"(d[43]), "+f"(d[44]), "+f"(d[45]), "+f"(d[46]), "+f"(d[47]), "+f"(d[48]), "+f"(d[49]), "+f"(d[50]), "+f"(d[51]), "+f"(d[52]), "+f"(d[53]), "+f"(d[54]), "+f"(d[55]), "+f"(d[56]), "+f"(d[57]), "+f"(d[58]), "+f"(d[59]), "+f"(d[60]), "+f"(d[61]), "+f"(d[62]), "+f"(d[63])
        : "l"(da), "l"(db), "r"(scale_d), "n"(TB));
}

template <int TB>
__device__ __forceinline__ void wgmma_n176(float (&d)[88], uint64_t da, uint64_t db, int scale_d) {
    asm volatile("{\n.reg .pred p;\nsetp.ne.b32 p, %90, 0;\n"
        "wgmma.mma_async.sync.aligned.m64n176k16.f32.bf16.bf16 {%0, %1, %2, %3, %4, %5, %6, %7, %8, %9, %10, %11, %12, %13, %14, %15, %16, %17, %18, %19, %20, %21, %22, %23, %24, %25, %26, %27, %28, %29, %30, %31, %32, %33, %34, %35, %36, %37, %38, %39, %40, %41, %42, %43, %44, %45, %46, %47, %48, %49, %50, %51, %52, %53, %54, %55, %56, %57, %58, %59, %60, %61, %62, %63, %64, %65, %66, %67, %68, %69, %70, %71, %72, %73, %74, %75, %76, %77, %78, %79, %80, %81, %82, %83, %84, %85, %86, %87}, %88, %89, p, 1, 1, 0, %91;\n}\n"
        : "+f"(d[0]), "+f"(d[1]), "+f"(d[2]), "+f"(d[3]), "+f"(d[4]), "+f"(d[5]), "+f"(d[6]), "+f"(d[7]), "+f"(d[8]), "+f"(d[9]), "+f"(d[10]), "+f"(d[11]), "+f"(d[12]), "+f"(d[13]), "+f"(d[14]), "+f"(d[15]), "+f"(d[16]), "+f"(d[17]), "+f"(d[18]), "+f"(d[19]), "+f"(d[20]), "+f"(d[21]), "+f"(d[22]), "+f"(d[23]), "+f"(d[24]), "+f"(d[25]), "+f"(d[26]), "+f"(d[27]), "+f"(d[28]), "+f"(d[29]), "+f"(d[30]), "+f"(d[31]), "+f"(d[32]), "+f"(d[33]), "+f"(d[34]), "+f"(d[35]), "+f"(d[36]), "+f"(d[37]), "+f"(d[38]), "+f"(d[39]), "+f"(d[40]), "+f"(d[41]), "+f"(d[42]), "+f"(d[43]), "+f"(d[44]), "+f"(d[45]), "+f"(d[46]), "+f"(d[47]), "+f"(d[48]), "+f"(d[49]), "+f"(d[50]), "+f"(d[51]), "+f"(d[52]), "+f"(d[53]), "+f"(d[54]), "+f"(d[55]), "+f"(d[56]), "+f"(d[57]), "+f"(d[58]), "+f"(d[59]), "+f"(d[60]), "+f"(d[61]), "+f"(d[62]), "+f"(d[63]), "+f"(d[64]), "+f"(d[65]), "+f"(d[66]), "+f"(d[67]), "+f"(d[68]), "+f"(d[69]), "+f"(d[70]), "+f"(d[71]), "+f"(d[72]), "+f"(d[73]), "+f"(d[74]), "+f"(d[75]), "+f"(d[76]), "+f"(d[77]), "+f"(d[78]), "+f"(d[79]), "+f"(d[80]), "+f"(d[81]), "+f"(d[82]), "+f"(d[83]), "+f"(d[84]), "+f"(d[85]), "+f"(d[86]), "+f"(d[87])
        : "l"(da), "l"(db), "r"(scale_d), "n"(TB));
}

template <int TB>
__device__ __forceinline__ void wgmma_n192(float (&d)[96], uint64_t da, uint64_t db, int scale_d) {
    asm volatile("{\n.reg .pred p;\nsetp.ne.b32 p, %98, 0;\n"
        "wgmma.mma_async.sync.aligned.m64n192k16.f32.bf16.bf16 {%0, %1, %2, %3, %4, %5, %6, %7, %8, %9, %10, %11, %12, %13, %14, %15, %16, %17, %18, %19, %20, %21, %22, %23, %24, %25, %26, %27, %28, %29, %30, %31, %32, %33, %34, %35, %36, %37, %38, %39, %40, %41, %42, %43, %44, %45, %46, %47, %48, %49, %50, %51, %52, %53, %54, %55, %56, %57, %58, %59, %60, %61, %62, %63, %64, %65, %66, %67, %68, %69, %70, %71, %72, %73, %74, %75, %76, %77, %78, %79, %80, %81, %82, %83, %84, %85, %86, %87, %88, %89, %90, %91, %92, %93, %94, %95}, %96, %97, p, 1, 1, 0, %99;\n}\n"
        : "+f"(d[0]), "+f"(d[1]), "+f"(d[2]), "+f"(d[3]), "+f"(d[4]), "+f"(d[5]), "+f"(d[6]), "+f"(d[7]), "+f"(d[8]), "+f"(d[9]), "+f"(d[10]), "+f"(d[11]), "+f"(d[12]), "+f"(d[13]), "+f"(d[14]), "+f"(d[15]), "+f"(d[16]), "+f"(d[17]), "+f"(d[18]), "+f"(d[19]), "+f"(d[20]), "+f"(d[21]), "+f"(d[22]), "+f"(d[23]), "+f"(d[24]), "+f"(d[25]), "+f"(d[26]), "+f"(d[27]), "+f"(d[28]), "+f"(d[29]), "+f"(d[30]), "+f"(d[31]), "+f"(d[32]), "+f"(d[33]), "+f"(d[34]), "+f"(d[35]), "+f"(d[36]), "+f"(d[37]), "+f"(d[38]), "+f"(d[39]), "+f"(d[40]), "+f"(d[41]), "+f"(d[42]), "+f"(d[43]), "+f"(d[44]), "+f"(d[45]), "+f"(d[46]), "+f"(d[47]), "+f"(d[48]), "+f"(d[49]), "+f"(d[50]), "+f"(d[51]), "+f"(d[52]), "+f"(d[53]), "+f"(d[54]), "+f"(d[55]), "+f"(d[56]), "+f"(d[57]), "+f"(d[58]), "+f"(d[59]), "+f"(d[60]), "+f"(d[61]), "+f"(d[62]), "+f"(d[63]), "+f"(d[64]), "+f"(d[65]), "+f"(d[66]), "+f"(d[67]), "+f"(d[68]), "+f"(d[69]), "+f"(d[70]), "+f"(d[71]), "+f"(d[72]), "+f"(d[73]), "+f"(d[74]), "+f"(d[75]), "+f"(d[76]), "+f"(d[77]), "+f"(d[78]), "+f"(d[79]), "+f"(d[80]), "+f"(d[81]), "+f"(d[82]), "+f"(d[83]), "+f"(d[84]), "+f"(d[85]), "+f"(d[86]), "+f"(d[87]), "+f"(d[88]), "+f"(d[89]), "+f"(d[90]), "+f"(d[91]), "+f"(d[92]), "+f"(d[93]), "+f"(d[94]), "+f"(d[95])
        : "l"(da), "l"(db), "r"(scale_d), "n"(TB));
}

__device__ __forceinline__ uint32_t pack_bf16(float lo, float hi) {
    uint32_t r;
    asm("cvt.rn.bf16x2.f32 %0, %1, %2;" : "=r"(r) : "f"(hi), "f"(lo));
    return r;
}
__device__ __forceinline__ float bf_lo(uint32_t v) { return __uint_as_float(v << 16); }
__device__ __forceinline__ float bf_hi(uint32_t v) { return __uint_as_float(v & 0xffff0000u); }

__device__ __forceinline__ void quad_transpose(uint32_t (&w)[4], int q) {
    const bool o1 = q & 1, o2 = q & 2;
    {
        uint32_t s0 = o1 ? w[0] : w[1], s1 = o1 ? w[2] : w[3];
        s0 = __shfl_xor_sync(0xffffffffu, s0, 1); s1 = __shfl_xor_sync(0xffffffffu, s1, 1);
        if (o1) { w[0] = s0; w[2] = s1; } else { w[1] = s0; w[3] = s1; }
    }
    {
        uint32_t s0 = o2 ? w[0] : w[2], s1 = o2 ? w[1] : w[3];
        s0 = __shfl_xor_sync(0xffffffffu, s0, 2); s1 = __shfl_xor_sync(0xffffffffu, s1, 2);
        if (o2) { w[0] = s0; w[1] = s1; } else { w[2] = s0; w[3] = s1; }
    }
}

__device__ __forceinline__ float ex2(float x) { float y; asm("ex2.approx.ftz.f32 %0, %1;" : "=f"(y) : "f"(x)); return y; }
__device__ __forceinline__ float rcp(float x) { float y; asm("rcp.approx.ftz.f32 %0, %1;" : "=f"(y) : "f"(x)); return y; }

__device__ __forceinline__ float ex2v(float x) { float y; asm volatile("ex2.approx.ftz.f32 %0, %1;" : "=f"(y) : "f"(x)); return y; }
__device__ __forceinline__ float rcpv(float x) { float y; asm volatile("rcp.approx.ftz.f32 %0, %1;" : "=f"(y) : "f"(x)); return y; }
__device__ __forceinline__ float mish_f(float h) {
    const float e = ex2v(1.4426950408889634f * fminf(h, 20.f));
    const float n = fmaf(e, e, e + e);
    return h * n * rcpv(n + 2.f);
}

__device__ __forceinline__ void pdl_wait()   { asm volatile("griddepcontrol.wait;" ::: "memory"); }
__device__ __forceinline__ void pdl_launch() { asm volatile("griddepcontrol.launch_dependents;" ::: "memory"); }

constexpr int K1_STAGES = 4;
constexpr int K1_XBYTES = 128 * 512 * 2;
constexpr int K1_BSTAGE = 3 * 8192;
constexpr int K1_SMEM   = K1_XBYTES + K1_STAGES * K1_BSTAGE + 2048   + 1024  ;

__global__ void __launch_bounds__(384, 1)
k1_kernel(const __grid_constant__ CUtensorMap tmX, const __grid_constant__ CUtensorMap tmWqkv,
          const __grid_constant__ CUtensorMap tmW1, const bf16* __restrict__ b1,
          const bf16* __restrict__ gate_w, const bf16* __restrict__ w1p, const bf16* __restrict__ wqkvp,
          const bf16* __restrict__ w2p, const bf16* __restrict__ wop)
{

    extern __shared__ uint8_t smem_raw[];
    const uint32_t sbase = (smem_u32(smem_raw) + 1023u) & ~1023u;
    uint8_t* sgen = smem_raw + (sbase - smem_u32(smem_raw));
    const uint32_t sX = sbase;
    const uint32_t sB = sbase + K1_XBYTES;
    const uint32_t sBar = sB + K1_STAGES * K1_BSTAGE;
    const uint32_t x_full = sBar;
    const uint32_t b_full = sBar + 64;
    const uint32_t b_empty = sBar + 96;
    float* sGate = (float*)(sgen + K1_XBYTES + K1_STAGES * K1_BSTAGE + 128);
    uint8_t* sGw = sgen + K1_XBYTES + K1_STAGES * K1_BSTAGE + 640;
    uint32_t* sBias = (uint32_t*)(sgen + K1_XBYTES + K1_STAGES * K1_BSTAGE + 1664);

    const int rb = blockIdx.x >> 3, j = blockIdx.x & 7;
    const int tid = threadIdx.x, lane = tid & 31;
    const int warp = __shfl_sync(0xffffffffu, tid >> 5, 0), wg = warp >> 2;
    TS(0, tid == 0);
    pdl_launch();

    if (tid == 0) {
        for (int i = 0; i < 8; i++) mbar_init(x_full + 8 * i, 1);
        for (int i = 0; i < K1_STAGES; i++) { mbar_init(b_full + 8 * i, 1); mbar_init(b_empty + 8 * i, 8); }
        fence_barrier_init();
    }
    __syncthreads();

    if (wg == 2) {
        reg_dealloc<40>();
        if (tid == 288) {
            const int b = blockIdx.x;
            mbar_wait(b_full + 8, 0);
            l2_prefetch((const uint8_t*)wqkvp + b * 12288, 12288);
            l2_prefetch((const uint8_t*)w2p + b * 11008, 11008);
            l2_prefetch((const uint8_t*)wop + b * 4096, 4096);
        }
        if (tid == 256) {
            for (int it = 0; it < 16; it++) {
                if (it < 8) {
                    mbar_expect_tx(x_full + 8 * it, 16384);
                    tma_load_2d(sX + it * 16384, &tmX, it * 64, rb * 128, x_full + 8 * it);
                }
                const int st = it & 3;
                if (it >= K1_STAGES) mbar_wait(b_empty + 8 * st, ((it >> 2) - 1) & 1);
                mbar_expect_tx(b_full + 8 * st, K1_BSTAGE);
                const uint32_t dst = sB + st * K1_BSTAGE;
                if (it < 8) {
                    for (int b = 0; b < 3; b++) tma_load_2d(dst + b * 8192, &tmW1, j * FCH + b * 64, it * 64, b_full + 8 * st);
                } else {
                    for (int b = 0; b < 3; b++) tma_load_2d(dst + b * 8192, &tmWqkv, b * 512 + j * 64, (it - 8) * 64, b_full + 8 * st);
                }
            }
        }
    } else {
        reg_alloc<232>();
        if (tid < 64) ((uint4*)sGw)[tid] = __ldg((const uint4*)gate_w + tid);
        else if (tid < 64 + 88) {
            const int c = j * FCH + (tid - 64) * 2;
            sBias[tid - 64] = c < F_ ? __ldg((const uint32_t*)(b1 + c)) : 0u;
        }
        bar_sync(3, 256);
        const int t128 = tid & 127, w4 = warp & 3, q = lane & 3;
        float accF[88], accQ[96];
        float gs = 0.f;
        const int grow = wg * 64 + (t128 >> 1), ghalf = t128 & 1;
#pragma unroll
        for (int kc = 0; kc < 8; kc++) {
            const int st = kc & 3;
            mbar_wait(x_full + 8 * kc, 0);
            mbar_wait(b_full + 8 * st, (kc >> 2) & 1);
            TS(1, tid == 0 && kc == 0); TS(2, tid == 0 && kc == 4);
            wgmma_fence();
#pragma unroll
            for (int k16 = 0; k16 < 4; k16++) {
                const uint64_t db = make_desc(sB + st * K1_BSTAGE + k16 * 2048, 8192, 1024);
                const uint64_t da = make_desc(sX + kc * 16384 + wg * 8192 + k16 * 32, 16, 1024);
                wgmma_n176<1>(accF, da, db, (kc | k16) != 0);
            }
            wgmma_commit();
#pragma unroll
            for (int c = 0; c < 4; c++) {
                const int cc = ghalf * 4 + c;
                const uint4 xv = *(const uint4*)(sgen + kc * 16384 + grow * 128 + ((cc ^ (grow & 7)) << 4));
                const uint4 gv = *(const uint4*)(sGw + kc * 128 + cc * 16);
                gs = fmaf(bf_lo(xv.x), bf_lo(gv.x), gs); gs = fmaf(bf_hi(xv.x), bf_hi(gv.x), gs);
                gs = fmaf(bf_lo(xv.y), bf_lo(gv.y), gs); gs = fmaf(bf_hi(xv.y), bf_hi(gv.y), gs);
                gs = fmaf(bf_lo(xv.z), bf_lo(gv.z), gs); gs = fmaf(bf_hi(xv.z), bf_hi(gv.z), gs);
                gs = fmaf(bf_lo(xv.w), bf_lo(gv.w), gs); gs = fmaf(bf_hi(xv.w), bf_hi(gv.w), gs);
            }
            if (kc > 0) { wgmma_wait<1>(); if (lane == 0) mbar_arrive(b_empty + 8 * ((kc - 1) & 3)); }
        }
        gs += __shfl_xor_sync(0xffffffffu, gs, 1);
        {
            const float g = 1.f / (1.f + __expf(-gs));
            if (ghalf == 0) {
                sGate[grow] = g;
                if (j == 0) g_gate[rb * 128 + grow] = g;
            }
        }
        wgmma_wait<0>();
        if (lane == 0) mbar_arrive(b_empty + 8 * 3);
        bar_sync(1 + wg, 128);
        TS(3, tid == 0);
        const int n0 = j * FCH;
        const int rl = wg * 64 + w4 * 16 + (lane >> 2);
        const float om0 = 1.f - sGate[rl], om1 = 1.f - sGate[rl + 8];
        bf16* frow0 = g_a2 + (size_t)(rb * 128 + rl) * KA2 + D_ + n0;
        bf16* frow1 = frow0 + 8 * KA2;
        auto ffn_chunk = [&](int u) {
            uint32_t w0[4], w1[4];
#pragma unroll
            for (int i = 0; i < 4; i++) {
                const int t = u * 4 + i;
                if (t < 22) {
                    const uint32_t bv = sBias[t * 4 + q];
                    const float bb0 = bf_lo(bv), bb1 = bf_hi(bv);
                    w0[i] = pack_bf16(mish_f(accF[t * 4 + 0] + bb0) * om0, mish_f(accF[t * 4 + 1] + bb1) * om0);
                    w1[i] = pack_bf16(mish_f(accF[t * 4 + 2] + bb0) * om1, mish_f(accF[t * 4 + 3] + bb1) * om1);
                } else { w0[i] = 0; w1[i] = 0; }
            }
            quad_transpose(w0, q);
            quad_transpose(w1, q);
            const int c = (u * 4 + q) * 8;
            if (c < FCH && n0 + c < F_) {
                *(uint4*)(frow0 + c) = make_uint4(w0[0], w0[1], w0[2], w0[3]);
                *(uint4*)(frow1 + c) = make_uint4(w1[0], w1[1], w1[2], w1[3]);
            }
        };
#pragma unroll
        for (int kc = 0; kc < 8; kc++) {
            const int st = kc & 3;
            mbar_wait(b_full + 8 * st, ((kc + 8) >> 2) & 1);
            wgmma_fence();
#pragma unroll
            for (int k16 = 0; k16 < 4; k16++) {
                const uint64_t db = make_desc(sB + st * K1_BSTAGE + k16 * 2048, 8192, 1024);
                const uint64_t da = make_desc(sX + kc * 16384 + wg * 8192 + k16 * 32, 16, 1024);
                wgmma_n192<1>(accQ, da, db, (kc | k16) != 0);
            }
            wgmma_commit();
            if (kc < 6) ffn_chunk(kc);
            if (kc > 0) { wgmma_wait<1>(); if (lane == 0) mbar_arrive(b_empty + 8 * ((kc - 1) & 3)); }
        }
        wgmma_wait<0>();
        TS(4, tid == 0);
        {
            bf16* orow0 = g_qkv + ((size_t)j * S_ + rb * 128 + rl) * 192;
            bf16* orow1 = orow0 + 8 * 192;
#pragma unroll
            for (int u = 0; u < 6; u++) {
                uint32_t w0[4], w1[4];
#pragma unroll
                for (int i = 0; i < 4; i++) {
                    const int t = u * 4 + i;
                    w0[i] = pack_bf16(accQ[t * 4 + 0], accQ[t * 4 + 1]);
                    w1[i] = pack_bf16(accQ[t * 4 + 2], accQ[t * 4 + 3]);
                }
                quad_transpose(w0, q);
                quad_transpose(w1, q);
                const int c = (u * 4 + q) * 8;
                *(uint4*)(orow0 + c) = make_uint4(w0[0], w0[1], w0[2], w0[3]);
                *(uint4*)(orow1 + c) = make_uint4(w1[0], w1[1], w1[2], w1[3]);
            }
        }
        TS(5, tid == 0);
    }
}

__device__ __forceinline__ void ldsm_x4(uint32_t (&r)[4], uint32_t addr) {
    asm("ldmatrix.sync.aligned.m8n8.x4.shared.b16 {%0,%1,%2,%3}, [%4];"
                 : "=r"(r[0]), "=r"(r[1]), "=r"(r[2]), "=r"(r[3]) : "r"(addr));
}
__device__ __forceinline__ void ldsm_x4_t(uint32_t (&r)[4], uint32_t addr) {
    asm("ldmatrix.sync.aligned.m8n8.x4.trans.shared.b16 {%0,%1,%2,%3}, [%4];"
                 : "=r"(r[0]), "=r"(r[1]), "=r"(r[2]), "=r"(r[3]) : "r"(addr));
}
__device__ __forceinline__ void mma16816(float (&d)[4], const uint32_t (&a)[4], uint32_t b0, uint32_t b1) {
    asm("mma.sync.aligned.m16n8k16.row.col.f32.bf16.bf16.f32 {%0,%1,%2,%3}, {%4,%5,%6,%7}, {%8,%9}, {%0,%1,%2,%3};"
                 : "+f"(d[0]), "+f"(d[1]), "+f"(d[2]), "+f"(d[3])
                 : "r"(a[0]), "r"(a[1]), "r"(a[2]), "r"(a[3]), "r"(b0), "r"(b1));
}
__device__ __forceinline__ void mma16816_z(float (&d)[4], const uint32_t (&a)[4], uint32_t b0, uint32_t b1) {
    asm("mma.sync.aligned.m16n8k16.row.col.f32.bf16.bf16.f32 {%0,%1,%2,%3}, {%4,%5,%6,%7}, {%8,%9}, {%10,%10,%10,%10};"
                 : "=f"(d[0]), "=f"(d[1]), "=f"(d[2]), "=f"(d[3])
                 : "r"(a[0]), "r"(a[1]), "r"(a[2]), "r"(a[3]), "r"(b0), "r"(b1), "f"(0.f));
}

constexpr int KV_PITCH = 128;

template <int EDGE, bool HEAD>
__device__ __forceinline__ void blk_scores(float (&s)[2][4], const uint32_t (&qa)[4], uint32_t kaddr, bool dead, int r0, int c0)
{
    uint32_t kf[4];
    ldsm_x4(kf, kaddr);
    mma16816_z(s[0], qa, kf[0], kf[1]);
    mma16816_z(s[1], qa, kf[2], kf[3]);
#pragma unroll
    for (int t = 0; t < 2; t++)
#pragma unroll
        for (int e = 0; e < 4; e++) {
            const int r = r0 + (e >> 1) * 8, c = t * 8 + c0 + (e & 1);
            if (EDGE == 1 && c <= r) s[t][e] = -1e30f;
            if (EDGE == 2 && c > r) s[t][e] = -1e30f;
            if (HEAD && dead) s[t][e] = -1e30f;
        }
}
__device__ __forceinline__ void blk_max(const float (&s)[2][4], float& n0, float& n1) {
    n0 = fmaxf(n0, fmaxf(fmaxf(s[0][0], s[0][1]), fmaxf(s[1][0], s[1][1])));
    n1 = fmaxf(n1, fmaxf(fmaxf(s[0][2], s[0][3]), fmaxf(s[1][2], s[1][3])));
}
__device__ __forceinline__ void blk_pv(const float (&s)[2][4], float mc0, float mc1, float (&l)[4],
                                       float (&o)[2][4], uint32_t vaddr) {
    const float C = 0.25f * 1.4426950408889634f;
    uint32_t pa[4];
#pragma unroll
    for (int t = 0; t < 2; t++) {
        const float p0 = ex2(fmaf(s[t][0], C, -mc0)), p1 = ex2(fmaf(s[t][1], C, -mc0));
        const float p2 = ex2(fmaf(s[t][2], C, -mc1)), p3 = ex2(fmaf(s[t][3], C, -mc1));
        pa[2 * t] = pack_bf16(p0, p1); pa[2 * t + 1] = pack_bf16(p2, p3);
    }
    uint32_t vf[4];
    ldsm_x4_t(vf, vaddr);
    mma16816(o[0], pa, vf[0], vf[1]);
    mma16816(o[1], pa, vf[2], vf[3]);
    mma16816(l, pa, 0x3F803F80u, 0x3F803F80u);
}
__device__ __forceinline__ void quad_max(float& n0, float& n1) {
    n0 = fmaxf(n0, __shfl_xor_sync(0xffffffffu, n0, 1)); n1 = fmaxf(n1, __shfl_xor_sync(0xffffffffu, n1, 1));
    n0 = fmaxf(n0, __shfl_xor_sync(0xffffffffu, n0, 2)); n1 = fmaxf(n1, __shfl_xor_sync(0xffffffffu, n1, 2));
}
template <int NC, int NN, bool FIRST, bool NEXT_IS_EDGE, bool HEAD>
__device__ __forceinline__ void pipe_step(const float (&sc)[5][2][4], float (&sn)[5][2][4], const uint32_t (&qa)[4],
                                          uint32_t ka, uint32_t va, int kc, int kn, int kb0, int r0, int c0,
                                          float& m0, float& m1, float& n0, float& n1, float (&l)[4], float (&o)[2][4])
{
    const float C = 0.25f * 1.4426950408889634f;
    const float mc0 = n0 * C, mc1 = n1 * C;
    if (!FIRST) {
        const float a0 = ex2(fmaf(m0, C, -mc0)), a1 = ex2(fmaf(m1, C, -mc1));
        l[0] *= a0; l[2] *= a1;
        o[0][0] *= a0; o[0][1] *= a0; o[1][0] *= a0; o[1][1] *= a0;
        o[0][2] *= a1; o[0][3] *= a1; o[1][2] *= a1; o[1][3] *= a1;
    }
    m0 = n0; m1 = n1;
#pragma unroll
    for (int b = 0; b < NC; b++) {
        if (b < NN) {
            if (NEXT_IS_EDGE && b == 0) blk_scores<1, HEAD>(sn[b], qa, ka + (kn + b) * 16 * KV_PITCH, kn + b < kb0, r0, c0);
            else                        blk_scores<0, HEAD>(sn[b], qa, ka + (kn + b) * 16 * KV_PITCH, kn + b < kb0, r0, c0);
        }
        blk_pv(sc[b], mc0, mc1, l, o, va + (kc + b) * 16 * KV_PITCH);
        if (b < NN) blk_max(sn[b], n0, n1);
    }
    if (NN > 0) quad_max(n0, n1);
}

__device__ __forceinline__ void kv_need(uint32_t kvbar, int blk, uint32_t& ka, uint32_t& va) {
    mbar_wait(kvbar + 8 * blk, 0);
    asm volatile("" : "+r"(ka), "+r"(va) :: "memory");
}
template <bool HEAD>
__device__ __forceinline__ void attn_task(const uint32_t (&qa)[4], uint32_t ka, uint32_t va, int kb0, int lane, int qt, uint32_t kvbar,
                                          bf16* __restrict__ out  , float g0, float g1)
{
    const int r0 = lane >> 2, c0 = (lane & 3) * 2;
    float m0 = -1e30f, m1 = -1e30f, n0 = -1e30f, n1 = -1e30f;
    float l[4] = {0.f, 0.f, 0.f, 0.f};
    float o[2][4] = {{0.f, 0.f, 0.f, 0.f}, {0.f, 0.f, 0.f, 0.f}};
    float sa[5][2][4], sb[5][2][4];
    kv_need(kvbar, 2, ka, va);
    if (qt < 4) kv_need(kvbar, 1, ka, va);
#pragma unroll
    for (int b = 0; b < 5; b++) {
        if (b == 4) blk_scores<2, HEAD>(sa[b], qa, ka + (12 + b) * 16 * KV_PITCH, false, r0, c0);
        else        blk_scores<0, HEAD>(sa[b], qa, ka + (12 + b) * 16 * KV_PITCH, 12 + b < kb0, r0, c0);
        blk_max(sa[b], n0, n1);
    }
    quad_max(n0, n1);
    kv_need(kvbar, 1, ka, va);
    if (HEAD) {
        pipe_step<5, 0, true, false, HEAD>(sa, sb, qa, ka, va, 12, 0, kb0, r0, c0, m0, m1, n0, n1, l, o);
        kv_need(kvbar, 0, ka, va);
#pragma unroll 1
        for (int kc = 8; kc >= 0 && kb0 < kc + 4; kc -= 4) {
#pragma unroll
            for (int b = 0; b < 4; b++) {
                blk_scores<0, HEAD>(sa[b], qa, ka + (kc + b) * 16 * KV_PITCH, kc + b < kb0, r0, c0);
                blk_max(sa[b], n0, n1);
            }
            quad_max(n0, n1);
            pipe_step<4, 0, false, false, HEAD>(sa, sb, qa, ka, va, kc, 0, kb0, r0, c0, m0, m1, n0, n1, l, o);
        }
    } else {
        pipe_step<5, 4, true,  false, HEAD>(sa, sb, qa, ka, va, 12, 8, kb0, r0, c0, m0, m1, n0, n1, l, o);
        if (qt < 4) kv_need(kvbar, 0, ka, va);
        pipe_step<4, 4, false, false, HEAD>(sb, sa, qa, ka, va, 8, 4, kb0, r0, c0, m0, m1, n0, n1, l, o);
        kv_need(kvbar, 0, ka, va);
        pipe_step<4, 4, false, true,  HEAD>(sa, sb, qa, ka, va, 4, 0, kb0, r0, c0, m0, m1, n0, n1, l, o);
        pipe_step<4, 0, false, false, HEAD>(sb, sa, qa, ka, va, 0, 0, kb0, r0, c0, m0, m1, n0, n1, l, o);
    }
    const float f0 = __fdividef(g0, l[0]), f1 = __fdividef(g1, l[2]);
#pragma unroll
    for (int t = 0; t < 2; t++) {
        *(uint32_t*)(out + (size_t)r0 * KA2 + t * 8 + c0) = pack_bf16(o[t][0] * f0, o[t][1] * f0);
        *(uint32_t*)(out + (size_t)(r0 + 8) * KA2 + t * 8 + c0) = pack_bf16(o[t][2] * f1, o[t][3] * f1);
    }
}

constexpr int K2_SMEM = 2 * 384 * KV_PITCH + 1024 + 64;

__global__ void __launch_bounds__(512, 1) k2_kernel(const __grid_constant__ CUtensorMap tmQKV)
{
    extern __shared__ uint8_t smem_raw[];
    const uint32_t sbase = (smem_u32(smem_raw) + 1023u) & ~1023u;
    uint8_t* sgen = smem_raw + (sbase - smem_u32(smem_raw));
    const uint32_t sK = sbase, sV = sK + 384 * KV_PITCH, kv_full = sbase + 2 * 384 * KV_PITCH;
    const int rb = blockIdx.x >> 3, j = blockIdx.x & 7;
    const int tid = threadIdx.x, warp = tid >> 5, lane = tid & 31;
    pdl_launch();
    if (tid == 0) {
        for (int i = 0; i < 3; i++) mbar_init(kv_full + 8 * i, 1);
        fence_barrier_init();
    }
    pdl_wait();
    TS(6, tid == 0);
    if (tid == 0) {
        for (int i = 0; i < 3; i++) {
            const uint32_t bar = kv_full + 8 * (2 - i);
            if (rb - i >= 0) {
                const int row = j * S_ + (rb - i) * 128;
                mbar_expect_tx(bar, 2 * 16384);
                tma_load_2d(sK + (2 - i) * 16384, &tmQKV, 64, row, bar);
                tma_load_2d(sV + (2 - i) * 16384, &tmQKV, 128, row, bar);
            } else {
                mbar_arrive(bar);
            }
        }
    }
    if (rb < 2) {
        for (int i = tid; i < (2 - rb) * 1024; i += 512) {
            *(uint4*)(sgen + i * 16) = make_uint4(0, 0, 0, 0);
            *(uint4*)(sgen + 384 * KV_PITCH + i * 16) = make_uint4(0, 0, 0, 0);
        }
    }
    const int qt = warp & 7, h0 = (warp >> 3) * 2;
    const int q0g = rb * 128 + qt * 16;
    const int r0 = lane >> 2, c0 = (lane & 3) * 2;
    const bf16* qsrc = g_qkv + ((size_t)j * S_ + q0g) * 192 + h0 * 16;
    uint32_t qa[4], qn[4];
    qa[0] = *(const uint32_t*)(qsrc + (size_t)r0 * 192 + c0);
    qa[1] = *(const uint32_t*)(qsrc + (size_t)(r0 + 8) * 192 + c0);
    qa[2] = *(const uint32_t*)(qsrc + (size_t)r0 * 192 + c0 + 8);
    qa[3] = *(const uint32_t*)(qsrc + (size_t)(r0 + 8) * 192 + c0 + 8);
    qn[0] = *(const uint32_t*)(qsrc + (size_t)r0 * 192 + 16 + c0);
    qn[1] = *(const uint32_t*)(qsrc + (size_t)(r0 + 8) * 192 + 16 + c0);
    qn[2] = *(const uint32_t*)(qsrc + (size_t)r0 * 192 + 16 + c0 + 8);
    qn[3] = *(const uint32_t*)(qsrc + (size_t)(r0 + 8) * 192 + 16 + c0 + 8);
    const float g0 = g_gate[q0g + r0], g1 = g_gate[q0g + r0 + 8];
    const int kb0 = q0g < 256 ? (256 - q0g) >> 4 : 0;
    __syncthreads();
    const uint32_t sKd = sK, sVd = sV;
    TS(7, tid == 0);
    const int krow = qt * 16 + (lane & 7) + ((lane >> 4) << 3);
    const int vrow = qt * 16 + (lane & 15);
#pragma unroll 1
    for (int hh = 0; hh < 2; hh++) {
        const int hl = h0 + hh;
        const uint32_t ka = sKd + krow * KV_PITCH + (((2 * hl + ((lane >> 3) & 1)) ^ (lane & 7)) << 4);
        const uint32_t va = sVd + vrow * KV_PITCH + (((2 * hl + (lane >> 4)) ^ (lane & 7)) << 4);
        if (rb < 2) attn_task<true>(qa, ka, va, kb0, lane, qt, kv_full, g_a2 + (size_t)q0g * KA2 + (j * 4 + hl) * 16, g0, g1);
        else        attn_task<false>(qa, ka, va, kb0, lane, qt, kv_full, g_a2 + (size_t)q0g * KA2 + (j * 4 + hl) * 16, g0, g1);
        TS(8 + hh, tid == 0);
        qa[0] = qn[0]; qa[1] = qn[1]; qa[2] = qn[2]; qa[3] = qn[3];
    }
}

constexpr int K3_STAGES = 8;
constexpr int K3_STAGE = 16384 + 8192;
constexpr int K3_SMEM = K3_STAGES * K3_STAGE + 1024 + 1024;
constexpr int K3_KSTEPS = 30;

__global__ void __launch_bounds__(384, 1)
k3_kernel(const __grid_constant__ CUtensorMap tmA2, const __grid_constant__ CUtensorMap tmWo,
          const __grid_constant__ CUtensorMap tmW2, bf16* __restrict__ out)
{
    extern __shared__ uint8_t smem_raw[];
    const uint32_t sbase = (smem_u32(smem_raw) + 1023u) & ~1023u;
    const uint32_t sBar = sbase + K3_STAGES * K3_STAGE;
    const uint32_t full = sBar, empty = sBar + 64;
    const int rb = blockIdx.x >> 3, nb = blockIdx.x & 7;
    const int tid = threadIdx.x, lane = tid & 31;
    const int warp = __shfl_sync(0xffffffffu, tid >> 5, 0), wg = warp >> 2;
    if (tid == 0) {
        for (int i = 0; i < K3_STAGES; i++) { mbar_init(full + 8 * i, 1); mbar_init(empty + 8 * i, 8); }
        fence_barrier_init();
    }
    __syncthreads();
    pdl_wait();
    TS(10, tid == 0);
    if (wg == 2) {
        reg_dealloc<40>();
        if (tid == 256) {
            for (int ks = 0; ks < K3_KSTEPS; ks++) {
                const int st = ks % K3_STAGES;
                if (ks >= K3_STAGES) mbar_wait(empty + 8 * st, ((ks / K3_STAGES) - 1) & 1);
                mbar_expect_tx(full + 8 * st, K3_STAGE);
                const uint32_t dst = sbase + st * K3_STAGE;
                tma_load_2d(dst, &tmA2, ks * 64, rb * 128, full + 8 * st);
                if (ks < 8) tma_load_2d(dst + 16384, &tmWo, nb * 64, ks * 64, full + 8 * st);
                else        tma_load_2d(dst + 16384, &tmW2, nb * 64, (ks - 8) * 64, full + 8 * st);
            }
        }
    } else {
        reg_alloc<232>();
        float acc[32];
        for (int ks = 0; ks < K3_KSTEPS; ks++) {
            const int st = ks % K3_STAGES;
            mbar_wait(full + 8 * st, (ks / K3_STAGES) & 1);
            TS(11, tid == 0 && ks == 0); TS(12, tid == 0 && ks == 8); TS(13, tid == 0 && ks == 16);
            wgmma_fence();
#pragma unroll
            for (int k16 = 0; k16 < 4; k16++) {
                const uint64_t da = make_desc(sbase + st * K3_STAGE + wg * 8192 + k16 * 32, 16, 1024);
                const uint64_t db = make_desc(sbase + st * K3_STAGE + 16384 + k16 * 2048, 8192, 1024);
                wgmma_n64<1>(acc, da, db, (ks | k16) != 0);
            }
            wgmma_commit();
            if (ks > 0) { wgmma_wait<1>(); if (lane == 0) mbar_arrive(empty + 8 * ((ks - 1) % K3_STAGES)); }
        }
        wgmma_wait<0>();
        TS(14, tid == 0);
        const int q = lane & 3;
        const int r = rb * 128 + wg * 64 + (warp & 3) * 16 + (lane >> 2);
        bf16* orow0 = out + (size_t)r * D_ + nb * 64;
        bf16* orow1 = orow0 + 8 * D_;
#pragma unroll
        for (int u = 0; u < 2; u++) {
            uint32_t w0[4], w1[4];
#pragma unroll
            for (int i = 0; i < 4; i++) {
                const int t = u * 4 + i;
                w0[i] = pack_bf16(acc[t * 4 + 0], acc[t * 4 + 1]);
                w1[i] = pack_bf16(acc[t * 4 + 2], acc[t * 4 + 3]);
            }
            quad_transpose(w0, q);
            quad_transpose(w1, q);
            const int c = (u * 4 + q) * 8;
            *(uint4*)(orow0 + c) = make_uint4(w0[0], w0[1], w0[2], w0[3]);
            *(uint4*)(orow1 + c) = make_uint4(w1[0], w1[1], w1[2], w1[3]);
        }
        TS(15, tid == 0);
    }
}

typedef CUresult (*PFN_encodeTiled)(CUtensorMap*, CUtensorMapDataType, cuuint32_t, void*, const cuuint64_t*,
                                    const cuuint64_t*, const cuuint32_t*, const cuuint32_t*, CUtensorMapInterleave,
                                    CUtensorMapSwizzle, CUtensorMapL2promotion, CUtensorMapFloatOOBfill);

static void make_map(PFN_encodeTiled enc, CUtensorMap* m, const void* ptr, uint64_t cols, uint64_t rows,
                     uint32_t box_cols, uint32_t box_rows)
{
    cuuint64_t dims[2] = {cols, rows};
    cuuint64_t strides[1] = {cols * 2};
    cuuint32_t box[2] = {box_cols, box_rows};
    cuuint32_t es[2] = {1, 1};
    enc(m, CU_TENSOR_MAP_DATA_TYPE_BFLOAT16, 2, const_cast<void*>(ptr), dims, strides, box, es,
        CU_TENSOR_MAP_INTERLEAVE_NONE, CU_TENSOR_MAP_SWIZZLE_128B, CU_TENSOR_MAP_L2_PROMOTION_L2_128B,
        CU_TENSOR_MAP_FLOAT_OOB_FILL_NONE);
}

extern "C" void kernel_launch(void* const* d_in, const int* in_sizes, int n_in, void* d_out, int out_size)
{
    const bf16* x    = (const bf16*)d_in[0];
    const bf16* wqkv = (const bf16*)d_in[1];
    const bf16* wo   = (const bf16*)d_in[2];
    const bf16* w1   = (const bf16*)d_in[4];
    const bf16* b1   = (const bf16*)d_in[5];
    const bf16* w2   = (const bf16*)d_in[6];
    const bf16* gw   = (const bf16*)d_in[7];

    static PFN_encodeTiled enc = nullptr;
    if (!enc) {
        void* fn = nullptr;
        cudaDriverEntryPointQueryResult qr;
        cudaGetDriverEntryPoint("cuTensorMapEncodeTiled", &fn, cudaEnableDefault, &qr);
        enc = (PFN_encodeTiled)fn;
        cudaFuncSetAttribute(k1_kernel, cudaFuncAttributeMaxDynamicSharedMemorySize, K1_SMEM);
        cudaFuncSetAttribute(k2_kernel, cudaFuncAttributeMaxDynamicSharedMemorySize, K2_SMEM);
        cudaFuncSetAttribute(k3_kernel, cudaFuncAttributeMaxDynamicSharedMemorySize, K3_SMEM);
    }
    void* a2p = nullptr;
    cudaGetSymbolAddress(&a2p, g_a2);
    void* qkvp = nullptr;
    cudaGetSymbolAddress(&qkvp, g_qkv);
    CUtensorMap tmX, tmWqkv, tmW1, tmA2, tmWo, tmW2, tmQKV;
    make_map(enc, &tmQKV, qkvp, 192, 8 * S_, 64, 128);
    make_map(enc, &tmX, x, D_, S_, 64, 128);
    make_map(enc, &tmWqkv, wqkv, 3 * D_, D_, 64, 64);
    make_map(enc, &tmW1, w1, F_, D_, 64, 64);
    make_map(enc, &tmA2, a2p, KA2, S_, 64, 128);
    make_map(enc, &tmWo, wo, D_, D_, 64, 64);
    make_map(enc, &tmW2, w2, D_, F_, 64, 64);

    cudaStream_t st = cudaStreamPerThread;
    k1_kernel<<<128, 384, K1_SMEM, st>>>(tmX, tmWqkv, tmW1, b1, gw, w1, wqkv, w2, wo);
    cudaLaunchAttribute at[1];
    at[0].id = cudaLaunchAttributeProgrammaticStreamSerialization;
    at[0].val.programmaticStreamSerializationAllowed = 1;
    cudaLaunchConfig_t cfg = {};
    cfg.gridDim = dim3(128); cfg.stream = st; cfg.attrs = at; cfg.numAttrs = 1;
    cfg.blockDim = dim3(512); cfg.dynamicSmemBytes = K2_SMEM;
    cudaLaunchKernelEx(&cfg, k2_kernel, tmQKV);
    k3_kernel<<<128, 384, K3_SMEM, st>>>(tmA2, tmWo, tmW2, (bf16*)d_out);
}
```

```cpp
#include <cuda_runtime.h>
#include <cuda_bf16.h>
#include <cuda.h>
#include <stdint.h>

typedef __nv_bfloat16 bf16;

constexpr int S_ = 2048, D_ = 512, F_ = 1376;
constexpr int KA2 = D_ + F_;
constexpr int FCH = 176;

__device__ bf16  g_qkv[8 * S_ * 192];
__device__ bf16  g_a2[S_ * KA2];
__device__ float g_gate[S_];

#define TS(k, cond) do { } while (0)

__device__ __forceinline__ uint32_t smem_u32(const void* p) { return (uint32_t)__cvta_generic_to_shared(p); }
__device__ __forceinline__ void mbar_init(uint32_t bar, uint32_t count) {
    asm volatile("mbarrier.init.shared::cta.b64 [%0], %1;" :: "r"(bar), "r"(count) : "memory");
}
__device__ __forceinline__ void mbar_expect_tx(uint32_t bar, uint32_t bytes) {
    asm volatile("mbarrier.arrive.expect_tx.shared::cta.b64 _, [%0], %1;" :: "r"(bar), "r"(bytes) : "memory");
}
__device__ __forceinline__ void mbar_arrive(uint32_t bar) {
    asm volatile("mbarrier.arrive.shared::cta.b64 _, [%0];" :: "r"(bar) : "memory");
}
__device__ __forceinline__ bool mbar_try_wait(uint32_t bar, uint32_t parity) {
    uint32_t ok;
    asm volatile("{\n.reg .pred p;\nmbarrier.try_wait.parity.shared::cta.b64 p, [%1], %2;\nselp.u32 %0, 1, 0, p;\n}"
                 : "=r"(ok) : "r"(bar), "r"(parity) : "memory");
    return ok != 0;
}
__device__ __forceinline__ void mbar_wait(uint32_t bar, uint32_t parity) {
    for (uint32_t it = 0; it < (1u << 22); ++it) { if (mbar_try_wait(bar, parity)) break; }
}
__device__ __forceinline__ void tma_load_2d(uint32_t dst, const CUtensorMap* map, int c0, int c1, uint32_t bar) {
    asm volatile("cp.async.bulk.tensor.2d.shared::cluster.global.mbarrier::complete_tx::bytes [%0], [%1, {%3, %4}], [%2];"
                 :: "r"(dst), "l"(map), "r"(bar), "r"(c0), "r"(c1) : "memory");
}
__device__ __forceinline__ void l2_prefetch(const void* p, uint32_t bytes) {
    asm volatile("cp.async.bulk.prefetch.L2.global [%0], %1;" :: "l"(p), "r"(bytes) : "memory");
}
__device__ __forceinline__ void fence_barrier_init() { asm volatile("fence.mbarrier_init.release.cluster;" ::: "memory"); }
__device__ __forceinline__ void wgmma_fence()  { asm volatile("wgmma.fence.sync.aligned;" ::: "memory"); }
__device__ __forceinline__ void wgmma_commit() { asm volatile("wgmma.commit_group.sync.aligned;" ::: "memory"); }
template <int N> __device__ __forceinline__ void wgmma_wait() { asm volatile("wgmma.wait_group.sync.aligned %0;" :: "n"(N) : "memory"); }
template <int R> __device__ __forceinline__ void reg_alloc()   { asm volatile("setmaxnreg.inc.sync.aligned.u32 %0;" :: "n"(R)); }
template <int R> __device__ __forceinline__ void reg_dealloc() { asm volatile("setmaxnreg.dec.sync.aligned.u32 %0;" :: "n"(R)); }
__device__ __forceinline__ void bar_sync(int id, int n)   { asm volatile("bar.sync %0, %1;" :: "r"(id), "r"(n) : "memory"); }
__device__ __forceinline__ void bar_arrive(int id, int n) { asm volatile("bar.arrive %0, %1;" :: "r"(id), "r"(n) : "memory"); }

__device__ __forceinline__ uint64_t make_desc(uint32_t addr, uint32_t lbo, uint32_t sbo) {
    uint64_t d = (uint64_t)((addr & 0x3FFFF) >> 4);
    d |= (uint64_t)((lbo & 0x3FFFF) >> 4) << 16;
    d |= (uint64_t)((sbo & 0x3FFFF) >> 4) << 32;
    d |= (uint64_t)1 << 62;
    return d;
}

template <int TB>
__device__ __forceinline__ void wgmma_n64(float (&d)[32], uint64_t da, uint64_t db, int scale_d) {
    asm volatile("{\n.reg .pred p;\nsetp.ne.b32 p, %34, 0;\n"
        "wgmma.mma_async.sync.aligned.m64n64k16.f32.bf16.bf16 {%0, %1, %2, %3, %4, %5, %6, %7, %8, %9, %10, %11, %12, %13, %14, %15, %16, %17, %18, %19, %20, %21, %22, %23, %24, %25, %26, %27, %28, %29, %30, %31}, %32, %33, p, 1, 1, 0, %35;\n}\n"
        : "+f"(d[0]), "+f"(d[1]), "+f"(d[2]), "+f"(d[3]), "+f"(d[4]), "+f"(d[5]), "+f"(d[6]), "+f"(d[7]), "+f"(d[8]), "+f"(d[9]), "+f"(d[10]), "+f"(d[11]), "+f"(d[12]), "+f"(d[13]), "+f"(d[14]), "+f"(d[15]), "+f"(d[16]), "+f"(d[17]), "+f"(d[18]), "+f"(d[19]), "+f"(d[20]), "+f"(d[21]), "+f"(d[22]), "+f"(d[23]), "+f"(d[24]), "+f"(d[25]), "+f"(d[26]), "+f"(d[27]), "+f"(d[28]), "+f"(d[29]), "+f"(d[30]), "+f"(d[31])
        : "l"(da), "l"(db), "r"(scale_d), "n"(TB));
}

template <int TB>
__device__ __forceinline__ void wgmma_n128(float (&d)[64], uint64_t da, uint64_t db, int scale_d) {
    asm volatile("{\n.reg .pred p;\nsetp.ne.b32 p, %66, 0;\n"
        "wgmma.mma_async.sync.aligned.m64n128k16.f32.bf16.bf16 {%0, %1, %2, %3, %4, %5, %6, %7, %8, %9, %10, %11, %12, %13, %14, %15, %16, %17, %18, %19, %20, %21, %22, %23, %24, %25, %26, %27, %28, %29, %30, %31, %32, %33, %34, %35, %36, %37, %38, %39, %40, %41, %42, %43, %44, %45, %46, %47, %48, %49, %50, %51, %52, %53, %54, %55, %56, %57, %58, %59, %60, %61, %62, %63}, %64, %65, p, 1, 1, 0, %67;\n}\n"
        : "+f"(d[0]), "+f"(d[1]), "+f"(d[2]), "+f"(d[3]), "+f"(d[4]), "+f"(d[5]), "+f"(d[6]), "+f"(d[7]), "+f"(d[8]), "+f"(d[9]), "+f"(d[10]), "+f"(d[11]), "+f"(d[12]), "+f"(d[13]), "+f"(d[14]), "+f"(d[15]), "+f"(d[16]), "+f"(d[17]), "+f"(d[18]), "+f"(d[19]), "+f"(d[20]), "+f"(d[21]), "+f"(d[22]), "+f"(d[23]), "+f"(d[24]), "+f"(d[25]), "+f"(d[26]), "+f"(d[27]), "+f"(d[28]), "+f"(d[29]), "+f"(d[30]), "+f"(d[31]), "+f"(d[32]), "+f"(d[33]), "+f"(d[34]), "+f"(d[35]), "+f"(d[36]), "+f"(d[37]), "+f"(d[38]), "+f"(d[39]), "+f"(d[40]), "+f"(d[41]), "+f"(d[42]), "+f"(d[43]), "+f"(d[44]), "+f"(d[45]), "+f"(d[46]), "+f"(d[47]), "+f"(d[48]), "+f"(d[49]), "+f"(d[50]), "+f"(d[51]), "+f"(d[52]), "+f"(d[53]), "+f"(d[54]), "+f"(d[55]), "+f"(d[56]), "+f"(d[57]), "+f"(d[58]), "+f"(d[59]), "+f"(d[60]), "+f"(d[61]), "+f"(d[62]), "+f"(d[63])
        : "l"(da), "l"(db), "r"(scale_d), "n"(TB));
}

template <int TB>
__device__ __forceinline__ void wgmma_n176(float (&d)[88], uint64_t da, uint64_t db, int scale_d) {
    asm volatile("{\n.reg .pred p;\nsetp.ne.b32 p, %90, 0;\n"
        "wgmma.mma_async.sync.aligned.m64n176k16.f32.bf16.bf16 {%0, %1, %2, %3, %4, %5, %6, %7, %8, %9, %10, %11, %12, %13, %14, %15, %16, %17, %18, %19, %20, %21, %22, %23, %24, %25, %26, %27, %28, %29, %30, %31, %32, %33, %34, %35, %36, %37, %38, %39, %40, %41, %42, %43, %44, %45, %46, %47, %48, %49, %50, %51, %52, %53, %54, %55, %56, %57, %58, %59, %60, %61, %62, %63, %64, %65, %66, %67, %68, %69, %70, %71, %72, %73, %74, %75, %76, %77, %78, %79, %80, %81, %82, %83, %84, %85, %86, %87}, %88, %89, p, 1, 1, 0, %91;\n}\n"
        : "+f"(d[0]), "+f"(d[1]), "+f"(d[2]), "+f"(d[3]), "+f"(d[4]), "+f"(d[5]), "+f"(d[6]), "+f"(d[7]), "+f"(d[8]), "+f"(d[9]), "+f"(d[10]), "+f"(d[11]), "+f"(d[12]), "+f"(d[13]), "+f"(d[14]), "+f"(d[15]), "+f"(d[16]), "+f"(d[17]), "+f"(d[18]), "+f"(d[19]), "+f"(d[20]), "+f"(d[21]), "+f"(d[22]), "+f"(d[23]), "+f"(d[24]), "+f"(d[25]), "+f"(d[26]), "+f"(d[27]), "+f"(d[28]), "+f"(d[29]), "+f"(d[30]), "+f"(d[31]), "+f"(d[32]), "+f"(d[33]), "+f"(d[34]), "+f"(d[35]), "+f"(d[36]), "+f"(d[37]), "+f"(d[38]), "+f"(d[39]), "+f"(d[40]), "+f"(d[41]), "+f"(d[42]), "+f"(d[43]), "+f"(d[44]), "+f"(d[45]), "+f"(d[46]), "+f"(d[47]), "+f"(d[48]), "+f"(d[49]), "+f"(d[50]), "+f"(d[51]), "+f"(d[52]), "+f"(d[53]), "+f"(d[54]), "+f"(d[55]), "+f"(d[56]), "+f"(d[57]), "+f"(d[58]), "+f"(d[59]), "+f"(d[60]), "+f"(d[61]), "+f"(d[62]), "+f"(d[63]), "+f"(d[64]), "+f"(d[65]), "+f"(d[66]), "+f"(d[67]), "+f"(d[68]), "+f"(d[69]), "+f"(d[70]), "+f"(d[71]), "+f"(d[72]), "+f"(d[73]), "+f"(d[74]), "+f"(d[75]), "+f"(d[76]), "+f"(d[77]), "+f"(d[78]), "+f"(d[79]), "+f"(d[80]), "+f"(d[81]), "+f"(d[82]), "+f"(d[83]), "+f"(d[84]), "+f"(d[85]), "+f"(d[86]), "+f"(d[87])
        : "l"(da), "l"(db), "r"(scale_d), "n"(TB));
}

template <int TB>
__device__ __forceinline__ void wgmma_n192(float (&d)[96], uint64_t da, uint64_t db, int scale_d) {
    asm volatile("{\n.reg .pred p;\nsetp.ne.b32 p, %98, 0;\n"
        "wgmma.mma_async.sync.aligned.m64n192k16.f32.bf16.bf16 {%0, %1, %2, %3, %4, %5, %6, %7, %8, %9, %10, %11, %12, %13, %14, %15, %16, %17, %18, %19, %20, %21, %22, %23, %24, %25, %26, %27, %28, %29, %30, %31, %32, %33, %34, %35, %36, %37, %38, %39, %40, %41, %42, %43, %44, %45, %46, %47, %48, %49, %50, %51, %52, %53, %54, %55, %56, %57, %58, %59, %60, %61, %62, %63, %64, %65, %66, %67, %68, %69, %70, %71, %72, %73, %74, %75, %76, %77, %78, %79, %80, %81, %82, %83, %84, %85, %86, %87, %88, %89, %90, %91, %92, %93, %94, %95}, %96, %97, p, 1, 1, 0, %99;\n}\n"
        : "+f"(d[0]), "+f"(d[1]), "+f"(d[2]), "+f"(d[3]), "+f"(d[4]), "+f"(d[5]), "+f"(d[6]), "+f"(d[7]), "+f"(d[8]), "+f"(d[9]), "+f"(d[10]), "+f"(d[11]), "+f"(d[12]), "+f"(d[13]), "+f"(d[14]), "+f"(d[15]), "+f"(d[16]), "+f"(d[17]), "+f"(d[18]), "+f"(d[19]), "+f"(d[20]), "+f"(d[21]), "+f"(d[22]), "+f"(d[23]), "+f"(d[24]), "+f"(d[25]), "+f"(d[26]), "+f"(d[27]), "+f"(d[28]), "+f"(d[29]), "+f"(d[30]), "+f"(d[31]), "+f"(d[32]), "+f"(d[33]), "+f"(d[34]), "+f"(d[35]), "+f"(d[36]), "+f"(d[37]), "+f"(d[38]), "+f"(d[39]), "+f"(d[40]), "+f"(d[41]), "+f"(d[42]), "+f"(d[43]), "+f"(d[44]), "+f"(d[45]), "+f"(d[46]), "+f"(d[47]), "+f"(d[48]), "+f"(d[49]), "+f"(d[50]), "+f"(d[51]), "+f"(d[52]), "+f"(d[53]), "+f"(d[54]), "+f"(d[55]), "+f"(d[56]), "+f"(d[57]), "+f"(d[58]), "+f"(d[59]), "+f"(d[60]), "+f"(d[61]), "+f"(d[62]), "+f"(d[63]), "+f"(d[64]), "+f"(d[65]), "+f"(d[66]), "+f"(d[67]), "+f"(d[68]), "+f"(d[69]), "+f"(d[70]), "+f"(d[71]), "+f"(d[72]), "+f"(d[73]), "+f"(d[74]), "+f"(d[75]), "+f"(d[76]), "+f"(d[77]), "+f"(d[78]), "+f"(d[79]), "+f"(d[80]), "+f"(d[81]), "+f"(d[82]), "+f"(d[83]), "+f"(d[84]), "+f"(d[85]), "+f"(d[86]), "+f"(d[87]), "+f"(d[88]), "+f"(d[89]), "+f"(d[90]), "+f"(d[91]), "+f"(d[92]), "+f"(d[93]), "+f"(d[94]), "+f"(d[95])
        : "l"(da), "l"(db), "r"(scale_d), "n"(TB));
}

__device__ __forceinline__ uint32_t pack_bf16(float lo, float hi) {
    uint32_t r;
    asm("cvt.rn.bf16x2.f32 %0, %1, %2;" : "=r"(r) : "f"(hi), "f"(lo));
    return r;
}
__device__ __forceinline__ float bf_lo(uint32_t v) { return __uint_as_float(v << 16); }
__device__ __forceinline__ float bf_hi(uint32_t v) { return __uint_as_float(v & 0xffff0000u); }

__device__ __forceinline__ void quad_transpose(uint32_t (&w)[4], int q) {
    const bool o1 = q & 1, o2 = q & 2;
    {
        uint32_t s0 = o1 ? w[0] : w[1], s1 = o1 ? w[2] : w[3];
        s0 = __shfl_xor_sync(0xffffffffu, s0, 1); s1 = __shfl_xor_sync(0xffffffffu, s1, 1);
        if (o1) { w[0] = s0; w[2] = s1; } else { w[1] = s0; w[3] = s1; }
    }
    {
        uint32_t s0 = o2 ? w[0] : w[2], s1 = o2 ? w[1] : w[3];
        s0 = __shfl_xor_sync(0xffffffffu, s0, 2); s1 = __shfl_xor_sync(0xffffffffu, s1, 2);
        if (o2) { w[0] = s0; w[1] = s1; } else { w[2] = s0; w[3] = s1; }
    }
}

__device__ __forceinline__ float ex2(float x) { float y; asm("ex2.approx.ftz.f32 %0, %1;" : "=f"(y) : "f"(x)); return y; }
__device__ __forceinline__ float rcp(float x) { float y; asm("rcp.approx.ftz.f32 %0, %1;" : "=f"(y) : "f"(x)); return y; }

__device__ __forceinline__ float ex2v(float x) { float y; asm volatile("ex2.approx.ftz.f32 %0, %1;" : "=f"(y) : "f"(x)); return y; }
__device__ __forceinline__ float rcpv(float x) { float y; asm volatile("rcp.approx.ftz.f32 %0, %1;" : "=f"(y) : "f"(x)); return y; }
__device__ __forceinline__ float mish_f(float h) {
    const float e = ex2v(1.4426950408889634f * fminf(h, 20.f));
    const float n = fmaf(e, e, e + e);
    return h * n * rcpv(n + 2.f);
}

__device__ __forceinline__ void pdl_wait()   { asm volatile("griddepcontrol.wait;" ::: "memory"); }
__device__ __forceinline__ void pdl_launch() { asm volatile("griddepcontrol.launch_dependents;" ::: "memory"); }

constexpr int K1_STAGES = 4;
constexpr int K1_XBYTES = 128 * 512 * 2;
constexpr int K1_BSTAGE = 3 * 8192;
constexpr int K1_SMEM   = K1_XBYTES + K1_STAGES * K1_BSTAGE + 2048   + 1024  ;

__global__ void __launch_bounds__(384, 1)
k1_kernel(const __grid_constant__ CUtensorMap tmX, const __grid_constant__ CUtensorMap tmWqkv,
          const __grid_constant__ CUtensorMap tmW1, const bf16* __restrict__ b1,
          const bf16* __restrict__ gate_w, const bf16* __restrict__ w1p, const bf16* __restrict__ wqkvp,
          const bf16* __restrict__ w2p, const bf16* __restrict__ wop)
{

    extern __shared__ uint8_t smem_raw[];
    const uint32_t sbase = (smem_u32(smem_raw) + 1023u) & ~1023u;
    uint8_t* sgen = smem_raw + (sbase - smem_u32(smem_raw));
    const uint32_t sX = sbase;
    const uint32_t sB = sbase + K1_XBYTES;
    const uint32_t sBar = sB + K1_STAGES * K1_BSTAGE;
    const uint32_t x_full = sBar;
    const uint32_t b_full = sBar + 64;
    const uint32_t b_empty = sBar + 96;
    float* sGate = (float*)(sgen + K1_XBYTES + K1_STAGES * K1_BSTAGE + 128);
    uint8_t* sGw = sgen + K1_XBYTES + K1_STAGES * K1_BSTAGE + 640;
    uint32_t* sBias = (uint32_t*)(sgen + K1_XBYTES + K1_STAGES * K1_BSTAGE + 1664);

    const int rb = blockIdx.x >> 3, j = blockIdx.x & 7;
    const int tid = threadIdx.x, lane = tid & 31;
    const int warp = __shfl_sync(0xffffffffu, tid >> 5, 0), wg = warp >> 2;
    TS(0, tid == 0);
    pdl_launch();

    if (tid == 0) {
        for (int i = 0; i < 8; i++) mbar_init(x_full + 8 * i, 1);
        for (int i = 0; i < K1_STAGES; i++) { mbar_init(b_full + 8 * i, 1); mbar_init(b_empty + 8 * i, 8); }
        fence_barrier_init();
    }
    __syncthreads();

    if (wg == 2) {
        reg_dealloc<40>();
        if (tid == 288) {
            const int b = blockIdx.x;
            mbar_wait(b_full + 8, 0);
            l2_prefetch((const uint8_t*)wqkvp + b * 12288, 12288);
            l2_prefetch((const uint8_t*)w2p + b * 11008, 11008);
            l2_prefetch((const uint8_t*)wop + b * 4096, 4096);
        }
        if (tid == 256) {
            for (int it = 0; it < 16; it++) {
                if (it < 8) {
                    mbar_expect_tx(x_full + 8 * it, 16384);
                    tma_load_2d(sX + it * 16384, &tmX, it * 64, rb * 128, x_full + 8 * it);
                }
                const int st = it & 3;
                if (it >= K1_STAGES) mbar_wait(b_empty + 8 * st, ((it >> 2) - 1) & 1);
                mbar_expect_tx(b_full + 8 * st, K1_BSTAGE);
                const uint32_t dst = sB + st * K1_BSTAGE;
                if (it < 8) {
                    for (int b = 0; b < 3; b++) tma_load_2d(dst + b * 8192, &tmW1, j * FCH + b * 64, it * 64, b_full + 8 * st);
                } else {
                    for (int b = 0; b < 3; b++) tma_load_2d(dst + b * 8192, &tmWqkv, b * 512 + j * 64, (it - 8) * 64, b_full + 8 * st);
                }
            }
        }
    } else {
        reg_alloc<232>();
        if (tid < 64) ((uint4*)sGw)[tid] = __ldg((const uint4*)gate_w + tid);
        else if (tid < 64 + 88) {
            const int c = j * FCH + (tid - 64) * 2;
            sBias[tid - 64] = c < F_ ? __ldg((const uint32_t*)(b1 + c)) : 0u;
        }
        bar_sync(3, 256);
        const int t128 = tid & 127, w4 = warp & 3, q = lane & 3;
        float accF[88], accQ[96];
        const uint64_t da0 = make_desc(sX + wg * 8192, 16, 1024);
        const uint64_t db0 = make_desc(sB, 8192, 1024);
        float gs = 0.f;
        const int grow = wg * 64 + (t128 >> 1), ghalf = t128 & 1;
#pragma unroll
        for (int kc = 0; kc < 8; kc++) {
            const int st = kc & 3;
            mbar_wait(x_full + 8 * kc, 0);
            mbar_wait(b_full + 8 * st, (kc >> 2) & 1);
            TS(1, tid == 0 && kc == 0); TS(2, tid == 0 && kc == 4);
            wgmma_fence();
#pragma unroll
            for (int k16 = 0; k16 < 4; k16++) {
                wgmma_n176<1>(accF, da0 + (kc * 1024 + k16 * 2), db0 + (st * (K1_BSTAGE >> 4) + k16 * 128), (kc | k16) != 0);
            }
            wgmma_commit();
#pragma unroll
            for (int c = 0; c < 4; c++) {
                const int cc = ghalf * 4 + c;
                const uint4 xv = *(const uint4*)(sgen + kc * 16384 + grow * 128 + ((cc ^ (grow & 7)) << 4));
                const uint4 gv = *(const uint4*)(sGw + kc * 128 + cc * 16);
                gs = fmaf(bf_lo(xv.x), bf_lo(gv.x), gs); gs = fmaf(bf_hi(xv.x), bf_hi(gv.x), gs);
                gs = fmaf(bf_lo(xv.y), bf_lo(gv.y), gs); gs = fmaf(bf_hi(xv.y), bf_hi(gv.y), gs);
                gs = fmaf(bf_lo(xv.z), bf_lo(gv.z), gs); gs = fmaf(bf_hi(xv.z), bf_hi(gv.z), gs);
                gs = fmaf(bf_lo(xv.w), bf_lo(gv.w), gs); gs = fmaf(bf_hi(xv.w), bf_hi(gv.w), gs);
            }
            if (kc > 0) { wgmma_wait<1>(); if (lane == 0) mbar_arrive(b_empty + 8 * ((kc - 1) & 3)); }
        }
        gs += __shfl_xor_sync(0xffffffffu, gs, 1);
        {
            const float g = 1.f / (1.f + __expf(-gs));
            if (ghalf == 0) {
                sGate[grow] = g;
                if (j == 0) g_gate[rb * 128 + grow] = g;
            }
        }
        wgmma_wait<0>();
        if (lane == 0) mbar_arrive(b_empty + 8 * 3);
        bar_sync(1 + wg, 128);
        TS(3, tid == 0);
        const int n0 = j * FCH;
        const int rl = wg * 64 + w4 * 16 + (lane >> 2);
        const float om0 = 1.f - sGate[rl], om1 = 1.f - sGate[rl + 8];
        bf16* frow0 = g_a2 + (size_t)(rb * 128 + rl) * KA2 + D_ + n0;
        bf16* frow1 = frow0 + 8 * KA2;
        auto ffn_chunk = [&](int u) {
            uint32_t w0[4], w1[4];
#pragma unroll
            for (int i = 0; i < 4; i++) {
                const int t = u * 4 + i;
                if (t < 22) {
                    const uint32_t bv = sBias[t * 4 + q];
                    const float bb0 = bf_lo(bv), bb1 = bf_hi(bv);
                    w0[i] = pack_bf16(mish_f(accF[t * 4 + 0] + bb0) * om0, mish_f(accF[t * 4 + 1] + bb1) * om0);
                    w1[i] = pack_bf16(mish_f(accF[t * 4 + 2] + bb0) * om1, mish_f(accF[t * 4 + 3] + bb1) * om1);
                } else { w0[i] = 0; w1[i] = 0; }
            }
            quad_transpose(w0, q);
            quad_transpose(w1, q);
            const int c = (u * 4 + q) * 8;
            if (c < FCH && n0 + c < F_) {
                *(uint4*)(frow0 + c) = make_uint4(w0[0], w0[1], w0[2], w0[3]);
                *(uint4*)(frow1 + c) = make_uint4(w1[0], w1[1], w1[2], w1[3]);
            }
        };
#pragma unroll
        for (int kc = 0; kc < 8; kc++) {
            const int st = kc & 3;
            mbar_wait(b_full + 8 * st, ((kc + 8) >> 2) & 1);
            wgmma_fence();
#pragma unroll
            for (int k16 = 0; k16 < 4; k16++) {
                wgmma_n192<1>(accQ, da0 + (kc * 1024 + k16 * 2), db0 + (st * (K1_BSTAGE >> 4) + k16 * 128), (kc | k16) != 0);
            }
            wgmma_commit();
            if (kc < 6) ffn_chunk(kc);
            if (kc > 0) { wgmma_wait<1>(); if (lane == 0) mbar_arrive(b_empty + 8 * ((kc - 1) & 3)); }
        }
        wgmma_wait<0>();
        TS(4, tid == 0);
        {
            bf16* orow0 = g_qkv + ((size_t)j * S_ + rb * 128 + rl) * 192;
            bf16* orow1 = orow0 + 8 * 192;
#pragma unroll
            for (int u = 0; u < 6; u++) {
                uint32_t w0[4], w1[4];
#pragma unroll
                for (int i = 0; i < 4; i++) {
                    const int t = u * 4 + i;
                    w0[i] = pack_bf16(accQ[t * 4 + 0], accQ[t * 4 + 1]);
                    w1[i] = pack_bf16(accQ[t * 4 + 2], accQ[t * 4 + 3]);
                }
                quad_transpose(w0, q);
                quad_transpose(w1, q);
                const int c = (u * 4 + q) * 8;
                *(uint4*)(orow0 + c) = make_uint4(w0[0], w0[1], w0[2], w0[3]);
                *(uint4*)(orow1 + c) = make_uint4(w1[0], w1[1], w1[2], w1[3]);
            }
        }
        TS(5, tid == 0);
    }
}

__device__ __forceinline__ void ldsm_x4(uint32_t (&r)[4], uint32_t addr) {
    asm("ldmatrix.sync.aligned.m8n8.x4.shared.b16 {%0,%1,%2,%3}, [%4];"
                 : "=r"(r[0]), "=r"(r[1]), "=r"(r[2]), "=r"(r[3]) : "r"(addr));
}
__device__ __forceinline__ void ldsm_x4_t(uint32_t (&r)[4], uint32_t addr) {
    asm("ldmatrix.sync.aligned.m8n8.x4.trans.shared.b16 {%0,%1,%2,%3}, [%4];"
                 : "=r"(r[0]), "=r"(r[1]), "=r"(r[2]), "=r"(r[3]) : "r"(addr));
}
__device__ __forceinline__ void mma16816(float (&d)[4], const uint32_t (&a)[4], uint32_t b0, uint32_t b1) {
    asm("mma.sync.aligned.m16n8k16.row.col.f32.bf16.bf16.f32 {%0,%1,%2,%3}, {%4,%5,%6,%7}, {%8,%9}, {%0,%1,%2,%3};"
                 : "+f"(d[0]), "+f"(d[1]), "+f"(d[2]), "+f"(d[3])
                 : "r"(a[0]), "r"(a[1]), "r"(a[2]), "r"(a[3]), "r"(b0), "r"(b1));
}
__device__ __forceinline__ void mma16816_z(float (&d)[4], const uint32_t (&a)[4], uint32_t b0, uint32_t b1) {
    asm("mma.sync.aligned.m16n8k16.row.col.f32.bf16.bf16.f32 {%0,%1,%2,%3}, {%4,%5,%6,%7}, {%8,%9}, {%10,%10,%10,%10};"
                 : "=f"(d[0]), "=f"(d[1]), "=f"(d[2]), "=f"(d[3])
                 : "r"(a[0]), "r"(a[1]), "r"(a[2]), "r"(a[3]), "r"(b0), "r"(b1), "f"(0.f));
}

constexpr int KV_PITCH = 128;

template <int EDGE, bool HEAD>
__device__ __forceinline__ void blk_scores(float (&s)[2][4], const uint32_t (&qa)[4], uint32_t kaddr, bool dead, int r0, int c0)
{
    uint32_t kf[4];
    ldsm_x4(kf, kaddr);
    mma16816_z(s[0], qa, kf[0], kf[1]);
    mma16816_z(s[1], qa, kf[2], kf[3]);
#pragma unroll
    for (int t = 0; t < 2; t++)
#pragma unroll
        for (int e = 0; e < 4; e++) {
            const int r = r0 + (e >> 1) * 8, c = t * 8 + c0 + (e & 1);
            if (EDGE == 1 && c <= r) s[t][e] = -1e30f;
            if (EDGE == 2 && c > r) s[t][e] = -1e30f;
            if (HEAD && dead) s[t][e] = -1e30f;
        }
}
__device__ __forceinline__ void blk_max(const float (&s)[2][4], float& n0, float& n1) {
    n0 = fmaxf(n0, fmaxf(fmaxf(s[0][0], s[0][1]), fmaxf(s[1][0], s[1][1])));
    n1 = fmaxf(n1, fmaxf(fmaxf(s[0][2], s[0][3]), fmaxf(s[1][2], s[1][3])));
}
__device__ __forceinline__ void blk_pv(const float (&s)[2][4], float mc0, float mc1, float (&l)[4],
                                       float (&o)[2][4], uint32_t vaddr) {
    const float C = 0.25f * 1.4426950408889634f;
    uint32_t pa[4];
#pragma unroll
    for (int t = 0; t < 2; t++) {
        const float p0 = ex2(fmaf(s[t][0], C, -mc0)), p1 = ex2(fmaf(s[t][1], C, -mc0));
        const float p2 = ex2(fmaf(s[t][2], C, -mc1)), p3 = ex2(fmaf(s[t][3], C, -mc1));
        pa[2 * t] = pack_bf16(p0, p1); pa[2 * t + 1] = pack_bf16(p2, p3);
    }
    uint32_t vf[4];
    ldsm_x4_t(vf, vaddr);
    mma16816(o[0], pa, vf[0], vf[1]);
    mma16816(o[1], pa, vf[2], vf[3]);
    mma16816(l, pa, 0x3F803F80u, 0x3F803F80u);
}
__device__ __forceinline__ void quad_max(float& n0, float& n1) {
    n0 = fmaxf(n0, __shfl_xor_sync(0xffffffffu, n0, 1)); n1 = fmaxf(n1, __shfl_xor_sync(0xffffffffu, n1, 1));
    n0 = fmaxf(n0, __shfl_xor_sync(0xffffffffu, n0, 2)); n1 = fmaxf(n1, __shfl_xor_sync(0xffffffffu, n1, 2));
}
template <int NC, int NN, bool FIRST, bool NEXT_IS_EDGE, bool HEAD>
__device__ __forceinline__ void pipe_step(const float (&sc)[5][2][4], float (&sn)[5][2][4], const uint32_t (&qa)[4],
                                          uint32_t ka, uint32_t va, int kc, int kn, int kb0, int r0, int c0,
                                          float& m0, float& m1, float& n0, float& n1, float (&l)[4], float (&o)[2][4])
{
    const float C = 0.25f * 1.4426950408889634f;
    const float mc0 = n0 * C, mc1 = n1 * C;
    if (!FIRST) {
        const float a0 = ex2(fmaf(m0, C, -mc0)), a1 = ex2(fmaf(m1, C, -mc1));
        l[0] *= a0; l[2] *= a1;
        o[0][0] *= a0; o[0][1] *= a0; o[1][0] *= a0; o[1][1] *= a0;
        o[0][2] *= a1; o[0][3] *= a1; o[1][2] *= a1; o[1][3] *= a1;
    }
    m0 = n0; m1 = n1;
#pragma unroll
    for (int b = 0; b < NC; b++) {
        if (b < NN) {
            if (NEXT_IS_EDGE && b == 0) blk_scores<1, HEAD>(sn[b], qa, ka + (kn + b) * 16 * KV_PITCH, kn + b < kb0, r0, c0);
            else                        blk_scores<0, HEAD>(sn[b], qa, ka + (kn + b) * 16 * KV_PITCH, kn + b < kb0, r0, c0);
        }
        blk_pv(sc[b], mc0, mc1, l, o, va + (kc + b) * 16 * KV_PITCH);
        if (b < NN) blk_max(sn[b], n0, n1);
    }
    if (NN > 0) quad_max(n0, n1);
}

__device__ __forceinline__ void kv_need(uint32_t kvbar, int blk, uint32_t& ka, uint32_t& va) {
    mbar_wait(kvbar + 8 * blk, 0);
    asm volatile("" : "+r"(ka), "+r"(va) :: "memory");
}
template <bool HEAD>
__device__ __forceinline__ void attn_task(const uint32_t (&qa)[4], uint32_t ka, uint32_t va, int kb0, int lane, int qt, uint32_t kvbar,
                                          bf16* __restrict__ out  , float g0, float g1)
{
    const int r0 = lane >> 2, c0 = (lane & 3) * 2;
    float m0 = -1e30f, m1 = -1e30f, n0 = -1e30f, n1 = -1e30f;
    float l[4] = {0.f, 0.f, 0.f, 0.f};
    float o[2][4] = {{0.f, 0.f, 0.f, 0.f}, {0.f, 0.f, 0.f, 0.f}};
    float sa[5][2][4], sb[5][2][4];
    kv_need(kvbar, 2, ka, va);
    if (qt < 4) kv_need(kvbar, 1, ka, va);
#pragma unroll
    for (int b = 0; b < 5; b++) {
        if (b == 4) blk_scores<2, HEAD>(sa[b], qa, ka + (12 + b) * 16 * KV_PITCH, false, r0, c0);
        else        blk_scores<0, HEAD>(sa[b], qa, ka + (12 + b) * 16 * KV_PITCH, 12 + b < kb0, r0, c0);
        blk_max(sa[b], n0, n1);
    }
    quad_max(n0, n1);
    kv_need(kvbar, 1, ka, va);
    if (HEAD) {
        pipe_step<5, 0, true, false, HEAD>(sa, sb, qa, ka, va, 12, 0, kb0, r0, c0, m0, m1, n0, n1, l, o);
        kv_need(kvbar, 0, ka, va);
#pragma unroll 1
        for (int kc = 8; kc >= 0 && kb0 < kc + 4; kc -= 4) {
#pragma unroll
            for (int b = 0; b < 4; b++) {
                blk_scores<0, HEAD>(sa[b], qa, ka + (kc + b) * 16 * KV_PITCH, kc + b < kb0, r0, c0);
                blk_max(sa[b], n0, n1);
            }
            quad_max(n0, n1);
            pipe_step<4, 0, false, false, HEAD>(sa, sb, qa, ka, va, kc, 0, kb0, r0, c0, m0, m1, n0, n1, l, o);
        }
    } else {
        pipe_step<5, 4, true,  false, HEAD>(sa, sb, qa, ka, va, 12, 8, kb0, r0, c0, m0, m1, n0, n1, l, o);
        if (qt < 4) kv_need(kvbar, 0, ka, va);
        pipe_step<4, 4, false, false, HEAD>(sb, sa, qa, ka, va, 8, 4, kb0, r0, c0, m0, m1, n0, n1, l, o);
        kv_need(kvbar, 0, ka, va);
        pipe_step<4, 4, false, true,  HEAD>(sa, sb, qa, ka, va, 4, 0, kb0, r0, c0, m0, m1, n0, n1, l, o);
        pipe_step<4, 0, false, false, HEAD>(sb, sa, qa, ka, va, 0, 0, kb0, r0, c0, m0, m1, n0, n1, l, o);
    }
    const float f0 = __fdividef(g0, l[0]), f1 = __fdividef(g1, l[2]);
#pragma unroll
    for (int t = 0; t < 2; t++) {
        *(uint32_t*)(out + (size_t)r0 * KA2 + t * 8 + c0) = pack_bf16(o[t][0] * f0, o[t][1] * f0);
        *(uint32_t*)(out + (size_t)(r0 + 8) * KA2 + t * 8 + c0) = pack_bf16(o[t][2] * f1, o[t][3] * f1);
    }
}

constexpr int K2_SMEM = 2 * 384 * KV_PITCH + 1024 + 64;

__global__ void __launch_bounds__(512, 1) k2_kernel(const __grid_constant__ CUtensorMap tmQKV)
{
    extern __shared__ uint8_t smem_raw[];
    const uint32_t sbase = (smem_u32(smem_raw) + 1023u) & ~1023u;
    uint8_t* sgen = smem_raw + (sbase - smem_u32(smem_raw));
    const uint32_t sK = sbase, sV = sK + 384 * KV_PITCH, kv_full = sbase + 2 * 384 * KV_PITCH;
    const int rb = blockIdx.x >> 3, j = blockIdx.x & 7;
    const int tid = threadIdx.x, warp = tid >> 5, lane = tid & 31;
    pdl_launch();
    if (tid == 0) {
        for (int i = 0; i < 3; i++) mbar_init(kv_full + 8 * i, 1);
        fence_barrier_init();
    }
    pdl_wait();
    TS(6, tid == 0);
    if (tid == 0) {
        for (int i = 0; i < 3; i++) {
            const uint32_t bar = kv_full + 8 * (2 - i);
            if (rb - i >= 0) {
                const int row = j * S_ + (rb - i) * 128;
                mbar_expect_tx(bar, 2 * 16384);
                tma_load_2d(sK + (2 - i) * 16384, &tmQKV, 64, row, bar);
                tma_load_2d(sV + (2 - i) * 16384, &tmQKV, 128, row, bar);
            } else {
                mbar_arrive(bar);
            }
        }
    }
    if (rb < 2) {
        for (int i = tid; i < (2 - rb) * 1024; i += 512) {
            *(uint4*)(sgen + i * 16) = make_uint4(0, 0, 0, 0);
            *(uint4*)(sgen + 384 * KV_PITCH + i * 16) = make_uint4(0, 0, 0, 0);
        }
    }
    const int qt = warp & 7, h0 = (warp >> 3) * 2;
    const int q0g = rb * 128 + qt * 16;
    const int r0 = lane >> 2, c0 = (lane & 3) * 2;
    const bf16* qsrc = g_qkv + ((size_t)j * S_ + q0g) * 192 + h0 * 16;
    uint32_t qa[4], qn[4];
    qa[0] = *(const uint32_t*)(qsrc + (size_t)r0 * 192 + c0);
    qa[1] = *(const uint32_t*)(qsrc + (size_t)(r0 + 8) * 192 + c0);
    qa[2] = *(const uint32_t*)(qsrc + (size_t)r0 * 192 + c0 + 8);
    qa[3] = *(const uint32_t*)(qsrc + (size_t)(r0 + 8) * 192 + c0 + 8);
    qn[0] = *(const uint32_t*)(qsrc + (size_t)r0 * 192 + 16 + c0);
    qn[1] = *(const uint32_t*)(qsrc + (size_t)(r0 + 8) * 192 + 16 + c0);
    qn[2] = *(const uint32_t*)(qsrc + (size_t)r0 * 192 + 16 + c0 + 8);
    qn[3] = *(const uint32_t*)(qsrc + (size_t)(r0 + 8) * 192 + 16 + c0 + 8);
    const float g0 = g_gate[q0g + r0], g1 = g_gate[q0g + r0 + 8];
    const int kb0 = q0g < 256 ? (256 - q0g) >> 4 : 0;
    __syncthreads();
    const uint32_t sKd = sK, sVd = sV;
    TS(7, tid == 0);
    const int krow = qt * 16 + (lane & 7) + ((lane >> 4) << 3);
    const int vrow = qt * 16 + (lane & 15);
#pragma unroll 1
    for (int hh = 0; hh < 2; hh++) {
        const int hl = h0 + hh;
        const uint32_t ka = sKd + krow * KV_PITCH + (((2 * hl + ((lane >> 3) & 1)) ^ (lane & 7)) << 4);
        const uint32_t va = sVd + vrow * KV_PITCH + (((2 * hl + (lane >> 4)) ^ (lane & 7)) << 4);
        if (rb < 2) attn_task<true>(qa, ka, va, kb0, lane, qt, kv_full, g_a2 + (size_t)q0g * KA2 + (j * 4 + hl) * 16, g0, g1);
        else        attn_task<false>(qa, ka, va, kb0, lane, qt, kv_full, g_a2 + (size_t)q0g * KA2 + (j * 4 + hl) * 16, g0, g1);
        TS(8 + hh, tid == 0);
        qa[0] = qn[0]; qa[1] = qn[1]; qa[2] = qn[2]; qa[3] = qn[3];
    }
}

constexpr int K3_STAGES = 8;
constexpr int K3_STAGE = 16384 + 8192;
constexpr int K3_SMEM = K3_STAGES * K3_STAGE + 1024 + 1024;
constexpr int K3_KSTEPS = 30;

__global__ void __launch_bounds__(384, 1)
k3_kernel(const __grid_constant__ CUtensorMap tmA2, const __grid_constant__ CUtensorMap tmWo,
          const __grid_constant__ CUtensorMap tmW2, bf16* __restrict__ out)
{
    extern __shared__ uint8_t smem_raw[];
    const uint32_t sbase = (smem_u32(smem_raw) + 1023u) & ~1023u;
    const uint32_t sBar = sbase + K3_STAGES * K3_STAGE;
    const uint32_t full = sBar, empty = sBar + 64;
    const int rb = blockIdx.x >> 3, nb = blockIdx.x & 7;
    const int tid = threadIdx.x, lane = tid & 31;
    const int warp = __shfl_sync(0xffffffffu, tid >> 5, 0), wg = warp >> 2;
    if (tid == 0) {
        for (int i = 0; i < K3_STAGES; i++) { mbar_init(full + 8 * i, 1); mbar_init(empty + 8 * i, 8); }
        fence_barrier_init();
    }
    __syncthreads();
    pdl_wait();
    TS(10, tid == 0);
    if (wg == 2) {
        reg_dealloc<40>();
        if (tid == 256) {
            for (int ks = 0; ks < K3_KSTEPS; ks++) {
                const int st = ks % K3_STAGES;
                if (ks >= K3_STAGES) mbar_wait(empty + 8 * st, ((ks / K3_STAGES) - 1) & 1);
                mbar_expect_tx(full + 8 * st, K3_STAGE);
                const uint32_t dst = sbase + st * K3_STAGE;
                tma_load_2d(dst, &tmA2, ks * 64, rb * 128, full + 8 * st);
                if (ks < 8) tma_load_2d(dst + 16384, &tmWo, nb * 64, ks * 64, full + 8 * st);
                else        tma_load_2d(dst + 16384, &tmW2, nb * 64, (ks - 8) * 64, full + 8 * st);
            }
        }
    } else {
        reg_alloc<232>();
        float acc[32];
        const uint64_t da0 = make_desc(sbase + wg * 8192, 16, 1024);
        const uint64_t db0 = make_desc(sbase + 16384, 8192, 1024);
        for (int ks = 0; ks < K3_KSTEPS; ks++) {
            const int st = ks % K3_STAGES;
            mbar_wait(full + 8 * st, (ks / K3_STAGES) & 1);
            TS(11, tid == 0 && ks == 0); TS(12, tid == 0 && ks == 8); TS(13, tid == 0 && ks == 16);
            wgmma_fence();
            const uint32_t so = (uint32_t)(st * K3_STAGE) >> 4;
#pragma unroll
            for (int k16 = 0; k16 < 4; k16++)
                wgmma_n64<1>(acc, da0 + (so + k16 * 2), db0 + (so + k16 * 128), (ks | k16) != 0);
            wgmma_commit();
            if (ks > 0) { wgmma_wait<1>(); if (lane == 0) mbar_arrive(empty + 8 * ((ks - 1) % K3_STAGES)); }
        }
        wgmma_wait<0>();
        TS(14, tid == 0);
        const int q = lane & 3;
        const int r = rb * 128 + wg * 64 + (warp & 3) * 16 + (lane >> 2);
        bf16* orow0 = out + (size_t)r * D_ + nb * 64;
        bf16* orow1 = orow0 + 8 * D_;
#pragma unroll
        for (int u = 0; u < 2; u++) {
            uint32_t w0[4], w1[4];
#pragma unroll
            for (int i = 0; i < 4; i++) {
                const int t = u * 4 + i;
                w0[i] = pack_bf16(acc[t * 4 + 0], acc[t * 4 + 1]);
                w1[i] = pack_bf16(acc[t * 4 + 2], acc[t * 4 + 3]);
            }
            quad_transpose(w0, q);
            quad_transpose(w1, q);
            const int c = (u * 4 + q) * 8;
            *(uint4*)(orow0 + c) = make_uint4(w0[0], w0[1], w0[2], w0[3]);
            *(uint4*)(orow1 + c) = make_uint4(w1[0], w1[1], w1[2], w1[3]);
        }
        TS(15, tid == 0);
    }
}

typedef CUresult (*PFN_encodeTiled)(CUtensorMap*, CUtensorMapDataType, cuuint32_t, void*, const cuuint64_t*,
                                    const cuuint64_t*, const cuuint32_t*, const cuuint32_t*, CUtensorMapInterleave,
                                    CUtensorMapSwizzle, CUtensorMapL2promotion, CUtensorMapFloatOOBfill);

static void make_map(PFN_encodeTiled enc, CUtensorMap* m, const void* ptr, uint64_t cols, uint64_t rows,
                     uint32_t box_cols, uint32_t box_rows)
{
    cuuint64_t dims[2] = {cols, rows};
    cuuint64_t strides[1] = {cols * 2};
    cuuint32_t box[2] = {box_cols, box_rows};
    cuuint32_t es[2] = {1, 1};
    enc(m, CU_TENSOR_MAP_DATA_TYPE_BFLOAT16, 2, const_cast<void*>(ptr), dims, strides, box, es,
        CU_TENSOR_MAP_INTERLEAVE_NONE, CU_TENSOR_MAP_SWIZZLE_128B, CU_TENSOR_MAP_L2_PROMOTION_L2_128B,
        CU_TENSOR_MAP_FLOAT_OOB_FILL_NONE);
}

extern "C" void kernel_launch(void* const* d_in, const int* in_sizes, int n_in, void* d_out, int out_size)
{
    const bf16* x    = (const bf16*)d_in[0];
    const bf16* wqkv = (const bf16*)d_in[1];
    const bf16* wo   = (const bf16*)d_in[2];
    const bf16* w1   = (const bf16*)d_in[4];
    const bf16* b1   = (const bf16*)d_in[5];
    const bf16* w2   = (const bf16*)d_in[6];
    const bf16* gw   = (const bf16*)d_in[7];

    static PFN_encodeTiled enc = nullptr;
    if (!enc) {
        void* fn = nullptr;
        cudaDriverEntryPointQueryResult qr;
        cudaGetDriverEntryPoint("cuTensorMapEncodeTiled", &fn, cudaEnableDefault, &qr);
        enc = (PFN_encodeTiled)fn;
        cudaFuncSetAttribute(k1_kernel, cudaFuncAttributeMaxDynamicSharedMemorySize, K1_SMEM);
        cudaFuncSetAttribute(k2_kernel, cudaFuncAttributeMaxDynamicSharedMemorySize, K2_SMEM);
        cudaFuncSetAttribute(k3_kernel, cudaFuncAttributeMaxDynamicSharedMemorySize, K3_SMEM);
    }
    void* a2p = nullptr;
    cudaGetSymbolAddress(&a2p, g_a2);
    void* qkvp = nullptr;
    cudaGetSymbolAddress(&qkvp, g_qkv);
    CUtensorMap tmX, tmWqkv, tmW1, tmA2, tmWo, tmW2, tmQKV;
    make_map(enc, &tmQKV, qkvp, 192, 8 * S_, 64, 128);
    make_map(enc, &tmX, x, D_, S_, 64, 128);
    make_map(enc, &tmWqkv, wqkv, 3 * D_, D_, 64, 64);
    make_map(enc, &tmW1, w1, F_, D_, 64, 64);
    make_map(enc, &tmA2, a2p, KA2, S_, 64, 128);
    make_map(enc, &tmWo, wo, D_, D_, 64, 64);
    make_map(enc, &tmW2, w2, D_, F_, 64, 64);

    cudaStream_t st = cudaStreamPerThread;
    k1_kernel<<<128, 384, K1_SMEM, st>>>(tmX, tmWqkv, tmW1, b1, gw, w1, wqkv, w2, wo);
    cudaLaunchAttribute at[1];
    at[0].id = cudaLaunchAttributeProgrammaticStreamSerialization;
    at[0].val.programmaticStreamSerializationAllowed = 1;
    cudaLaunchConfig_t cfg = {};
    cfg.gridDim = dim3(128); cfg.stream = st; cfg.attrs = at; cfg.numAttrs = 1;
    cfg.blockDim = dim3(512); cfg.dynamicSmemBytes = K2_SMEM;
    cudaLaunchKernelEx(&cfg, k2_kernel, tmQKV);
    k3_kernel<<<128, 384, K3_SMEM, st>>>(tmA2, tmWo, tmW2, (bf16*)d_out);
}
```

```cpp
#include <cuda_runtime.h>
#include <cuda_bf16.h>
#include <cuda.h>
#include <stdint.h>

typedef __nv_bfloat16 bf16;

constexpr int S_ = 2048, D_ = 512, F_ = 1376;
constexpr int KA2 = D_ + F_;
constexpr int FCH = 176;

__device__ bf16  g_qkv[8 * S_ * 192];
__device__ bf16  g_a2[S_ * KA2];
__device__ float g_gate[S_];

#define TS(k, cond) do { } while (0)

__device__ __forceinline__ uint32_t smem_u32(const void* p) { return (uint32_t)__cvta_generic_to_shared(p); }
__device__ __forceinline__ void mbar_init(uint32_t bar, uint32_t count) {
    asm volatile("mbarrier.init.shared::cta.b64 [%0], %1;" :: "r"(bar), "r"(count) : "memory");
}
__device__ __forceinline__ void mbar_expect_tx(uint32_t bar, uint32_t bytes) {
    asm volatile("mbarrier.arrive.expect_tx.shared::cta.b64 _, [%0], %1;" :: "r"(bar), "r"(bytes) : "memory");
}
__device__ __forceinline__ void mbar_arrive(uint32_t bar) {
    asm volatile("mbarrier.arrive.shared::cta.b64 _, [%0];" :: "r"(bar) : "memory");
}
__device__ __forceinline__ bool mbar_try_wait(uint32_t bar, uint32_t parity) {
    uint32_t ok;
    asm volatile("{\n.reg .pred p;\nmbarrier.try_wait.parity.shared::cta.b64 p, [%1], %2;\nselp.u32 %0, 1, 0, p;\n}"
                 : "=r"(ok) : "r"(bar), "r"(parity) : "memory");
    return ok != 0;
}
__device__ __forceinline__ void mbar_wait(uint32_t bar, uint32_t parity) {
    for (uint32_t it = 0; it < (1u << 22); ++it) { if (mbar_try_wait(bar, parity)) break; }
}
__device__ __forceinline__ void tma_load_2d(uint32_t dst, const CUtensorMap* map, int c0, int c1, uint32_t bar) {
    asm volatile("cp.async.bulk.tensor.2d.shared::cluster.global.mbarrier::complete_tx::bytes [%0], [%1, {%3, %4}], [%2];"
                 :: "r"(dst), "l"(map), "r"(bar), "r"(c0), "r"(c1) : "memory");
}
__device__ __forceinline__ void l2_prefetch(const void* p, uint32_t bytes) {
    asm volatile("cp.async.bulk.prefetch.L2.global [%0], %1;" :: "l"(p), "r"(bytes) : "memory");
}
__device__ __forceinline__ void fence_barrier_init() { asm volatile("fence.mbarrier_init.release.cluster;" ::: "memory"); }
__device__ __forceinline__ void wgmma_fence()  { asm volatile("wgmma.fence.sync.aligned;" ::: "memory"); }
__device__ __forceinline__ void wgmma_commit() { asm volatile("wgmma.commit_group.sync.aligned;" ::: "memory"); }
template <int N> __device__ __forceinline__ void wgmma_wait() { asm volatile("wgmma.wait_group.sync.aligned %0;" :: "n"(N) : "memory"); }
template <int R> __device__ __forceinline__ void reg_alloc()   { asm volatile("setmaxnreg.inc.sync.aligned.u32 %0;" :: "n"(R)); }
template <int R> __device__ __forceinline__ void reg_dealloc() { asm volatile("setmaxnreg.dec.sync.aligned.u32 %0;" :: "n"(R)); }
__device__ __forceinline__ void bar_sync(int id, int n)   { asm volatile("bar.sync %0, %1;" :: "r"(id), "r"(n) : "memory"); }
__device__ __forceinline__ void bar_arrive(int id, int n) { asm volatile("bar.arrive %0, %1;" :: "r"(id), "r"(n) : "memory"); }

__device__ __forceinline__ uint64_t make_desc(uint32_t addr, uint32_t lbo, uint32_t sbo) {
    uint64_t d = (uint64_t)((addr & 0x3FFFF) >> 4);
    d |= (uint64_t)((lbo & 0x3FFFF) >> 4) << 16;
    d |= (uint64_t)((sbo & 0x3FFFF) >> 4) << 32;
    d |= (uint64_t)1 << 62;
    return d;
}

template <int TB>
__device__ __forceinline__ void wgmma_n64(float (&d)[32], uint64_t da, uint64_t db, int scale_d) {
    asm volatile("{\n.reg .pred p;\nsetp.ne.b32 p, %34, 0;\n"
        "wgmma.mma_async.sync.aligned.m64n64k16.f32.bf16.bf16 {%0, %1, %2, %3, %4, %5, %6, %7, %8, %9, %10, %11, %12, %13, %14, %15, %16, %17, %18, %19, %20, %21, %22, %23, %24, %25, %26, %27, %28, %29, %30, %31}, %32, %33, p, 1, 1, 0, %35;\n}\n"
        : "+f"(d[0]), "+f"(d[1]), "+f"(d[2]), "+f"(d[3]), "+f"(d[4]), "+f"(d[5]), "+f"(d[6]), "+f"(d[7]), "+f"(d[8]), "+f"(d[9]), "+f"(d[10]), "+f"(d[11]), "+f"(d[12]), "+f"(d[13]), "+f"(d[14]), "+f"(d[15]), "+f"(d[16]), "+f"(d[17]), "+f"(d[18]), "+f"(d[19]), "+f"(d[20]), "+f"(d[21]), "+f"(d[22]), "+f"(d[23]), "+f"(d[24]), "+f"(d[25]), "+f"(d[26]), "+f"(d[27]), "+f"(d[28]), "+f"(d[29]), "+f"(d[30]), "+f"(d[31])
        : "l"(da), "l"(db), "r"(scale_d), "n"(TB));
}

template <int TB>
__device__ __forceinline__ void wgmma_n128(float (&d)[64], uint64_t da, uint64_t db, int scale_d) {
    asm volatile("{\n.reg .pred p;\nsetp.ne.b32 p, %66, 0;\n"
        "wgmma.mma_async.sync.aligned.m64n128k16.f32.bf16.bf16 {%0, %1, %2, %3, %4, %5, %6, %7, %8, %9, %10, %11, %12, %13, %14, %15, %16, %17, %18, %19, %20, %21, %22, %23, %24, %25, %26, %27, %28, %29, %30, %31, %32, %33, %34, %35, %36, %37, %38, %39, %40, %41, %42, %43, %44, %45, %46, %47, %48, %49, %50, %51, %52, %53, %54, %55, %56, %57, %58, %59, %60, %61, %62, %63}, %64, %65, p, 1, 1, 0, %67;\n}\n"
        : "+f"(d[0]), "+f"(d[1]), "+f"(d[2]), "+f"(d[3]), "+f"(d[4]), "+f"(d[5]), "+f"(d[6]), "+f"(d[7]), "+f"(d[8]), "+f"(d[9]), "+f"(d[10]), "+f"(d[11]), "+f"(d[12]), "+f"(d[13]), "+f"(d[14]), "+f"(d[15]), "+f"(d[16]), "+f"(d[17]), "+f"(d[18]), "+f"(d[19]), "+f"(d[20]), "+f"(d[21]), "+f"(d[22]), "+f"(d[23]), "+f"(d[24]), "+f"(d[25]), "+f"(d[26]), "+f"(d[27]), "+f"(d[28]), "+f"(d[29]), "+f"(d[30]), "+f"(d[31]), "+f"(d[32]), "+f"(d[33]), "+f"(d[34]), "+f"(d[35]), "+f"(d[36]), "+f"(d[37]), "+f"(d[38]), "+f"(d[39]), "+f"(d[40]), "+f"(d[41]), "+f"(d[42]), "+f"(d[43]), "+f"(d[44]), "+f"(d[45]), "+f"(d[46]), "+f"(d[47]), "+f"(d[48]), "+f"(d[49]), "+f"(d[50]), "+f"(d[51]), "+f"(d[52]), "+f"(d[53]), "+f"(d[54]), "+f"(d[55]), "+f"(d[56]), "+f"(d[57]), "+f"(d[58]), "+f"(d[59]), "+f"(d[60]), "+f"(d[61]), "+f"(d[62]), "+f"(d[63])
        : "l"(da), "l"(db), "r"(scale_d), "n"(TB));
}

template <int TB>
__device__ __forceinline__ void wgmma_n176(float (&d)[88], uint64_t da, uint64_t db, int scale_d) {
    asm volatile("{\n.reg .pred p;\nsetp.ne.b32 p, %90, 0;\n"
        "wgmma.mma_async.sync.aligned.m64n176k16.f32.bf16.bf16 {%0, %1, %2, %3, %4, %5, %6, %7, %8, %9, %10, %11, %12, %13, %14, %15, %16, %17, %18, %19, %20, %21, %22, %23, %24, %25, %26, %27, %28, %29, %30, %31, %32, %33, %34, %35, %36, %37, %38, %39, %40, %41, %42, %43, %44, %45, %46, %47, %48, %49, %50, %51, %52, %53, %54, %55, %56, %57, %58, %59, %60, %61, %62, %63, %64, %65, %66, %67, %68, %69, %70, %71, %72, %73, %74, %75, %76, %77, %78, %79, %80, %81, %82, %83, %84, %85, %86, %87}, %88, %89, p, 1, 1, 0, %91;\n}\n"
        : "+f"(d[0]), "+f"(d[1]), "+f"(d[2]), "+f"(d[3]), "+f"(d[4]), "+f"(d[5]), "+f"(d[6]), "+f"(d[7]), "+f"(d[8]), "+f"(d[9]), "+f"(d[10]), "+f"(d[11]), "+f"(d[12]), "+f"(d[13]), "+f"(d[14]), "+f"(d[15]), "+f"(d[16]), "+f"(d[17]), "+f"(d[18]), "+f"(d[19]), "+f"(d[20]), "+f"(d[21]), "+f"(d[22]), "+f"(d[23]), "+f"(d[24]), "+f"(d[25]), "+f"(d[26]), "+f"(d[27]), "+f"(d[28]), "+f"(d[29]), "+f"(d[30]), "+f"(d[31]), "+f"(d[32]), "+f"(d[33]), "+f"(d[34]), "+f"(d[35]), "+f"(d[36]), "+f"(d[37]), "+f"(d[38]), "+f"(d[39]), "+f"(d[40]), "+f"(d[41]), "+f"(d[42]), "+f"(d[43]), "+f"(d[44]), "+f"(d[45]), "+f"(d[46]), "+f"(d[47]), "+f"(d[48]), "+f"(d[49]), "+f"(d[50]), "+f"(d[51]), "+f"(d[52]), "+f"(d[53]), "+f"(d[54]), "+f"(d[55]), "+f"(d[56]), "+f"(d[57]), "+f"(d[58]), "+f"(d[59]), "+f"(d[60]), "+f"(d[61]), "+f"(d[62]), "+f"(d[63]), "+f"(d[64]), "+f"(d[65]), "+f"(d[66]), "+f"(d[67]), "+f"(d[68]), "+f"(d[69]), "+f"(d[70]), "+f"(d[71]), "+f"(d[72]), "+f"(d[73]), "+f"(d[74]), "+f"(d[75]), "+f"(d[76]), "+f"(d[77]), "+f"(d[78]), "+f"(d[79]), "+f"(d[80]), "+f"(d[81]), "+f"(d[82]), "+f"(d[83]), "+f"(d[84]), "+f"(d[85]), "+f"(d[86]), "+f"(d[87])
        : "l"(da), "l"(db), "r"(scale_d), "n"(TB));
}

template <int TB>
__device__ __forceinline__ void wgmma_n192(float (&d)[96], uint64_t da, uint64_t db, int scale_d) {
    asm volatile("{\n.reg .pred p;\nsetp.ne.b32 p, %98, 0;\n"
        "wgmma.mma_async.sync.aligned.m64n192k16.f32.bf16.bf16 {%0, %1, %2, %3, %4, %5, %6, %7, %8, %9, %10, %11, %12, %13, %14, %15, %16, %17, %18, %19, %20, %21, %22, %23, %24, %25, %26, %27, %28, %29, %30, %31, %32, %33, %34, %35, %36, %37, %38, %39, %40, %41, %42, %43, %44, %45, %46, %47, %48, %49, %50, %51, %52, %53, %54, %55, %56, %57, %58, %59, %60, %61, %62, %63, %64, %65, %66, %67, %68, %69, %70, %71, %72, %73, %74, %75, %76, %77, %78, %79, %80, %81, %82, %83, %84, %85, %86, %87, %88, %89, %90, %91, %92, %93, %94, %95}, %96, %97, p, 1, 1, 0, %99;\n}\n"
        : "+f"(d[0]), "+f"(d[1]), "+f"(d[2]), "+f"(d[3]), "+f"(d[4]), "+f"(d[5]), "+f"(d[6]), "+f"(d[7]), "+f"(d[8]), "+f"(d[9]), "+f"(d[10]), "+f"(d[11]), "+f"(d[12]), "+f"(d[13]), "+f"(d[14]), "+f"(d[15]), "+f"(d[16]), "+f"(d[17]), "+f"(d[18]), "+f"(d[19]), "+f"(d[20]), "+f"(d[21]), "+f"(d[22]), "+f"(d[23]), "+f"(d[24]), "+f"(d[25]), "+f"(d[26]), "+f"(d[27]), "+f"(d[28]), "+f"(d[29]), "+f"(d[30]), "+f"(d[31]), "+f"(d[32]), "+f"(d[33]), "+f"(d[34]), "+f"(d[35]), "+f"(d[36]), "+f"(d[37]), "+f"(d[38]), "+f"(d[39]), "+f"(d[40]), "+f"(d[41]), "+f"(d[42]), "+f"(d[43]), "+f"(d[44]), "+f"(d[45]), "+f"(d[46]), "+f"(d[47]), "+f"(d[48]), "+f"(d[49]), "+f"(d[50]), "+f"(d[51]), "+f"(d[52]), "+f"(d[53]), "+f"(d[54]), "+f"(d[55]), "+f"(d[56]), "+f"(d[57]), "+f"(d[58]), "+f"(d[59]), "+f"(d[60]), "+f"(d[61]), "+f"(d[62]), "+f"(d[63]), "+f"(d[64]), "+f"(d[65]), "+f"(d[66]), "+f"(d[67]), "+f"(d[68]), "+f"(d[69]), "+f"(d[70]), "+f"(d[71]), "+f"(d[72]), "+f"(d[73]), "+f"(d[74]), "+f"(d[75]), "+f"(d[76]), "+f"(d[77]), "+f"(d[78]), "+f"(d[79]), "+f"(d[80]), "+f"(d[81]), "+f"(d[82]), "+f"(d[83]), "+f"(d[84]), "+f"(d[85]), "+f"(d[86]), "+f"(d[87]), "+f"(d[88]), "+f"(d[89]), "+f"(d[90]), "+f"(d[91]), "+f"(d[92]), "+f"(d[93]), "+f"(d[94]), "+f"(d[95])
        : "l"(da), "l"(db), "r"(scale_d), "n"(TB));
}

__device__ __forceinline__ uint32_t pack_bf16(float lo, float hi) {
    uint32_t r;
    asm("cvt.rn.bf16x2.f32 %0, %1, %2;" : "=r"(r) : "f"(hi), "f"(lo));
    return r;
}
__device__ __forceinline__ float bf_lo(uint32_t v) { return __uint_as_float(v << 16); }
__device__ __forceinline__ float bf_hi(uint32_t v) { return __uint_as_float(v & 0xffff0000u); }

__device__ __forceinline__ void quad_transpose(uint32_t (&w)[4], int q) {
    const bool o1 = q & 1, o2 = q & 2;
    {
        uint32_t s0 = o1 ? w[0] : w[1], s1 = o1 ? w[2] : w[3];
        s0 = __shfl_xor_sync(0xffffffffu, s0, 1); s1 = __shfl_xor_sync(0xffffffffu, s1, 1);
        if (o1) { w[0] = s0; w[2] = s1; } else { w[1] = s0; w[3] = s1; }
    }
    {
        uint32_t s0 = o2 ? w[0] : w[2], s1 = o2 ? w[1] : w[3];
        s0 = __shfl_xor_sync(0xffffffffu, s0, 2); s1 = __shfl_xor_sync(0xffffffffu, s1, 2);
        if (o2) { w[0] = s0; w[1] = s1; } else { w[2] = s0; w[3] = s1; }
    }
}

__device__ __forceinline__ float ex2(float x) { float y; asm("ex2.approx.ftz.f32 %0, %1;" : "=f"(y) : "f"(x)); return y; }
__device__ __forceinline__ float rcp(float x) { float y; asm("rcp.approx.ftz.f32 %0, %1;" : "=f"(y) : "f"(x)); return y; }

__device__ __forceinline__ float ex2v(float x) { float y; asm volatile("ex2.approx.ftz.f32 %0, %1;" : "=f"(y) : "f"(x)); return y; }
__device__ __forceinline__ float rcpv(float x) { float y; asm volatile("rcp.approx.ftz.f32 %0, %1;" : "=f"(y) : "f"(x)); return y; }
__device__ __forceinline__ float mish_f(float h) {
    const float e = ex2v(1.4426950408889634f * fminf(h, 20.f));
    const float n = fmaf(e, e, e + e);
    return h * n * rcpv(n + 2.f);
}

__device__ __forceinline__ void pdl_wait()   { asm volatile("griddepcontrol.wait;" ::: "memory"); }
__device__ __forceinline__ void pdl_launch() { asm volatile("griddepcontrol.launch_dependents;" ::: "memory"); }

constexpr int K1_STAGES = 4;
constexpr int K1_XBYTES = 128 * 512 * 2;
constexpr int K1_BSTAGE = 3 * 8192;
constexpr int K1_SMEM   = K1_XBYTES + K1_STAGES * K1_BSTAGE + 2048   + 1024  ;

__global__ void __launch_bounds__(384, 1)
k1_kernel(const __grid_constant__ CUtensorMap tmX, const __grid_constant__ CUtensorMap tmWqkv,
          const __grid_constant__ CUtensorMap tmW1, const bf16* __restrict__ b1,
          const bf16* __restrict__ gate_w, const bf16* __restrict__ w1p, const bf16* __restrict__ wqkvp,
          const bf16* __restrict__ w2p, const bf16* __restrict__ wop)
{

    extern __shared__ uint8_t smem_raw[];
    const uint32_t sbase = (smem_u32(smem_raw) + 1023u) & ~1023u;
    uint8_t* sgen = smem_raw + (sbase - smem_u32(smem_raw));
    const uint32_t sX = sbase;
    const uint32_t sB = sbase + K1_XBYTES;
    const uint32_t sBar = sB + K1_STAGES * K1_BSTAGE;
    const uint32_t x_full = sBar;
    const uint32_t b_full = sBar + 64;
    const uint32_t b_empty = sBar + 96;
    float* sGate = (float*)(sgen + K1_XBYTES + K1_STAGES * K1_BSTAGE + 128);
    uint8_t* sGw = sgen + K1_XBYTES + K1_STAGES * K1_BSTAGE + 640;
    uint32_t* sBias = (uint32_t*)(sgen + K1_XBYTES + K1_STAGES * K1_BSTAGE + 1664);

    const int rb = blockIdx.x >> 3, j = blockIdx.x & 7;
    const int tid = threadIdx.x, lane = tid & 31;
    const int warp = __shfl_sync(0xffffffffu, tid >> 5, 0), wg = warp >> 2;
    TS(0, tid == 0);
    pdl_launch();

    if (tid == 0) {
        for (int i = 0; i < 8; i++) mbar_init(x_full + 8 * i, 1);
        for (int i = 0; i < K1_STAGES; i++) { mbar_init(b_full + 8 * i, 1); mbar_init(b_empty + 8 * i, 8); }
        fence_barrier_init();
    }
    __syncthreads();

    if (wg == 2) {
        reg_dealloc<40>();
        if (tid == 288) {
            const int b = blockIdx.x;
            mbar_wait(b_full + 8, 0);
            l2_prefetch((const uint8_t*)wqkvp + b * 12288, 12288);
            l2_prefetch((const uint8_t*)w2p + b * 11008, 11008);
            l2_prefetch((const uint8_t*)wop + b * 4096, 4096);
        }
        if (tid == 256) {
            for (int it = 0; it < 16; it++) {
                if (it < 8) {
                    mbar_expect_tx(x_full + 8 * it, 16384);
                    tma_load_2d(sX + it * 16384, &tmX, it * 64, rb * 128, x_full + 8 * it);
                }
                const int st = it & 3;
                if (it >= K1_STAGES) mbar_wait(b_empty + 8 * st, ((it >> 2) - 1) & 1);
                mbar_expect_tx(b_full + 8 * st, K1_BSTAGE);
                const uint32_t dst = sB + st * K1_BSTAGE;
                if (it < 8) {
                    for (int b = 0; b < 3; b++) tma_load_2d(dst + b * 8192, &tmW1, j * FCH + b * 64, it * 64, b_full + 8 * st);
                } else {
                    for (int b = 0; b < 3; b++) tma_load_2d(dst + b * 8192, &tmWqkv, b * 512 + j * 64, (it - 8) * 64, b_full + 8 * st);
                }
            }
        }
    } else {
        reg_alloc<232>();
        if (tid < 64) ((uint4*)sGw)[tid] = __ldg((const uint4*)gate_w + tid);
        else if (tid < 64 + 88) {
            const int c = j * FCH + (tid - 64) * 2;
            sBias[tid - 64] = c < F_ ? __ldg((const uint32_t*)(b1 + c)) : 0u;
        }
        bar_sync(3, 256);
        const int t128 = tid & 127, w4 = warp & 3, q = lane & 3;
        float accF[88], accQ[96];
        const uint64_t da0 = make_desc(sX + wg * 8192, 16, 1024);
        const uint64_t db0 = make_desc(sB, 8192, 1024);
        float gs = 0.f;
        const int grow = wg * 64 + (t128 >> 1), ghalf = t128 & 1;
#pragma unroll
        for (int kc = 0; kc < 8; kc++) {
            const int st = kc & 3;
            mbar_wait(x_full + 8 * kc, 0);
            mbar_wait(b_full + 8 * st, (kc >> 2) & 1);
            TS(1, tid == 0 && kc == 0); TS(2, tid == 0 && kc == 4);
            wgmma_fence();
#pragma unroll
            for (int k16 = 0; k16 < 4; k16++) {
                wgmma_n176<1>(accF, da0 + (kc * 1024 + k16 * 2), db0 + (st * (K1_BSTAGE >> 4) + k16 * 128), (kc | k16) != 0);
            }
            wgmma_commit();
#pragma unroll
            for (int c = 0; c < 4; c++) {
                const int cc = ghalf * 4 + c;
                const uint4 xv = *(const uint4*)(sgen + kc * 16384 + grow * 128 + ((cc ^ (grow & 7)) << 4));
                const uint4 gv = *(const uint4*)(sGw + kc * 128 + cc * 16);
                gs = fmaf(bf_lo(xv.x), bf_lo(gv.x), gs); gs = fmaf(bf_hi(xv.x), bf_hi(gv.x), gs);
                gs = fmaf(bf_lo(xv.y), bf_lo(gv.y), gs); gs = fmaf(bf_hi(xv.y), bf_hi(gv.y), gs);
                gs = fmaf(bf_lo(xv.z), bf_lo(gv.z), gs); gs = fmaf(bf_hi(xv.z), bf_hi(gv.z), gs);
                gs = fmaf(bf_lo(xv.w), bf_lo(gv.w), gs); gs = fmaf(bf_hi(xv.w), bf_hi(gv.w), gs);
            }
            if (kc > 0) { wgmma_wait<1>(); if (lane == 0) mbar_arrive(b_empty + 8 * ((kc - 1) & 3)); }
        }
        gs += __shfl_xor_sync(0xffffffffu, gs, 1);
        {
            const float g = 1.f / (1.f + __expf(-gs));
            if (ghalf == 0) {
                sGate[grow] = g;
                if (j == 0) g_gate[rb * 128 + grow] = g;
            }
        }
        wgmma_wait<0>();
        if (lane == 0) mbar_arrive(b_empty + 8 * 3);
        bar_sync(1 + wg, 128);
        TS(3, tid == 0);
        const int n0 = j * FCH;
        const int rl = wg * 64 + w4 * 16 + (lane >> 2);
        const float om0 = 1.f - sGate[rl], om1 = 1.f - sGate[rl + 8];
        bf16* frow0 = g_a2 + (size_t)(rb * 128 + rl) * KA2 + D_ + n0;
        bf16* frow1 = frow0 + 8 * KA2;
        auto ffn_chunk = [&](int u) {
            uint32_t w0[4], w1[4];
#pragma unroll
            for (int i = 0; i < 4; i++) {
                const int t = u * 4 + i;
                if (t < 22) {
                    const uint32_t bv = sBias[t * 4 + q];
                    const float bb0 = bf_lo(bv), bb1 = bf_hi(bv);
                    w0[i] = pack_bf16(mish_f(accF[t * 4 + 0] + bb0) * om0, mish_f(accF[t * 4 + 1] + bb1) * om0);
                    w1[i] = pack_bf16(mish_f(accF[t * 4 + 2] + bb0) * om1, mish_f(accF[t * 4 + 3] + bb1) * om1);
                } else { w0[i] = 0; w1[i] = 0; }
            }
            quad_transpose(w0, q);
            quad_transpose(w1, q);
            const int c = (u * 4 + q) * 8;
            if (c < FCH && n0 + c < F_) {
                *(uint4*)(frow0 + c) = make_uint4(w0[0], w0[1], w0[2], w0[3]);
                *(uint4*)(frow1 + c) = make_uint4(w1[0], w1[1], w1[2], w1[3]);
            }
        };
#pragma unroll
        for (int kc = 0; kc < 8; kc++) {
            const int st = kc & 3;
            mbar_wait(b_full + 8 * st, ((kc + 8) >> 2) & 1);
            wgmma_fence();
#pragma unroll
            for (int k16 = 0; k16 < 4; k16++) {
                wgmma_n192<1>(accQ, da0 + (kc * 1024 + k16 * 2), db0 + (st * (K1_BSTAGE >> 4) + k16 * 128), (kc | k16) != 0);
            }
            wgmma_commit();
            if (kc < 6) ffn_chunk(kc);
            if (kc > 0) { wgmma_wait<1>(); if (lane == 0) mbar_arrive(b_empty + 8 * ((kc - 1) & 3)); }
        }
        wgmma_wait<0>();
        TS(4, tid == 0);
        {
            bf16* orow0 = g_qkv + ((size_t)j * S_ + rb * 128 + rl) * 192;
            bf16* orow1 = orow0 + 8 * 192;
#pragma unroll
            for (int u = 0; u < 6; u++) {
                uint32_t w0[4], w1[4];
#pragma unroll
                for (int i = 0; i < 4; i++) {
                    const int t = u * 4 + i;
                    w0[i] = pack_bf16(accQ[t * 4 + 0], accQ[t * 4 + 1]);
                    w1[i] = pack_bf16(accQ[t * 4 + 2], accQ[t * 4 + 3]);
                }
                quad_transpose(w0, q);
                quad_transpose(w1, q);
                const int c = (u * 4 + q) * 8;
                *(uint4*)(orow0 + c) = make_uint4(w0[0], w0[1], w0[2], w0[3]);
                *(uint4*)(orow1 + c) = make_uint4(w1[0], w1[1], w1[2], w1[3]);
            }
        }
        TS(5, tid == 0);
    }
}

__device__ __forceinline__ void ldsm_x4(uint32_t (&r)[4], uint32_t addr) {
    asm("ldmatrix.sync.aligned.m8n8.x4.shared.b16 {%0,%1,%2,%3}, [%4];"
                 : "=r"(r[0]), "=r"(r[1]), "=r"(r[2]), "=r"(r[3]) : "r"(addr));
}
__device__ __forceinline__ void ldsm_x4_t(uint32_t (&r)[4], uint32_t addr) {
    asm("ldmatrix.sync.aligned.m8n8.x4.trans.shared.b16 {%0,%1,%2,%3}, [%4];"
                 : "=r"(r[0]), "=r"(r[1]), "=r"(r[2]), "=r"(r[3]) : "r"(addr));
}
__device__ __forceinline__ void mma16816(float (&d)[4], const uint32_t (&a)[4], uint32_t b0, uint32_t b1) {
    asm("mma.sync.aligned.m16n8k16.row.col.f32.bf16.bf16.f32 {%0,%1,%2,%3}, {%4,%5,%6,%7}, {%8,%9}, {%0,%1,%2,%3};"
                 : "+f"(d[0]), "+f"(d[1]), "+f"(d[2]), "+f"(d[3])
                 : "r"(a[0]), "r"(a[1]), "r"(a[2]), "r"(a[3]), "r"(b0), "r"(b1));
}
__device__ __forceinline__ void mma16816_z(float (&d)[4], const uint32_t (&a)[4], uint32_t b0, uint32_t b1) {
    asm("mma.sync.aligned.m16n8k16.row.col.f32.bf16.bf16.f32 {%0,%1,%2,%3}, {%4,%5,%6,%7}, {%8,%9}, {%10,%10,%10,%10};"
                 : "=f"(d[0]), "=f"(d[1]), "=f"(d[2]), "=f"(d[3])
                 : "r"(a[0]), "r"(a[1]), "r"(a[2]), "r"(a[3]), "r"(b0), "r"(b1), "f"(0.f));
}

constexpr int KV_PITCH = 128;

template <int EDGE, bool HEAD>
__device__ __forceinline__ void blk_scores(float (&s)[2][4], const uint32_t (&qa)[4], uint32_t kaddr, bool dead, int r0, int c0)
{
    uint32_t kf[4];
    ldsm_x4(kf, kaddr);
    mma16816_z(s[0], qa, kf[0], kf[1]);
    mma16816_z(s[1], qa, kf[2], kf[3]);
#pragma unroll
    for (int t = 0; t < 2; t++)
#pragma unroll
        for (int e = 0; e < 4; e++) {
            const int r = r0 + (e >> 1) * 8, c = t * 8 + c0 + (e & 1);
            if (EDGE == 1 && c <= r) s[t][e] = -1e30f;
            if (EDGE == 2 && c > r) s[t][e] = -1e30f;
            if (HEAD && dead) s[t][e] = -1e30f;
        }
}
__device__ __forceinline__ void blk_max(const float (&s)[2][4], float& n0, float& n1) {
    n0 = fmaxf(n0, fmaxf(fmaxf(s[0][0], s[0][1]), fmaxf(s[1][0], s[1][1])));
    n1 = fmaxf(n1, fmaxf(fmaxf(s[0][2], s[0][3]), fmaxf(s[1][2], s[1][3])));
}
__device__ __forceinline__ void blk_pv(const float (&s)[2][4], float mc0, float mc1, float (&l)[4],
                                       float (&o)[2][4], uint32_t vaddr) {
    const float C = 0.25f * 1.4426950408889634f;
    uint32_t pa[4];
#pragma unroll
    for (int t = 0; t < 2; t++) {
        const float p0 = ex2(fmaf(s[t][0], C, -mc0)), p1 = ex2(fmaf(s[t][1], C, -mc0));
        const float p2 = ex2(fmaf(s[t][2], C, -mc1)), p3 = ex2(fmaf(s[t][3], C, -mc1));
        pa[2 * t] = pack_bf16(p0, p1); pa[2 * t + 1] = pack_bf16(p2, p3);
    }
    uint32_t vf[4];
    ldsm_x4_t(vf, vaddr);
    mma16816(o[0], pa, vf[0], vf[1]);
    mma16816(o[1], pa, vf[2], vf[3]);
    mma16816(l, pa, 0x3F803F80u, 0x3F803F80u);
}
__device__ __forceinline__ void quad_max(float& n0, float& n1) {
    n0 = fmaxf(n0, __shfl_xor_sync(0xffffffffu, n0, 1)); n1 = fmaxf(n1, __shfl_xor_sync(0xffffffffu, n1, 1));
    n0 = fmaxf(n0, __shfl_xor_sync(0xffffffffu, n0, 2)); n1 = fmaxf(n1, __shfl_xor_sync(0xffffffffu, n1, 2));
}
template <int NC, int NN, bool FIRST, bool NEXT_IS_EDGE, bool HEAD>
__device__ __forceinline__ void pipe_step(const float (&sc)[5][2][4], float (&sn)[5][2][4], const uint32_t (&qa)[4],
                                          uint32_t ka, uint32_t va, int kc, int kn, int kb0, int r0, int c0,
                                          float& m0, float& m1, float& n0, float& n1, float (&l)[4], float (&o)[2][4])
{
    const float C = 0.25f * 1.4426950408889634f;
    const float mc0 = n0 * C, mc1 = n1 * C;
    if (!FIRST) {
        const float a0 = ex2(fmaf(m0, C, -mc0)), a1 = ex2(fmaf(m1, C, -mc1));
        l[0] *= a0; l[2] *= a1;
        o[0][0] *= a0; o[0][1] *= a0; o[1][0] *= a0; o[1][1] *= a0;
        o[0][2] *= a1; o[0][3] *= a1; o[1][2] *= a1; o[1][3] *= a1;
    }
    m0 = n0; m1 = n1;
#pragma unroll
    for (int b = 0; b < NC; b++) {
        if (b < NN) {
            if (NEXT_IS_EDGE && b == 0) blk_scores<1, HEAD>(sn[b], qa, ka + (kn + b) * 16 * KV_PITCH, kn + b < kb0, r0, c0);
            else                        blk_scores<0, HEAD>(sn[b], qa, ka + (kn + b) * 16 * KV_PITCH, kn + b < kb0, r0, c0);
        }
        blk_pv(sc[b], mc0, mc1, l, o, va + (kc + b) * 16 * KV_PITCH);
        if (b < NN) blk_max(sn[b], n0, n1);
    }
    if (NN > 0) quad_max(n0, n1);
}

__device__ __forceinline__ void kv_need(uint32_t kvbar, int blk, uint32_t& ka, uint32_t& va) {
    mbar_wait(kvbar + 8 * blk, 0);
    asm volatile("" : "+r"(ka), "+r"(va) :: "memory");
}
template <bool HEAD>
__device__ __forceinline__ void attn_task(const uint32_t (&qa)[4], uint32_t ka, uint32_t va, int kb0, int lane, int qt, uint32_t kvbar,
                                          bf16* __restrict__ out  , float g0, float g1)
{
    const int r0 = lane >> 2, c0 = (lane & 3) * 2;
    float m0 = -1e30f, m1 = -1e30f, n0 = -1e30f, n1 = -1e30f;
    float l[4] = {0.f, 0.f, 0.f, 0.f};
    float o[2][4] = {{0.f, 0.f, 0.f, 0.f}, {0.f, 0.f, 0.f, 0.f}};
    float sa[5][2][4], sb[5][2][4];
    kv_need(kvbar, 2, ka, va);
    if (qt < 4) kv_need(kvbar, 1, ka, va);
#pragma unroll
    for (int b = 0; b < 5; b++) {
        if (b == 4) blk_scores<2, HEAD>(sa[b], qa, ka + (12 + b) * 16 * KV_PITCH, false, r0, c0);
        else        blk_scores<0, HEAD>(sa[b], qa, ka + (12 + b) * 16 * KV_PITCH, 12 + b < kb0, r0, c0);
        blk_max(sa[b], n0, n1);
    }
    quad_max(n0, n1);
    kv_need(kvbar, 1, ka, va);
    if (HEAD) {
        pipe_step<5, 0, true, false, HEAD>(sa, sb, qa, ka, va, 12, 0, kb0, r0, c0, m0, m1, n0, n1, l, o);
        kv_need(kvbar, 0, ka, va);
#pragma unroll 1
        for (int kc = 8; kc >= 0 && kb0 < kc + 4; kc -= 4) {
#pragma unroll
            for (int b = 0; b < 4; b++) {
                blk_scores<0, HEAD>(sa[b], qa, ka + (kc + b) * 16 * KV_PITCH, kc + b < kb0, r0, c0);
                blk_max(sa[b], n0, n1);
            }
            quad_max(n0, n1);
            pipe_step<4, 0, false, false, HEAD>(sa, sb, qa, ka, va, kc, 0, kb0, r0, c0, m0, m1, n0, n1, l, o);
        }
    } else {
        pipe_step<5, 4, true,  false, HEAD>(sa, sb, qa, ka, va, 12, 8, kb0, r0, c0, m0, m1, n0, n1, l, o);
        if (qt < 4) kv_need(kvbar, 0, ka, va);
        pipe_step<4, 4, false, false, HEAD>(sb, sa, qa, ka, va, 8, 4, kb0, r0, c0, m0, m1, n0, n1, l, o);
        kv_need(kvbar, 0, ka, va);
        pipe_step<4, 4, false, true,  HEAD>(sa, sb, qa, ka, va, 4, 0, kb0, r0, c0, m0, m1, n0, n1, l, o);
        pipe_step<4, 0, false, false, HEAD>(sb, sa, qa, ka, va, 0, 0, kb0, r0, c0, m0, m1, n0, n1, l, o);
    }
    const float f0 = __fdividef(g0, l[0]), f1 = __fdividef(g1, l[2]);
#pragma unroll
    for (int t = 0; t < 2; t++) {
        *(uint32_t*)(out + (size_t)r0 * KA2 + t * 8 + c0) = pack_bf16(o[t][0] * f0, o[t][1] * f0);
        *(uint32_t*)(out + (size_t)(r0 + 8) * KA2 + t * 8 + c0) = pack_bf16(o[t][2] * f1, o[t][3] * f1);
    }
}

__device__ unsigned int g_epoch;
__device__ unsigned int g_done;
__device__ unsigned int g_flag_att[128];

constexpr int G_STAGES = 9;
constexpr int G_PRE = 5;
constexpr int G_STAGE = 16384 + 8192;
constexpr int G_KSTEPS = 30;
constexpr int K23_OFF_KV = G_PRE * G_STAGE;
constexpr int K23_OFF_BAR = K23_OFF_KV + 2 * 384 * KV_PITCH;
constexpr int K23_SMEM = K23_OFF_BAR + 256 + 1024;

__global__ void __launch_bounds__(512, 1)
k23_kernel(const __grid_constant__ CUtensorMap tmQKV, const __grid_constant__ CUtensorMap tmA2,
           const __grid_constant__ CUtensorMap tmWo, const __grid_constant__ CUtensorMap tmW2, bf16* __restrict__ out)
{
    extern __shared__ uint8_t smem_raw[];
    const uint32_t sbase = (smem_u32(smem_raw) + 1023u) & ~1023u;
    uint8_t* sgen = smem_raw + (sbase - smem_u32(smem_raw));
    const uint32_t sK = sbase + K23_OFF_KV, sV = sK + 384 * KV_PITCH;
    const uint32_t sBar = sbase + K23_OFF_BAR;
    const uint32_t full = sBar, empty = sBar + 80, kv_full = sBar + 160;
    const int rb = blockIdx.x >> 3, j = blockIdx.x & 7;
    const int tid = threadIdx.x, lane = tid & 31;
    const int warp = __shfl_sync(0xffffffffu, tid >> 5, 0), wg = warp >> 2;

    auto gload = [&](int ks) {
        const int st = ks % G_STAGES;
        mbar_expect_tx(full + 8 * st, G_STAGE);
        const uint32_t dst = sbase + st * G_STAGE;
        if (ks < 22) {
            tma_load_2d(dst, &tmA2, D_ + ks * 64, rb * 128, full + 8 * st);
            tma_load_2d(dst + 16384, &tmW2, j * 64, ks * 64, full + 8 * st);
        } else {
            tma_load_2d(dst, &tmA2, (ks - 22) * 64, rb * 128, full + 8 * st);
            tma_load_2d(dst + 16384, &tmWo, j * 64, (ks - 22) * 64, full + 8 * st);
        }
    };

    if (tid == 0) {
        for (int i = 0; i < 3; i++) mbar_init(kv_full + 8 * i, 1);
        for (int i = 0; i < G_STAGES; i++) { mbar_init(full + 8 * i, 1); mbar_init(empty + 8 * i, 8); }
        fence_barrier_init();
    }
    pdl_wait();
    TS(6, tid == 0);
    const unsigned int ep = *(volatile unsigned int*)&g_epoch + 1;
    if (tid == 0) {
        for (int i = 0; i < 3; i++) {
            const uint32_t bar = kv_full + 8 * (2 - i);
            if (rb - i >= 0) {
                const int row = j * S_ + (rb - i) * 128;
                mbar_expect_tx(bar, 2 * 16384);
                tma_load_2d(sK + (2 - i) * 16384, &tmQKV, 64, row, bar);
                tma_load_2d(sV + (2 - i) * 16384, &tmQKV, 128, row, bar);
            } else {
                mbar_arrive(bar);
            }
        }
        for (int ks = 0; ks < G_PRE; ks++) gload(ks);
    }
    if (rb < 2) {
        for (int i = tid; i < (2 - rb) * 1024; i += 512) {
            *(uint4*)(sgen + K23_OFF_KV + i * 16) = make_uint4(0, 0, 0, 0);
            *(uint4*)(sgen + K23_OFF_KV + 384 * KV_PITCH + i * 16) = make_uint4(0, 0, 0, 0);
        }
    }
    {
        const int qt = warp & 7, h0 = (warp >> 3) * 2;
        const int q0g = rb * 128 + qt * 16;
        const int r0 = lane >> 2, c0 = (lane & 3) * 2;
        const bf16* qsrc = g_qkv + ((size_t)j * S_ + q0g) * 192 + h0 * 16;
        uint32_t qa[4], qn[4];
        qa[0] = *(const uint32_t*)(qsrc + (size_t)r0 * 192 + c0);
        qa[1] = *(const uint32_t*)(qsrc + (size_t)(r0 + 8) * 192 + c0);
        qa[2] = *(const uint32_t*)(qsrc + (size_t)r0 * 192 + c0 + 8);
        qa[3] = *(const uint32_t*)(qsrc + (size_t)(r0 + 8) * 192 + c0 + 8);
        qn[0] = *(const uint32_t*)(qsrc + (size_t)r0 * 192 + 16 + c0);
        qn[1] = *(const uint32_t*)(qsrc + (size_t)(r0 + 8) * 192 + 16 + c0);
        qn[2] = *(const uint32_t*)(qsrc + (size_t)r0 * 192 + 16 + c0 + 8);
        qn[3] = *(const uint32_t*)(qsrc + (size_t)(r0 + 8) * 192 + 16 + c0 + 8);
        const float g0 = g_gate[q0g + r0], g1 = g_gate[q0g + r0 + 8];
        const int kb0 = q0g < 256 ? (256 - q0g) >> 4 : 0;
        __syncthreads();
        TS(7, tid == 0);
        const int krow = qt * 16 + (lane & 7) + ((lane >> 4) << 3);
        const int vrow = qt * 16 + (lane & 15);
#pragma unroll 1
        for (int hh = 0; hh < 2; hh++) {
            const int hl = h0 + hh;
            const uint32_t ka = sK + krow * KV_PITCH + (((2 * hl + ((lane >> 3) & 1)) ^ (lane & 7)) << 4);
            const uint32_t va = sV + vrow * KV_PITCH + (((2 * hl + (lane >> 4)) ^ (lane & 7)) << 4);
            if (rb < 2) attn_task<true>(qa, ka, va, kb0, lane, qt, kv_full, g_a2 + (size_t)q0g * KA2 + (j * 4 + hl) * 16, g0, g1);
            else        attn_task<false>(qa, ka, va, kb0, lane, qt, kv_full, g_a2 + (size_t)q0g * KA2 + (j * 4 + hl) * 16, g0, g1);
            TS(8 + hh, tid == 0);
            qa[0] = qn[0]; qa[1] = qn[1]; qa[2] = qn[2]; qa[3] = qn[3];
        }
    }
    __syncthreads();
    if (wg >= 2) {
        if (tid == 288) {
            __threadfence();
            asm volatile("st.release.gpu.global.u32 [%0], %1;" :: "l"(&g_flag_att[blockIdx.x]), "r"(ep) : "memory");
        }
        if (tid == 256) {
            asm volatile("fence.proxy.async;" ::: "memory");
            for (int ks = G_PRE; ks < G_KSTEPS; ks++) {
                if (ks >= G_STAGES) mbar_wait(empty + 8 * (ks % G_STAGES), ((ks / G_STAGES) - 1) & 1);
                if (ks == 22) {
                    for (int i = 0; i < 8; i++) {
                        for (uint32_t it = 0; it < (1u << 22); ++it) {
                            unsigned int x;
                            asm volatile("ld.acquire.gpu.global.u32 %0, [%1];" : "=r"(x) : "l"(&g_flag_att[rb * 8 + i]) : "memory");
                            if (x == ep) break;
                        }
                    }
                    asm volatile("fence.proxy.async;" ::: "memory");
                }
                gload(ks);
            }
        }
    } else {
        TS(10, tid == 0);
        float acc[32];
        const uint64_t da0 = make_desc(sbase + wg * 8192, 16, 1024);
        const uint64_t db0 = make_desc(sbase + 16384, 8192, 1024);
        for (int ks = 0; ks < G_KSTEPS; ks++) {
            const int st = ks % G_STAGES;
            mbar_wait(full + 8 * st, (ks / G_STAGES) & 1);
            TS(11, tid == 0 && ks == 0); TS(12, tid == 0 && ks == 8); TS(13, tid == 0 && ks == 22);
            wgmma_fence();
            const uint32_t so = (uint32_t)(st * G_STAGE) >> 4;
#pragma unroll
            for (int k16 = 0; k16 < 4; k16++)
                wgmma_n64<1>(acc, da0 + (so + k16 * 2), db0 + (so + k16 * 128), (ks | k16) != 0);
            wgmma_commit();
            if (ks > 0) { wgmma_wait<1>(); if (lane == 0) mbar_arrive(empty + 8 * ((ks - 1) % G_STAGES)); }
        }
        wgmma_wait<0>();
        TS(14, tid == 0);
        const int q = lane & 3;
        const int r = rb * 128 + wg * 64 + (warp & 3) * 16 + (lane >> 2);
        bf16* orow0 = out + (size_t)r * D_ + j * 64;
        bf16* orow1 = orow0 + 8 * D_;
#pragma unroll
        for (int u = 0; u < 2; u++) {
            uint32_t w0[4], w1[4];
#pragma unroll
            for (int i = 0; i < 4; i++) {
                const int t = u * 4 + i;
                w0[i] = pack_bf16(acc[t * 4 + 0], acc[t * 4 + 1]);
                w1[i] = pack_bf16(acc[t * 4 + 2], acc[t * 4 + 3]);
            }
            quad_transpose(w0, q);
            quad_transpose(w1, q);
            const int c = (u * 4 + q) * 8;
            *(uint4*)(orow0 + c) = make_uint4(w0[0], w0[1], w0[2], w0[3]);
            *(uint4*)(orow1 + c) = make_uint4(w1[0], w1[1], w1[2], w1[3]);
        }
        TS(15, tid == 0);
        if (tid == 0) {
            __threadfence();
            if (atomicAdd(&g_done, 1u) == gridDim.x - 1) {
                g_done = 0;
                __threadfence();
                atomicAdd(&g_epoch, 1u);
            }
        }
    }
}

typedef CUresult (*PFN_encodeTiled)(CUtensorMap*, CUtensorMapDataType, cuuint32_t, void*, const cuuint64_t*,
                                    const cuuint64_t*, const cuuint32_t*, const cuuint32_t*, CUtensorMapInterleave,
                                    CUtensorMapSwizzle, CUtensorMapL2promotion, CUtensorMapFloatOOBfill);

static void make_map(PFN_encodeTiled enc, CUtensorMap* m, const void* ptr, uint64_t cols, uint64_t rows,
                     uint32_t box_cols, uint32_t box_rows)
{
    cuuint64_t dims[2] = {cols, rows};
    cuuint64_t strides[1] = {cols * 2};
    cuuint32_t box[2] = {box_cols, box_rows};
    cuuint32_t es[2] = {1, 1};
    enc(m, CU_TENSOR_MAP_DATA_TYPE_BFLOAT16, 2, const_cast<void*>(ptr), dims, strides, box, es,
        CU_TENSOR_MAP_INTERLEAVE_NONE, CU_TENSOR_MAP_SWIZZLE_128B, CU_TENSOR_MAP_L2_PROMOTION_L2_128B,
        CU_TENSOR_MAP_FLOAT_OOB_FILL_NONE);
}

extern "C" void kernel_launch(void* const* d_in, const int* in_sizes, int n_in, void* d_out, int out_size)
{
    const bf16* x    = (const bf16*)d_in[0];
    const bf16* wqkv = (const bf16*)d_in[1];
    const bf16* wo   = (const bf16*)d_in[2];
    const bf16* w1   = (const bf16*)d_in[4];
    const bf16* b1   = (const bf16*)d_in[5];
    const bf16* w2   = (const bf16*)d_in[6];
    const bf16* gw   = (const bf16*)d_in[7];

    static PFN_encodeTiled enc = nullptr;
    if (!enc) {
        void* fn = nullptr;
        cudaDriverEntryPointQueryResult qr;
        cudaGetDriverEntryPoint("cuTensorMapEncodeTiled", &fn, cudaEnableDefault, &qr);
        enc = (PFN_encodeTiled)fn;
        cudaFuncSetAttribute(k1_kernel, cudaFuncAttributeMaxDynamicSharedMemorySize, K1_SMEM);
        cudaFuncSetAttribute(k23_kernel, cudaFuncAttributeMaxDynamicSharedMemorySize, K23_SMEM);
    }
    void* a2p = nullptr;
    cudaGetSymbolAddress(&a2p, g_a2);
    void* qkvp = nullptr;
    cudaGetSymbolAddress(&qkvp, g_qkv);
    CUtensorMap tmX, tmWqkv, tmW1, tmA2, tmWo, tmW2, tmQKV;
    make_map(enc, &tmQKV, qkvp, 192, 8 * S_, 64, 128);
    make_map(enc, &tmX, x, D_, S_, 64, 128);
    make_map(enc, &tmWqkv, wqkv, 3 * D_, D_, 64, 64);
    make_map(enc, &tmW1, w1, F_, D_, 64, 64);
    make_map(enc, &tmA2, a2p, KA2, S_, 64, 128);
    make_map(enc, &tmWo, wo, D_, D_, 64, 64);
    make_map(enc, &tmW2, w2, D_, F_, 64, 64);

    cudaStream_t st = cudaStreamPerThread;
    k1_kernel<<<128, 384, K1_SMEM, st>>>(tmX, tmWqkv, tmW1, b1, gw, w1, wqkv, w2, wo);
    cudaLaunchAttribute at[1];
    at[0].id = cudaLaunchAttributeProgrammaticStreamSerialization;
    at[0].val.programmaticStreamSerializationAllowed = 1;
    cudaLaunchConfig_t cfg = {};
    cfg.gridDim = dim3(128); cfg.stream = st; cfg.attrs = at; cfg.numAttrs = 1;
    cfg.blockDim = dim3(512); cfg.dynamicSmemBytes = K23_SMEM;
    k23_kernel<<<128, 512, K23_SMEM, st>>>(tmQKV, tmA2, tmWo, tmW2, (bf16*)d_out);
}
```

```cpp
#include <cuda_runtime.h>
#include <cuda_bf16.h>
#include <cuda.h>
#include <stdint.h>

typedef __nv_bfloat16 bf16;

constexpr int S_ = 2048, D_ = 512, F_ = 1376;
constexpr int KA2 = D_ + F_;
constexpr int FCH = 176;

__device__ bf16  g_qkv[8 * S_ * 192];
__device__ bf16  g_a2[S_ * KA2];
__device__ float g_gate[S_];

#define TS(k, cond) do { } while (0)

__device__ __forceinline__ uint32_t smem_u32(const void* p) { return (uint32_t)__cvta_generic_to_shared(p); }
__device__ __forceinline__ void mbar_init(uint32_t bar, uint32_t count) {
    asm volatile("mbarrier.init.shared::cta.b64 [%0], %1;" :: "r"(bar), "r"(count) : "memory");
}
__device__ __forceinline__ void mbar_expect_tx(uint32_t bar, uint32_t bytes) {
    asm volatile("mbarrier.arrive.expect_tx.shared::cta.b64 _, [%0], %1;" :: "r"(bar), "r"(bytes) : "memory");
}
__device__ __forceinline__ void mbar_arrive(uint32_t bar) {
    asm volatile("mbarrier.arrive.shared::cta.b64 _, [%0];" :: "r"(bar) : "memory");
}
__device__ __forceinline__ bool mbar_try_wait(uint32_t bar, uint32_t parity) {
    uint32_t ok;
    asm volatile("{\n.reg .pred p;\nmbarrier.try_wait.parity.shared::cta.b64 p, [%1], %2;\nselp.u32 %0, 1, 0, p;\n}"
                 : "=r"(ok) : "r"(bar), "r"(parity) : "memory");
    return ok != 0;
}
__device__ __forceinline__ void mbar_wait(uint32_t bar, uint32_t parity) {
    for (uint32_t it = 0; it < (1u << 22); ++it) { if (mbar_try_wait(bar, parity)) break; }
}
__device__ __forceinline__ void tma_load_2d(uint32_t dst, const CUtensorMap* map, int c0, int c1, uint32_t bar) {
    asm volatile("cp.async.bulk.tensor.2d.shared::cluster.global.mbarrier::complete_tx::bytes [%0], [%1, {%3, %4}], [%2];"
                 :: "r"(dst), "l"(map), "r"(bar), "r"(c0), "r"(c1) : "memory");
}
__device__ __forceinline__ void l2_prefetch(const void* p, uint32_t bytes) {
    asm volatile("cp.async.bulk.prefetch.L2.global [%0], %1;" :: "l"(p), "r"(bytes) : "memory");
}
__device__ __forceinline__ void fence_barrier_init() { asm volatile("fence.mbarrier_init.release.cluster;" ::: "memory"); }
__device__ __forceinline__ void wgmma_fence()  { asm volatile("wgmma.fence.sync.aligned;" ::: "memory"); }
__device__ __forceinline__ void wgmma_commit() { asm volatile("wgmma.commit_group.sync.aligned;" ::: "memory"); }
template <int N> __device__ __forceinline__ void wgmma_wait() { asm volatile("wgmma.wait_group.sync.aligned %0;" :: "n"(N) : "memory"); }
template <int R> __device__ __forceinline__ void reg_alloc()   { asm volatile("setmaxnreg.inc.sync.aligned.u32 %0;" :: "n"(R)); }
template <int R> __device__ __forceinline__ void reg_dealloc() { asm volatile("setmaxnreg.dec.sync.aligned.u32 %0;" :: "n"(R)); }
__device__ __forceinline__ void bar_sync(int id, int n)   { asm volatile("bar.sync %0, %1;" :: "r"(id), "r"(n) : "memory"); }
__device__ __forceinline__ void bar_arrive(int id, int n) { asm volatile("bar.arrive %0, %1;" :: "r"(id), "r"(n) : "memory"); }

__device__ __forceinline__ uint64_t make_desc(uint32_t addr, uint32_t lbo, uint32_t sbo) {
    uint64_t d = (uint64_t)((addr & 0x3FFFF) >> 4);
    d |= (uint64_t)((lbo & 0x3FFFF) >> 4) << 16;
    d |= (uint64_t)((sbo & 0x3FFFF) >> 4) << 32;
    d |= (uint64_t)1 << 62;
    return d;
}

template <int TB>
__device__ __forceinline__ void wgmma_n64(float (&d)[32], uint64_t da, uint64_t db, int scale_d) {
    asm volatile("{\n.reg .pred p;\nsetp.ne.b32 p, %34, 0;\n"
        "wgmma.mma_async.sync.aligned.m64n64k16.f32.bf16.bf16 {%0, %1, %2, %3, %4, %5, %6, %7, %8, %9, %10, %11, %12, %13, %14, %15, %16, %17, %18, %19, %20, %21, %22, %23, %24, %25, %26, %27, %28, %29, %30, %31}, %32, %33, p, 1, 1, 0, %35;\n}\n"
        : "+f"(d[0]), "+f"(d[1]), "+f"(d[2]), "+f"(d[3]), "+f"(d[4]), "+f"(d[5]), "+f"(d[6]), "+f"(d[7]), "+f"(d[8]), "+f"(d[9]), "+f"(d[10]), "+f"(d[11]), "+f"(d[12]), "+f"(d[13]), "+f"(d[14]), "+f"(d[15]), "+f"(d[16]), "+f"(d[17]), "+f"(d[18]), "+f"(d[19]), "+f"(d[20]), "+f"(d[21]), "+f"(d[22]), "+f"(d[23]), "+f"(d[24]), "+f"(d[25]), "+f"(d[26]), "+f"(d[27]), "+f"(d[28]), "+f"(d[29]), "+f"(d[30]), "+f"(d[31])
        : "l"(da), "l"(db), "r"(scale_d), "n"(TB));
}

template <int TB>
__device__ __forceinline__ void wgmma_n128(float (&d)[64], uint64_t da, uint64_t db, int scale_d) {
    asm volatile("{\n.reg .pred p;\nsetp.ne.b32 p, %66, 0;\n"
        "wgmma.mma_async.sync.aligned.m64n128k16.f32.bf16.bf16 {%0, %1, %2, %3, %4, %5, %6, %7, %8, %9, %10, %11, %12, %13, %14, %15, %16, %17, %18, %19, %20, %21, %22, %23, %24, %25, %26, %27, %28, %29, %30, %31, %32, %33, %34, %35, %36, %37, %38, %39, %40, %41, %42, %43, %44, %45, %46, %47, %48, %49, %50, %51, %52, %53, %54, %55, %56, %57, %58, %59, %60, %61, %62, %63}, %64, %65, p, 1, 1, 0, %67;\n}\n"
        : "+f"(d[0]), "+f"(d[1]), "+f"(d[2]), "+f"(d[3]), "+f"(d[4]), "+f"(d[5]), "+f"(d[6]), "+f"(d[7]), "+f"(d[8]), "+f"(d[9]), "+f"(d[10]), "+f"(d[11]), "+f"(d[12]), "+f"(d[13]), "+f"(d[14]), "+f"(d[15]), "+f"(d[16]), "+f"(d[17]), "+f"(d[18]), "+f"(d[19]), "+f"(d[20]), "+f"(d[21]), "+f"(d[22]), "+f"(d[23]), "+f"(d[24]), "+f"(d[25]), "+f"(d[26]), "+f"(d[27]), "+f"(d[28]), "+f"(d[29]), "+f"(d[30]), "+f"(d[31]), "+f"(d[32]), "+f"(d[33]), "+f"(d[34]), "+f"(d[35]), "+f"(d[36]), "+f"(d[37]), "+f"(d[38]), "+f"(d[39]), "+f"(d[40]), "+f"(d[41]), "+f"(d[42]), "+f"(d[43]), "+f"(d[44]), "+f"(d[45]), "+f"(d[46]), "+f"(d[47]), "+f"(d[48]), "+f"(d[49]), "+f"(d[50]), "+f"(d[51]), "+f"(d[52]), "+f"(d[53]), "+f"(d[54]), "+f"(d[55]), "+f"(d[56]), "+f"(d[57]), "+f"(d[58]), "+f"(d[59]), "+f"(d[60]), "+f"(d[61]), "+f"(d[62]), "+f"(d[63])
        : "l"(da), "l"(db), "r"(scale_d), "n"(TB));
}

template <int TB>
__device__ __forceinline__ void wgmma_n176(float (&d)[88], uint64_t da, uint64_t db, int scale_d) {
    asm volatile("{\n.reg .pred p;\nsetp.ne.b32 p, %90, 0;\n"
        "wgmma.mma_async.sync.aligned.m64n176k16.f32.bf16.bf16 {%0, %1, %2, %3, %4, %5, %6, %7, %8, %9, %10, %11, %12, %13, %14, %15, %16, %17, %18, %19, %20, %21, %22, %23, %24, %25, %26, %27, %28, %29, %30, %31, %32, %33, %34, %35, %36, %37, %38, %39, %40, %41, %42, %43, %44, %45, %46, %47, %48, %49, %50, %51, %52, %53, %54, %55, %56, %57, %58, %59, %60, %61, %62, %63, %64, %65, %66, %67, %68, %69, %70, %71, %72, %73, %74, %75, %76, %77, %78, %79, %80, %81, %82, %83, %84, %85, %86, %87}, %88, %89, p, 1, 1, 0, %91;\n}\n"
        : "+f"(d[0]), "+f"(d[1]), "+f"(d[2]), "+f"(d[3]), "+f"(d[4]), "+f"(d[5]), "+f"(d[6]), "+f"(d[7]), "+f"(d[8]), "+f"(d[9]), "+f"(d[10]), "+f"(d[11]), "+f"(d[12]), "+f"(d[13]), "+f"(d[14]), "+f"(d[15]), "+f"(d[16]), "+f"(d[17]), "+f"(d[18]), "+f"(d[19]), "+f"(d[20]), "+f"(d[21]), "+f"(d[22]), "+f"(d[23]), "+f"(d[24]), "+f"(d[25]), "+f"(d[26]), "+f"(d[27]), "+f"(d[28]), "+f"(d[29]), "+f"(d[30]), "+f"(d[31]), "+f"(d[32]), "+f"(d[33]), "+f"(d[34]), "+f"(d[35]), "+f"(d[36]), "+f"(d[37]), "+f"(d[38]), "+f"(d[39]), "+f"(d[40]), "+f"(d[41]), "+f"(d[42]), "+f"(d[43]), "+f"(d[44]), "+f"(d[45]), "+f"(d[46]), "+f"(d[47]), "+f"(d[48]), "+f"(d[49]), "+f"(d[50]), "+f"(d[51]), "+f"(d[52]), "+f"(d[53]), "+f"(d[54]), "+f"(d[55]), "+f"(d[56]), "+f"(d[57]), "+f"(d[58]), "+f"(d[59]), "+f"(d[60]), "+f"(d[61]), "+f"(d[62]), "+f"(d[63]), "+f"(d[64]), "+f"(d[65]), "+f"(d[66]), "+f"(d[67]), "+f"(d[68]), "+f"(d[69]), "+f"(d[70]), "+f"(d[71]), "+f"(d[72]), "+f"(d[73]), "+f"(d[74]), "+f"(d[75]), "+f"(d[76]), "+f"(d[77]), "+f"(d[78]), "+f"(d[79]), "+f"(d[80]), "+f"(d[81]), "+f"(d[82]), "+f"(d[83]), "+f"(d[84]), "+f"(d[85]), "+f"(d[86]), "+f"(d[87])
        : "l"(da), "l"(db), "r"(scale_d), "n"(TB));
}

template <int TB>
__device__ __forceinline__ void wgmma_n192(float (&d)[96], uint64_t da, uint64_t db, int scale_d) {
    asm volatile("{\n.reg .pred p;\nsetp.ne.b32 p, %98, 0;\n"
        "wgmma.mma_async.sync.aligned.m64n192k16.f32.bf16.bf16 {%0, %1, %2, %3, %4, %5, %6, %7, %8, %9, %10, %11, %12, %13, %14, %15, %16, %17, %18, %19, %20, %21, %22, %23, %24, %25, %26, %27, %28, %29, %30, %31, %32, %33, %34, %35, %36, %37, %38, %39, %40, %41, %42, %43, %44, %45, %46, %47, %48, %49, %50, %51, %52, %53, %54, %55, %56, %57, %58, %59, %60, %61, %62, %63, %64, %65, %66, %67, %68, %69, %70, %71, %72, %73, %74, %75, %76, %77, %78, %79, %80, %81, %82, %83, %84, %85, %86, %87, %88, %89, %90, %91, %92, %93, %94, %95}, %96, %97, p, 1, 1, 0, %99;\n}\n"
        : "+f"(d[0]), "+f"(d[1]), "+f"(d[2]), "+f"(d[3]), "+f"(d[4]), "+f"(d[5]), "+f"(d[6]), "+f"(d[7]), "+f"(d[8]), "+f"(d[9]), "+f"(d[10]), "+f"(d[11]), "+f"(d[12]), "+f"(d[13]), "+f"(d[14]), "+f"(d[15]), "+f"(d[16]), "+f"(d[17]), "+f"(d[18]), "+f"(d[19]), "+f"(d[20]), "+f"(d[21]), "+f"(d[22]), "+f"(d[23]), "+f"(d[24]), "+f"(d[25]), "+f"(d[26]), "+f"(d[27]), "+f"(d[28]), "+f"(d[29]), "+f"(d[30]), "+f"(d[31]), "+f"(d[32]), "+f"(d[33]), "+f"(d[34]), "+f"(d[35]), "+f"(d[36]), "+f"(d[37]), "+f"(d[38]), "+f"(d[39]), "+f"(d[40]), "+f"(d[41]), "+f"(d[42]), "+f"(d[43]), "+f"(d[44]), "+f"(d[45]), "+f"(d[46]), "+f"(d[47]), "+f"(d[48]), "+f"(d[49]), "+f"(d[50]), "+f"(d[51]), "+f"(d[52]), "+f"(d[53]), "+f"(d[54]), "+f"(d[55]), "+f"(d[56]), "+f"(d[57]), "+f"(d[58]), "+f"(d[59]), "+f"(d[60]), "+f"(d[61]), "+f"(d[62]), "+f"(d[63]), "+f"(d[64]), "+f"(d[65]), "+f"(d[66]), "+f"(d[67]), "+f"(d[68]), "+f"(d[69]), "+f"(d[70]), "+f"(d[71]), "+f"(d[72]), "+f"(d[73]), "+f"(d[74]), "+f"(d[75]), "+f"(d[76]), "+f"(d[77]), "+f"(d[78]), "+f"(d[79]), "+f"(d[80]), "+f"(d[81]), "+f"(d[82]), "+f"(d[83]), "+f"(d[84]), "+f"(d[85]), "+f"(d[86]), "+f"(d[87]), "+f"(d[88]), "+f"(d[89]), "+f"(d[90]), "+f"(d[91]), "+f"(d[92]), "+f"(d[93]), "+f"(d[94]), "+f"(d[95])
        : "l"(da), "l"(db), "r"(scale_d), "n"(TB));
}

__device__ __forceinline__ uint32_t pack_bf16(float lo, float hi) {
    uint32_t r;
    asm("cvt.rn.bf16x2.f32 %0, %1, %2;" : "=r"(r) : "f"(hi), "f"(lo));
    return r;
}
__device__ __forceinline__ float bf_lo(uint32_t v) { return __uint_as_float(v << 16); }
__device__ __forceinline__ float bf_hi(uint32_t v) { return __uint_as_float(v & 0xffff0000u); }

__device__ __forceinline__ void quad_transpose(uint32_t (&w)[4], int q) {
    const bool o1 = q & 1, o2 = q & 2;
    {
        uint32_t s0 = o1 ? w[0] : w[1], s1 = o1 ? w[2] : w[3];
        s0 = __shfl_xor_sync(0xffffffffu, s0, 1); s1 = __shfl_xor_sync(0xffffffffu, s1, 1);
        if (o1) { w[0] = s0; w[2] = s1; } else { w[1] = s0; w[3] = s1; }
    }
    {
        uint32_t s0 = o2 ? w[0] : w[2], s1 = o2 ? w[1] : w[3];
        s0 = __shfl_xor_sync(0xffffffffu, s0, 2); s1 = __shfl_xor_sync(0xffffffffu, s1, 2);
        if (o2) { w[0] = s0; w[1] = s1; } else { w[2] = s0; w[3] = s1; }
    }
}

__device__ __forceinline__ float ex2(float x) { float y; asm("ex2.approx.ftz.f32 %0, %1;" : "=f"(y) : "f"(x)); return y; }
__device__ __forceinline__ float rcp(float x) { float y; asm("rcp.approx.ftz.f32 %0, %1;" : "=f"(y) : "f"(x)); return y; }

__device__ __forceinline__ float ex2v(float x) { float y; asm volatile("ex2.approx.ftz.f32 %0, %1;" : "=f"(y) : "f"(x)); return y; }
__device__ __forceinline__ float rcpv(float x) { float y; asm volatile("rcp.approx.ftz.f32 %0, %1;" : "=f"(y) : "f"(x)); return y; }
__device__ __forceinline__ float mish_f(float h) {
    const float e = ex2v(1.4426950408889634f * fminf(h, 20.f));
    const float n = fmaf(e, e, e + e);
    return h * n * rcpv(n + 2.f);
}

__device__ __forceinline__ void pdl_wait()   { asm volatile("griddepcontrol.wait;" ::: "memory"); }
__device__ __forceinline__ void pdl_launch() { asm volatile("griddepcontrol.launch_dependents;" ::: "memory"); }

constexpr int K1_STAGES = 4;
constexpr int K1_XBYTES = 128 * 512 * 2;
constexpr int K1_BSTAGE = 3 * 8192;
constexpr int K1_SMEM   = K1_XBYTES + K1_STAGES * K1_BSTAGE + 2048   + 1024  ;

__global__ void __launch_bounds__(384, 1)
k1_kernel(const __grid_constant__ CUtensorMap tmX, const __grid_constant__ CUtensorMap tmWqkv,
          const __grid_constant__ CUtensorMap tmW1, const bf16* __restrict__ b1,
          const bf16* __restrict__ gate_w, const bf16* __restrict__ w1p, const bf16* __restrict__ wqkvp,
          const bf16* __restrict__ w2p, const bf16* __restrict__ wop)
{

    extern __shared__ uint8_t smem_raw[];
    const uint32_t sbase = (smem_u32(smem_raw) + 1023u) & ~1023u;
    uint8_t* sgen = smem_raw + (sbase - smem_u32(smem_raw));
    const uint32_t sX = sbase;
    const uint32_t sB = sbase + K1_XBYTES;
    const uint32_t sBar = sB + K1_STAGES * K1_BSTAGE;
    const uint32_t x_full = sBar;
    const uint32_t b_full = sBar + 64;
    const uint32_t b_empty = sBar + 96;
    float* sGate = (float*)(sgen + K1_XBYTES + K1_STAGES * K1_BSTAGE + 128);
    uint8_t* sGw = sgen + K1_XBYTES + K1_STAGES * K1_BSTAGE + 640;
    uint32_t* sBias = (uint32_t*)(sgen + K1_XBYTES + K1_STAGES * K1_BSTAGE + 1664);

    const int rb = blockIdx.x >> 3, j = blockIdx.x & 7;
    const int tid = threadIdx.x, lane = tid & 31;
    const int warp = __shfl_sync(0xffffffffu, tid >> 5, 0), wg = warp >> 2;
    TS(0, tid == 0);
    pdl_launch();

    if (tid == 0) {
        for (int i = 0; i < 8; i++) mbar_init(x_full + 8 * i, 1);
        for (int i = 0; i < K1_STAGES; i++) { mbar_init(b_full + 8 * i, 1); mbar_init(b_empty + 8 * i, 8); }
        fence_barrier_init();
    }
    __syncthreads();

    if (wg == 2) {
        reg_dealloc<40>();
        if (tid == 288) {
            const int b = blockIdx.x;
            mbar_wait(b_full + 8, 0);
            l2_prefetch((const uint8_t*)wqkvp + b * 12288, 12288);
            l2_prefetch((const uint8_t*)w2p + b * 11008, 11008);
            l2_prefetch((const uint8_t*)wop + b * 4096, 4096);
        }
        if (tid == 256) {
            for (int it = 0; it < 16; it++) {
                if (it < 8) {
                    mbar_expect_tx(x_full + 8 * it, 16384);
                    tma_load_2d(sX + it * 16384, &tmX, it * 64, rb * 128, x_full + 8 * it);
                }
                const int st = it & 3;
                if (it >= K1_STAGES) mbar_wait(b_empty + 8 * st, ((it >> 2) - 1) & 1);
                mbar_expect_tx(b_full + 8 * st, K1_BSTAGE);
                const uint32_t dst = sB + st * K1_BSTAGE;
                if (it < 8) {
                    for (int b = 0; b < 3; b++) tma_load_2d(dst + b * 8192, &tmW1, j * FCH + b * 64, it * 64, b_full + 8 * st);
                } else {
                    for (int b = 0; b < 3; b++) tma_load_2d(dst + b * 8192, &tmWqkv, b * 512 + j * 64, (it - 8) * 64, b_full + 8 * st);
                }
            }
        }
    } else {
        reg_alloc<232>();
        if (tid < 64) ((uint4*)sGw)[tid] = __ldg((const uint4*)gate_w + tid);
        else if (tid < 64 + 88) {
            const int c = j * FCH + (tid - 64) * 2;
            sBias[tid - 64] = c < F_ ? __ldg((const uint32_t*)(b1 + c)) : 0u;
        }
        bar_sync(3, 256);
        const int t128 = tid & 127, w4 = warp & 3, q = lane & 3;
        float accF[88], accQ[96];
        const uint64_t da0 = make_desc(sX + wg * 8192, 16, 1024);
        const uint64_t db0 = make_desc(sB, 8192, 1024);
        float gs = 0.f;
        const int grow = wg * 64 + (t128 >> 1), ghalf = t128 & 1;
#pragma unroll
        for (int kc = 0; kc < 8; kc++) {
            const int st = kc & 3;
            mbar_wait(x_full + 8 * kc, 0);
            mbar_wait(b_full + 8 * st, (kc >> 2) & 1);
            TS(1, tid == 0 && kc == 0); TS(2, tid == 0 && kc == 4);
            wgmma_fence();
#pragma unroll
            for (int k16 = 0; k16 < 4; k16++) {
                wgmma_n176<1>(accF, da0 + (kc * 1024 + k16 * 2), db0 + (st * (K1_BSTAGE >> 4) + k16 * 128), (kc | k16) != 0);
            }
            wgmma_commit();
#pragma unroll
            for (int c = 0; c < 4; c++) {
                const int cc = ghalf * 4 + c;
                const uint4 xv = *(const uint4*)(sgen + kc * 16384 + grow * 128 + ((cc ^ (grow & 7)) << 4));
                const uint4 gv = *(const uint4*)(sGw + kc * 128 + cc * 16);
                gs = fmaf(bf_lo(xv.x), bf_lo(gv.x), gs); gs = fmaf(bf_hi(xv.x), bf_hi(gv.x), gs);
                gs = fmaf(bf_lo(xv.y), bf_lo(gv.y), gs); gs = fmaf(bf_hi(xv.y), bf_hi(gv.y), gs);
                gs = fmaf(bf_lo(xv.z), bf_lo(gv.z), gs); gs = fmaf(bf_hi(xv.z), bf_hi(gv.z), gs);
                gs = fmaf(bf_lo(xv.w), bf_lo(gv.w), gs); gs = fmaf(bf_hi(xv.w), bf_hi(gv.w), gs);
            }
            if (kc > 0) { wgmma_wait<1>(); if (lane == 0) mbar_arrive(b_empty + 8 * ((kc - 1) & 3)); }
        }
        gs += __shfl_xor_sync(0xffffffffu, gs, 1);
        {
            const float g = 1.f / (1.f + __expf(-gs));
            if (ghalf == 0) {
                sGate[grow] = g;
                if (j == 0) g_gate[rb * 128 + grow] = g;
            }
        }
        wgmma_wait<0>();
        if (lane == 0) mbar_arrive(b_empty + 8 * 3);
        bar_sync(1 + wg, 128);
        TS(3, tid == 0);
        const int n0 = j * FCH;
        const int rl = wg * 64 + w4 * 16 + (lane >> 2);
        const float om0 = 1.f - sGate[rl], om1 = 1.f - sGate[rl + 8];
        bf16* frow0 = g_a2 + (size_t)(rb * 128 + rl) * KA2 + D_ + n0;
        bf16* frow1 = frow0 + 8 * KA2;
        auto ffn_chunk = [&](int u) {
            uint32_t w0[4], w1[4];
#pragma unroll
            for (int i = 0; i < 4; i++) {
                const int t = u * 4 + i;
                if (t < 22) {
                    const uint32_t bv = sBias[t * 4 + q];
                    const float bb0 = bf_lo(bv), bb1 = bf_hi(bv);
                    w0[i] = pack_bf16(mish_f(accF[t * 4 + 0] + bb0) * om0, mish_f(accF[t * 4 + 1] + bb1) * om0);
                    w1[i] = pack_bf16(mish_f(accF[t * 4 + 2] + bb0) * om1, mish_f(accF[t * 4 + 3] + bb1) * om1);
                } else { w0[i] = 0; w1[i] = 0; }
            }
            quad_transpose(w0, q);
            quad_transpose(w1, q);
            const int c = (u * 4 + q) * 8;
            if (c < FCH && n0 + c < F_) {
                *(uint4*)(frow0 + c) = make_uint4(w0[0], w0[1], w0[2], w0[3]);
                *(uint4*)(frow1 + c) = make_uint4(w1[0], w1[1], w1[2], w1[3]);
            }
        };
#pragma unroll
        for (int kc = 0; kc < 8; kc++) {
            const int st = kc & 3;
            mbar_wait(b_full + 8 * st, ((kc + 8) >> 2) & 1);
            wgmma_fence();
#pragma unroll
            for (int k16 = 0; k16 < 4; k16++) {
                wgmma_n192<1>(accQ, da0 + (kc * 1024 + k16 * 2), db0 + (st * (K1_BSTAGE >> 4) + k16 * 128), (kc | k16) != 0);
            }
            wgmma_commit();
            if (kc < 6) ffn_chunk(kc);
            if (kc > 0) { wgmma_wait<1>(); if (lane == 0) mbar_arrive(b_empty + 8 * ((kc - 1) & 3)); }
        }
        wgmma_wait<0>();
        TS(4, tid == 0);
        {
            bf16* orow0 = g_qkv + ((size_t)j * S_ + rb * 128 + rl) * 192;
            bf16* orow1 = orow0 + 8 * 192;
#pragma unroll
            for (int u = 0; u < 6; u++) {
                uint32_t w0[4], w1[4];
#pragma unroll
                for (int i = 0; i < 4; i++) {
                    const int t = u * 4 + i;
                    w0[i] = pack_bf16(accQ[t * 4 + 0], accQ[t * 4 + 1]);
                    w1[i] = pack_bf16(accQ[t * 4 + 2], accQ[t * 4 + 3]);
                }
                quad_transpose(w0, q);
                quad_transpose(w1, q);
                const int c = (u * 4 + q) * 8;
                *(uint4*)(orow0 + c) = make_uint4(w0[0], w0[1], w0[2], w0[3]);
                *(uint4*)(orow1 + c) = make_uint4(w1[0], w1[1], w1[2], w1[3]);
            }
        }
        TS(5, tid == 0);
    }
}

__device__ __forceinline__ void ldsm_x4(uint32_t (&r)[4], uint32_t addr) {
    asm("ldmatrix.sync.aligned.m8n8.x4.shared.b16 {%0,%1,%2,%3}, [%4];"
                 : "=r"(r[0]), "=r"(r[1]), "=r"(r[2]), "=r"(r[3]) : "r"(addr));
}
__device__ __forceinline__ void ldsm_x4_t(uint32_t (&r)[4], uint32_t addr) {
    asm("ldmatrix.sync.aligned.m8n8.x4.trans.shared.b16 {%0,%1,%2,%3}, [%4];"
                 : "=r"(r[0]), "=r"(r[1]), "=r"(r[2]), "=r"(r[3]) : "r"(addr));
}
__device__ __forceinline__ void mma16816(float (&d)[4], const uint32_t (&a)[4], uint32_t b0, uint32_t b1) {
    asm("mma.sync.aligned.m16n8k16.row.col.f32.bf16.bf16.f32 {%0,%1,%2,%3}, {%4,%5,%6,%7}, {%8,%9}, {%0,%1,%2,%3};"
                 : "+f"(d[0]), "+f"(d[1]), "+f"(d[2]), "+f"(d[3])
                 : "r"(a[0]), "r"(a[1]), "r"(a[2]), "r"(a[3]), "r"(b0), "r"(b1));
}
__device__ __forceinline__ void mma16816_z(float (&d)[4], const uint32_t (&a)[4], uint32_t b0, uint32_t b1) {
    asm("mma.sync.aligned.m16n8k16.row.col.f32.bf16.bf16.f32 {%0,%1,%2,%3}, {%4,%5,%6,%7}, {%8,%9}, {%10,%10,%10,%10};"
                 : "=f"(d[0]), "=f"(d[1]), "=f"(d[2]), "=f"(d[3])
                 : "r"(a[0]), "r"(a[1]), "r"(a[2]), "r"(a[3]), "r"(b0), "r"(b1), "f"(0.f));
}

constexpr int KV_PITCH = 128;

template <int EDGE, bool HEAD>
__device__ __forceinline__ void blk_scores(float (&s)[2][4], const uint32_t (&qa)[4], uint32_t kaddr, bool dead, int r0, int c0)
{
    uint32_t kf[4];
    ldsm_x4(kf, kaddr);
    mma16816_z(s[0], qa, kf[0], kf[1]);
    mma16816_z(s[1], qa, kf[2], kf[3]);
#pragma unroll
    for (int t = 0; t < 2; t++)
#pragma unroll
        for (int e = 0; e < 4; e++) {
            const int r = r0 + (e >> 1) * 8, c = t * 8 + c0 + (e & 1);
            if (EDGE == 1 && c <= r) s[t][e] = -1e30f;
            if (EDGE == 2 && c > r) s[t][e] = -1e30f;
            if (HEAD && dead) s[t][e] = -1e30f;
        }
}
__device__ __forceinline__ void blk_max(const float (&s)[2][4], float& n0, float& n1) {
    n0 = fmaxf(n0, fmaxf(fmaxf(s[0][0], s[0][1]), fmaxf(s[1][0], s[1][1])));
    n1 = fmaxf(n1, fmaxf(fmaxf(s[0][2], s[0][3]), fmaxf(s[1][2], s[1][3])));
}
__device__ __forceinline__ void blk_pv(const float (&s)[2][4], float mc0, float mc1, float (&l)[4],
                                       float (&o)[2][4], uint32_t vaddr) {
    const float C = 0.25f * 1.4426950408889634f;
    uint32_t pa[4];
#pragma unroll
    for (int t = 0; t < 2; t++) {
        const float p0 = ex2(fmaf(s[t][0], C, -mc0)), p1 = ex2(fmaf(s[t][1], C, -mc0));
        const float p2 = ex2(fmaf(s[t][2], C, -mc1)), p3 = ex2(fmaf(s[t][3], C, -mc1));
        pa[2 * t] = pack_bf16(p0, p1); pa[2 * t + 1] = pack_bf16(p2, p3);
    }
    uint32_t vf[4];
    ldsm_x4_t(vf, vaddr);
    mma16816(o[0], pa, vf[0], vf[1]);
    mma16816(o[1], pa, vf[2], vf[3]);
    mma16816(l, pa, 0x3F803F80u, 0x3F803F80u);
}
__device__ __forceinline__ void quad_max(float& n0, float& n1) {
    n0 = fmaxf(n0, __shfl_xor_sync(0xffffffffu, n0, 1)); n1 = fmaxf(n1, __shfl_xor_sync(0xffffffffu, n1, 1));
    n0 = fmaxf(n0, __shfl_xor_sync(0xffffffffu, n0, 2)); n1 = fmaxf(n1, __shfl_xor_sync(0xffffffffu, n1, 2));
}
template <int NC, int NN, bool FIRST, bool NEXT_IS_EDGE, bool HEAD>
__device__ __forceinline__ void pipe_step(const float (&sc)[5][2][4], float (&sn)[5][2][4], const uint32_t (&qa)[4],
                                          uint32_t ka, uint32_t va, int kc, int kn, int kb0, int r0, int c0,
                                          float& m0, float& m1, float& n0, float& n1, float (&l)[4], float (&o)[2][4])
{
    const float C = 0.25f * 1.4426950408889634f;
    const float mc0 = n0 * C, mc1 = n1 * C;
    if (!FIRST) {
        const float a0 = ex2(fmaf(m0, C, -mc0)), a1 = ex2(fmaf(m1, C, -mc1));
        l[0] *= a0; l[2] *= a1;
        o[0][0] *= a0; o[0][1] *= a0; o[1][0] *= a0; o[1][1] *= a0;
        o[0][2] *= a1; o[0][3] *= a1; o[1][2] *= a1; o[1][3] *= a1;
    }
    m0 = n0; m1 = n1;
#pragma unroll
    for (int b = 0; b < NC; b++) {
        if (b < NN) {
            if (NEXT_IS_EDGE && b == 0) blk_scores<1, HEAD>(sn[b], qa, ka + (kn + b) * 16 * KV_PITCH, kn + b < kb0, r0, c0);
            else                        blk_scores<0, HEAD>(sn[b], qa, ka + (kn + b) * 16 * KV_PITCH, kn + b < kb0, r0, c0);
        }
        blk_pv(sc[b], mc0, mc1, l, o, va + (kc + b) * 16 * KV_PITCH);
        if (b < NN) blk_max(sn[b], n0, n1);
    }
    if (NN > 0) quad_max(n0, n1);
}

__device__ __forceinline__ void kv_need(uint32_t kvbar, int blk, uint32_t& ka, uint32_t& va) {
    mbar_wait(kvbar + 8 * blk, 0);
    asm volatile("" : "+r"(ka), "+r"(va) :: "memory");
}
template <bool HEAD>
__device__ __forceinline__ void attn_task(const uint32_t (&qa)[4], uint32_t ka, uint32_t va, int kb0, int lane, int qt, uint32_t kvbar,
                                          bf16* __restrict__ out  , float g0, float g1)
{
    const int r0 = lane >> 2, c0 = (lane & 3) * 2;
    float m0 = -1e30f, m1 = -1e30f, n0 = -1e30f, n1 = -1e30f;
    float l[4] = {0.f, 0.f, 0.f, 0.f};
    float o[2][4] = {{0.f, 0.f, 0.f, 0.f}, {0.f, 0.f, 0.f, 0.f}};
    float sa[5][2][4], sb[5][2][4];
    kv_need(kvbar, 2, ka, va);
    if (qt < 4) kv_need(kvbar, 1, ka, va);
#pragma unroll
    for (int b = 0; b < 5; b++) {
        if (b == 4) blk_scores<2, HEAD>(sa[b], qa, ka + (12 + b) * 16 * KV_PITCH, false, r0, c0);
        else        blk_scores<0, HEAD>(sa[b], qa, ka + (12 + b) * 16 * KV_PITCH, 12 + b < kb0, r0, c0);
        blk_max(sa[b], n0, n1);
    }
    quad_max(n0, n1);
    kv_need(kvbar, 1, ka, va);
    if (HEAD) {
        pipe_step<5, 0, true, false, HEAD>(sa, sb, qa, ka, va, 12, 0, kb0, r0, c0, m0, m1, n0, n1, l, o);
        kv_need(kvbar, 0, ka, va);
#pragma unroll 1
        for (int kc = 8; kc >= 0 && kb0 < kc + 4; kc -= 4) {
#pragma unroll
            for (int b = 0; b < 4; b++) {
                blk_scores<0, HEAD>(sa[b], qa, ka + (kc + b) * 16 * KV_PITCH, kc + b < kb0, r0, c0);
                blk_max(sa[b], n0, n1);
            }
            quad_max(n0, n1);
            pipe_step<4, 0, false, false, HEAD>(sa, sb, qa, ka, va, kc, 0, kb0, r0, c0, m0, m1, n0, n1, l, o);
        }
    } else {
        pipe_step<5, 4, true,  false, HEAD>(sa, sb, qa, ka, va, 12, 8, kb0, r0, c0, m0, m1, n0, n1, l, o);
        if (qt < 4) kv_need(kvbar, 0, ka, va);
        pipe_step<4, 4, false, false, HEAD>(sb, sa, qa, ka, va, 8, 4, kb0, r0, c0, m0, m1, n0, n1, l, o);
        kv_need(kvbar, 0, ka, va);
        pipe_step<4, 4, false, true,  HEAD>(sa, sb, qa, ka, va, 4, 0, kb0, r0, c0, m0, m1, n0, n1, l, o);
        pipe_step<4, 0, false, false, HEAD>(sb, sa, qa, ka, va, 0, 0, kb0, r0, c0, m0, m1, n0, n1, l, o);
    }
    const float f0 = __fdividef(g0, l[0]), f1 = __fdividef(g1, l[2]);
#pragma unroll
    for (int t = 0; t < 2; t++) {
        *(uint32_t*)(out + (size_t)r0 * KA2 + t * 8 + c0) = pack_bf16(o[t][0] * f0, o[t][1] * f0);
        *(uint32_t*)(out + (size_t)(r0 + 8) * KA2 + t * 8 + c0) = pack_bf16(o[t][2] * f1, o[t][3] * f1);
    }
}

constexpr int K2_SMEM = 2 * 384 * KV_PITCH + 1024 + 64;

__global__ void __launch_bounds__(512, 1) k2_kernel(const __grid_constant__ CUtensorMap tmQKV)
{
    extern __shared__ uint8_t smem_raw[];
    const uint32_t sbase = (smem_u32(smem_raw) + 1023u) & ~1023u;
    uint8_t* sgen = smem_raw + (sbase - smem_u32(smem_raw));
    const uint32_t sK = sbase, sV = sK + 384 * KV_PITCH, kv_full = sbase + 2 * 384 * KV_PITCH;
    const int rb = blockIdx.x >> 3, j = blockIdx.x & 7;
    const int tid = threadIdx.x, warp = tid >> 5, lane = tid & 31;
    pdl_launch();
    if (tid == 0) {
        for (int i = 0; i < 3; i++) mbar_init(kv_full + 8 * i, 1);
        fence_barrier_init();
    }
    pdl_wait();
    TS(6, tid == 0);
    if (tid == 0) {
        for (int i = 0; i < 3; i++) {
            const uint32_t bar = kv_full + 8 * (2 - i);
            if (rb - i >= 0) {
                const int row = j * S_ + (rb - i) * 128;
                mbar_expect_tx(bar, 2 * 16384);
                tma_load_2d(sK + (2 - i) * 16384, &tmQKV, 64, row, bar);
                tma_load_2d(sV + (2 - i) * 16384, &tmQKV, 128, row, bar);
            } else {
                mbar_arrive(bar);
            }
        }
    }
    if (rb < 2) {
        for (int i = tid; i < (2 - rb) * 1024; i += 512) {
            *(uint4*)(sgen + i * 16) = make_uint4(0, 0, 0, 0);
            *(uint4*)(sgen + 384 * KV_PITCH + i * 16) = make_uint4(0, 0, 0, 0);
        }
    }
    const int qt = warp & 7, h0 = (warp >> 3) * 2;
    const int q0g = rb * 128 + qt * 16;
    const int r0 = lane >> 2, c0 = (lane & 3) * 2;
    const bf16* qsrc = g_qkv + ((size_t)j * S_ + q0g) * 192 + h0 * 16;
    uint32_t qa[4], qn[4];
    qa[0] = *(const uint32_t*)(qsrc + (size_t)r0 * 192 + c0);
    qa[1] = *(const uint32_t*)(qsrc + (size_t)(r0 + 8) * 192 + c0);
    qa[2] = *(const uint32_t*)(qsrc + (size_t)r0 * 192 + c0 + 8);
    qa[3] = *(const uint32_t*)(qsrc + (size_t)(r0 + 8) * 192 + c0 + 8);
    qn[0] = *(const uint32_t*)(qsrc + (size_t)r0 * 192 + 16 + c0);
    qn[1] = *(const uint32_t*)(qsrc + (size_t)(r0 + 8) * 192 + 16 + c0);
    qn[2] = *(const uint32_t*)(qsrc + (size_t)r0 * 192 + 16 + c0 + 8);
    qn[3] = *(const uint32_t*)(qsrc + (size_t)(r0 + 8) * 192 + 16 + c0 + 8);
    const float g0 = g_gate[q0g + r0], g1 = g_gate[q0g + r0 + 8];
    const int kb0 = q0g < 256 ? (256 - q0g) >> 4 : 0;
    __syncthreads();
    const uint32_t sKd = sK, sVd = sV;
    TS(7, tid == 0);
    const int krow = qt * 16 + (lane & 7) + ((lane >> 4) << 3);
    const int vrow = qt * 16 + (lane & 15);
#pragma unroll 1
    for (int hh = 0; hh < 2; hh++) {
        const int hl = h0 + hh;
        const uint32_t ka = sKd + krow * KV_PITCH + (((2 * hl + ((lane >> 3) & 1)) ^ (lane & 7)) << 4);
        const uint32_t va = sVd + vrow * KV_PITCH + (((2 * hl + (lane >> 4)) ^ (lane & 7)) << 4);
        if (rb < 2) attn_task<true>(qa, ka, va, kb0, lane, qt, kv_full, g_a2 + (size_t)q0g * KA2 + (j * 4 + hl) * 16, g0, g1);
        else        attn_task<false>(qa, ka, va, kb0, lane, qt, kv_full, g_a2 + (size_t)q0g * KA2 + (j * 4 + hl) * 16, g0, g1);
        TS(8 + hh, tid == 0);
        qa[0] = qn[0]; qa[1] = qn[1]; qa[2] = qn[2]; qa[3] = qn[3];
    }
}

constexpr int K3_STAGES = 8;
constexpr int K3_STAGE = 8192 + 16384;
constexpr int K3_SMEM = K3_STAGES * K3_STAGE + 1024 + 1024;
constexpr int K3_KSTEPS = 30;

__global__ void __launch_bounds__(384, 1)
k3_kernel(const __grid_constant__ CUtensorMap tmA2, const __grid_constant__ CUtensorMap tmWo,
          const __grid_constant__ CUtensorMap tmW2, bf16* __restrict__ out)
{
    extern __shared__ uint8_t smem_raw[];
    const uint32_t sbase = (smem_u32(smem_raw) + 1023u) & ~1023u;
    uint8_t* sgen = smem_raw + (sbase - smem_u32(smem_raw));
    const uint32_t sBar = sbase + K3_STAGES * K3_STAGE;
    const uint32_t full = sBar, empty = sBar + 64;
    const int mb = blockIdx.x >> 2, nb = blockIdx.x & 3;
    const int tid = threadIdx.x, lane = tid & 31;
    const int warp = __shfl_sync(0xffffffffu, tid >> 5, 0), wg = warp >> 2;
    if (tid == 0) {
        for (int i = 0; i < K3_STAGES; i++) { mbar_init(full + 8 * i, 1); mbar_init(empty + 8 * i, 8); }
        fence_barrier_init();
    }
    __syncthreads();
    TS(10, tid == 0);
    if (wg == 2) {
        reg_dealloc<40>();
        if (tid == 256) {
            for (int ks = 0; ks < K3_KSTEPS; ks++) {
                const int st = ks % K3_STAGES;
                if (ks >= K3_STAGES) mbar_wait(empty + 8 * st, ((ks / K3_STAGES) - 1) & 1);
                mbar_expect_tx(full + 8 * st, K3_STAGE);
                const uint32_t dst = sbase + st * K3_STAGE;
                tma_load_2d(dst, &tmA2, ks * 64, mb * 64, full + 8 * st);
                const CUtensorMap* tm = ks < 8 ? &tmWo : &tmW2;
                const int kr = (ks < 8 ? ks : ks - 8) * 64;
                tma_load_2d(dst + 8192, tm, nb * 128, kr, full + 8 * st);
                tma_load_2d(dst + 16384, tm, nb * 128 + 64, kr, full + 8 * st);
            }
        }
    } else {
        reg_alloc<232>();
        const int q = lane & 3;
        const int rl = (warp & 3) * 16 + (lane >> 2);
        float acc[64];
        const uint64_t da0 = make_desc(sbase + wg * 64, 16, 1024);
        const uint64_t db0 = make_desc(sbase + 8192 + wg * 4096, 8192, 1024);
        for (int ks = 0; ks < K3_KSTEPS; ks++) {
            const int st = ks % K3_STAGES;
            mbar_wait(full + 8 * st, (ks / K3_STAGES) & 1);
            TS(11, tid == 0 && ks == 0); TS(12, tid == 0 && ks == 8); TS(13, tid == 0 && ks == 16);
            wgmma_fence();
            const uint32_t so = (uint32_t)(st * K3_STAGE) >> 4;
#pragma unroll
            for (int kk = 0; kk < 2; kk++)
                wgmma_n128<1>(acc, da0 + (so + kk * 2), db0 + (so + kk * 128), (ks | kk) != 0);
            wgmma_commit();
            if (ks > 0) { wgmma_wait<1>(); if (lane == 0) mbar_arrive(empty + 8 * ((ks - 1) % K3_STAGES)); }
        }
        wgmma_wait<0>();
        TS(14, tid == 0);
        bar_sync(1, 256);
        const int t128 = tid & 127;
        float4* xch = (float4*)(sgen + wg * 16384) + t128;
        if (wg == 0) {
#pragma unroll
            for (int i = 0; i < 8; i++) xch[i * 128] = make_float4(acc[32 + 4 * i], acc[33 + 4 * i], acc[34 + 4 * i], acc[35 + 4 * i]);
        } else {
#pragma unroll
            for (int i = 0; i < 8; i++) xch[i * 128] = make_float4(acc[4 * i], acc[1 + 4 * i], acc[2 + 4 * i], acc[3 + 4 * i]);
        }
        bar_sync(1, 256);
        const float4* rcv = (const float4*)(sgen + (wg ^ 1) * 16384) + t128;
        float v[32];
#pragma unroll
        for (int i = 0; i < 8; i++) {
            const float4 r = rcv[i * 128];
            const float a0 = wg == 0 ? acc[4 * i] : acc[32 + 4 * i], a1 = wg == 0 ? acc[4 * i + 1] : acc[33 + 4 * i];
            const float a2 = wg == 0 ? acc[4 * i + 2] : acc[34 + 4 * i], a3 = wg == 0 ? acc[4 * i + 3] : acc[35 + 4 * i];
            v[4 * i] = a0 + r.x; v[4 * i + 1] = a1 + r.y; v[4 * i + 2] = a2 + r.z; v[4 * i + 3] = a3 + r.w;
        }
        bf16* orow0 = out + (size_t)(mb * 64 + rl) * D_ + nb * 128 + wg * 64;
        bf16* orow1 = orow0 + 8 * D_;
#pragma unroll
        for (int u = 0; u < 2; u++) {
            uint32_t w0[4], w1[4];
#pragma unroll
            for (int i = 0; i < 4; i++) {
                const int t = u * 4 + i;
                w0[i] = pack_bf16(v[t * 4 + 0], v[t * 4 + 1]);
                w1[i] = pack_bf16(v[t * 4 + 2], v[t * 4 + 3]);
            }
            quad_transpose(w0, q);
            quad_transpose(w1, q);
            const int c = (u * 4 + q) * 8;
            *(uint4*)(orow0 + c) = make_uint4(w0[0], w0[1], w0[2], w0[3]);
            *(uint4*)(orow1 + c) = make_uint4(w1[0], w1[1], w1[2], w1[3]);
        }
        TS(15, tid == 0);
    }
}

typedef CUresult (*PFN_encodeTiled)(CUtensorMap*, CUtensorMapDataType, cuuint32_t, void*, const cuuint64_t*,
                                    const cuuint64_t*, const cuuint32_t*, const cuuint32_t*, CUtensorMapInterleave,
                                    CUtensorMapSwizzle, CUtensorMapL2promotion, CUtensorMapFloatOOBfill);

static void make_map(PFN_encodeTiled enc, CUtensorMap* m, const void* ptr, uint64_t cols, uint64_t rows,
                     uint32_t box_cols, uint32_t box_rows)
{
    cuuint64_t dims[2] = {cols, rows};
    cuuint64_t strides[1] = {cols * 2};
    cuuint32_t box[2] = {box_cols, box_rows};
    cuuint32_t es[2] = {1, 1};
    enc(m, CU_TENSOR_MAP_DATA_TYPE_BFLOAT16, 2, const_cast<void*>(ptr), dims, strides, box, es,
        CU_TENSOR_MAP_INTERLEAVE_NONE, CU_TENSOR_MAP_SWIZZLE_128B, CU_TENSOR_MAP_L2_PROMOTION_L2_128B,
        CU_TENSOR_MAP_FLOAT_OOB_FILL_NONE);
}

extern "C" void kernel_launch(void* const* d_in, const int* in_sizes, int n_in, void* d_out, int out_size)
{
    const bf16* x    = (const bf16*)d_in[0];
    const bf16* wqkv = (const bf16*)d_in[1];
    const bf16* wo   = (const bf16*)d_in[2];
    const bf16* w1   = (const bf16*)d_in[4];
    const bf16* b1   = (const bf16*)d_in[5];
    const bf16* w2   = (const bf16*)d_in[6];
    const bf16* gw   = (const bf16*)d_in[7];

    static PFN_encodeTiled enc = nullptr;
    if (!enc) {
        void* fn = nullptr;
        cudaDriverEntryPointQueryResult qr;
        cudaGetDriverEntryPoint("cuTensorMapEncodeTiled", &fn, cudaEnableDefault, &qr);
        enc = (PFN_encodeTiled)fn;
        cudaFuncSetAttribute(k1_kernel, cudaFuncAttributeMaxDynamicSharedMemorySize, K1_SMEM);
        cudaFuncSetAttribute(k2_kernel, cudaFuncAttributeMaxDynamicSharedMemorySize, K2_SMEM);
        cudaFuncSetAttribute(k3_kernel, cudaFuncAttributeMaxDynamicSharedMemorySize, K3_SMEM);
    }
    void* a2p = nullptr;
    cudaGetSymbolAddress(&a2p, g_a2);
    void* qkvp = nullptr;
    cudaGetSymbolAddress(&qkvp, g_qkv);
    CUtensorMap tmX, tmWqkv, tmW1, tmA2, tmWo, tmW2, tmQKV;
    make_map(enc, &tmQKV, qkvp, 192, 8 * S_, 64, 128);
    make_map(enc, &tmX, x, D_, S_, 64, 128);
    make_map(enc, &tmWqkv, wqkv, 3 * D_, D_, 64, 64);
    make_map(enc, &tmW1, w1, F_, D_, 64, 64);
    make_map(enc, &tmA2, a2p, KA2, S_, 64, 64);
    make_map(enc, &tmWo, wo, D_, D_, 64, 64);
    make_map(enc, &tmW2, w2, D_, F_, 64, 64);

    cudaStream_t st = cudaStreamPerThread;
    k1_kernel<<<128, 384, K1_SMEM, st>>>(tmX, tmWqkv, tmW1, b1, gw, w1, wqkv, w2, wo);
    cudaLaunchAttribute at[1];
    at[0].id = cudaLaunchAttributeProgrammaticStreamSerialization;
    at[0].val.programmaticStreamSerializationAllowed = 1;
    cudaLaunchConfig_t cfg = {};
    cfg.gridDim = dim3(128); cfg.stream = st; cfg.attrs = at; cfg.numAttrs = 1;
    cfg.blockDim = dim3(512); cfg.dynamicSmemBytes = K2_SMEM;
    cudaLaunchKernelEx(&cfg, k2_kernel, tmQKV);
    k3_kernel<<<128, 384, K3_SMEM, st>>>(tmA2, tmWo, tmW2, (bf16*)d_out);
}
```

```cpp
#include <cuda_runtime.h>
#include <cuda_bf16.h>
#include <cuda.h>
#include <stdint.h>

typedef __nv_bfloat16 bf16;

constexpr int S_ = 2048, D_ = 512, F_ = 1376;
constexpr int KA2 = D_ + F_;
constexpr int FCH = 176;

__device__ bf16  g_qkv[8 * S_ * 192];
__device__ bf16  g_a2[S_ * KA2];
__device__ float g_gate[S_];

#define TS(k, cond) do { } while (0)

__device__ __forceinline__ uint32_t smem_u32(const void* p) { return (uint32_t)__cvta_generic_to_shared(p); }
__device__ __forceinline__ void mbar_init(uint32_t bar, uint32_t count) {
    asm volatile("mbarrier.init.shared::cta.b64 [%0], %1;" :: "r"(bar), "r"(count) : "memory");
}
__device__ __forceinline__ void mbar_expect_tx(uint32_t bar, uint32_t bytes) {
    asm volatile("mbarrier.arrive.expect_tx.shared::cta.b64 _, [%0], %1;" :: "r"(bar), "r"(bytes) : "memory");
}
__device__ __forceinline__ void mbar_arrive(uint32_t bar) {
    asm volatile("mbarrier.arrive.shared::cta.b64 _, [%0];" :: "r"(bar) : "memory");
}
__device__ __forceinline__ bool mbar_try_wait(uint32_t bar, uint32_t parity) {
    uint32_t ok;
    asm volatile("{\n.reg .pred p;\nmbarrier.try_wait.parity.shared::cta.b64 p, [%1], %2;\nselp.u32 %0, 1, 0, p;\n}"
                 : "=r"(ok) : "r"(bar), "r"(parity) : "memory");
    return ok != 0;
}
__device__ __forceinline__ void mbar_wait(uint32_t bar, uint32_t parity) {
    for (uint32_t it = 0; it < (1u << 22); ++it) { if (mbar_try_wait(bar, parity)) break; }
}
__device__ __forceinline__ void tma_load_2d(uint32_t dst, const CUtensorMap* map, int c0, int c1, uint32_t bar) {
    asm volatile("cp.async.bulk.tensor.2d.shared::cluster.global.mbarrier::complete_tx::bytes [%0], [%1, {%3, %4}], [%2];"
                 :: "r"(dst), "l"(map), "r"(bar), "r"(c0), "r"(c1) : "memory");
}
__device__ __forceinline__ void l2_prefetch(const void* p, uint32_t bytes) {
    asm volatile("cp.async.bulk.prefetch.L2.global [%0], %1;" :: "l"(p), "r"(bytes) : "memory");
}
__device__ __forceinline__ void fence_barrier_init() { asm volatile("fence.mbarrier_init.release.cluster;" ::: "memory"); }
__device__ __forceinline__ void wgmma_fence()  { asm volatile("wgmma.fence.sync.aligned;" ::: "memory"); }
__device__ __forceinline__ void wgmma_commit() { asm volatile("wgmma.commit_group.sync.aligned;" ::: "memory"); }
template <int N> __device__ __forceinline__ void wgmma_wait() { asm volatile("wgmma.wait_group.sync.aligned %0;" :: "n"(N) : "memory"); }
template <int R> __device__ __forceinline__ void reg_alloc()   { asm volatile("setmaxnreg.inc.sync.aligned.u32 %0;" :: "n"(R)); }
template <int R> __device__ __forceinline__ void reg_dealloc() { asm volatile("setmaxnreg.dec.sync.aligned.u32 %0;" :: "n"(R)); }
__device__ __forceinline__ void bar_sync(int id, int n)   { asm volatile("bar.sync %0, %1;" :: "r"(id), "r"(n) : "memory"); }
__device__ __forceinline__ void bar_arrive(int id, int n) { asm volatile("bar.arrive %0, %1;" :: "r"(id), "r"(n) : "memory"); }

__device__ __forceinline__ uint64_t make_desc(uint32_t addr, uint32_t lbo, uint32_t sbo) {
    uint64_t d = (uint64_t)((addr & 0x3FFFF) >> 4);
    d |= (uint64_t)((lbo & 0x3FFFF) >> 4) << 16;
    d |= (uint64_t)((sbo & 0x3FFFF) >> 4) << 32;
    d |= (uint64_t)1 << 62;
    return d;
}

template <int TB>
__device__ __forceinline__ void wgmma_n64(float (&d)[32], uint64_t da, uint64_t db, int scale_d) {
    asm volatile("{\n.reg .pred p;\nsetp.ne.b32 p, %34, 0;\n"
        "wgmma.mma_async.sync.aligned.m64n64k16.f32.bf16.bf16 {%0, %1, %2, %3, %4, %5, %6, %7, %8, %9, %10, %11, %12, %13, %14, %15, %16, %17, %18, %19, %20, %21, %22, %23, %24, %25, %26, %27, %28, %29, %30, %31}, %32, %33, p, 1, 1, 0, %35;\n}\n"
        : "+f"(d[0]), "+f"(d[1]), "+f"(d[2]), "+f"(d[3]), "+f"(d[4]), "+f"(d[5]), "+f"(d[6]), "+f"(d[7]), "+f"(d[8]), "+f"(d[9]), "+f"(d[10]), "+f"(d[11]), "+f"(d[12]), "+f"(d[13]), "+f"(d[14]), "+f"(d[15]), "+f"(d[16]), "+f"(d[17]), "+f"(d[18]), "+f"(d[19]), "+f"(d[20]), "+f"(d[21]), "+f"(d[22]), "+f"(d[23]), "+f"(d[24]), "+f"(d[25]), "+f"(d[26]), "+f"(d[27]), "+f"(d[28]), "+f"(d[29]), "+f"(d[30]), "+f"(d[31])
        : "l"(da), "l"(db), "r"(scale_d), "n"(TB));
}

template <int TB>
__device__ __forceinline__ void wgmma_n128(float (&d)[64], uint64_t da, uint64_t db, int scale_d) {
    asm volatile("{\n.reg .pred p;\nsetp.ne.b32 p, %66, 0;\n"
        "wgmma.mma_async.sync.aligned.m64n128k16.f32.bf16.bf16 {%0, %1, %2, %3, %4, %5, %6, %7, %8, %9, %10, %11, %12, %13, %14, %15, %16, %17, %18, %19, %20, %21, %22, %23, %24, %25, %26, %27, %28, %29, %30, %31, %32, %33, %34, %35, %36, %37, %38, %39, %40, %41, %42, %43, %44, %45, %46, %47, %48, %49, %50, %51, %52, %53, %54, %55, %56, %57, %58, %59, %60, %61, %62, %63}, %64, %65, p, 1, 1, 0, %67;\n}\n"
        : "+f"(d[0]), "+f"(d[1]), "+f"(d[2]), "+f"(d[3]), "+f"(d[4]), "+f"(d[5]), "+f"(d[6]), "+f"(d[7]), "+f"(d[8]), "+f"(d[9]), "+f"(d[10]), "+f"(d[11]), "+f"(d[12]), "+f"(d[13]), "+f"(d[14]), "+f"(d[15]), "+f"(d[16]), "+f"(d[17]), "+f"(d[18]), "+f"(d[19]), "+f"(d[20]), "+f"(d[21]), "+f"(d[22]), "+f"(d[23]), "+f"(d[24]), "+f"(d[25]), "+f"(d[26]), "+f"(d[27]), "+f"(d[28]), "+f"(d[29]), "+f"(d[30]), "+f"(d[31]), "+f"(d[32]), "+f"(d[33]), "+f"(d[34]), "+f"(d[35]), "+f"(d[36]), "+f"(d[37]), "+f"(d[38]), "+f"(d[39]), "+f"(d[40]), "+f"(d[41]), "+f"(d[42]), "+f"(d[43]), "+f"(d[44]), "+f"(d[45]), "+f"(d[46]), "+f"(d[47]), "+f"(d[48]), "+f"(d[49]), "+f"(d[50]), "+f"(d[51]), "+f"(d[52]), "+f"(d[53]), "+f"(d[54]), "+f"(d[55]), "+f"(d[56]), "+f"(d[57]), "+f"(d[58]), "+f"(d[59]), "+f"(d[60]), "+f"(d[61]), "+f"(d[62]), "+f"(d[63])
        : "l"(da), "l"(db), "r"(scale_d), "n"(TB));
}

template <int TB>
__device__ __forceinline__ void wgmma_n176(float (&d)[88], uint64_t da, uint64_t db, int scale_d) {
    asm volatile("{\n.reg .pred p;\nsetp.ne.b32 p, %90, 0;\n"
        "wgmma.mma_async.sync.aligned.m64n176k16.f32.bf16.bf16 {%0, %1, %2, %3, %4, %5, %6, %7, %8, %9, %10, %11, %12, %13, %14, %15, %16, %17, %18, %19, %20, %21, %22, %23, %24, %25, %26, %27, %28, %29, %30, %31, %32, %33, %34, %35, %36, %37, %38, %39, %40, %41, %42, %43, %44, %45, %46, %47, %48, %49, %50, %51, %52, %53, %54, %55, %56, %57, %58, %59, %60, %61, %62, %63, %64, %65, %66, %67, %68, %69, %70, %71, %72, %73, %74, %75, %76, %77, %78, %79, %80, %81, %82, %83, %84, %85, %86, %87}, %88, %89, p, 1, 1, 0, %91;\n}\n"
        : "+f"(d[0]), "+f"(d[1]), "+f"(d[2]), "+f"(d[3]), "+f"(d[4]), "+f"(d[5]), "+f"(d[6]), "+f"(d[7]), "+f"(d[8]), "+f"(d[9]), "+f"(d[10]), "+f"(d[11]), "+f"(d[12]), "+f"(d[13]), "+f"(d[14]), "+f"(d[15]), "+f"(d[16]), "+f"(d[17]), "+f"(d[18]), "+f"(d[19]), "+f"(d[20]), "+f"(d[21]), "+f"(d[22]), "+f"(d[23]), "+f"(d[24]), "+f"(d[25]), "+f"(d[26]), "+f"(d[27]), "+f"(d[28]), "+f"(d[29]), "+f"(d[30]), "+f"(d[31]), "+f"(d[32]), "+f"(d[33]), "+f"(d[34]), "+f"(d[35]), "+f"(d[36]), "+f"(d[37]), "+f"(d[38]), "+f"(d[39]), "+f"(d[40]), "+f"(d[41]), "+f"(d[42]), "+f"(d[43]), "+f"(d[44]), "+f"(d[45]), "+f"(d[46]), "+f"(d[47]), "+f"(d[48]), "+f"(d[49]), "+f"(d[50]), "+f"(d[51]), "+f"(d[52]), "+f"(d[53]), "+f"(d[54]), "+f"(d[55]), "+f"(d[56]), "+f"(d[57]), "+f"(d[58]), "+f"(d[59]), "+f"(d[60]), "+f"(d[61]), "+f"(d[62]), "+f"(d[63]), "+f"(d[64]), "+f"(d[65]), "+f"(d[66]), "+f"(d[67]), "+f"(d[68]), "+f"(d[69]), "+f"(d[70]), "+f"(d[71]), "+f"(d[72]), "+f"(d[73]), "+f"(d[74]), "+f"(d[75]), "+f"(d[76]), "+f"(d[77]), "+f"(d[78]), "+f"(d[79]), "+f"(d[80]), "+f"(d[81]), "+f"(d[82]), "+f"(d[83]), "+f"(d[84]), "+f"(d[85]), "+f"(d[86]), "+f"(d[87])
        : "l"(da), "l"(db), "r"(scale_d), "n"(TB));
}

template <int TB>
__device__ __forceinline__ void wgmma_n192(float (&d)[96], uint64_t da, uint64_t db, int scale_d) {
    asm volatile("{\n.reg .pred p;\nsetp.ne.b32 p, %98, 0;\n"
        "wgmma.mma_async.sync.aligned.m64n192k16.f32.bf16.bf16 {%0, %1, %2, %3, %4, %5, %6, %7, %8, %9, %10, %11, %12, %13, %14, %15, %16, %17, %18, %19, %20, %21, %22, %23, %24, %25, %26, %27, %28, %29, %30, %31, %32, %33, %34, %35, %36, %37, %38, %39, %40, %41, %42, %43, %44, %45, %46, %47, %48, %49, %50, %51, %52, %53, %54, %55, %56, %57, %58, %59, %60, %61, %62, %63, %64, %65, %66, %67, %68, %69, %70, %71, %72, %73, %74, %75, %76, %77, %78, %79, %80, %81, %82, %83, %84, %85, %86, %87, %88, %89, %90, %91, %92, %93, %94, %95}, %96, %97, p, 1, 1, 0, %99;\n}\n"
        : "+f"(d[0]), "+f"(d[1]), "+f"(d[2]), "+f"(d[3]), "+f"(d[4]), "+f"(d[5]), "+f"(d[6]), "+f"(d[7]), "+f"(d[8]), "+f"(d[9]), "+f"(d[10]), "+f"(d[11]), "+f"(d[12]), "+f"(d[13]), "+f"(d[14]), "+f"(d[15]), "+f"(d[16]), "+f"(d[17]), "+f"(d[18]), "+f"(d[19]), "+f"(d[20]), "+f"(d[21]), "+f"(d[22]), "+f"(d[23]), "+f"(d[24]), "+f"(d[25]), "+f"(d[26]), "+f"(d[27]), "+f"(d[28]), "+f"(d[29]), "+f"(d[30]), "+f"(d[31]), "+f"(d[32]), "+f"(d[33]), "+f"(d[34]), "+f"(d[35]), "+f"(d[36]), "+f"(d[37]), "+f"(d[38]), "+f"(d[39]), "+f"(d[40]), "+f"(d[41]), "+f"(d[42]), "+f"(d[43]), "+f"(d[44]), "+f"(d[45]), "+f"(d[46]), "+f"(d[47]), "+f"(d[48]), "+f"(d[49]), "+f"(d[50]), "+f"(d[51]), "+f"(d[52]), "+f"(d[53]), "+f"(d[54]), "+f"(d[55]), "+f"(d[56]), "+f"(d[57]), "+f"(d[58]), "+f"(d[59]), "+f"(d[60]), "+f"(d[61]), "+f"(d[62]), "+f"(d[63]), "+f"(d[64]), "+f"(d[65]), "+f"(d[66]), "+f"(d[67]), "+f"(d[68]), "+f"(d[69]), "+f"(d[70]), "+f"(d[71]), "+f"(d[72]), "+f"(d[73]), "+f"(d[74]), "+f"(d[75]), "+f"(d[76]), "+f"(d[77]), "+f"(d[78]), "+f"(d[79]), "+f"(d[80]), "+f"(d[81]), "+f"(d[82]), "+f"(d[83]), "+f"(d[84]), "+f"(d[85]), "+f"(d[86]), "+f"(d[87]), "+f"(d[88]), "+f"(d[89]), "+f"(d[90]), "+f"(d[91]), "+f"(d[92]), "+f"(d[93]), "+f"(d[94]), "+f"(d[95])
        : "l"(da), "l"(db), "r"(scale_d), "n"(TB));
}

__device__ __forceinline__ uint32_t pack_bf16(float lo, float hi) {
    uint32_t r;
    asm("cvt.rn.bf16x2.f32 %0, %1, %2;" : "=r"(r) : "f"(hi), "f"(lo));
    return r;
}
__device__ __forceinline__ float bf_lo(uint32_t v) { return __uint_as_float(v << 16); }
__device__ __forceinline__ float bf_hi(uint32_t v) { return __uint_as_float(v & 0xffff0000u); }

__device__ __forceinline__ void quad_transpose(uint32_t (&w)[4], int q) {
    const bool o1 = q & 1, o2 = q & 2;
    {
        uint32_t s0 = o1 ? w[0] : w[1], s1 = o1 ? w[2] : w[3];
        s0 = __shfl_xor_sync(0xffffffffu, s0, 1); s1 = __shfl_xor_sync(0xffffffffu, s1, 1);
        if (o1) { w[0] = s0; w[2] = s1; } else { w[1] = s0; w[3] = s1; }
    }
    {
        uint32_t s0 = o2 ? w[0] : w[2], s1 = o2 ? w[1] : w[3];
        s0 = __shfl_xor_sync(0xffffffffu, s0, 2); s1 = __shfl_xor_sync(0xffffffffu, s1, 2);
        if (o2) { w[0] = s0; w[1] = s1; } else { w[2] = s0; w[3] = s1; }
    }
}

__device__ __forceinline__ float ex2(float x) { float y; asm("ex2.approx.ftz.f32 %0, %1;" : "=f"(y) : "f"(x)); return y; }
__device__ __forceinline__ float rcp(float x) { float y; asm("rcp.approx.ftz.f32 %0, %1;" : "=f"(y) : "f"(x)); return y; }

__device__ __forceinline__ float ex2v(float x) { float y; asm volatile("ex2.approx.ftz.f32 %0, %1;" : "=f"(y) : "f"(x)); return y; }
__device__ __forceinline__ float rcpv(float x) { float y; asm volatile("rcp.approx.ftz.f32 %0, %1;" : "=f"(y) : "f"(x)); return y; }
__device__ __forceinline__ float mish_f(float h) {
    const float e = ex2v(1.4426950408889634f * fminf(h, 20.f));
    const float n = fmaf(e, e, e + e);
    return h * n * rcpv(n + 2.f);
}

__device__ __forceinline__ void pdl_wait()   { asm volatile("griddepcontrol.wait;" ::: "memory"); }
__device__ __forceinline__ void pdl_launch() { asm volatile("griddepcontrol.launch_dependents;" ::: "memory"); }

constexpr int K1_STAGES = 4;
constexpr int K1_XBYTES = 128 * 512 * 2;
constexpr int K1_BSTAGE = 3 * 8192;
constexpr int K1_SMEM   = K1_XBYTES + K1_STAGES * K1_BSTAGE + 2048   + 1024  ;

constexpr int HPITCH = 176;

__global__ void __launch_bounds__(512, 1)
k1_kernel(const __grid_constant__ CUtensorMap tmX, const __grid_constant__ CUtensorMap tmWqkv,
          const __grid_constant__ CUtensorMap tmW1, const bf16* __restrict__ b1,
          const bf16* __restrict__ gate_w, const bf16* __restrict__ w1p, const bf16* __restrict__ wqkvp,
          const bf16* __restrict__ w2p, const bf16* __restrict__ wop)
{

    extern __shared__ uint8_t smem_raw[];
    const uint32_t sbase = (smem_u32(smem_raw) + 1023u) & ~1023u;
    uint8_t* sgen = smem_raw + (sbase - smem_u32(smem_raw));
    const uint32_t sX = sbase;
    const uint32_t sB = sbase + K1_XBYTES;
    const uint32_t sBar = sB + K1_STAGES * K1_BSTAGE;
    const uint32_t x_full = sBar;
    const uint32_t b_full = sBar + 64;
    const uint32_t b_empty = sBar + 96;
    float* sGate = (float*)(sgen + K1_XBYTES + K1_STAGES * K1_BSTAGE + 128);
    uint8_t* sGw = sgen + K1_XBYTES + K1_STAGES * K1_BSTAGE + 640;
    uint32_t* sBias = (uint32_t*)(sgen + K1_XBYTES + K1_STAGES * K1_BSTAGE + 1664);

    const int rb = blockIdx.x >> 3, j = blockIdx.x & 7;
    const int tid = threadIdx.x, lane = tid & 31;
    const int warp = __shfl_sync(0xffffffffu, tid >> 5, 0), wg = warp >> 2;
    TS(0, tid == 0);
    pdl_launch();

    if (tid == 0) {
        for (int i = 0; i < 8; i++) mbar_init(x_full + 8 * i, 1);
        for (int i = 0; i < K1_STAGES; i++) { mbar_init(b_full + 8 * i, 1); mbar_init(b_empty + 8 * i, 8); }
        fence_barrier_init();
    }
    __syncthreads();

    if (wg >= 2) {
        reg_dealloc<40>();
        if (warp == 8) {
            if (lane == 0) {
                for (int it = 0; it < 16; it++) {
                    if (it < 8) {
                        mbar_expect_tx(x_full + 8 * it, 16384);
                        tma_load_2d(sX + it * 16384, &tmX, it * 64, rb * 128, x_full + 8 * it);
                    }
                    const int st = it & 3;
                    if (it >= K1_STAGES) mbar_wait(b_empty + 8 * st, ((it >> 2) - 1) & 1);
                    mbar_expect_tx(b_full + 8 * st, K1_BSTAGE);
                    const uint32_t dst = sB + st * K1_BSTAGE;
                    if (it < 8) {
                        for (int b = 0; b < 3; b++) tma_load_2d(dst + b * 8192, &tmW1, j * FCH + b * 64, it * 64, b_full + 8 * st);
                    } else {
                        for (int b = 0; b < 3; b++) tma_load_2d(dst + b * 8192, &tmWqkv, b * 512 + j * 64, (it - 8) * 64, b_full + 8 * st);
                    }
                }
            }
        } else {
            if (tid == 288) {
                const int b = blockIdx.x;
                mbar_wait(b_full + 8, 0);
                l2_prefetch((const uint8_t*)wqkvp + b * 12288, 12288);
                l2_prefetch((const uint8_t*)w2p + b * 11008, 11008);
                l2_prefetch((const uint8_t*)wop + b * 4096, 4096);
            }
            __syncwarp();
            const int ht = tid - 288;
            const int n0 = j * FCH + 96;
            bar_sync(4, 256 + 224);
#pragma unroll 2
            for (int it = ht; it < 128 * 10; it += 224) {
                const int r = it / 10, c = it - r * 10;
                const int w = r >> 6, rl = r & 63;
                const int p = rl >= 46, rr = rl - p * 46;
                const uint4 hv = *(const uint4*)(sgen + p * 16384 + w * 8192 + rr * HPITCH + c * 16);
                const float om = 1.f - sGate[r];
                uint4 o;
                o.x = pack_bf16(mish_f(bf_lo(hv.x)) * om, mish_f(bf_hi(hv.x)) * om);
                o.y = pack_bf16(mish_f(bf_lo(hv.y)) * om, mish_f(bf_hi(hv.y)) * om);
                o.z = pack_bf16(mish_f(bf_lo(hv.z)) * om, mish_f(bf_hi(hv.z)) * om);
                o.w = pack_bf16(mish_f(bf_lo(hv.w)) * om, mish_f(bf_hi(hv.w)) * om);
                if (n0 + c * 8 < F_)
                    *(uint4*)(g_a2 + (size_t)(rb * 128 + r) * KA2 + D_ + n0 + c * 8) = o;
            }
            TS(16, tid == 288);
        }
    } else {
        reg_alloc<216>();
        if (tid < 64) ((uint4*)sGw)[tid] = __ldg((const uint4*)gate_w + tid);
        else if (tid < 64 + 88) {
            const int c = j * FCH + (tid - 64) * 2;
            sBias[tid - 64] = c < F_ ? __ldg((const uint32_t*)(b1 + c)) : 0u;
        }
        bar_sync(3, 256);
        const int t128 = tid & 127, w4 = warp & 3, q = lane & 3;
        float accF[88], accQ[96];
        const uint64_t da0 = make_desc(sX + wg * 8192, 16, 1024);
        const uint64_t db0 = make_desc(sB, 8192, 1024);
        float gs = 0.f;
        const int grow = wg * 64 + (t128 >> 1), ghalf = t128 & 1;
#pragma unroll
        for (int kc = 0; kc < 8; kc++) {
            const int st = kc & 3;
            mbar_wait(x_full + 8 * kc, 0);
            mbar_wait(b_full + 8 * st, (kc >> 2) & 1);
            TS(1, tid == 0 && kc == 0); TS(2, tid == 0 && kc == 4);
            wgmma_fence();
#pragma unroll
            for (int k16 = 0; k16 < 4; k16++) {
                wgmma_n176<1>(accF, da0 + (kc * 1024 + k16 * 2), db0 + (st * (K1_BSTAGE >> 4) + k16 * 128), (kc | k16) != 0);
            }
            wgmma_commit();
#pragma unroll
            for (int c = 0; c < 4; c++) {
                const int cc = ghalf * 4 + c;
                const uint4 xv = *(const uint4*)(sgen + kc * 16384 + grow * 128 + ((cc ^ (grow & 7)) << 4));
                const uint4 gv = *(const uint4*)(sGw + kc * 128 + cc * 16);
                gs = fmaf(bf_lo(xv.x), bf_lo(gv.x), gs); gs = fmaf(bf_hi(xv.x), bf_hi(gv.x), gs);
                gs = fmaf(bf_lo(xv.y), bf_lo(gv.y), gs); gs = fmaf(bf_hi(xv.y), bf_hi(gv.y), gs);
                gs = fmaf(bf_lo(xv.z), bf_lo(gv.z), gs); gs = fmaf(bf_hi(xv.z), bf_hi(gv.z), gs);
                gs = fmaf(bf_lo(xv.w), bf_lo(gv.w), gs); gs = fmaf(bf_hi(xv.w), bf_hi(gv.w), gs);
            }
            if (kc > 0) { wgmma_wait<1>(); if (lane == 0) mbar_arrive(b_empty + 8 * ((kc - 1) & 3)); }
        }
        gs += __shfl_xor_sync(0xffffffffu, gs, 1);
        {
            const float g = 1.f / (1.f + __expf(-gs));
            if (ghalf == 0) {
                sGate[grow] = g;
                if (j == 0) g_gate[rb * 128 + grow] = g;
            }
        }
        wgmma_wait<0>();
        if (lane == 0) mbar_arrive(b_empty + 8 * 3);
        bar_sync(1 + wg, 128);
        TS(3, tid == 0);
        const int n0 = j * FCH;
        const int rl = wg * 64 + w4 * 16 + (lane >> 2);
        const float om0 = 1.f - sGate[rl], om1 = 1.f - sGate[rl + 8];
        bf16* frow0 = g_a2 + (size_t)(rb * 128 + rl) * KA2 + D_ + n0;
        bf16* frow1 = frow0 + 8 * KA2;
        auto ffn_chunk = [&](int u) {
            uint32_t w0[4], w1[4];
#pragma unroll
            for (int i = 0; i < 4; i++) {
                const int t = u * 4 + i;
                if (t < 22) {
                    const uint32_t bv = sBias[t * 4 + q];
                    const float bb0 = bf_lo(bv), bb1 = bf_hi(bv);
                    w0[i] = pack_bf16(mish_f(accF[t * 4 + 0] + bb0) * om0, mish_f(accF[t * 4 + 1] + bb1) * om0);
                    w1[i] = pack_bf16(mish_f(accF[t * 4 + 2] + bb0) * om1, mish_f(accF[t * 4 + 3] + bb1) * om1);
                } else { w0[i] = 0; w1[i] = 0; }
            }
            quad_transpose(w0, q);
            quad_transpose(w1, q);
            const int c = (u * 4 + q) * 8;
            if (c < FCH && n0 + c < F_) {
                *(uint4*)(frow0 + c) = make_uint4(w0[0], w0[1], w0[2], w0[3]);
                *(uint4*)(frow1 + c) = make_uint4(w1[0], w1[1], w1[2], w1[3]);
            }
        };
#pragma unroll
        for (int kc = 0; kc < 8; kc++) {
            const int st = kc & 3;
            mbar_wait(b_full + 8 * st, ((kc + 8) >> 2) & 1);
            wgmma_fence();
#pragma unroll
            for (int k16 = 0; k16 < 4; k16++) {
                wgmma_n192<1>(accQ, da0 + (kc * 1024 + k16 * 2), db0 + (st * (K1_BSTAGE >> 4) + k16 * 128), (kc | k16) != 0);
            }
            wgmma_commit();
            if (kc < 3) ffn_chunk(kc);
            if (kc > 0) { wgmma_wait<1>(); if (lane == 0) mbar_arrive(b_empty + 8 * ((kc - 1) & 3)); }
            if (kc == 2) {
                const int r0 = w4 * 16 + (lane >> 2), r1 = r0 + 8;
                uint8_t* d0 = sgen + (r0 >= 46) * 16384 + wg * 8192 + (r0 - (r0 >= 46) * 46) * HPITCH + q * 4;
                uint8_t* d1 = sgen + (r1 >= 46) * 16384 + wg * 8192 + (r1 - (r1 >= 46) * 46) * HPITCH + q * 4;
#pragma unroll
                for (int t = 12; t < 22; t++) {
                    const uint32_t bv = sBias[t * 4 + q];
                    const float bb0 = bf_lo(bv), bb1 = bf_hi(bv);
                    *(uint32_t*)(d0 + (t - 12) * 16) = pack_bf16(accF[t * 4 + 0] + bb0, accF[t * 4 + 1] + bb1);
                    *(uint32_t*)(d1 + (t - 12) * 16) = pack_bf16(accF[t * 4 + 2] + bb0, accF[t * 4 + 3] + bb1);
                }
                bar_arrive(4, 256 + 224);
            }
        }
        wgmma_wait<0>();
        TS(4, tid == 0);
        {
            bf16* orow0 = g_qkv + ((size_t)j * S_ + rb * 128 + rl) * 192;
            bf16* orow1 = orow0 + 8 * 192;
#pragma unroll
            for (int u = 0; u < 6; u++) {
                uint32_t w0[4], w1[4];
#pragma unroll
                for (int i = 0; i < 4; i++) {
                    const int t = u * 4 + i;
                    w0[i] = pack_bf16(accQ[t * 4 + 0], accQ[t * 4 + 1]);
                    w1[i] = pack_bf16(accQ[t * 4 + 2], accQ[t * 4 + 3]);
                }
                quad_transpose(w0, q);
                quad_transpose(w1, q);
                const int c = (u * 4 + q) * 8;
                *(uint4*)(orow0 + c) = make_uint4(w0[0], w0[1], w0[2], w0[3]);
                *(uint4*)(orow1 + c) = make_uint4(w1[0], w1[1], w1[2], w1[3]);
            }
        }
        TS(5, tid == 0);
    }
}

__device__ __forceinline__ void ldsm_x4(uint32_t (&r)[4], uint32_t addr) {
    asm("ldmatrix.sync.aligned.m8n8.x4.shared.b16 {%0,%1,%2,%3}, [%4];"
                 : "=r"(r[0]), "=r"(r[1]), "=r"(r[2]), "=r"(r[3]) : "r"(addr));
}
__device__ __forceinline__ void ldsm_x4_t(uint32_t (&r)[4], uint32_t addr) {
    asm("ldmatrix.sync.aligned.m8n8.x4.trans.shared.b16 {%0,%1,%2,%3}, [%4];"
                 : "=r"(r[0]), "=r"(r[1]), "=r"(r[2]), "=r"(r[3]) : "r"(addr));
}
__device__ __forceinline__ void mma16816(float (&d)[4], const uint32_t (&a)[4], uint32_t b0, uint32_t b1) {
    asm("mma.sync.aligned.m16n8k16.row.col.f32.bf16.bf16.f32 {%0,%1,%2,%3}, {%4,%5,%6,%7}, {%8,%9}, {%0,%1,%2,%3};"
                 : "+f"(d[0]), "+f"(d[1]), "+f"(d[2]), "+f"(d[3])
                 : "r"(a[0]), "r"(a[1]), "r"(a[2]), "r"(a[3]), "r"(b0), "r"(b1));
}
__device__ __forceinline__ void mma16816_z(float (&d)[4], const uint32_t (&a)[4], uint32_t b0, uint32_t b1) {
    asm("mma.sync.aligned.m16n8k16.row.col.f32.bf16.bf16.f32 {%0,%1,%2,%3}, {%4,%5,%6,%7}, {%8,%9}, {%10,%10,%10,%10};"
                 : "=f"(d[0]), "=f"(d[1]), "=f"(d[2]), "=f"(d[3])
                 : "r"(a[0]), "r"(a[1]), "r"(a[2]), "r"(a[3]), "r"(b0), "r"(b1), "f"(0.f));
}

constexpr int KV_PITCH = 128;

template <int EDGE, bool HEAD>
__device__ __forceinline__ void blk_scores(float (&s)[2][4], const uint32_t (&qa)[4], uint32_t kaddr, bool dead, int r0, int c0)
{
    uint32_t kf[4];
    ldsm_x4(kf, kaddr);
    mma16816_z(s[0], qa, kf[0], kf[1]);
    mma16816_z(s[1], qa, kf[2], kf[3]);
#pragma unroll
    for (int t = 0; t < 2; t++)
#pragma unroll
        for (int e = 0; e < 4; e++) {
            const int r = r0 + (e >> 1) * 8, c = t * 8 + c0 + (e & 1);
            if (EDGE == 1 && c <= r) s[t][e] = -1e30f;
            if (EDGE == 2 && c > r) s[t][e] = -1e30f;
            if (HEAD && dead) s[t][e] = -1e30f;
        }
}
__device__ __forceinline__ void blk_max(const float (&s)[2][4], float& n0, float& n1) {
    n0 = fmaxf(n0, fmaxf(fmaxf(s[0][0], s[0][1]), fmaxf(s[1][0], s[1][1])));
    n1 = fmaxf(n1, fmaxf(fmaxf(s[0][2], s[0][3]), fmaxf(s[1][2], s[1][3])));
}
__device__ __forceinline__ void blk_pv(const float (&s)[2][4], float mc0, float mc1, float (&l)[4],
                                       float (&o)[2][4], uint32_t vaddr) {
    const float C = 0.25f * 1.4426950408889634f;
    uint32_t pa[4];
#pragma unroll
    for (int t = 0; t < 2; t++) {
        const float p0 = ex2(fmaf(s[t][0], C, -mc0)), p1 = ex2(fmaf(s[t][1], C, -mc0));
        const float p2 = ex2(fmaf(s[t][2], C, -mc1)), p3 = ex2(fmaf(s[t][3], C, -mc1));
        pa[2 * t] = pack_bf16(p0, p1); pa[2 * t + 1] = pack_bf16(p2, p3);
    }
    uint32_t vf[4];
    ldsm_x4_t(vf, vaddr);
    mma16816(o[0], pa, vf[0], vf[1]);
    mma16816(o[1], pa, vf[2], vf[3]);
    mma16816(l, pa, 0x3F803F80u, 0x3F803F80u);
}
__device__ __forceinline__ void quad_max(float& n0, float& n1) {
    n0 = fmaxf(n0, __shfl_xor_sync(0xffffffffu, n0, 1)); n1 = fmaxf(n1, __shfl_xor_sync(0xffffffffu, n1, 1));
    n0 = fmaxf(n0, __shfl_xor_sync(0xffffffffu, n0, 2)); n1 = fmaxf(n1, __shfl_xor_sync(0xffffffffu, n1, 2));
}
template <int NC, int NN, bool FIRST, bool NEXT_IS_EDGE, bool HEAD>
__device__ __forceinline__ void pipe_step(const float (&sc)[5][2][4], float (&sn)[5][2][4], const uint32_t (&qa)[4],
                                          uint32_t ka, uint32_t va, int kc, int kn, int kb0, int r0, int c0,
                                          float& m0, float& m1, float& n0, float& n1, float (&l)[4], float (&o)[2][4])
{
    const float C = 0.25f * 1.4426950408889634f;
    const float mc0 = n0 * C, mc1 = n1 * C;
    if (!FIRST) {
        const float a0 = ex2(fmaf(m0, C, -mc0)), a1 = ex2(fmaf(m1, C, -mc1));
        l[0] *= a0; l[2] *= a1;
        o[0][0] *= a0; o[0][1] *= a0; o[1][0] *= a0; o[1][1] *= a0;
        o[0][2] *= a1; o[0][3] *= a1; o[1][2] *= a1; o[1][3] *= a1;
    }
    m0 = n0; m1 = n1;
#pragma unroll
    for (int b = 0; b < NC; b++) {
        if (b < NN) {
            if (NEXT_IS_EDGE && b == 0) blk_scores<1, HEAD>(sn[b], qa, ka + (kn + b) * 16 * KV_PITCH, kn + b < kb0, r0, c0);
            else                        blk_scores<0, HEAD>(sn[b], qa, ka + (kn + b) * 16 * KV_PITCH, kn + b < kb0, r0, c0);
        }
        blk_pv(sc[b], mc0, mc1, l, o, va + (kc + b) * 16 * KV_PITCH);
        if (b < NN) blk_max(sn[b], n0, n1);
    }
    if (NN > 0) quad_max(n0, n1);
}

__device__ __forceinline__ void kv_need(uint32_t kvbar, int blk, uint32_t& ka, uint32_t& va) {
    mbar_wait(kvbar + 8 * blk, 0);
    asm volatile("" : "+r"(ka), "+r"(va) :: "memory");
}
template <bool HEAD>
__device__ __forceinline__ void attn_task(const uint32_t (&qa)[4], uint32_t ka, uint32_t va, int kb0, int lane, int qt, uint32_t kvbar,
                                          bf16* __restrict__ out  , float g0, float g1)
{
    const int r0 = lane >> 2, c0 = (lane & 3) * 2;
    float m0 = -1e30f, m1 = -1e30f, n0 = -1e30f, n1 = -1e30f;
    float l[4] = {0.f, 0.f, 0.f, 0.f};
    float o[2][4] = {{0.f, 0.f, 0.f, 0.f}, {0.f, 0.f, 0.f, 0.f}};
    float sa[5][2][4], sb[5][2][4];
    kv_need(kvbar, 2, ka, va);
    if (qt < 4) kv_need(kvbar, 1, ka, va);
#pragma unroll
    for (int b = 0; b < 5; b++) {
        if (b == 4) blk_scores<2, HEAD>(sa[b], qa, ka + (12 + b) * 16 * KV_PITCH, false, r0, c0);
        else        blk_scores<0, HEAD>(sa[b], qa, ka + (12 + b) * 16 * KV_PITCH, 12 + b < kb0, r0, c0);
        blk_max(sa[b], n0, n1);
    }
    quad_max(n0, n1);
    kv_need(kvbar, 1, ka, va);
    if (HEAD) {
        pipe_step<5, 0, true, false, HEAD>(sa, sb, qa, ka, va, 12, 0, kb0, r0, c0, m0, m1, n0, n1, l, o);
        kv_need(kvbar, 0, ka, va);
#pragma unroll 1
        for (int kc = 8; kc >= 0 && kb0 < kc + 4; kc -= 4) {
#pragma unroll
            for (int b = 0; b < 4; b++) {
                blk_scores<0, HEAD>(sa[b], qa, ka + (kc + b) * 16 * KV_PITCH, kc + b < kb0, r0, c0);
                blk_max(sa[b], n0, n1);
            }
            quad_max(n0, n1);
            pipe_step<4, 0, false, false, HEAD>(sa, sb, qa, ka, va, kc, 0, kb0, r0, c0, m0, m1, n0, n1, l, o);
        }
    } else {
        pipe_step<5, 4, true,  false, HEAD>(sa, sb, qa, ka, va, 12, 8, kb0, r0, c0, m0, m1, n0, n1, l, o);
        if (qt < 4) kv_need(kvbar, 0, ka, va);
        pipe_step<4, 4, false, false, HEAD>(sb, sa, qa, ka, va, 8, 4, kb0, r0, c0, m0, m1, n0, n1, l, o);
        kv_need(kvbar, 0, ka, va);
        pipe_step<4, 4, false, true,  HEAD>(sa, sb, qa, ka, va, 4, 0, kb0, r0, c0, m0, m1, n0, n1, l, o);
        pipe_step<4, 0, false, false, HEAD>(sb, sa, qa, ka, va, 0, 0, kb0, r0, c0, m0, m1, n0, n1, l, o);
    }
    const float f0 = __fdividef(g0, l[0]), f1 = __fdividef(g1, l[2]);
#pragma unroll
    for (int t = 0; t < 2; t++) {
        *(uint32_t*)(out + (size_t)r0 * KA2 + t * 8 + c0) = pack_bf16(o[t][0] * f0, o[t][1] * f0);
        *(uint32_t*)(out + (size_t)(r0 + 8) * KA2 + t * 8 + c0) = pack_bf16(o[t][2] * f1, o[t][3] * f1);
    }
}

constexpr int K2_SMEM = 2 * 384 * KV_PITCH + 1024 + 64;

__global__ void __launch_bounds__(512, 1) k2_kernel(const __grid_constant__ CUtensorMap tmQKV)
{
    extern __shared__ uint8_t smem_raw[];
    const uint32_t sbase = (smem_u32(smem_raw) + 1023u) & ~1023u;
    uint8_t* sgen = smem_raw + (sbase - smem_u32(smem_raw));
    const uint32_t sK = sbase, sV = sK + 384 * KV_PITCH, kv_full = sbase + 2 * 384 * KV_PITCH;
    const int rb = blockIdx.x >> 3, j = blockIdx.x & 7;
    const int tid = threadIdx.x, warp = tid >> 5, lane = tid & 31;
    pdl_launch();
    if (tid == 0) {
        for (int i = 0; i < 3; i++) mbar_init(kv_full + 8 * i, 1);
        fence_barrier_init();
    }
    pdl_wait();
    TS(6, tid == 0);
    if (tid == 0) {
        for (int i = 0; i < 3; i++) {
            const uint32_t bar = kv_full + 8 * (2 - i);
            if (rb - i >= 0) {
                const int row = j * S_ + (rb - i) * 128;
                mbar_expect_tx(bar, 2 * 16384);
                tma_load_2d(sK + (2 - i) * 16384, &tmQKV, 64, row, bar);
                tma_load_2d(sV + (2 - i) * 16384, &tmQKV, 128, row, bar);
            } else {
                mbar_arrive(bar);
            }
        }
    }
    if (rb < 2) {
        for (int i = tid; i < (2 - rb) * 1024; i += 512) {
            *(uint4*)(sgen + i * 16) = make_uint4(0, 0, 0, 0);
            *(uint4*)(sgen + 384 * KV_PITCH + i * 16) = make_uint4(0, 0, 0, 0);
        }
    }
    const int qt = warp & 7, h0 = (warp >> 3) * 2;
    const int q0g = rb * 128 + qt * 16;
    const int r0 = lane >> 2, c0 = (lane & 3) * 2;
    const bf16* qsrc = g_qkv + ((size_t)j * S_ + q0g) * 192 + h0 * 16;
    uint32_t qa[4], qn[4];
    qa[0] = *(const uint32_t*)(qsrc + (size_t)r0 * 192 + c0);
    qa[1] = *(const uint32_t*)(qsrc + (size_t)(r0 + 8) * 192 + c0);
    qa[2] = *(const uint32_t*)(qsrc + (size_t)r0 * 192 + c0 + 8);
    qa[3] = *(const uint32_t*)(qsrc + (size_t)(r0 + 8) * 192 + c0 + 8);
    qn[0] = *(const uint32_t*)(qsrc + (size_t)r0 * 192 + 16 + c0);
    qn[1] = *(const uint32_t*)(qsrc + (size_t)(r0 + 8) * 192 + 16 + c0);
    qn[2] = *(const uint32_t*)(qsrc + (size_t)r0 * 192 + 16 + c0 + 8);
    qn[3] = *(const uint32_t*)(qsrc + (size_t)(r0 + 8) * 192 + 16 + c0 + 8);
    const float g0 = g_gate[q0g + r0], g1 = g_gate[q0g + r0 + 8];
    const int kb0 = q0g < 256 ? (256 - q0g) >> 4 : 0;
    __syncthreads();
    const uint32_t sKd = sK, sVd = sV;
    TS(7, tid == 0);
    const int krow = qt * 16 + (lane & 7) + ((lane >> 4) << 3);
    const int vrow = qt * 16 + (lane & 15);
#pragma unroll 1
    for (int hh = 0; hh < 2; hh++) {
        const int hl = h0 + hh;
        const uint32_t ka = sKd + krow * KV_PITCH + (((2 * hl + ((lane >> 3) & 1)) ^ (lane & 7)) << 4);
        const uint32_t va = sVd + vrow * KV_PITCH + (((2 * hl + (lane >> 4)) ^ (lane & 7)) << 4);
        if (rb < 2) attn_task<true>(qa, ka, va, kb0, lane, qt, kv_full, g_a2 + (size_t)q0g * KA2 + (j * 4 + hl) * 16, g0, g1);
        else        attn_task<false>(qa, ka, va, kb0, lane, qt, kv_full, g_a2 + (size_t)q0g * KA2 + (j * 4 + hl) * 16, g0, g1);
        TS(8 + hh, tid == 0);
        qa[0] = qn[0]; qa[1] = qn[1]; qa[2] = qn[2]; qa[3] = qn[3];
    }
}

constexpr int K3_STAGES = 8;
constexpr int K3_STAGE = 16384 + 8192;
constexpr int K3_SMEM = K3_STAGES * K3_STAGE + 1024 + 1024;
constexpr int K3_KSTEPS = 30;

__global__ void __launch_bounds__(384, 1)
k3_kernel(const __grid_constant__ CUtensorMap tmA2, const __grid_constant__ CUtensorMap tmWo,
          const __grid_constant__ CUtensorMap tmW2, bf16* __restrict__ out)
{
    extern __shared__ uint8_t smem_raw[];
    const uint32_t sbase = (smem_u32(smem_raw) + 1023u) & ~1023u;
    const uint32_t sBar = sbase + K3_STAGES * K3_STAGE;
    const uint32_t full = sBar, empty = sBar + 64;
    const int rb = blockIdx.x >> 3, nb = blockIdx.x & 7;
    const int tid = threadIdx.x, lane = tid & 31;
    const int warp = __shfl_sync(0xffffffffu, tid >> 5, 0), wg = warp >> 2;
    if (tid == 0) {
        for (int i = 0; i < K3_STAGES; i++) { mbar_init(full + 8 * i, 1); mbar_init(empty + 8 * i, 8); }
        fence_barrier_init();
    }
    __syncthreads();
    pdl_wait();
    TS(10, tid == 0);
    if (wg == 2) {
        reg_dealloc<40>();
        if (tid == 256) {
            for (int ks = 0; ks < K3_KSTEPS; ks++) {
                const int st = ks % K3_STAGES;
                if (ks >= K3_STAGES) mbar_wait(empty + 8 * st, ((ks / K3_STAGES) - 1) & 1);
                mbar_expect_tx(full + 8 * st, K3_STAGE);
                const uint32_t dst = sbase + st * K3_STAGE;
                tma_load_2d(dst, &tmA2, ks * 64, rb * 128, full + 8 * st);
                if (ks < 8) tma_load_2d(dst + 16384, &tmWo, nb * 64, ks * 64, full + 8 * st);
                else        tma_load_2d(dst + 16384, &tmW2, nb * 64, (ks - 8) * 64, full + 8 * st);
            }
        }
    } else {
        reg_alloc<232>();
        float acc[32];
        const uint64_t da0 = make_desc(sbase + wg * 8192, 16, 1024);
        const uint64_t db0 = make_desc(sbase + 16384, 8192, 1024);
        for (int ks = 0; ks < K3_KSTEPS; ks++) {
            const int st = ks % K3_STAGES;
            mbar_wait(full + 8 * st, (ks / K3_STAGES) & 1);
            TS(11, tid == 0 && ks == 0); TS(12, tid == 0 && ks == 8); TS(13, tid == 0 && ks == 16);
            wgmma_fence();
            const uint32_t so = (uint32_t)(st * K3_STAGE) >> 4;
#pragma unroll
            for (int k16 = 0; k16 < 4; k16++)
                wgmma_n64<1>(acc, da0 + (so + k16 * 2), db0 + (so + k16 * 128), (ks | k16) != 0);
            wgmma_commit();
            if (ks > 0) { wgmma_wait<1>(); if (lane == 0) mbar_arrive(empty + 8 * ((ks - 1) % K3_STAGES)); }
        }
        wgmma_wait<0>();
        TS(14, tid == 0);
        const int q = lane & 3;
        const int r = rb * 128 + wg * 64 + (warp & 3) * 16 + (lane >> 2);
        bf16* orow0 = out + (size_t)r * D_ + nb * 64;
        bf16* orow1 = orow0 + 8 * D_;
#pragma unroll
        for (int u = 0; u < 2; u++) {
            uint32_t w0[4], w1[4];
#pragma unroll
            for (int i = 0; i < 4; i++) {
                const int t = u * 4 + i;
                w0[i] = pack_bf16(acc[t * 4 + 0], acc[t * 4 + 1]);
                w1[i] = pack_bf16(acc[t * 4 + 2], acc[t * 4 + 3]);
            }
            quad_transpose(w0, q);
            quad_transpose(w1, q);
            const int c = (u * 4 + q) * 8;
            *(uint4*)(orow0 + c) = make_uint4(w0[0], w0[1], w0[2], w0[3]);
            *(uint4*)(orow1 + c) = make_uint4(w1[0], w1[1], w1[2], w1[3]);
        }
        TS(15, tid == 0);
    }
}

typedef CUresult (*PFN_encodeTiled)(CUtensorMap*, CUtensorMapDataType, cuuint32_t, void*, const cuuint64_t*,
                                    const cuuint64_t*, const cuuint32_t*, const cuuint32_t*, CUtensorMapInterleave,
                                    CUtensorMapSwizzle, CUtensorMapL2promotion, CUtensorMapFloatOOBfill);

static void make_map(PFN_encodeTiled enc, CUtensorMap* m, const void* ptr, uint64_t cols, uint64_t rows,
                     uint32_t box_cols, uint32_t box_rows)
{
    cuuint64_t dims[2] = {cols, rows};
    cuuint64_t strides[1] = {cols * 2};
    cuuint32_t box[2] = {box_cols, box_rows};
    cuuint32_t es[2] = {1, 1};
    enc(m, CU_TENSOR_MAP_DATA_TYPE_BFLOAT16, 2, const_cast<void*>(ptr), dims, strides, box, es,
        CU_TENSOR_MAP_INTERLEAVE_NONE, CU_TENSOR_MAP_SWIZZLE_128B, CU_TENSOR_MAP_L2_PROMOTION_L2_128B,
        CU_TENSOR_MAP_FLOAT_OOB_FILL_NONE);
}

extern "C" void kernel_launch(void* const* d_in, const int* in_sizes, int n_in, void* d_out, int out_size)
{
    const bf16* x    = (const bf16*)d_in[0];
    const bf16* wqkv = (const bf16*)d_in[1];
    const bf16* wo   = (const bf16*)d_in[2];
    const bf16* w1   = (const bf16*)d_in[4];
    const bf16* b1   = (const bf16*)d_in[5];
    const bf16* w2   = (const bf16*)d_in[6];
    const bf16* gw   = (const bf16*)d_in[7];

    static PFN_encodeTiled enc = nullptr;
    if (!enc) {
        void* fn = nullptr;
        cudaDriverEntryPointQueryResult qr;
        cudaGetDriverEntryPoint("cuTensorMapEncodeTiled", &fn, cudaEnableDefault, &qr);
        enc = (PFN_encodeTiled)fn;
        cudaFuncSetAttribute(k1_kernel, cudaFuncAttributeMaxDynamicSharedMemorySize, K1_SMEM);
        cudaFuncSetAttribute(k2_kernel, cudaFuncAttributeMaxDynamicSharedMemorySize, K2_SMEM);
        cudaFuncSetAttribute(k3_kernel, cudaFuncAttributeMaxDynamicSharedMemorySize, K3_SMEM);
    }
    void* a2p = nullptr;
    cudaGetSymbolAddress(&a2p, g_a2);
    void* qkvp = nullptr;
    cudaGetSymbolAddress(&qkvp, g_qkv);
    CUtensorMap tmX, tmWqkv, tmW1, tmA2, tmWo, tmW2, tmQKV;
    make_map(enc, &tmQKV, qkvp, 192, 8 * S_, 64, 128);
    make_map(enc, &tmX, x, D_, S_, 64, 128);
    make_map(enc, &tmWqkv, wqkv, 3 * D_, D_, 64, 64);
    make_map(enc, &tmW1, w1, F_, D_, 64, 64);
    make_map(enc, &tmA2, a2p, KA2, S_, 64, 128);
    make_map(enc, &tmWo, wo, D_, D_, 64, 64);
    make_map(enc, &tmW2, w2, D_, F_, 64, 64);

    cudaStream_t st = cudaStreamPerThread;
    k1_kernel<<<128, 512, K1_SMEM, st>>>(tmX, tmWqkv, tmW1, b1, gw, w1, wqkv, w2, wo);
    cudaLaunchAttribute at[1];
    at[0].id = cudaLaunchAttributeProgrammaticStreamSerialization;
    at[0].val.programmaticStreamSerializationAllowed = 1;
    cudaLaunchConfig_t cfg = {};
    cfg.gridDim = dim3(128); cfg.stream = st; cfg.attrs = at; cfg.numAttrs = 1;
    cfg.blockDim = dim3(512); cfg.dynamicSmemBytes = K2_SMEM;
    cudaLaunchKernelEx(&cfg, k2_kernel, tmQKV);
    k3_kernel<<<128, 384, K3_SMEM, st>>>(tmA2, tmWo, tmW2, (bf16*)d_out);
}
```

```cpp
#include <cuda_runtime.h>
#include <cuda_bf16.h>
#include <cuda.h>
#include <stdint.h>

typedef __nv_bfloat16 bf16;

constexpr int S_ = 2048, D_ = 512, F_ = 1376;
constexpr int KA2 = D_ + F_;
constexpr int FCH = 176;

__device__ bf16  g_qkv[8 * S_ * 192];
__device__ bf16  g_a2[S_ * KA2];
__device__ float g_gate[S_];

#define TS(k, cond) do { } while (0)

__device__ __forceinline__ uint32_t smem_u32(const void* p) { return (uint32_t)__cvta_generic_to_shared(p); }
__device__ __forceinline__ void mbar_init(uint32_t bar, uint32_t count) {
    asm volatile("mbarrier.init.shared::cta.b64 [%0], %1;" :: "r"(bar), "r"(count) : "memory");
}
__device__ __forceinline__ void mbar_expect_tx(uint32_t bar, uint32_t bytes) {
    asm volatile("mbarrier.arrive.expect_tx.shared::cta.b64 _, [%0], %1;" :: "r"(bar), "r"(bytes) : "memory");
}
__device__ __forceinline__ void mbar_arrive(uint32_t bar) {
    asm volatile("mbarrier.arrive.shared::cta.b64 _, [%0];" :: "r"(bar) : "memory");
}
__device__ __forceinline__ bool mbar_try_wait(uint32_t bar, uint32_t parity) {
    uint32_t ok;
    asm volatile("{\n.reg .pred p;\nmbarrier.try_wait.parity.shared::cta.b64 p, [%1], %2;\nselp.u32 %0, 1, 0, p;\n}"
                 : "=r"(ok) : "r"(bar), "r"(parity) : "memory");
    return ok != 0;
}
__device__ __forceinline__ void mbar_wait(uint32_t bar, uint32_t parity) {
    for (uint32_t it = 0; it < (1u << 22); ++it) { if (mbar_try_wait(bar, parity)) break; }
}
__device__ __forceinline__ void tma_load_2d(uint32_t dst, const CUtensorMap* map, int c0, int c1, uint32_t bar) {
    asm volatile("cp.async.bulk.tensor.2d.shared::cluster.global.mbarrier::complete_tx::bytes [%0], [%1, {%3, %4}], [%2];"
                 :: "r"(dst), "l"(map), "r"(bar), "r"(c0), "r"(c1) : "memory");
}
__device__ __forceinline__ void l2_prefetch(const void* p, uint32_t bytes) {
    asm volatile("cp.async.bulk.prefetch.L2.global [%0], %1;" :: "l"(p), "r"(bytes) : "memory");
}
__device__ __forceinline__ void fence_barrier_init() { asm volatile("fence.mbarrier_init.release.cluster;" ::: "memory"); }
__device__ __forceinline__ void wgmma_fence()  { asm volatile("wgmma.fence.sync.aligned;" ::: "memory"); }
__device__ __forceinline__ void wgmma_commit() { asm volatile("wgmma.commit_group.sync.aligned;" ::: "memory"); }
template <int N> __device__ __forceinline__ void wgmma_wait() { asm volatile("wgmma.wait_group.sync.aligned %0;" :: "n"(N) : "memory"); }
template <int R> __device__ __forceinline__ void reg_alloc()   { asm volatile("setmaxnreg.inc.sync.aligned.u32 %0;" :: "n"(R)); }
template <int R> __device__ __forceinline__ void reg_dealloc() { asm volatile("setmaxnreg.dec.sync.aligned.u32 %0;" :: "n"(R)); }
__device__ __forceinline__ void bar_sync(int id, int n)   { asm volatile("bar.sync %0, %1;" :: "r"(id), "r"(n) : "memory"); }
__device__ __forceinline__ void bar_arrive(int id, int n) { asm volatile("bar.arrive %0, %1;" :: "r"(id), "r"(n) : "memory"); }

__device__ __forceinline__ uint64_t make_desc(uint32_t addr, uint32_t lbo, uint32_t sbo) {
    uint64_t d = (uint64_t)((addr & 0x3FFFF) >> 4);
    d |= (uint64_t)((lbo & 0x3FFFF) >> 4) << 16;
    d |= (uint64_t)((sbo & 0x3FFFF) >> 4) << 32;
    d |= (uint64_t)1 << 62;
    return d;
}

template <int TB>
__device__ __forceinline__ void wgmma_n64(float (&d)[32], uint64_t da, uint64_t db, int scale_d) {
    asm volatile("{\n.reg .pred p;\nsetp.ne.b32 p, %34, 0;\n"
        "wgmma.mma_async.sync.aligned.m64n64k16.f32.bf16.bf16 {%0, %1, %2, %3, %4, %5, %6, %7, %8, %9, %10, %11, %12, %13, %14, %15, %16, %17, %18, %19, %20, %21, %22, %23, %24, %25, %26, %27, %28, %29, %30, %31}, %32, %33, p, 1, 1, 0, %35;\n}\n"
        : "+f"(d[0]), "+f"(d[1]), "+f"(d[2]), "+f"(d[3]), "+f"(d[4]), "+f"(d[5]), "+f"(d[6]), "+f"(d[7]), "+f"(d[8]), "+f"(d[9]), "+f"(d[10]), "+f"(d[11]), "+f"(d[12]), "+f"(d[13]), "+f"(d[14]), "+f"(d[15]), "+f"(d[16]), "+f"(d[17]), "+f"(d[18]), "+f"(d[19]), "+f"(d[20]), "+f"(d[21]), "+f"(d[22]), "+f"(d[23]), "+f"(d[24]), "+f"(d[25]), "+f"(d[26]), "+f"(d[27]), "+f"(d[28]), "+f"(d[29]), "+f"(d[30]), "+f"(d[31])
        : "l"(da), "l"(db), "r"(scale_d), "n"(TB));
}

template <int TB>
__device__ __forceinline__ void wgmma_n128(float (&d)[64], uint64_t da, uint64_t db, int scale_d) {
    asm volatile("{\n.reg .pred p;\nsetp.ne.b32 p, %66, 0;\n"
        "wgmma.mma_async.sync.aligned.m64n128k16.f32.bf16.bf16 {%0, %1, %2, %3, %4, %5, %6, %7, %8, %9, %10, %11, %12, %13, %14, %15, %16, %17, %18, %19, %20, %21, %22, %23, %24, %25, %26, %27, %28, %29, %30, %31, %32, %33, %34, %35, %36, %37, %38, %39, %40, %41, %42, %43, %44, %45, %46, %47, %48, %49, %50, %51, %52, %53, %54, %55, %56, %57, %58, %59, %60, %61, %62, %63}, %64, %65, p, 1, 1, 0, %67;\n}\n"
        : "+f"(d[0]), "+f"(d[1]), "+f"(d[2]), "+f"(d[3]), "+f"(d[4]), "+f"(d[5]), "+f"(d[6]), "+f"(d[7]), "+f"(d[8]), "+f"(d[9]), "+f"(d[10]), "+f"(d[11]), "+f"(d[12]), "+f"(d[13]), "+f"(d[14]), "+f"(d[15]), "+f"(d[16]), "+f"(d[17]), "+f"(d[18]), "+f"(d[19]), "+f"(d[20]), "+f"(d[21]), "+f"(d[22]), "+f"(d[23]), "+f"(d[24]), "+f"(d[25]), "+f"(d[26]), "+f"(d[27]), "+f"(d[28]), "+f"(d[29]), "+f"(d[30]), "+f"(d[31]), "+f"(d[32]), "+f"(d[33]), "+f"(d[34]), "+f"(d[35]), "+f"(d[36]), "+f"(d[37]), "+f"(d[38]), "+f"(d[39]), "+f"(d[40]), "+f"(d[41]), "+f"(d[42]), "+f"(d[43]), "+f"(d[44]), "+f"(d[45]), "+f"(d[46]), "+f"(d[47]), "+f"(d[48]), "+f"(d[49]), "+f"(d[50]), "+f"(d[51]), "+f"(d[52]), "+f"(d[53]), "+f"(d[54]), "+f"(d[55]), "+f"(d[56]), "+f"(d[57]), "+f"(d[58]), "+f"(d[59]), "+f"(d[60]), "+f"(d[61]), "+f"(d[62]), "+f"(d[63])
        : "l"(da), "l"(db), "r"(scale_d), "n"(TB));
}

template <int TB>
__device__ __forceinline__ void wgmma_n176(float (&d)[88], uint64_t da, uint64_t db, int scale_d) {
    asm volatile("{\n.reg .pred p;\nsetp.ne.b32 p, %90, 0;\n"
        "wgmma.mma_async.sync.aligned.m64n176k16.f32.bf16.bf16 {%0, %1, %2, %3, %4, %5, %6, %7, %8, %9, %10, %11, %12, %13, %14, %15, %16, %17, %18, %19, %20, %21, %22, %23, %24, %25, %26, %27, %28, %29, %30, %31, %32, %33, %34, %35, %36, %37, %38, %39, %40, %41, %42, %43, %44, %45, %46, %47, %48, %49, %50, %51, %52, %53, %54, %55, %56, %57, %58, %59, %60, %61, %62, %63, %64, %65, %66, %67, %68, %69, %70, %71, %72, %73, %74, %75, %76, %77, %78, %79, %80, %81, %82, %83, %84, %85, %86, %87}, %88, %89, p, 1, 1, 0, %91;\n}\n"
        : "+f"(d[0]), "+f"(d[1]), "+f"(d[2]), "+f"(d[3]), "+f"(d[4]), "+f"(d[5]), "+f"(d[6]), "+f"(d[7]), "+f"(d[8]), "+f"(d[9]), "+f"(d[10]), "+f"(d[11]), "+f"(d[12]), "+f"(d[13]), "+f"(d[14]), "+f"(d[15]), "+f"(d[16]), "+f"(d[17]), "+f"(d[18]), "+f"(d[19]), "+f"(d[20]), "+f"(d[21]), "+f"(d[22]), "+f"(d[23]), "+f"(d[24]), "+f"(d[25]), "+f"(d[26]), "+f"(d[27]), "+f"(d[28]), "+f"(d[29]), "+f"(d[30]), "+f"(d[31]), "+f"(d[32]), "+f"(d[33]), "+f"(d[34]), "+f"(d[35]), "+f"(d[36]), "+f"(d[37]), "+f"(d[38]), "+f"(d[39]), "+f"(d[40]), "+f"(d[41]), "+f"(d[42]), "+f"(d[43]), "+f"(d[44]), "+f"(d[45]), "+f"(d[46]), "+f"(d[47]), "+f"(d[48]), "+f"(d[49]), "+f"(d[50]), "+f"(d[51]), "+f"(d[52]), "+f"(d[53]), "+f"(d[54]), "+f"(d[55]), "+f"(d[56]), "+f"(d[57]), "+f"(d[58]), "+f"(d[59]), "+f"(d[60]), "+f"(d[61]), "+f"(d[62]), "+f"(d[63]), "+f"(d[64]), "+f"(d[65]), "+f"(d[66]), "+f"(d[67]), "+f"(d[68]), "+f"(d[69]), "+f"(d[70]), "+f"(d[71]), "+f"(d[72]), "+f"(d[73]), "+f"(d[74]), "+f"(d[75]), "+f"(d[76]), "+f"(d[77]), "+f"(d[78]), "+f"(d[79]), "+f"(d[80]), "+f"(d[81]), "+f"(d[82]), "+f"(d[83]), "+f"(d[84]), "+f"(d[85]), "+f"(d[86]), "+f"(d[87])
        : "l"(da), "l"(db), "r"(scale_d), "n"(TB));
}

template <int TB>
__device__ __forceinline__ void wgmma_n192(float (&d)[96], uint64_t da, uint64_t db, int scale_d) {
    asm volatile("{\n.reg .pred p;\nsetp.ne.b32 p, %98, 0;\n"
        "wgmma.mma_async.sync.aligned.m64n192k16.f32.bf16.bf16 {%0, %1, %2, %3, %4, %5, %6, %7, %8, %9, %10, %11, %12, %13, %14, %15, %16, %17, %18, %19, %20, %21, %22, %23, %24, %25, %26, %27, %28, %29, %30, %31, %32, %33, %34, %35, %36, %37, %38, %39, %40, %41, %42, %43, %44, %45, %46, %47, %48, %49, %50, %51, %52, %53, %54, %55, %56, %57, %58, %59, %60, %61, %62, %63, %64, %65, %66, %67, %68, %69, %70, %71, %72, %73, %74, %75, %76, %77, %78, %79, %80, %81, %82, %83, %84, %85, %86, %87, %88, %89, %90, %91, %92, %93, %94, %95}, %96, %97, p, 1, 1, 0, %99;\n}\n"
        : "+f"(d[0]), "+f"(d[1]), "+f"(d[2]), "+f"(d[3]), "+f"(d[4]), "+f"(d[5]), "+f"(d[6]), "+f"(d[7]), "+f"(d[8]), "+f"(d[9]), "+f"(d[10]), "+f"(d[11]), "+f"(d[12]), "+f"(d[13]), "+f"(d[14]), "+f"(d[15]), "+f"(d[16]), "+f"(d[17]), "+f"(d[18]), "+f"(d[19]), "+f"(d[20]), "+f"(d[21]), "+f"(d[22]), "+f"(d[23]), "+f"(d[24]), "+f"(d[25]), "+f"(d[26]), "+f"(d[27]), "+f"(d[28]), "+f"(d[29]), "+f"(d[30]), "+f"(d[31]), "+f"(d[32]), "+f"(d[33]), "+f"(d[34]), "+f"(d[35]), "+f"(d[36]), "+f"(d[37]), "+f"(d[38]), "+f"(d[39]), "+f"(d[40]), "+f"(d[41]), "+f"(d[42]), "+f"(d[43]), "+f"(d[44]), "+f"(d[45]), "+f"(d[46]), "+f"(d[47]), "+f"(d[48]), "+f"(d[49]), "+f"(d[50]), "+f"(d[51]), "+f"(d[52]), "+f"(d[53]), "+f"(d[54]), "+f"(d[55]), "+f"(d[56]), "+f"(d[57]), "+f"(d[58]), "+f"(d[59]), "+f"(d[60]), "+f"(d[61]), "+f"(d[62]), "+f"(d[63]), "+f"(d[64]), "+f"(d[65]), "+f"(d[66]), "+f"(d[67]), "+f"(d[68]), "+f"(d[69]), "+f"(d[70]), "+f"(d[71]), "+f"(d[72]), "+f"(d[73]), "+f"(d[74]), "+f"(d[75]), "+f"(d[76]), "+f"(d[77]), "+f"(d[78]), "+f"(d[79]), "+f"(d[80]), "+f"(d[81]), "+f"(d[82]), "+f"(d[83]), "+f"(d[84]), "+f"(d[85]), "+f"(d[86]), "+f"(d[87]), "+f"(d[88]), "+f"(d[89]), "+f"(d[90]), "+f"(d[91]), "+f"(d[92]), "+f"(d[93]), "+f"(d[94]), "+f"(d[95])
        : "l"(da), "l"(db), "r"(scale_d), "n"(TB));
}

__device__ __forceinline__ uint32_t pack_bf16(float lo, float hi) {
    uint32_t r;
    asm("cvt.rn.bf16x2.f32 %0, %1, %2;" : "=r"(r) : "f"(hi), "f"(lo));
    return r;
}
__device__ __forceinline__ float bf_lo(uint32_t v) { return __uint_as_float(v << 16); }
__device__ __forceinline__ float bf_hi(uint32_t v) { return __uint_as_float(v & 0xffff0000u); }

__device__ __forceinline__ void quad_transpose(uint32_t (&w)[4], int q) {
    const bool o1 = q & 1, o2 = q & 2;
    {
        uint32_t s0 = o1 ? w[0] : w[1], s1 = o1 ? w[2] : w[3];
        s0 = __shfl_xor_sync(0xffffffffu, s0, 1); s1 = __shfl_xor_sync(0xffffffffu, s1, 1);
        if (o1) { w[0] = s0; w[2] = s1; } else { w[1] = s0; w[3] = s1; }
    }
    {
        uint32_t s0 = o2 ? w[0] : w[2], s1 = o2 ? w[1] : w[3];
        s0 = __shfl_xor_sync(0xffffffffu, s0, 2); s1 = __shfl_xor_sync(0xffffffffu, s1, 2);
        if (o2) { w[0] = s0; w[1] = s1; } else { w[2] = s0; w[3] = s1; }
    }
}

__device__ __forceinline__ float ex2(float x) { float y; asm("ex2.approx.ftz.f32 %0, %1;" : "=f"(y) : "f"(x)); return y; }
__device__ __forceinline__ float rcp(float x) { float y; asm("rcp.approx.ftz.f32 %0, %1;" : "=f"(y) : "f"(x)); return y; }

__device__ __forceinline__ float ex2v(float x) { float y; asm volatile("ex2.approx.ftz.f32 %0, %1;" : "=f"(y) : "f"(x)); return y; }
__device__ __forceinline__ float rcpv(float x) { float y; asm volatile("rcp.approx.ftz.f32 %0, %1;" : "=f"(y) : "f"(x)); return y; }
__device__ __forceinline__ float mish_f(float h) {
    const float e = ex2v(1.4426950408889634f * fminf(h, 20.f));
    const float n = fmaf(e, e, e + e);
    return h * n * rcpv(n + 2.f);
}

__device__ __forceinline__ void pdl_wait()   { asm volatile("griddepcontrol.wait;" ::: "memory"); }
__device__ __forceinline__ void pdl_launch() { asm volatile("griddepcontrol.launch_dependents;" ::: "memory"); }

constexpr int K1_STAGES = 4;
constexpr int K1_XBYTES = 128 * 512 * 2;
constexpr int K1_BSTAGE = 3 * 8192;
constexpr int K1_SMEM   = K1_XBYTES + K1_STAGES * K1_BSTAGE + 2048   + 1024  ;

__global__ void __launch_bounds__(384, 1)
k1_kernel(const __grid_constant__ CUtensorMap tmX, const __grid_constant__ CUtensorMap tmWqkv,
          const __grid_constant__ CUtensorMap tmW1, const bf16* __restrict__ b1,
          const bf16* __restrict__ gate_w, const bf16* __restrict__ w1p, const bf16* __restrict__ wqkvp,
          const bf16* __restrict__ w2p, const bf16* __restrict__ wop)
{

    extern __shared__ uint8_t smem_raw[];
    const uint32_t sbase = (smem_u32(smem_raw) + 1023u) & ~1023u;
    uint8_t* sgen = smem_raw + (sbase - smem_u32(smem_raw));
    const uint32_t sX = sbase;
    const uint32_t sB = sbase + K1_XBYTES;
    const uint32_t sBar = sB + K1_STAGES * K1_BSTAGE;
    const uint32_t x_full = sBar;
    const uint32_t b_full = sBar + 64;
    const uint32_t b_empty = sBar + 96;
    float* sGate = (float*)(sgen + K1_XBYTES + K1_STAGES * K1_BSTAGE + 128);
    uint8_t* sGw = sgen + K1_XBYTES + K1_STAGES * K1_BSTAGE + 640;
    uint32_t* sBias = (uint32_t*)(sgen + K1_XBYTES + K1_STAGES * K1_BSTAGE + 1664);

    const int rb = blockIdx.x >> 3, j = blockIdx.x & 7;
    const int tid = threadIdx.x, lane = tid & 31;
    const int warp = __shfl_sync(0xffffffffu, tid >> 5, 0), wg = warp >> 2;
    TS(0, tid == 0);
    pdl_launch();

    if (tid == 0) {
        for (int i = 0; i < 8; i++) mbar_init(x_full + 8 * i, 1);
        for (int i = 0; i < K1_STAGES; i++) { mbar_init(b_full + 8 * i, 1); mbar_init(b_empty + 8 * i, 8); }
        fence_barrier_init();
    }
    __syncthreads();

    if (wg == 2) {
        reg_dealloc<40>();
        if (tid == 288) {
            const int b = blockIdx.x;
            mbar_wait(b_full + 8, 0);
            l2_prefetch((const uint8_t*)wqkvp + b * 12288, 12288);
            l2_prefetch((const uint8_t*)w2p + b * 11008, 11008);
            l2_prefetch((const uint8_t*)wop + b * 4096, 4096);
        }
        if (tid == 256) {
            for (int it = 0; it < 16; it++) {
                if (it < 8) {
                    mbar_expect_tx(x_full + 8 * it, 16384);
                    tma_load_2d(sX + it * 16384, &tmX, it * 64, rb * 128, x_full + 8 * it);
                }
                const int st = it & 3;
                if (it >= K1_STAGES) mbar_wait(b_empty + 8 * st, ((it >> 2) - 1) & 1);
                mbar_expect_tx(b_full + 8 * st, K1_BSTAGE);
                const uint32_t dst = sB + st * K1_BSTAGE;
                if (it < 8) {
                    for (int b = 0; b < 3; b++) tma_load_2d(dst + b * 8192, &tmW1, j * FCH + b * 64, it * 64, b_full + 8 * st);
                } else {
                    for (int b = 0; b < 3; b++) tma_load_2d(dst + b * 8192, &tmWqkv, b * 512 + j * 64, (it - 8) * 64, b_full + 8 * st);
                }
            }
        }
    } else {
        reg_alloc<232>();
        if (tid < 64) ((uint4*)sGw)[tid] = __ldg((const uint4*)gate_w + tid);
        else if (tid < 64 + 88) {
            const int c = j * FCH + (tid - 64) * 2;
            sBias[tid - 64] = c < F_ ? __ldg((const uint32_t*)(b1 + c)) : 0u;
        }
        bar_sync(3, 256);
        const int t128 = tid & 127, w4 = warp & 3, q = lane & 3;
        float accF[88], accQ[96];
        const uint64_t da0 = make_desc(sX + wg * 8192, 16, 1024);
        const uint64_t db0 = make_desc(sB, 8192, 1024);
        float gs = 0.f;
        const int grow = wg * 64 + (t128 >> 1), ghalf = t128 & 1;
#pragma unroll
        for (int kc = 0; kc < 8; kc++) {
            const int st = kc & 3;
            mbar_wait(x_full + 8 * kc, 0);
            mbar_wait(b_full + 8 * st, (kc >> 2) & 1);
            TS(1, tid == 0 && kc == 0); TS(2, tid == 0 && kc == 4);
            wgmma_fence();
#pragma unroll
            for (int k16 = 0; k16 < 4; k16++) {
                wgmma_n176<1>(accF, da0 + (kc * 1024 + k16 * 2), db0 + (st * (K1_BSTAGE >> 4) + k16 * 128), (kc | k16) != 0);
            }
            wgmma_commit();
#pragma unroll
            for (int c = 0; c < 4; c++) {
                const int cc = ghalf * 4 + c;
                const uint4 xv = *(const uint4*)(sgen + kc * 16384 + grow * 128 + ((cc ^ (grow & 7)) << 4));
                const uint4 gv = *(const uint4*)(sGw + kc * 128 + cc * 16);
                gs = fmaf(bf_lo(xv.x), bf_lo(gv.x), gs); gs = fmaf(bf_hi(xv.x), bf_hi(gv.x), gs);
                gs = fmaf(bf_lo(xv.y), bf_lo(gv.y), gs); gs = fmaf(bf_hi(xv.y), bf_hi(gv.y), gs);
                gs = fmaf(bf_lo(xv.z), bf_lo(gv.z), gs); gs = fmaf(bf_hi(xv.z), bf_hi(gv.z), gs);
                gs = fmaf(bf_lo(xv.w), bf_lo(gv.w), gs); gs = fmaf(bf_hi(xv.w), bf_hi(gv.w), gs);
            }
            if (kc > 0) { wgmma_wait<1>(); if (lane == 0) mbar_arrive(b_empty + 8 * ((kc - 1) & 3)); }
        }
        gs += __shfl_xor_sync(0xffffffffu, gs, 1);
        {
            const float g = 1.f / (1.f + __expf(-gs));
            if (ghalf == 0) {
                sGate[grow] = g;
                if (j == 0) g_gate[rb * 128 + grow] = g;
            }
        }
        wgmma_wait<0>();
        if (lane == 0) mbar_arrive(b_empty + 8 * 3);
        bar_sync(1 + wg, 128);
        TS(3, tid == 0);
        const int n0 = j * FCH;
        const int rl = wg * 64 + w4 * 16 + (lane >> 2);
        const float om0 = 1.f - sGate[rl], om1 = 1.f - sGate[rl + 8];
        bf16* frow0 = g_a2 + (size_t)(rb * 128 + rl) * KA2 + D_ + n0;
        bf16* frow1 = frow0 + 8 * KA2;
        auto ffn_chunk = [&](int u) {
            uint32_t w0[4], w1[4];
#pragma unroll
            for (int i = 0; i < 4; i++) {
                const int t = u * 4 + i;
                if (t < 22) {
                    const uint32_t bv = sBias[t * 4 + q];
                    const float bb0 = bf_lo(bv), bb1 = bf_hi(bv);
                    w0[i] = pack_bf16(mish_f(accF[t * 4 + 0] + bb0) * om0, mish_f(accF[t * 4 + 1] + bb1) * om0);
                    w1[i] = pack_bf16(mish_f(accF[t * 4 + 2] + bb0) * om1, mish_f(accF[t * 4 + 3] + bb1) * om1);
                } else { w0[i] = 0; w1[i] = 0; }
            }
            quad_transpose(w0, q);
            quad_transpose(w1, q);
            const int c = (u * 4 + q) * 8;
            if (c < FCH && n0 + c < F_) {
                *(uint4*)(frow0 + c) = make_uint4(w0[0], w0[1], w0[2], w0[3]);
                *(uint4*)(frow1 + c) = make_uint4(w1[0], w1[1], w1[2], w1[3]);
            }
        };
#pragma unroll
        for (int kc = 0; kc < 8; kc++) {
            const int st = kc & 3;
            mbar_wait(b_full + 8 * st, ((kc + 8) >> 2) & 1);
            wgmma_fence();
#pragma unroll
            for (int k16 = 0; k16 < 4; k16++) {
                wgmma_n192<1>(accQ, da0 + (kc * 1024 + k16 * 2), db0 + (st * (K1_BSTAGE >> 4) + k16 * 128), (kc | k16) != 0);
            }
            wgmma_commit();
            if (kc < 6) ffn_chunk(kc);
            if (kc > 0) { wgmma_wait<1>(); if (lane == 0) mbar_arrive(b_empty + 8 * ((kc - 1) & 3)); }
        }
        wgmma_wait<0>();
        TS(4, tid == 0);
        {
            bf16* orow0 = g_qkv + ((size_t)j * S_ + rb * 128 + rl) * 192;
            bf16* orow1 = orow0 + 8 * 192;
#pragma unroll
            for (int u = 0; u < 6; u++) {
                uint32_t w0[4], w1[4];
#pragma unroll
                for (int i = 0; i < 4; i++) {
                    const int t = u * 4 + i;
                    w0[i] = pack_bf16(accQ[t * 4 + 0], accQ[t * 4 + 1]);
                    w1[i] = pack_bf16(accQ[t * 4 + 2], accQ[t * 4 + 3]);
                }
                quad_transpose(w0, q);
                quad_transpose(w1, q);
                const int c = (u * 4 + q) * 8;
                *(uint4*)(orow0 + c) = make_uint4(w0[0], w0[1], w0[2], w0[3]);
                *(uint4*)(orow1 + c) = make_uint4(w1[0], w1[1], w1[2], w1[3]);
            }
        }
        TS(5, tid == 0);
    }
}

__device__ __forceinline__ void ldsm_x4(uint32_t (&r)[4], uint32_t addr) {
    asm("ldmatrix.sync.aligned.m8n8.x4.shared.b16 {%0,%1,%2,%3}, [%4];"
                 : "=r"(r[0]), "=r"(r[1]), "=r"(r[2]), "=r"(r[3]) : "r"(addr));
}
__device__ __forceinline__ void ldsm_x4_t(uint32_t (&r)[4], uint32_t addr) {
    asm("ldmatrix.sync.aligned.m8n8.x4.trans.shared.b16 {%0,%1,%2,%3}, [%4];"
                 : "=r"(r[0]), "=r"(r[1]), "=r"(r[2]), "=r"(r[3]) : "r"(addr));
}
__device__ __forceinline__ void mma16816(float (&d)[4], const uint32_t (&a)[4], uint32_t b0, uint32_t b1) {
    asm("mma.sync.aligned.m16n8k16.row.col.f32.bf16.bf16.f32 {%0,%1,%2,%3}, {%4,%5,%6,%7}, {%8,%9}, {%0,%1,%2,%3};"
                 : "+f"(d[0]), "+f"(d[1]), "+f"(d[2]), "+f"(d[3])
                 : "r"(a[0]), "r"(a[1]), "r"(a[2]), "r"(a[3]), "r"(b0), "r"(b1));
}
__device__ __forceinline__ void mma16816_z(float (&d)[4], const uint32_t (&a)[4], uint32_t b0, uint32_t b1) {
    asm("mma.sync.aligned.m16n8k16.row.col.f32.bf16.bf16.f32 {%0,%1,%2,%3}, {%4,%5,%6,%7}, {%8,%9}, {%10,%10,%10,%10};"
                 : "=f"(d[0]), "=f"(d[1]), "=f"(d[2]), "=f"(d[3])
                 : "r"(a[0]), "r"(a[1]), "r"(a[2]), "r"(a[3]), "r"(b0), "r"(b1), "f"(0.f));
}

constexpr int KV_PITCH = 128;

template <int EDGE, bool HEAD>
__device__ __forceinline__ void blk_scores(float (&s)[2][4], const uint32_t (&qa)[4], uint32_t kaddr, bool dead, int r0, int c0)
{
    uint32_t kf[4];
    ldsm_x4(kf, kaddr);
    mma16816_z(s[0], qa, kf[0], kf[1]);
    mma16816_z(s[1], qa, kf[2], kf[3]);
#pragma unroll
    for (int t = 0; t < 2; t++)
#pragma unroll
        for (int e = 0; e < 4; e++) {
            const int r = r0 + (e >> 1) * 8, c = t * 8 + c0 + (e & 1);
            if (EDGE == 1 && c <= r) s[t][e] = -1e30f;
            if (EDGE == 2 && c > r) s[t][e] = -1e30f;
            if (HEAD && dead) s[t][e] = -1e30f;
        }
}
__device__ __forceinline__ void blk_max(const float (&s)[2][4], float& n0, float& n1) {
    n0 = fmaxf(n0, fmaxf(fmaxf(s[0][0], s[0][1]), fmaxf(s[1][0], s[1][1])));
    n1 = fmaxf(n1, fmaxf(fmaxf(s[0][2], s[0][3]), fmaxf(s[1][2], s[1][3])));
}
__device__ __forceinline__ void blk_pv(const float (&s)[2][4], float mc0, float mc1, float (&l)[4],
                                       float (&o)[2][4], uint32_t vaddr) {
    const float C = 0.25f * 1.4426950408889634f;
    uint32_t pa[4];
#pragma unroll
    for (int t = 0; t < 2; t++) {
        const float p0 = ex2(fmaf(s[t][0], C, -mc0)), p1 = ex2(fmaf(s[t][1], C, -mc0));
        const float p2 = ex2(fmaf(s[t][2], C, -mc1)), p3 = ex2(fmaf(s[t][3], C, -mc1));
        pa[2 * t] = pack_bf16(p0, p1); pa[2 * t + 1] = pack_bf16(p2, p3);
    }
    uint32_t vf[4];
    ldsm_x4_t(vf, vaddr);
    mma16816(o[0], pa, vf[0], vf[1]);
    mma16816(o[1], pa, vf[2], vf[3]);
    mma16816(l, pa, 0x3F803F80u, 0x3F803F80u);
}
__device__ __forceinline__ void quad_max(float& n0, float& n1) {
    n0 = fmaxf(n0, __shfl_xor_sync(0xffffffffu, n0, 1)); n1 = fmaxf(n1, __shfl_xor_sync(0xffffffffu, n1, 1));
    n0 = fmaxf(n0, __shfl_xor_sync(0xffffffffu, n0, 2)); n1 = fmaxf(n1, __shfl_xor_sync(0xffffffffu, n1, 2));
}
template <int NC, int NN, bool FIRST, bool NEXT_IS_EDGE, bool HEAD>
__device__ __forceinline__ void pipe_step(const float (&sc)[5][2][4], float (&sn)[5][2][4], const uint32_t (&qa)[4],
                                          uint32_t ka, uint32_t va, int kc, int kn, int kb0, int r0, int c0,
                                          float& m0, float& m1, float& n0, float& n1, float (&l)[4], float (&o)[2][4])
{
    const float C = 0.25f * 1.4426950408889634f;
    const float mc0 = n0 * C, mc1 = n1 * C;
    if (!FIRST) {
        const float a0 = ex2(fmaf(m0, C, -mc0)), a1 = ex2(fmaf(m1, C, -mc1));
        l[0] *= a0; l[2] *= a1;
        o[0][0] *= a0; o[0][1] *= a0; o[1][0] *= a0; o[1][1] *= a0;
        o[0][2] *= a1; o[0][3] *= a1; o[1][2] *= a1; o[1][3] *= a1;
    }
    m0 = n0; m1 = n1;
#pragma unroll
    for (int b = 0; b < NC; b++) {
        if (b < NN) {
            if (NEXT_IS_EDGE && b == 0) blk_scores<1, HEAD>(sn[b], qa, ka + (kn + b) * 16 * KV_PITCH, kn + b < kb0, r0, c0);
            else                        blk_scores<0, HEAD>(sn[b], qa, ka + (kn + b) * 16 * KV_PITCH, kn + b < kb0, r0, c0);
        }
        blk_pv(sc[b], mc0, mc1, l, o, va + (kc + b) * 16 * KV_PITCH);
        if (b < NN) blk_max(sn[b], n0, n1);
    }
    if (NN > 0) quad_max(n0, n1);
}

__device__ __forceinline__ void kv_need(uint32_t kvbar, int blk, uint32_t& ka, uint32_t& va) {
    mbar_wait(kvbar + 8 * blk, 0);
    asm volatile("" : "+r"(ka), "+r"(va) :: "memory");
}
template <bool HEAD>
__device__ __forceinline__ void attn_task(const uint32_t (&qa)[4], uint32_t ka, uint32_t va, int kb0, int lane, int qt, uint32_t kvbar,
                                          bf16* __restrict__ out  , float g0, float g1)
{
    const int r0 = lane >> 2, c0 = (lane & 3) * 2;
    float m0 = -1e30f, m1 = -1e30f, n0 = -1e30f, n1 = -1e30f;
    float l[4] = {0.f, 0.f, 0.f, 0.f};
    float o[2][4] = {{0.f, 0.f, 0.f, 0.f}, {0.f, 0.f, 0.f, 0.f}};
    float sa[5][2][4], sb[5][2][4];
    kv_need(kvbar, 2, ka, va);
    if (qt < 4) kv_need(kvbar, 1, ka, va);
#pragma unroll
    for (int b = 0; b < 5; b++) {
        if (b == 4) blk_scores<2, HEAD>(sa[b], qa, ka + (12 + b) * 16 * KV_PITCH, false, r0, c0);
        else        blk_scores<0, HEAD>(sa[b], qa, ka + (12 + b) * 16 * KV_PITCH, 12 + b < kb0, r0, c0);
        blk_max(sa[b], n0, n1);
    }
    quad_max(n0, n1);
    kv_need(kvbar, 1, ka, va);
    if (HEAD) {
        pipe_step<5, 0, true, false, HEAD>(sa, sb, qa, ka, va, 12, 0, kb0, r0, c0, m0, m1, n0, n1, l, o);
        kv_need(kvbar, 0, ka, va);
#pragma unroll 1
        for (int kc = 8; kc >= 0 && kb0 < kc + 4; kc -= 4) {
#pragma unroll
            for (int b = 0; b < 4; b++) {
                blk_scores<0, HEAD>(sa[b], qa, ka + (kc + b) * 16 * KV_PITCH, kc + b < kb0, r0, c0);
                blk_max(sa[b], n0, n1);
            }
            quad_max(n0, n1);
            pipe_step<4, 0, false, false, HEAD>(sa, sb, qa, ka, va, kc, 0, kb0, r0, c0, m0, m1, n0, n1, l, o);
        }
    } else {
        pipe_step<5, 4, true,  false, HEAD>(sa, sb, qa, ka, va, 12, 8, kb0, r0, c0, m0, m1, n0, n1, l, o);
        if (qt < 4) kv_need(kvbar, 0, ka, va);
        pipe_step<4, 4, false, false, HEAD>(sb, sa, qa, ka, va, 8, 4, kb0, r0, c0, m0, m1, n0, n1, l, o);
        kv_need(kvbar, 0, ka, va);
        pipe_step<4, 4, false, true,  HEAD>(sa, sb, qa, ka, va, 4, 0, kb0, r0, c0, m0, m1, n0, n1, l, o);
        pipe_step<4, 0, false, false, HEAD>(sb, sa, qa, ka, va, 0, 0, kb0, r0, c0, m0, m1, n0, n1, l, o);
    }
    const float f0 = __fdividef(g0, l[0]), f1 = __fdividef(g1, l[2]);
#pragma unroll
    for (int t = 0; t < 2; t++) {
        *(uint32_t*)(out + (size_t)r0 * KA2 + t * 8 + c0) = pack_bf16(o[t][0] * f0, o[t][1] * f0);
        *(uint32_t*)(out + (size_t)(r0 + 8) * KA2 + t * 8 + c0) = pack_bf16(o[t][2] * f1, o[t][3] * f1);
    }
}

constexpr int K2_SMEM = 2 * 384 * KV_PITCH + 1024 + 64;

__global__ void __launch_bounds__(512, 1) k2_kernel(const __grid_constant__ CUtensorMap tmQKV)
{
    extern __shared__ uint8_t smem_raw[];
    const uint32_t sbase = (smem_u32(smem_raw) + 1023u) & ~1023u;
    uint8_t* sgen = smem_raw + (sbase - smem_u32(smem_raw));
    const uint32_t sK = sbase, sV = sK + 384 * KV_PITCH, kv_full = sbase + 2 * 384 * KV_PITCH;
    const int rb = blockIdx.x >> 3, j = blockIdx.x & 7;
    const int tid = threadIdx.x, warp = tid >> 5, lane = tid & 31;
    pdl_launch();
    if (tid == 0) {
        for (int i = 0; i < 3; i++) mbar_init(kv_full + 8 * i, 1);
        fence_barrier_init();
    }
    pdl_wait();
    TS(6, tid == 0);
    if (tid == 0) {
        for (int i = 0; i < 3; i++) {
            const uint32_t bar = kv_full + 8 * (2 - i);
            if (rb - i >= 0) {
                const int row = j * S_ + (rb - i) * 128;
                mbar_expect_tx(bar, 2 * 16384);
                tma_load_2d(sK + (2 - i) * 16384, &tmQKV, 64, row, bar);
                tma_load_2d(sV + (2 - i) * 16384, &tmQKV, 128, row, bar);
            } else {
                mbar_arrive(bar);
            }
        }
    }
    if (rb < 2) {
        for (int i = tid; i < (2 - rb) * 1024; i += 512) {
            *(uint4*)(sgen + i * 16) = make_uint4(0, 0, 0, 0);
            *(uint4*)(sgen + 384 * KV_PITCH + i * 16) = make_uint4(0, 0, 0, 0);
        }
    }
    const int qt = warp & 7, h0 = (warp >> 3) * 2;
    const int q0g = rb * 128 + qt * 16;
    const int r0 = lane >> 2, c0 = (lane & 3) * 2;
    const bf16* qsrc = g_qkv + ((size_t)j * S_ + q0g) * 192 + h0 * 16;
    uint32_t qa[4], qn[4];
    qa[0] = *(const uint32_t*)(qsrc + (size_t)r0 * 192 + c0);
    qa[1] = *(const uint32_t*)(qsrc + (size_t)(r0 + 8) * 192 + c0);
    qa[2] = *(const uint32_t*)(qsrc + (size_t)r0 * 192 + c0 + 8);
    qa[3] = *(const uint32_t*)(qsrc + (size_t)(r0 + 8) * 192 + c0 + 8);
    qn[0] = *(const uint32_t*)(qsrc + (size_t)r0 * 192 + 16 + c0);
    qn[1] = *(const uint32_t*)(qsrc + (size_t)(r0 + 8) * 192 + 16 + c0);
    qn[2] = *(const uint32_t*)(qsrc + (size_t)r0 * 192 + 16 + c0 + 8);
    qn[3] = *(const uint32_t*)(qsrc + (size_t)(r0 + 8) * 192 + 16 + c0 + 8);
    const float g0 = g_gate[q0g + r0], g1 = g_gate[q0g + r0 + 8];
    const int kb0 = q0g < 256 ? (256 - q0g) >> 4 : 0;
    __syncthreads();
    const uint32_t sKd = sK, sVd = sV;
    TS(7, tid == 0);
    const int krow = qt * 16 + (lane & 7) + ((lane >> 4) << 3);
    const int vrow = qt * 16 + (lane & 15);
#pragma unroll 1
    for (int hh = 0; hh < 2; hh++) {
        const int hl = h0 + hh;
        const uint32_t ka = sKd + krow * KV_PITCH + (((2 * hl + ((lane >> 3) & 1)) ^ (lane & 7)) << 4);
        const uint32_t va = sVd + vrow * KV_PITCH + (((2 * hl + (lane >> 4)) ^ (lane & 7)) << 4);
        if (rb < 2) attn_task<true>(qa, ka, va, kb0, lane, qt, kv_full, g_a2 + (size_t)q0g * KA2 + (j * 4 + hl) * 16, g0, g1);
        else        attn_task<false>(qa, ka, va, kb0, lane, qt, kv_full, g_a2 + (size_t)q0g * KA2 + (j * 4 + hl) * 16, g0, g1);
        TS(8 + hh, tid == 0);
        qa[0] = qn[0]; qa[1] = qn[1]; qa[2] = qn[2]; qa[3] = qn[3];
    }
}

constexpr int K3_STAGES = 9;
constexpr int K3_STAGE = 16384 + 8192;
constexpr int K3_SMEM = K3_STAGES * K3_STAGE + 1024 + 1024;
constexpr int K3_KSTEPS = 30;

__global__ void __launch_bounds__(384, 1)
k3_kernel(const __grid_constant__ CUtensorMap tmA2, const __grid_constant__ CUtensorMap tmWo,
          const __grid_constant__ CUtensorMap tmW2, bf16* __restrict__ out)
{
    extern __shared__ uint8_t smem_raw[];
    const uint32_t sbase = (smem_u32(smem_raw) + 1023u) & ~1023u;
    const uint32_t sBar = sbase + K3_STAGES * K3_STAGE;
    const uint32_t full = sBar, empty = sBar + 128;
    const int rb = blockIdx.x >> 3, nb = blockIdx.x & 7;
    const int tid = threadIdx.x, lane = tid & 31;
    const int warp = __shfl_sync(0xffffffffu, tid >> 5, 0), wg = warp >> 2;
    if (tid == 0) {
        for (int i = 0; i < K3_STAGES; i++) { mbar_init(full + 8 * i, 1); mbar_init(empty + 8 * i, 8); }
        fence_barrier_init();
    }
    __syncthreads();
    pdl_wait();
    TS(10, tid == 0);
    if (wg == 2) {
        reg_dealloc<40>();
        if (tid == 256) {
            for (int ks = 0; ks < K3_KSTEPS; ks++) {
                const int st = ks % K3_STAGES;
                if (ks >= K3_STAGES) mbar_wait(empty + 8 * st, ((ks / K3_STAGES) - 1) & 1);
                mbar_expect_tx(full + 8 * st, K3_STAGE);
                const uint32_t dst = sbase + st * K3_STAGE;
                tma_load_2d(dst, &tmA2, ks * 64, rb * 128, full + 8 * st);
                if (ks < 8) tma_load_2d(dst + 16384, &tmWo, nb * 64, ks * 64, full + 8 * st);
                else        tma_load_2d(dst + 16384, &tmW2, nb * 64, (ks - 8) * 64, full + 8 * st);
            }
        }
    } else {
        reg_alloc<232>();
        float acc[32];
        const uint64_t da0 = make_desc(sbase + wg * 8192, 16, 1024);
        const uint64_t db0 = make_desc(sbase + 16384, 8192, 1024);
        for (int ks = 0; ks < K3_KSTEPS; ks++) {
            const int st = ks % K3_STAGES;
            mbar_wait(full + 8 * st, (ks / K3_STAGES) & 1);
            TS(11, tid == 0 && ks == 0); TS(12, tid == 0 && ks == 8); TS(13, tid == 0 && ks == 16);
            wgmma_fence();
            const uint32_t so = (uint32_t)(st * K3_STAGE) >> 4;
#pragma unroll
            for (int k16 = 0; k16 < 4; k16++)
                wgmma_n64<1>(acc, da0 + (so + k16 * 2), db0 + (so + k16 * 128), (ks | k16) != 0);
            wgmma_commit();
            if (ks > 0) { wgmma_wait<1>(); if (lane == 0) mbar_arrive(empty + 8 * ((ks - 1) % K3_STAGES)); }
        }
        wgmma_wait<0>();
        TS(14, tid == 0);
        const int q = lane & 3;
        const int r = rb * 128 + wg * 64 + (warp & 3) * 16 + (lane >> 2);
        bf16* orow0 = out + (size_t)r * D_ + nb * 64;
        bf16* orow1 = orow0 + 8 * D_;
#pragma unroll
        for (int u = 0; u < 2; u++) {
            uint32_t w0[4], w1[4];
#pragma unroll
            for (int i = 0; i < 4; i++) {
                const int t = u * 4 + i;
                w0[i] = pack_bf16(acc[t * 4 + 0], acc[t * 4 + 1]);
                w1[i] = pack_bf16(acc[t * 4 + 2], acc[t * 4 + 3]);
            }
            quad_transpose(w0, q);
            quad_transpose(w1, q);
            const int c = (u * 4 + q) * 8;
            *(uint4*)(orow0 + c) = make_uint4(w0[0], w0[1], w0[2], w0[3]);
            *(uint4*)(orow1 + c) = make_uint4(w1[0], w1[1], w1[2], w1[3]);
        }
        TS(15, tid == 0);
    }
}

typedef CUresult (*PFN_encodeTiled)(CUtensorMap*, CUtensorMapDataType, cuuint32_t, void*, const cuuint64_t*,
                                    const cuuint64_t*, const cuuint32_t*, const cuuint32_t*, CUtensorMapInterleave,
                                    CUtensorMapSwizzle, CUtensorMapL2promotion, CUtensorMapFloatOOBfill);

static void make_map(PFN_encodeTiled enc, CUtensorMap* m, const void* ptr, uint64_t cols, uint64_t rows,
                     uint32_t box_cols, uint32_t box_rows)
{
    cuuint64_t dims[2] = {cols, rows};
    cuuint64_t strides[1] = {cols * 2};
    cuuint32_t box[2] = {box_cols, box_rows};
    cuuint32_t es[2] = {1, 1};
    enc(m, CU_TENSOR_MAP_DATA_TYPE_BFLOAT16, 2, const_cast<void*>(ptr), dims, strides, box, es,
        CU_TENSOR_MAP_INTERLEAVE_NONE, CU_TENSOR_MAP_SWIZZLE_128B, CU_TENSOR_MAP_L2_PROMOTION_L2_128B,
        CU_TENSOR_MAP_FLOAT_OOB_FILL_NONE);
}

extern "C" void kernel_launch(void* const* d_in, const int* in_sizes, int n_in, void* d_out, int out_size)
{
    const bf16* x    = (const bf16*)d_in[0];
    const bf16* wqkv = (const bf16*)d_in[1];
    const bf16* wo   = (const bf16*)d_in[2];
    const bf16* w1   = (const bf16*)d_in[4];
    const bf16* b1   = (const bf16*)d_in[5];
    const bf16* w2   = (const bf16*)d_in[6];
    const bf16* gw   = (const bf16*)d_in[7];

    static PFN_encodeTiled enc = nullptr;
    if (!enc) {
        void* fn = nullptr;
        cudaDriverEntryPointQueryResult qr;
        cudaGetDriverEntryPoint("cuTensorMapEncodeTiled", &fn, cudaEnableDefault, &qr);
        enc = (PFN_encodeTiled)fn;
        cudaFuncSetAttribute(k1_kernel, cudaFuncAttributeMaxDynamicSharedMemorySize, K1_SMEM);
        cudaFuncSetAttribute(k2_kernel, cudaFuncAttributeMaxDynamicSharedMemorySize, K2_SMEM);
        cudaFuncSetAttribute(k3_kernel, cudaFuncAttributeMaxDynamicSharedMemorySize, K3_SMEM);
    }
    void* a2p = nullptr;
    cudaGetSymbolAddress(&a2p, g_a2);
    void* qkvp = nullptr;
    cudaGetSymbolAddress(&qkvp, g_qkv);
    CUtensorMap tmX, tmWqkv, tmW1, tmA2, tmWo, tmW2, tmQKV;
    make_map(enc, &tmQKV, qkvp, 192, 8 * S_, 64, 128);
    make_map(enc, &tmX, x, D_, S_, 64, 128);
    make_map(enc, &tmWqkv, wqkv, 3 * D_, D_, 64, 64);
    make_map(enc, &tmW1, w1, F_, D_, 64, 64);
    make_map(enc, &tmA2, a2p, KA2, S_, 64, 128);
    make_map(enc, &tmWo, wo, D_, D_, 64, 64);
    make_map(enc, &tmW2, w2, D_, F_, 64, 64);

    cudaStream_t st = cudaStreamPerThread;
    k1_kernel<<<128, 384, K1_SMEM, st>>>(tmX, tmWqkv, tmW1, b1, gw, w1, wqkv, w2, wo);
    cudaLaunchAttribute at[1];
    at[0].id = cudaLaunchAttributeProgrammaticStreamSerialization;
    at[0].val.programmaticStreamSerializationAllowed = 1;
    cudaLaunchConfig_t cfg = {};
    cfg.gridDim = dim3(128); cfg.stream = st; cfg.attrs = at; cfg.numAttrs = 1;
    cfg.blockDim = dim3(512); cfg.dynamicSmemBytes = K2_SMEM;
    cudaLaunchKernelEx(&cfg, k2_kernel, tmQKV);
    k3_kernel<<<128, 384, K3_SMEM, st>>>(tmA2, tmWo, tmW2, (bf16*)d_out);
}
```

```cpp
#include <cuda_runtime.h>
#include <cuda_bf16.h>
#include <cuda.h>
#include <stdint.h>

typedef __nv_bfloat16 bf16;

constexpr int S_ = 2048, D_ = 512, F_ = 1376;
constexpr int KA2 = D_ + F_;
constexpr int FCH = 176;

__device__ bf16  g_qkv[8 * S_ * 192];
__device__ bf16  g_a2[S_ * KA2];
__device__ float g_gate[S_];

#define TS(k, cond) do { } while (0)

__device__ __forceinline__ uint32_t smem_u32(const void* p) { return (uint32_t)__cvta_generic_to_shared(p); }
__device__ __forceinline__ void mbar_init(uint32_t bar, uint32_t count) {
    asm volatile("mbarrier.init.shared::cta.b64 [%0], %1;" :: "r"(bar), "r"(count) : "memory");
}
__device__ __forceinline__ void mbar_expect_tx(uint32_t bar, uint32_t bytes) {
    asm volatile("mbarrier.arrive.expect_tx.shared::cta.b64 _, [%0], %1;" :: "r"(bar), "r"(bytes) : "memory");
}
__device__ __forceinline__ void mbar_arrive(uint32_t bar) {
    asm volatile("mbarrier.arrive.shared::cta.b64 _, [%0];" :: "r"(bar) : "memory");
}
__device__ __forceinline__ bool mbar_try_wait(uint32_t bar, uint32_t parity) {
    uint32_t ok;
    asm volatile("{\n.reg .pred p;\nmbarrier.try_wait.parity.shared::cta.b64 p, [%1], %2;\nselp.u32 %0, 1, 0, p;\n}"
                 : "=r"(ok) : "r"(bar), "r"(parity) : "memory");
    return ok != 0;
}
__device__ __forceinline__ void mbar_wait(uint32_t bar, uint32_t parity) {
    for (uint32_t it = 0; it < (1u << 22); ++it) { if (mbar_try_wait(bar, parity)) break; }
}
__device__ __forceinline__ void tma_load_2d(uint32_t dst, const CUtensorMap* map, int c0, int c1, uint32_t bar) {
    asm volatile("cp.async.bulk.tensor.2d.shared::cluster.global.mbarrier::complete_tx::bytes [%0], [%1, {%3, %4}], [%2];"
                 :: "r"(dst), "l"(map), "r"(bar), "r"(c0), "r"(c1) : "memory");
}
__device__ __forceinline__ void l2_prefetch(const void* p, uint32_t bytes) {
    asm volatile("cp.async.bulk.prefetch.L2.global [%0], %1;" :: "l"(p), "r"(bytes) : "memory");
}
__device__ __forceinline__ void fence_barrier_init() { asm volatile("fence.mbarrier_init.release.cluster;" ::: "memory"); }
__device__ __forceinline__ void wgmma_fence()  { asm volatile("wgmma.fence.sync.aligned;" ::: "memory"); }
__device__ __forceinline__ void wgmma_commit() { asm volatile("wgmma.commit_group.sync.aligned;" ::: "memory"); }
template <int N> __device__ __forceinline__ void wgmma_wait() { asm volatile("wgmma.wait_group.sync.aligned %0;" :: "n"(N) : "memory"); }
template <int R> __device__ __forceinline__ void reg_alloc()   { asm volatile("setmaxnreg.inc.sync.aligned.u32 %0;" :: "n"(R)); }
template <int R> __device__ __forceinline__ void reg_dealloc() { asm volatile("setmaxnreg.dec.sync.aligned.u32 %0;" :: "n"(R)); }
__device__ __forceinline__ void bar_sync(int id, int n)   { asm volatile("bar.sync %0, %1;" :: "r"(id), "r"(n) : "memory"); }
__device__ __forceinline__ void bar_arrive(int id, int n) { asm volatile("bar.arrive %0, %1;" :: "r"(id), "r"(n) : "memory"); }

__device__ __forceinline__ uint64_t make_desc(uint32_t addr, uint32_t lbo, uint32_t sbo) {
    uint64_t d = (uint64_t)((addr & 0x3FFFF) >> 4);
    d |= (uint64_t)((lbo & 0x3FFFF) >> 4) << 16;
    d |= (uint64_t)((sbo & 0x3FFFF) >> 4) << 32;
    d |= (uint64_t)1 << 62;
    return d;
}

template <int TB>
__device__ __forceinline__ void wgmma_n64(float (&d)[32], uint64_t da, uint64_t db, int scale_d) {
    asm volatile("{\n.reg .pred p;\nsetp.ne.b32 p, %34, 0;\n"
        "wgmma.mma_async.sync.aligned.m64n64k16.f32.bf16.bf16 {%0, %1, %2, %3, %4, %5, %6, %7, %8, %9, %10, %11, %12, %13, %14, %15, %16, %17, %18, %19, %20, %21, %22, %23, %24, %25, %26, %27, %28, %29, %30, %31}, %32, %33, p, 1, 1, 0, %35;\n}\n"
        : "+f"(d[0]), "+f"(d[1]), "+f"(d[2]), "+f"(d[3]), "+f"(d[4]), "+f"(d[5]), "+f"(d[6]), "+f"(d[7]), "+f"(d[8]), "+f"(d[9]), "+f"(d[10]), "+f"(d[11]), "+f"(d[12]), "+f"(d[13]), "+f"(d[14]), "+f"(d[15]), "+f"(d[16]), "+f"(d[17]), "+f"(d[18]), "+f"(d[19]), "+f"(d[20]), "+f"(d[21]), "+f"(d[22]), "+f"(d[23]), "+f"(d[24]), "+f"(d[25]), "+f"(d[26]), "+f"(d[27]), "+f"(d[28]), "+f"(d[29]), "+f"(d[30]), "+f"(d[31])
        : "l"(da), "l"(db), "r"(scale_d), "n"(TB));
}

template <int TB>
__device__ __forceinline__ void wgmma_n128(float (&d)[64], uint64_t da, uint64_t db, int scale_d) {
    asm volatile("{\n.reg .pred p;\nsetp.ne.b32 p, %66, 0;\n"
        "wgmma.mma_async.sync.aligned.m64n128k16.f32.bf16.bf16 {%0, %1, %2, %3, %4, %5, %6, %7, %8, %9, %10, %11, %12, %13, %14, %15, %16, %17, %18, %19, %20, %21, %22, %23, %24, %25, %26, %27, %28, %29, %30, %31, %32, %33, %34, %35, %36, %37, %38, %39, %40, %41, %42, %43, %44, %45, %46, %47, %48, %49, %50, %51, %52, %53, %54, %55, %56, %57, %58, %59, %60, %61, %62, %63}, %64, %65, p, 1, 1, 0, %67;\n}\n"
        : "+f"(d[0]), "+f"(d[1]), "+f"(d[2]), "+f"(d[3]), "+f"(d[4]), "+f"(d[5]), "+f"(d[6]), "+f"(d[7]), "+f"(d[8]), "+f"(d[9]), "+f"(d[10]), "+f"(d[11]), "+f"(d[12]), "+f"(d[13]), "+f"(d[14]), "+f"(d[15]), "+f"(d[16]), "+f"(d[17]), "+f"(d[18]), "+f"(d[19]), "+f"(d[20]), "+f"(d[21]), "+f"(d[22]), "+f"(d[23]), "+f"(d[24]), "+f"(d[25]), "+f"(d[26]), "+f"(d[27]), "+f"(d[28]), "+f"(d[29]), "+f"(d[30]), "+f"(d[31]), "+f"(d[32]), "+f"(d[33]), "+f"(d[34]), "+f"(d[35]), "+f"(d[36]), "+f"(d[37]), "+f"(d[38]), "+f"(d[39]), "+f"(d[40]), "+f"(d[41]), "+f"(d[42]), "+f"(d[43]), "+f"(d[44]), "+f"(d[45]), "+f"(d[46]), "+f"(d[47]), "+f"(d[48]), "+f"(d[49]), "+f"(d[50]), "+f"(d[51]), "+f"(d[52]), "+f"(d[53]), "+f"(d[54]), "+f"(d[55]), "+f"(d[56]), "+f"(d[57]), "+f"(d[58]), "+f"(d[59]), "+f"(d[60]), "+f"(d[61]), "+f"(d[62]), "+f"(d[63])
        : "l"(da), "l"(db), "r"(scale_d), "n"(TB));
}

template <int TB>
__device__ __forceinline__ void wgmma_n176(float (&d)[88], uint64_t da, uint64_t db, int scale_d) {
    asm volatile("{\n.reg .pred p;\nsetp.ne.b32 p, %90, 0;\n"
        "wgmma.mma_async.sync.aligned.m64n176k16.f32.bf16.bf16 {%0, %1, %2, %3, %4, %5, %6, %7, %8, %9, %10, %11, %12, %13, %14, %15, %16, %17, %18, %19, %20, %21, %22, %23, %24, %25, %26, %27, %28, %29, %30, %31, %32, %33, %34, %35, %36, %37, %38, %39, %40, %41, %42, %43, %44, %45, %46, %47, %48, %49, %50, %51, %52, %53, %54, %55, %56, %57, %58, %59, %60, %61, %62, %63, %64, %65, %66, %67, %68, %69, %70, %71, %72, %73, %74, %75, %76, %77, %78, %79, %80, %81, %82, %83, %84, %85, %86, %87}, %88, %89, p, 1, 1, 0, %91;\n}\n"
        : "+f"(d[0]), "+f"(d[1]), "+f"(d[2]), "+f"(d[3]), "+f"(d[4]), "+f"(d[5]), "+f"(d[6]), "+f"(d[7]), "+f"(d[8]), "+f"(d[9]), "+f"(d[10]), "+f"(d[11]), "+f"(d[12]), "+f"(d[13]), "+f"(d[14]), "+f"(d[15]), "+f"(d[16]), "+f"(d[17]), "+f"(d[18]), "+f"(d[19]), "+f"(d[20]), "+f"(d[21]), "+f"(d[22]), "+f"(d[23]), "+f"(d[24]), "+f"(d[25]), "+f"(d[26]), "+f"(d[27]), "+f"(d[28]), "+f"(d[29]), "+f"(d[30]), "+f"(d[31]), "+f"(d[32]), "+f"(d[33]), "+f"(d[34]), "+f"(d[35]), "+f"(d[36]), "+f"(d[37]), "+f"(d[38]), "+f"(d[39]), "+f"(d[40]), "+f"(d[41]), "+f"(d[42]), "+f"(d[43]), "+f"(d[44]), "+f"(d[45]), "+f"(d[46]), "+f"(d[47]), "+f"(d[48]), "+f"(d[49]), "+f"(d[50]), "+f"(d[51]), "+f"(d[52]), "+f"(d[53]), "+f"(d[54]), "+f"(d[55]), "+f"(d[56]), "+f"(d[57]), "+f"(d[58]), "+f"(d[59]), "+f"(d[60]), "+f"(d[61]), "+f"(d[62]), "+f"(d[63]), "+f"(d[64]), "+f"(d[65]), "+f"(d[66]), "+f"(d[67]), "+f"(d[68]), "+f"(d[69]), "+f"(d[70]), "+f"(d[71]), "+f"(d[72]), "+f"(d[73]), "+f"(d[74]), "+f"(d[75]), "+f"(d[76]), "+f"(d[77]), "+f"(d[78]), "+f"(d[79]), "+f"(d[80]), "+f"(d[81]), "+f"(d[82]), "+f"(d[83]), "+f"(d[84]), "+f"(d[85]), "+f"(d[86]), "+f"(d[87])
        : "l"(da), "l"(db), "r"(scale_d), "n"(TB));
}

template <int TB>
__device__ __forceinline__ void wgmma_n192(float (&d)[96], uint64_t da, uint64_t db, int scale_d) {
    asm volatile("{\n.reg .pred p;\nsetp.ne.b32 p, %98, 0;\n"
        "wgmma.mma_async.sync.aligned.m64n192k16.f32.bf16.bf16 {%0, %1, %2, %3, %4, %5, %6, %7, %8, %9, %10, %11, %12, %13, %14, %15, %16, %17, %18, %19, %20, %21, %22, %23, %24, %25, %26, %27, %28, %29, %30, %31, %32, %33, %34, %35, %36, %37, %38, %39, %40, %41, %42, %43, %44, %45, %46, %47, %48, %49, %50, %51, %52, %53, %54, %55, %56, %57, %58, %59, %60, %61, %62, %63, %64, %65, %66, %67, %68, %69, %70, %71, %72, %73, %74, %75, %76, %77, %78, %79, %80, %81, %82, %83, %84, %85, %86, %87, %88, %89, %90, %91, %92, %93, %94, %95}, %96, %97, p, 1, 1, 0, %99;\n}\n"
        : "+f"(d[0]), "+f"(d[1]), "+f"(d[2]), "+f"(d[3]), "+f"(d[4]), "+f"(d[5]), "+f"(d[6]), "+f"(d[7]), "+f"(d[8]), "+f"(d[9]), "+f"(d[10]), "+f"(d[11]), "+f"(d[12]), "+f"(d[13]), "+f"(d[14]), "+f"(d[15]), "+f"(d[16]), "+f"(d[17]), "+f"(d[18]), "+f"(d[19]), "+f"(d[20]), "+f"(d[21]), "+f"(d[22]), "+f"(d[23]), "+f"(d[24]), "+f"(d[25]), "+f"(d[26]), "+f"(d[27]), "+f"(d[28]), "+f"(d[29]), "+f"(d[30]), "+f"(d[31]), "+f"(d[32]), "+f"(d[33]), "+f"(d[34]), "+f"(d[35]), "+f"(d[36]), "+f"(d[37]), "+f"(d[38]), "+f"(d[39]), "+f"(d[40]), "+f"(d[41]), "+f"(d[42]), "+f"(d[43]), "+f"(d[44]), "+f"(d[45]), "+f"(d[46]), "+f"(d[47]), "+f"(d[48]), "+f"(d[49]), "+f"(d[50]), "+f"(d[51]), "+f"(d[52]), "+f"(d[53]), "+f"(d[54]), "+f"(d[55]), "+f"(d[56]), "+f"(d[57]), "+f"(d[58]), "+f"(d[59]), "+f"(d[60]), "+f"(d[61]), "+f"(d[62]), "+f"(d[63]), "+f"(d[64]), "+f"(d[65]), "+f"(d[66]), "+f"(d[67]), "+f"(d[68]), "+f"(d[69]), "+f"(d[70]), "+f"(d[71]), "+f"(d[72]), "+f"(d[73]), "+f"(d[74]), "+f"(d[75]), "+f"(d[76]), "+f"(d[77]), "+f"(d[78]), "+f"(d[79]), "+f"(d[80]), "+f"(d[81]), "+f"(d[82]), "+f"(d[83]), "+f"(d[84]), "+f"(d[85]), "+f"(d[86]), "+f"(d[87]), "+f"(d[88]), "+f"(d[89]), "+f"(d[90]), "+f"(d[91]), "+f"(d[92]), "+f"(d[93]), "+f"(d[94]), "+f"(d[95])
        : "l"(da), "l"(db), "r"(scale_d), "n"(TB));
}

__device__ __forceinline__ uint32_t pack_bf16(float lo, float hi) {
    uint32_t r;
    asm("cvt.rn.bf16x2.f32 %0, %1, %2;" : "=r"(r) : "f"(hi), "f"(lo));
    return r;
}
__device__ __forceinline__ float bf_lo(uint32_t v) { return __uint_as_float(v << 16); }
__device__ __forceinline__ float bf_hi(uint32_t v) { return __uint_as_float(v & 0xffff0000u); }

__device__ __forceinline__ void quad_transpose(uint32_t (&w)[4], int q) {
    const bool o1 = q & 1, o2 = q & 2;
    {
        uint32_t s0 = o1 ? w[0] : w[1], s1 = o1 ? w[2] : w[3];
        s0 = __shfl_xor_sync(0xffffffffu, s0, 1); s1 = __shfl_xor_sync(0xffffffffu, s1, 1);
        if (o1) { w[0] = s0; w[2] = s1; } else { w[1] = s0; w[3] = s1; }
    }
    {
        uint32_t s0 = o2 ? w[0] : w[2], s1 = o2 ? w[1] : w[3];
        s0 = __shfl_xor_sync(0xffffffffu, s0, 2); s1 = __shfl_xor_sync(0xffffffffu, s1, 2);
        if (o2) { w[0] = s0; w[1] = s1; } else { w[2] = s0; w[3] = s1; }
    }
}

__device__ __forceinline__ float ex2(float x) { float y; asm("ex2.approx.ftz.f32 %0, %1;" : "=f"(y) : "f"(x)); return y; }
__device__ __forceinline__ float rcp(float x) { float y; asm("rcp.approx.ftz.f32 %0, %1;" : "=f"(y) : "f"(x)); return y; }

__device__ __forceinline__ float ex2v(float x) { float y; asm volatile("ex2.approx.ftz.f32 %0, %1;" : "=f"(y) : "f"(x)); return y; }
__device__ __forceinline__ float rcpv(float x) { float y; asm volatile("rcp.approx.ftz.f32 %0, %1;" : "=f"(y) : "f"(x)); return y; }
__device__ __forceinline__ float mish_f(float h) {
    const float e = ex2v(1.4426950408889634f * fminf(h, 20.f));
    const float n = fmaf(e, e, e + e);
    return h * n * rcpv(n + 2.f);
}

__device__ __forceinline__ void pdl_wait()   { asm volatile("griddepcontrol.wait;" ::: "memory"); }
__device__ __forceinline__ void pdl_launch() { asm volatile("griddepcontrol.launch_dependents;" ::: "memory"); }

constexpr int K1_STAGES = 4;
constexpr int K1_XBYTES = 128 * 512 * 2;
constexpr int K1_BSTAGE = 3 * 8192;
constexpr int K1_SMEM   = K1_XBYTES + K1_STAGES * K1_BSTAGE + 2048   + 1024  ;

__global__ void __launch_bounds__(384, 1)
k1_kernel(const __grid_constant__ CUtensorMap tmX, const __grid_constant__ CUtensorMap tmWqkv,
          const __grid_constant__ CUtensorMap tmW1, const bf16* __restrict__ b1,
          const bf16* __restrict__ gate_w, const bf16* __restrict__ w1p, const bf16* __restrict__ wqkvp,
          const bf16* __restrict__ w2p, const bf16* __restrict__ wop)
{

    extern __shared__ uint8_t smem_raw[];
    const uint32_t sbase = (smem_u32(smem_raw) + 1023u) & ~1023u;
    uint8_t* sgen = smem_raw + (sbase - smem_u32(smem_raw));
    const uint32_t sX = sbase;
    const uint32_t sB = sbase + K1_XBYTES;
    const uint32_t sBar = sB + K1_STAGES * K1_BSTAGE;
    const uint32_t x_full = sBar;
    const uint32_t b_full = sBar + 64;
    const uint32_t b_empty = sBar + 96;
    float* sGate = (float*)(sgen + K1_XBYTES + K1_STAGES * K1_BSTAGE + 128);
    uint8_t* sGw = sgen + K1_XBYTES + K1_STAGES * K1_BSTAGE + 640;
    uint32_t* sBias = (uint32_t*)(sgen + K1_XBYTES + K1_STAGES * K1_BSTAGE + 1664);

    const int rb = blockIdx.x >> 3, j = blockIdx.x & 7;
    const int tid = threadIdx.x, lane = tid & 31;
    const int warp = __shfl_sync(0xffffffffu, tid >> 5, 0), wg = warp >> 2;
    TS(0, tid == 0);
    pdl_launch();

    if (tid == 0) {
        for (int i = 0; i < 8; i++) mbar_init(x_full + 8 * i, 1);
        for (int i = 0; i < K1_STAGES; i++) { mbar_init(b_full + 8 * i, 1); mbar_init(b_empty + 8 * i, 8); }
        fence_barrier_init();
    }
    __syncthreads();

    if (wg == 2) {
        reg_dealloc<40>();
        if (tid == 288) {
            const int b = blockIdx.x;
            mbar_wait(b_full + 8, 0);
            l2_prefetch((const uint8_t*)wqkvp + b * 12288, 12288);
            l2_prefetch((const uint8_t*)w2p + b * 11008, 11008);
            l2_prefetch((const uint8_t*)wop + b * 4096, 4096);
        }
        if (tid == 256) {
            for (int it = 0; it < 16; it++) {
                if (it < 8) {
                    mbar_expect_tx(x_full + 8 * it, 16384);
                    tma_load_2d(sX + it * 16384, &tmX, it * 64, rb * 128, x_full + 8 * it);
                }
                const int st = it & 3;
                if (it >= K1_STAGES) mbar_wait(b_empty + 8 * st, ((it >> 2) - 1) & 1);
                mbar_expect_tx(b_full + 8 * st, K1_BSTAGE);
                const uint32_t dst = sB + st * K1_BSTAGE;
                if (it < 8) {
                    for (int b = 0; b < 3; b++) tma_load_2d(dst + b * 8192, &tmW1, j * FCH + b * 64, it * 64, b_full + 8 * st);
                } else {
                    for (int b = 0; b < 3; b++) tma_load_2d(dst + b * 8192, &tmWqkv, b * 512 + j * 64, (it - 8) * 64, b_full + 8 * st);
                }
            }
        }
    } else {
        reg_alloc<232>();
        if (tid < 64) ((uint4*)sGw)[tid] = __ldg((const uint4*)gate_w + tid);
        else if (tid < 64 + 88) {
            const int c = j * FCH + (tid - 64) * 2;
            sBias[tid - 64] = c < F_ ? __ldg((const uint32_t*)(b1 + c)) : 0u;
        }
        bar_sync(3, 256);
        const int t128 = tid & 127, w4 = warp & 3, q = lane & 3;
        float accF[88], accQ[96];
        const uint64_t da0 = make_desc(sX + wg * 8192, 16, 1024);
        const uint64_t db0 = make_desc(sB, 8192, 1024);
        float gs = 0.f;
        const int grow = wg * 64 + (t128 >> 1), ghalf = t128 & 1;
#pragma unroll
        for (int kc = 0; kc < 8; kc++) {
            const int st = kc & 3;
            mbar_wait(x_full + 8 * kc, 0);
            mbar_wait(b_full + 8 * st, (kc >> 2) & 1);
            TS(1, tid == 0 && kc == 0); TS(2, tid == 0 && kc == 4);
            wgmma_fence();
#pragma unroll
            for (int k16 = 0; k16 < 4; k16++) {
                wgmma_n176<1>(accF, da0 + (kc * 1024 + k16 * 2), db0 + (st * (K1_BSTAGE >> 4) + k16 * 128), (kc | k16) != 0);
            }
            wgmma_commit();
#pragma unroll
            for (int c = 0; c < 4; c++) {
                const int cc = ghalf * 4 + c;
                const uint4 xv = *(const uint4*)(sgen + kc * 16384 + grow * 128 + ((cc ^ (grow & 7)) << 4));
                const uint4 gv = *(const uint4*)(sGw + kc * 128 + cc * 16);
                gs = fmaf(bf_lo(xv.x), bf_lo(gv.x), gs); gs = fmaf(bf_hi(xv.x), bf_hi(gv.x), gs);
                gs = fmaf(bf_lo(xv.y), bf_lo(gv.y), gs); gs = fmaf(bf_hi(xv.y), bf_hi(gv.y), gs);
                gs = fmaf(bf_lo(xv.z), bf_lo(gv.z), gs); gs = fmaf(bf_hi(xv.z), bf_hi(gv.z), gs);
                gs = fmaf(bf_lo(xv.w), bf_lo(gv.w), gs); gs = fmaf(bf_hi(xv.w), bf_hi(gv.w), gs);
            }
            if (kc > 0) { wgmma_wait<1>(); if (lane == 0) mbar_arrive(b_empty + 8 * ((kc - 1) & 3)); }
        }
        gs += __shfl_xor_sync(0xffffffffu, gs, 1);
        {
            const float g = 1.f / (1.f + __expf(-gs));
            if (ghalf == 0) {
                sGate[grow] = g;
                if (j == 0) g_gate[rb * 128 + grow] = g;
            }
        }
        wgmma_wait<0>();
        if (lane == 0) mbar_arrive(b_empty + 8 * 3);
        bar_sync(1 + wg, 128);
        TS(3, tid == 0);
        const int n0 = j * FCH;
        const int rl = wg * 64 + w4 * 16 + (lane >> 2);
        const float om0 = 1.f - sGate[rl], om1 = 1.f - sGate[rl + 8];
        bf16* frow0 = g_a2 + (size_t)(rb * 128 + rl) * KA2 + D_ + n0;
        bf16* frow1 = frow0 + 8 * KA2;
        auto ffn_chunk = [&](int u) {
            uint32_t w0[4], w1[4];
#pragma unroll
            for (int i = 0; i < 4; i++) {
                const int t = u * 4 + i;
                if (t < 22) {
                    const uint32_t bv = sBias[t * 4 + q];
                    const float bb0 = bf_lo(bv), bb1 = bf_hi(bv);
                    w0[i] = pack_bf16(mish_f(accF[t * 4 + 0] + bb0) * om0, mish_f(accF[t * 4 + 1] + bb1) * om0);
                    w1[i] = pack_bf16(mish_f(accF[t * 4 + 2] + bb0) * om1, mish_f(accF[t * 4 + 3] + bb1) * om1);
                } else { w0[i] = 0; w1[i] = 0; }
            }
            quad_transpose(w0, q);
            quad_transpose(w1, q);
            const int c = (u * 4 + q) * 8;
            if (c < FCH && n0 + c < F_) {
                *(uint4*)(frow0 + c) = make_uint4(w0[0], w0[1], w0[2], w0[3]);
                *(uint4*)(frow1 + c) = make_uint4(w1[0], w1[1], w1[2], w1[3]);
            }
        };
#pragma unroll
        for (int kc = 0; kc < 8; kc++) {
            const int st = kc & 3;
            mbar_wait(b_full + 8 * st, ((kc + 8) >> 2) & 1);
            wgmma_fence();
#pragma unroll
            for (int k16 = 0; k16 < 4; k16++) {
                wgmma_n192<1>(accQ, da0 + (kc * 1024 + k16 * 2), db0 + (st * (K1_BSTAGE >> 4) + k16 * 128), (kc | k16) != 0);
            }
            wgmma_commit();
            if (kc < 6) ffn_chunk(kc);
            if (kc > 0) { wgmma_wait<1>(); if (lane == 0) mbar_arrive(b_empty + 8 * ((kc - 1) & 3)); }
        }
        wgmma_wait<0>();
        TS(4, tid == 0);
        {
            bf16* orow0 = g_qkv + ((size_t)j * S_ + rb * 128 + rl) * 192;
            bf16* orow1 = orow0 + 8 * 192;
#pragma unroll
            for (int u = 0; u < 6; u++) {
                uint32_t w0[4], w1[4];
#pragma unroll
                for (int i = 0; i < 4; i++) {
                    const int t = u * 4 + i;
                    w0[i] = pack_bf16(accQ[t * 4 + 0], accQ[t * 4 + 1]);
                    w1[i] = pack_bf16(accQ[t * 4 + 2], accQ[t * 4 + 3]);
                }
                quad_transpose(w0, q);
                quad_transpose(w1, q);
                const int c = (u * 4 + q) * 8;
                *(uint4*)(orow0 + c) = make_uint4(w0[0], w0[1], w0[2], w0[3]);
                *(uint4*)(orow1 + c) = make_uint4(w1[0], w1[1], w1[2], w1[3]);
            }
        }
        TS(5, tid == 0);
    }
}

__device__ __forceinline__ void ldsm_x4(uint32_t (&r)[4], uint32_t addr) {
    asm("ldmatrix.sync.aligned.m8n8.x4.shared.b16 {%0,%1,%2,%3}, [%4];"
                 : "=r"(r[0]), "=r"(r[1]), "=r"(r[2]), "=r"(r[3]) : "r"(addr));
}
__device__ __forceinline__ void ldsm_x4_t(uint32_t (&r)[4], uint32_t addr) {
    asm("ldmatrix.sync.aligned.m8n8.x4.trans.shared.b16 {%0,%1,%2,%3}, [%4];"
                 : "=r"(r[0]), "=r"(r[1]), "=r"(r[2]), "=r"(r[3]) : "r"(addr));
}
__device__ __forceinline__ void mma16816(float (&d)[4], const uint32_t (&a)[4], uint32_t b0, uint32_t b1) {
    asm("mma.sync.aligned.m16n8k16.row.col.f32.bf16.bf16.f32 {%0,%1,%2,%3}, {%4,%5,%6,%7}, {%8,%9}, {%0,%1,%2,%3};"
                 : "+f"(d[0]), "+f"(d[1]), "+f"(d[2]), "+f"(d[3])
                 : "r"(a[0]), "r"(a[1]), "r"(a[2]), "r"(a[3]), "r"(b0), "r"(b1));
}
__device__ __forceinline__ void mma16816_z(float (&d)[4], const uint32_t (&a)[4], uint32_t b0, uint32_t b1) {
    asm("mma.sync.aligned.m16n8k16.row.col.f32.bf16.bf16.f32 {%0,%1,%2,%3}, {%4,%5,%6,%7}, {%8,%9}, {%10,%10,%10,%10};"
                 : "=f"(d[0]), "=f"(d[1]), "=f"(d[2]), "=f"(d[3])
                 : "r"(a[0]), "r"(a[1]), "r"(a[2]), "r"(a[3]), "r"(b0), "r"(b1), "f"(0.f));
}

constexpr int KV_PITCH = 128;

template <int EDGE, bool HEAD>
__device__ __forceinline__ void blk_scores(float (&s)[2][4], const uint32_t (&qa)[4], uint32_t kaddr, bool dead, int r0, int c0)
{
    uint32_t kf[4];
    ldsm_x4(kf, kaddr);
    mma16816_z(s[0], qa, kf[0], kf[1]);
    mma16816_z(s[1], qa, kf[2], kf[3]);
#pragma unroll
    for (int t = 0; t < 2; t++)
#pragma unroll
        for (int e = 0; e < 4; e++) {
            const int r = r0 + (e >> 1) * 8, c = t * 8 + c0 + (e & 1);
            if (EDGE == 1 && c <= r) s[t][e] = -1e30f;
            if (EDGE == 2 && c > r) s[t][e] = -1e30f;
            if (HEAD && dead) s[t][e] = -1e30f;
        }
}
__device__ __forceinline__ void blk_max(const float (&s)[2][4], float& n0, float& n1) {
    n0 = fmaxf(n0, fmaxf(fmaxf(s[0][0], s[0][1]), fmaxf(s[1][0], s[1][1])));
    n1 = fmaxf(n1, fmaxf(fmaxf(s[0][2], s[0][3]), fmaxf(s[1][2], s[1][3])));
}
__device__ __forceinline__ void blk_pv(const float (&s)[2][4], float mc0, float mc1, float (&l)[4],
                                       float (&o)[2][4], uint32_t vaddr) {
    const float C = 0.25f * 1.4426950408889634f;
    uint32_t pa[4];
#pragma unroll
    for (int t = 0; t < 2; t++) {
        const float p0 = ex2(fmaf(s[t][0], C, -mc0)), p1 = ex2(fmaf(s[t][1], C, -mc0));
        const float p2 = ex2(fmaf(s[t][2], C, -mc1)), p3 = ex2(fmaf(s[t][3], C, -mc1));
        pa[2 * t] = pack_bf16(p0, p1); pa[2 * t + 1] = pack_bf16(p2, p3);
    }
    uint32_t vf[4];
    ldsm_x4_t(vf, vaddr);
    mma16816(o[0], pa, vf[0], vf[1]);
    mma16816(o[1], pa, vf[2], vf[3]);
    mma16816(l, pa, 0x3F803F80u, 0x3F803F80u);
}
__device__ __forceinline__ void quad_max(float& n0, float& n1) {
    n0 = fmaxf(n0, __shfl_xor_sync(0xffffffffu, n0, 1)); n1 = fmaxf(n1, __shfl_xor_sync(0xffffffffu, n1, 1));
    n0 = fmaxf(n0, __shfl_xor_sync(0xffffffffu, n0, 2)); n1 = fmaxf(n1, __shfl_xor_sync(0xffffffffu, n1, 2));
}
template <int NC, int NN, bool FIRST, bool NEXT_IS_EDGE, bool HEAD>
__device__ __forceinline__ void pipe_step(const float (&sc)[5][2][4], float (&sn)[5][2][4], const uint32_t (&qa)[4],
                                          uint32_t ka, uint32_t va, int kc, int kn, int kb0, int r0, int c0,
                                          float& m0, float& m1, float& n0, float& n1, float (&l)[4], float (&o)[2][4])
{
    const float C = 0.25f * 1.4426950408889634f;
    const float mc0 = n0 * C, mc1 = n1 * C;
    if (!FIRST) {
        const float a0 = ex2(fmaf(m0, C, -mc0)), a1 = ex2(fmaf(m1, C, -mc1));
        l[0] *= a0; l[2] *= a1;
        o[0][0] *= a0; o[0][1] *= a0; o[1][0] *= a0; o[1][1] *= a0;
        o[0][2] *= a1; o[0][3] *= a1; o[1][2] *= a1; o[1][3] *= a1;
    }
    m0 = n0; m1 = n1;
#pragma unroll
    for (int b = 0; b < NC; b++) {
        if (b < NN) {
            if (NEXT_IS_EDGE && b == 0) blk_scores<1, HEAD>(sn[b], qa, ka + (kn + b) * 16 * KV_PITCH, kn + b < kb0, r0, c0);
            else                        blk_scores<0, HEAD>(sn[b], qa, ka + (kn + b) * 16 * KV_PITCH, kn + b < kb0, r0, c0);
        }
        blk_pv(sc[b], mc0, mc1, l, o, va + (kc + b) * 16 * KV_PITCH);
        if (b < NN) blk_max(sn[b], n0, n1);
    }
    if (NN > 0) quad_max(n0, n1);
}

__device__ __forceinline__ void kv_need(uint32_t kvbar, int blk, uint32_t& ka, uint32_t& va) {
    mbar_wait(kvbar + 8 * blk, 0);
    asm volatile("" : "+r"(ka), "+r"(va) :: "memory");
}
template <bool HEAD>
__device__ __forceinline__ void attn_task(const uint32_t (&qa)[4], uint32_t ka, uint32_t va, int kb0, int lane, int qt, uint32_t kvbar,
                                          bf16* __restrict__ out  , float g0, float g1)
{
    const int r0 = lane >> 2, c0 = (lane & 3) * 2;
    float m0 = -1e30f, m1 = -1e30f, n0 = -1e30f, n1 = -1e30f;
    float l[4] = {0.f, 0.f, 0.f, 0.f};
    float o[2][4] = {{0.f, 0.f, 0.f, 0.f}, {0.f, 0.f, 0.f, 0.f}};
    float sa[5][2][4], sb[5][2][4];
    kv_need(kvbar, 2, ka, va);
    if (qt < 4) kv_need(kvbar, 1, ka, va);
#pragma unroll
    for (int b = 0; b < 5; b++) {
        if (b == 4) blk_scores<2, HEAD>(sa[b], qa, ka + (12 + b) * 16 * KV_PITCH, false, r0, c0);
        else        blk_scores<0, HEAD>(sa[b], qa, ka + (12 + b) * 16 * KV_PITCH, 12 + b < kb0, r0, c0);
        blk_max(sa[b], n0, n1);
    }
    quad_max(n0, n1);
    kv_need(kvbar, 1, ka, va);
    if (HEAD) {
        pipe_step<5, 0, true, false, HEAD>(sa, sb, qa, ka, va, 12, 0, kb0, r0, c0, m0, m1, n0, n1, l, o);
        kv_need(kvbar, 0, ka, va);
#pragma unroll 1
        for (int kc = 8; kc >= 0 && kb0 < kc + 4; kc -= 4) {
#pragma unroll
            for (int b = 0; b < 4; b++) {
                blk_scores<0, HEAD>(sa[b], qa, ka + (kc + b) * 16 * KV_PITCH, kc + b < kb0, r0, c0);
                blk_max(sa[b], n0, n1);
            }
            quad_max(n0, n1);
            pipe_step<4, 0, false, false, HEAD>(sa, sb, qa, ka, va, kc, 0, kb0, r0, c0, m0, m1, n0, n1, l, o);
        }
    } else {
        pipe_step<5, 4, true,  false, HEAD>(sa, sb, qa, ka, va, 12, 8, kb0, r0, c0, m0, m1, n0, n1, l, o);
        if (qt < 4) kv_need(kvbar, 0, ka, va);
        pipe_step<4, 4, false, false, HEAD>(sb, sa, qa, ka, va, 8, 4, kb0, r0, c0, m0, m1, n0, n1, l, o);
        kv_need(kvbar, 0, ka, va);
        pipe_step<4, 4, false, true,  HEAD>(sa, sb, qa, ka, va, 4, 0, kb0, r0, c0, m0, m1, n0, n1, l, o);
        pipe_step<4, 0, false, false, HEAD>(sb, sa, qa, ka, va, 0, 0, kb0, r0, c0, m0, m1, n0, n1, l, o);
    }
    const float f0 = __fdividef(g0, l[0]), f1 = __fdividef(g1, l[2]);
#pragma unroll
    for (int t = 0; t < 2; t++) {
        *(uint32_t*)(out + (size_t)r0 * KA2 + t * 8 + c0) = pack_bf16(o[t][0] * f0, o[t][1] * f0);
        *(uint32_t*)(out + (size_t)(r0 + 8) * KA2 + t * 8 + c0) = pack_bf16(o[t][2] * f1, o[t][3] * f1);
    }
}

constexpr int K2_SMEM = 2 * 384 * KV_PITCH + 1024 + 64;

__global__ void __launch_bounds__(512, 1) k2_kernel(const __grid_constant__ CUtensorMap tmQKV)
{
    extern __shared__ uint8_t smem_raw[];
    const uint32_t sbase = (smem_u32(smem_raw) + 1023u) & ~1023u;
    uint8_t* sgen = smem_raw + (sbase - smem_u32(smem_raw));
    const uint32_t sK = sbase, sV = sK + 384 * KV_PITCH, kv_full = sbase + 2 * 384 * KV_PITCH;
    const int rb = blockIdx.x >> 3, j = blockIdx.x & 7;
    const int tid = threadIdx.x, warp = tid >> 5, lane = tid & 31;
    pdl_launch();
    if (tid == 0) {
        for (int i = 0; i < 3; i++) mbar_init(kv_full + 8 * i, 1);
        fence_barrier_init();
    }
    pdl_wait();
    TS(6, tid == 0);
    if (tid == 0) {
        for (int i = 0; i < 3; i++) {
            const uint32_t bar = kv_full + 8 * (2 - i);
            if (rb - i >= 0) {
                const int row = j * S_ + (rb - i) * 128;
                mbar_expect_tx(bar, 2 * 16384);
                tma_load_2d(sK + (2 - i) * 16384, &tmQKV, 64, row, bar);
                tma_load_2d(sV + (2 - i) * 16384, &tmQKV, 128, row, bar);
            } else {
                mbar_arrive(bar);
            }
        }
    }
    if (rb < 2) {
        for (int i = tid; i < (2 - rb) * 1024; i += 512) {
            *(uint4*)(sgen + i * 16) = make_uint4(0, 0, 0, 0);
            *(uint4*)(sgen + 384 * KV_PITCH + i * 16) = make_uint4(0, 0, 0, 0);
        }
    }
    const int qt = warp & 7, h0 = (warp >> 3) * 2;
    const int q0g = rb * 128 + qt * 16;
    const int r0 = lane >> 2, c0 = (lane & 3) * 2;
    const bf16* qsrc = g_qkv + ((size_t)j * S_ + q0g) * 192 + h0 * 16;
    uint32_t qa[4], qn[4];
    qa[0] = *(const uint32_t*)(qsrc + (size_t)r0 * 192 + c0);
    qa[1] = *(const uint32_t*)(qsrc + (size_t)(r0 + 8) * 192 + c0);
    qa[2] = *(const uint32_t*)(qsrc + (size_t)r0 * 192 + c0 + 8);
    qa[3] = *(const uint32_t*)(qsrc + (size_t)(r0 + 8) * 192 + c0 + 8);
    qn[0] = *(const uint32_t*)(qsrc + (size_t)r0 * 192 + 16 + c0);
    qn[1] = *(const uint32_t*)(qsrc + (size_t)(r0 + 8) * 192 + 16 + c0);
    qn[2] = *(const uint32_t*)(qsrc + (size_t)r0 * 192 + 16 + c0 + 8);
    qn[3] = *(const uint32_t*)(qsrc + (size_t)(r0 + 8) * 192 + 16 + c0 + 8);
    const float g0 = g_gate[q0g + r0], g1 = g_gate[q0g + r0 + 8];
    const int kb0 = q0g < 256 ? (256 - q0g) >> 4 : 0;
    __syncthreads();
    const uint32_t sKd = sK, sVd = sV;
    TS(7, tid == 0);
    const int krow = qt * 16 + (lane & 7) + ((lane >> 4) << 3);
    const int vrow = qt * 16 + (lane & 15);
#pragma unroll 1
    for (int hh = 0; hh < 2; hh++) {
        const int hl = h0 + hh;
        const uint32_t ka = sKd + krow * KV_PITCH + (((2 * hl + ((lane >> 3) & 1)) ^ (lane & 7)) << 4);
        const uint32_t va = sVd + vrow * KV_PITCH + (((2 * hl + (lane >> 4)) ^ (lane & 7)) << 4);
        if (rb < 2) attn_task<true>(qa, ka, va, kb0, lane, qt, kv_full, g_a2 + (size_t)q0g * KA2 + (j * 4 + hl) * 16, g0, g1);
        else        attn_task<false>(qa, ka, va, kb0, lane, qt, kv_full, g_a2 + (size_t)q0g * KA2 + (j * 4 + hl) * 16, g0, g1);
        TS(8 + hh, tid == 0);
        qa[0] = qn[0]; qa[1] = qn[1]; qa[2] = qn[2]; qa[3] = qn[3];
    }
}

constexpr int K3_STAGES = 8;
constexpr int K3_STAGE = 16384 + 8192;
constexpr int K3_SMEM = K3_STAGES * K3_STAGE + 1024 + 1024;
constexpr int K3_KSTEPS = 30;

__global__ void __launch_bounds__(384, 1)
k3_kernel(const __grid_constant__ CUtensorMap tmA2, const __grid_constant__ CUtensorMap tmWo,
          const __grid_constant__ CUtensorMap tmW2, bf16* __restrict__ out)
{
    extern __shared__ uint8_t smem_raw[];
    const uint32_t sbase = (smem_u32(smem_raw) + 1023u) & ~1023u;
    const uint32_t sBar = sbase + K3_STAGES * K3_STAGE;
    const uint32_t full = sBar, empty = sBar + 64;
    const int rb = blockIdx.x >> 3, nb = blockIdx.x & 7;
    const int tid = threadIdx.x, lane = tid & 31;
    const int warp = __shfl_sync(0xffffffffu, tid >> 5, 0), wg = warp >> 2;
    if (tid == 0) {
        for (int i = 0; i < K3_STAGES; i++) { mbar_init(full + 8 * i, 1); mbar_init(empty + 8 * i, 8); }
        fence_barrier_init();
    }
    __syncthreads();
    pdl_wait();
    TS(10, tid == 0);
    if (wg == 2) {
        reg_dealloc<40>();
        if (tid == 256) {
            for (int ks = 0; ks < K3_KSTEPS; ks++) {
                const int st = ks % K3_STAGES;
                if (ks >= K3_STAGES) mbar_wait(empty + 8 * st, ((ks / K3_STAGES) - 1) & 1);
                mbar_expect_tx(full + 8 * st, K3_STAGE);
                const uint32_t dst = sbase + st * K3_STAGE;
                tma_load_2d(dst, &tmA2, ks * 64, rb * 128, full + 8 * st);
                if (ks < 8) tma_load_2d(dst + 16384, &tmWo, nb * 64, ks * 64, full + 8 * st);
                else        tma_load_2d(dst + 16384, &tmW2, nb * 64, (ks - 8) * 64, full + 8 * st);
            }
        }
    } else {
        reg_alloc<232>();
        float acc[32];
        const uint64_t da0 = make_desc(sbase + wg * 8192, 16, 1024);
        const uint64_t db0 = make_desc(sbase + 16384, 8192, 1024);
#pragma unroll 1
        for (int r = 0; r < 4; r++) {
#pragma unroll
            for (int st = 0; st < K3_STAGES; st++) {
                if (r * K3_STAGES + st < K3_KSTEPS) {
                    mbar_wait(full + 8 * st, r & 1);
                    TS(11, tid == 0 && r == 0 && st == 0); TS(12, tid == 0 && r == 1 && st == 0); TS(13, tid == 0 && r == 2 && st == 0);
                    wgmma_fence();
#pragma unroll
                    for (int k16 = 0; k16 < 4; k16++)
                        wgmma_n64<1>(acc, da0 + (st * (K3_STAGE >> 4) + k16 * 2), db0 + (st * (K3_STAGE >> 4) + k16 * 128), (r | st | k16) != 0);
                    wgmma_commit();
                    if (r | st) { wgmma_wait<1>(); if (lane == 0) mbar_arrive(empty + 8 * ((st + K3_STAGES - 1) % K3_STAGES)); }
                }
            }
        }
        wgmma_wait<0>();
        TS(14, tid == 0);
        const int q = lane & 3;
        const int r = rb * 128 + wg * 64 + (warp & 3) * 16 + (lane >> 2);
        bf16* orow0 = out + (size_t)r * D_ + nb * 64;
        bf16* orow1 = orow0 + 8 * D_;
#pragma unroll
        for (int u = 0; u < 2; u++) {
            uint32_t w0[4], w1[4];
#pragma unroll
            for (int i = 0; i < 4; i++) {
                const int t = u * 4 + i;
                w0[i] = pack_bf16(acc[t * 4 + 0], acc[t * 4 + 1]);
                w1[i] = pack_bf16(acc[t * 4 + 2], acc[t * 4 + 3]);
            }
            quad_transpose(w0, q);
            quad_transpose(w1, q);
            const int c = (u * 4 + q) * 8;
            *(uint4*)(orow0 + c) = make_uint4(w0[0], w0[1], w0[2], w0[3]);
            *(uint4*)(orow1 + c) = make_uint4(w1[0], w1[1], w1[2], w1[3]);
        }
        TS(15, tid == 0);
    }
}

typedef CUresult (*PFN_encodeTiled)(CUtensorMap*, CUtensorMapDataType, cuuint32_t, void*, const cuuint64_t*,
                                    const cuuint64_t*, const cuuint32_t*, const cuuint32_t*, CUtensorMapInterleave,
                                    CUtensorMapSwizzle, CUtensorMapL2promotion, CUtensorMapFloatOOBfill);

static void make_map(PFN_encodeTiled enc, CUtensorMap* m, const void* ptr, uint64_t cols, uint64_t rows,
                     uint32_t box_cols, uint32_t box_rows)
{
    cuuint64_t dims[2] = {cols, rows};
    cuuint64_t strides[1] = {cols * 2};
    cuuint32_t box[2] = {box_cols, box_rows};
    cuuint32_t es[2] = {1, 1};
    enc(m, CU_TENSOR_MAP_DATA_TYPE_BFLOAT16, 2, const_cast<void*>(ptr), dims, strides, box, es,
        CU_TENSOR_MAP_INTERLEAVE_NONE, CU_TENSOR_MAP_SWIZZLE_128B, CU_TENSOR_MAP_L2_PROMOTION_L2_128B,
        CU_TENSOR_MAP_FLOAT_OOB_FILL_NONE);
}

extern "C" void kernel_launch(void* const* d_in, const int* in_sizes, int n_in, void* d_out, int out_size)
{
    const bf16* x    = (const bf16*)d_in[0];
    const bf16* wqkv = (const bf16*)d_in[1];
    const bf16* wo   = (const bf16*)d_in[2];
    const bf16* w1   = (const bf16*)d_in[4];
    const bf16* b1   = (const bf16*)d_in[5];
    const bf16* w2   = (const bf16*)d_in[6];
    const bf16* gw   = (const bf16*)d_in[7];

    static PFN_encodeTiled enc = nullptr;
    if (!enc) {
        void* fn = nullptr;
        cudaDriverEntryPointQueryResult qr;
        cudaGetDriverEntryPoint("cuTensorMapEncodeTiled", &fn, cudaEnableDefault, &qr);
        enc = (PFN_encodeTiled)fn;
        cudaFuncSetAttribute(k1_kernel, cudaFuncAttributeMaxDynamicSharedMemorySize, K1_SMEM);
        cudaFuncSetAttribute(k2_kernel, cudaFuncAttributeMaxDynamicSharedMemorySize, K2_SMEM);
        cudaFuncSetAttribute(k3_kernel, cudaFuncAttributeMaxDynamicSharedMemorySize, K3_SMEM);
    }
    void* a2p = nullptr;
    cudaGetSymbolAddress(&a2p, g_a2);
    void* qkvp = nullptr;
    cudaGetSymbolAddress(&qkvp, g_qkv);
    CUtensorMap tmX, tmWqkv, tmW1, tmA2, tmWo, tmW2, tmQKV;
    make_map(enc, &tmQKV, qkvp, 192, 8 * S_, 64, 128);
    make_map(enc, &tmX, x, D_, S_, 64, 128);
    make_map(enc, &tmWqkv, wqkv, 3 * D_, D_, 64, 64);
    make_map(enc, &tmW1, w1, F_, D_, 64, 64);
    make_map(enc, &tmA2, a2p, KA2, S_, 64, 128);
    make_map(enc, &tmWo, wo, D_, D_, 64, 64);
    make_map(enc, &tmW2, w2, D_, F_, 64, 64);

    cudaStream_t st = cudaStreamPerThread;
    k1_kernel<<<128, 384, K1_SMEM, st>>>(tmX, tmWqkv, tmW1, b1, gw, w1, wqkv, w2, wo);
    cudaLaunchAttribute at[1];
    at[0].id = cudaLaunchAttributeProgrammaticStreamSerialization;
    at[0].val.programmaticStreamSerializationAllowed = 1;
    cudaLaunchConfig_t cfg = {};
    cfg.gridDim = dim3(128); cfg.stream = st; cfg.attrs = at; cfg.numAttrs = 1;
    cfg.blockDim = dim3(512); cfg.dynamicSmemBytes = K2_SMEM;
    cudaLaunchKernelEx(&cfg, k2_kernel, tmQKV);
    k3_kernel<<<128, 384, K3_SMEM, st>>>(tmA2, tmWo, tmW2, (bf16*)d_out);
}
```

```cpp
#include <cuda_runtime.h>
#include <cuda_bf16.h>
#include <cuda.h>
#include <stdint.h>

typedef __nv_bfloat16 bf16;

constexpr int S_ = 2048, D_ = 512, F_ = 1376;
constexpr int KA2 = D_ + F_;
constexpr int FCH = 176;

__device__ bf16  g_qkv[8 * S_ * 192];
__device__ bf16  g_a2[S_ * KA2];
__device__ float g_gate[S_];

#define TS(k, cond) do { } while (0)

__device__ __forceinline__ uint32_t smem_u32(const void* p) { return (uint32_t)__cvta_generic_to_shared(p); }
__device__ __forceinline__ void mbar_init(uint32_t bar, uint32_t count) {
    asm volatile("mbarrier.init.shared::cta.b64 [%0], %1;" :: "r"(bar), "r"(count) : "memory");
}
__device__ __forceinline__ void mbar_expect_tx(uint32_t bar, uint32_t bytes) {
    asm volatile("mbarrier.arrive.expect_tx.shared::cta.b64 _, [%0], %1;" :: "r"(bar), "r"(bytes) : "memory");
}
__device__ __forceinline__ void mbar_arrive(uint32_t bar) {
    asm volatile("mbarrier.arrive.shared::cta.b64 _, [%0];" :: "r"(bar) : "memory");
}
__device__ __forceinline__ bool mbar_try_wait(uint32_t bar, uint32_t parity) {
    uint32_t ok;
    asm volatile("{\n.reg .pred p;\nmbarrier.try_wait.parity.shared::cta.b64 p, [%1], %2;\nselp.u32 %0, 1, 0, p;\n}"
                 : "=r"(ok) : "r"(bar), "r"(parity) : "memory");
    return ok != 0;
}
__device__ __forceinline__ void mbar_wait(uint32_t bar, uint32_t parity) {
    for (uint32_t it = 0; it < (1u << 22); ++it) { if (mbar_try_wait(bar, parity)) break; }
}
__device__ __forceinline__ void tma_load_2d(uint32_t dst, const CUtensorMap* map, int c0, int c1, uint32_t bar) {
    asm volatile("cp.async.bulk.tensor.2d.shared::cluster.global.mbarrier::complete_tx::bytes [%0], [%1, {%3, %4}], [%2];"
                 :: "r"(dst), "l"(map), "r"(bar), "r"(c0), "r"(c1) : "memory");
}
__device__ __forceinline__ void l2_prefetch(const void* p, uint32_t bytes) {
    asm volatile("cp.async.bulk.prefetch.L2.global [%0], %1;" :: "l"(p), "r"(bytes) : "memory");
}
__device__ __forceinline__ void fence_barrier_init() { asm volatile("fence.mbarrier_init.release.cluster;" ::: "memory"); }
__device__ __forceinline__ void wgmma_fence()  { asm volatile("wgmma.fence.sync.aligned;" ::: "memory"); }
__device__ __forceinline__ void wgmma_commit() { asm volatile("wgmma.commit_group.sync.aligned;" ::: "memory"); }
template <int N> __device__ __forceinline__ void wgmma_wait() { asm volatile("wgmma.wait_group.sync.aligned %0;" :: "n"(N) : "memory"); }
template <int R> __device__ __forceinline__ void reg_alloc()   { asm volatile("setmaxnreg.inc.sync.aligned.u32 %0;" :: "n"(R)); }
template <int R> __device__ __forceinline__ void reg_dealloc() { asm volatile("setmaxnreg.dec.sync.aligned.u32 %0;" :: "n"(R)); }
__device__ __forceinline__ void bar_sync(int id, int n)   { asm volatile("bar.sync %0, %1;" :: "r"(id), "r"(n) : "memory"); }
__device__ __forceinline__ void bar_arrive(int id, int n) { asm volatile("bar.arrive %0, %1;" :: "r"(id), "r"(n) : "memory"); }

__device__ __forceinline__ uint64_t make_desc(uint32_t addr, uint32_t lbo, uint32_t sbo) {
    uint64_t d = (uint64_t)((addr & 0x3FFFF) >> 4);
    d |= (uint64_t)((lbo & 0x3FFFF) >> 4) << 16;
    d |= (uint64_t)((sbo & 0x3FFFF) >> 4) << 32;
    d |= (uint64_t)1 << 62;
    return d;
}

template <int TB>
__device__ __forceinline__ void wgmma_n64(float (&d)[32], uint64_t da, uint64_t db, int scale_d) {
    asm volatile("{\n.reg .pred p;\nsetp.ne.b32 p, %34, 0;\n"
        "wgmma.mma_async.sync.aligned.m64n64k16.f32.bf16.bf16 {%0, %1, %2, %3, %4, %5, %6, %7, %8, %9, %10, %11, %12, %13, %14, %15, %16, %17, %18, %19, %20, %21, %22, %23, %24, %25, %26, %27, %28, %29, %30, %31}, %32, %33, p, 1, 1, 0, %35;\n}\n"
        : "+f"(d[0]), "+f"(d[1]), "+f"(d[2]), "+f"(d[3]), "+f"(d[4]), "+f"(d[5]), "+f"(d[6]), "+f"(d[7]), "+f"(d[8]), "+f"(d[9]), "+f"(d[10]), "+f"(d[11]), "+f"(d[12]), "+f"(d[13]), "+f"(d[14]), "+f"(d[15]), "+f"(d[16]), "+f"(d[17]), "+f"(d[18]), "+f"(d[19]), "+f"(d[20]), "+f"(d[21]), "+f"(d[22]), "+f"(d[23]), "+f"(d[24]), "+f"(d[25]), "+f"(d[26]), "+f"(d[27]), "+f"(d[28]), "+f"(d[29]), "+f"(d[30]), "+f"(d[31])
        : "l"(da), "l"(db), "r"(scale_d), "n"(TB));
}

template <int TB>
__device__ __forceinline__ void wgmma_n128(float (&d)[64], uint64_t da, uint64_t db, int scale_d) {
    asm volatile("{\n.reg .pred p;\nsetp.ne.b32 p, %66, 0;\n"
        "wgmma.mma_async.sync.aligned.m64n128k16.f32.bf16.bf16 {%0, %1, %2, %3, %4, %5, %6, %7, %8, %9, %10, %11, %12, %13, %14, %15, %16, %17, %18, %19, %20, %21, %22, %23, %24, %25, %26, %27, %28, %29, %30, %31, %32, %33, %34, %35, %36, %37, %38, %39, %40, %41, %42, %43, %44, %45, %46, %47, %48, %49, %50, %51, %52, %53, %54, %55, %56, %57, %58, %59, %60, %61, %62, %63}, %64, %65, p, 1, 1, 0, %67;\n}\n"
        : "+f"(d[0]), "+f"(d[1]), "+f"(d[2]), "+f"(d[3]), "+f"(d[4]), "+f"(d[5]), "+f"(d[6]), "+f"(d[7]), "+f"(d[8]), "+f"(d[9]), "+f"(d[10]), "+f"(d[11]), "+f"(d[12]), "+f"(d[13]), "+f"(d[14]), "+f"(d[15]), "+f"(d[16]), "+f"(d[17]), "+f"(d[18]), "+f"(d[19]), "+f"(d[20]), "+f"(d[21]), "+f"(d[22]), "+f"(d[23]), "+f"(d[24]), "+f"(d[25]), "+f"(d[26]), "+f"(d[27]), "+f"(d[28]), "+f"(d[29]), "+f"(d[30]), "+f"(d[31]), "+f"(d[32]), "+f"(d[33]), "+f"(d[34]), "+f"(d[35]), "+f"(d[36]), "+f"(d[37]), "+f"(d[38]), "+f"(d[39]), "+f"(d[40]), "+f"(d[41]), "+f"(d[42]), "+f"(d[43]), "+f"(d[44]), "+f"(d[45]), "+f"(d[46]), "+f"(d[47]), "+f"(d[48]), "+f"(d[49]), "+f"(d[50]), "+f"(d[51]), "+f"(d[52]), "+f"(d[53]), "+f"(d[54]), "+f"(d[55]), "+f"(d[56]), "+f"(d[57]), "+f"(d[58]), "+f"(d[59]), "+f"(d[60]), "+f"(d[61]), "+f"(d[62]), "+f"(d[63])
        : "l"(da), "l"(db), "r"(scale_d), "n"(TB));
}

template <int TB>
__device__ __forceinline__ void wgmma_n176(float (&d)[88], uint64_t da, uint64_t db, int scale_d) {
    asm volatile("{\n.reg .pred p;\nsetp.ne.b32 p, %90, 0;\n"
        "wgmma.mma_async.sync.aligned.m64n176k16.f32.bf16.bf16 {%0, %1, %2, %3, %4, %5, %6, %7, %8, %9, %10, %11, %12, %13, %14, %15, %16, %17, %18, %19, %20, %21, %22, %23, %24, %25, %26, %27, %28, %29, %30, %31, %32, %33, %34, %35, %36, %37, %38, %39, %40, %41, %42, %43, %44, %45, %46, %47, %48, %49, %50, %51, %52, %53, %54, %55, %56, %57, %58, %59, %60, %61, %62, %63, %64, %65, %66, %67, %68, %69, %70, %71, %72, %73, %74, %75, %76, %77, %78, %79, %80, %81, %82, %83, %84, %85, %86, %87}, %88, %89, p, 1, 1, 0, %91;\n}\n"
        : "+f"(d[0]), "+f"(d[1]), "+f"(d[2]), "+f"(d[3]), "+f"(d[4]), "+f"(d[5]), "+f"(d[6]), "+f"(d[7]), "+f"(d[8]), "+f"(d[9]), "+f"(d[10]), "+f"(d[11]), "+f"(d[12]), "+f"(d[13]), "+f"(d[14]), "+f"(d[15]), "+f"(d[16]), "+f"(d[17]), "+f"(d[18]), "+f"(d[19]), "+f"(d[20]), "+f"(d[21]), "+f"(d[22]), "+f"(d[23]), "+f"(d[24]), "+f"(d[25]), "+f"(d[26]), "+f"(d[27]), "+f"(d[28]), "+f"(d[29]), "+f"(d[30]), "+f"(d[31]), "+f"(d[32]), "+f"(d[33]), "+f"(d[34]), "+f"(d[35]), "+f"(d[36]), "+f"(d[37]), "+f"(d[38]), "+f"(d[39]), "+f"(d[40]), "+f"(d[41]), "+f"(d[42]), "+f"(d[43]), "+f"(d[44]), "+f"(d[45]), "+f"(d[46]), "+f"(d[47]), "+f"(d[48]), "+f"(d[49]), "+f"(d[50]), "+f"(d[51]), "+f"(d[52]), "+f"(d[53]), "+f"(d[54]), "+f"(d[55]), "+f"(d[56]), "+f"(d[57]), "+f"(d[58]), "+f"(d[59]), "+f"(d[60]), "+f"(d[61]), "+f"(d[62]), "+f"(d[63]), "+f"(d[64]), "+f"(d[65]), "+f"(d[66]), "+f"(d[67]), "+f"(d[68]), "+f"(d[69]), "+f"(d[70]), "+f"(d[71]), "+f"(d[72]), "+f"(d[73]), "+f"(d[74]), "+f"(d[75]), "+f"(d[76]), "+f"(d[77]), "+f"(d[78]), "+f"(d[79]), "+f"(d[80]), "+f"(d[81]), "+f"(d[82]), "+f"(d[83]), "+f"(d[84]), "+f"(d[85]), "+f"(d[86]), "+f"(d[87])
        : "l"(da), "l"(db), "r"(scale_d), "n"(TB));
}

template <int TB>
__device__ __forceinline__ void wgmma_n192(float (&d)[96], uint64_t da, uint64_t db, int scale_d) {
    asm volatile("{\n.reg .pred p;\nsetp.ne.b32 p, %98, 0;\n"
        "wgmma.mma_async.sync.aligned.m64n192k16.f32.bf16.bf16 {%0, %1, %2, %3, %4, %5, %6, %7, %8, %9, %10, %11, %12, %13, %14, %15, %16, %17, %18, %19, %20, %21, %22, %23, %24, %25, %26, %27, %28, %29, %30, %31, %32, %33, %34, %35, %36, %37, %38, %39, %40, %41, %42, %43, %44, %45, %46, %47, %48, %49, %50, %51, %52, %53, %54, %55, %56, %57, %58, %59, %60, %61, %62, %63, %64, %65, %66, %67, %68, %69, %70, %71, %72, %73, %74, %75, %76, %77, %78, %79, %80, %81, %82, %83, %84, %85, %86, %87, %88, %89, %90, %91, %92, %93, %94, %95}, %96, %97, p, 1, 1, 0, %99;\n}\n"
        : "+f"(d[0]), "+f"(d[1]), "+f"(d[2]), "+f"(d[3]), "+f"(d[4]), "+f"(d[5]), "+f"(d[6]), "+f"(d[7]), "+f"(d[8]), "+f"(d[9]), "+f"(d[10]), "+f"(d[11]), "+f"(d[12]), "+f"(d[13]), "+f"(d[14]), "+f"(d[15]), "+f"(d[16]), "+f"(d[17]), "+f"(d[18]), "+f"(d[19]), "+f"(d[20]), "+f"(d[21]), "+f"(d[22]), "+f"(d[23]), "+f"(d[24]), "+f"(d[25]), "+f"(d[26]), "+f"(d[27]), "+f"(d[28]), "+f"(d[29]), "+f"(d[30]), "+f"(d[31]), "+f"(d[32]), "+f"(d[33]), "+f"(d[34]), "+f"(d[35]), "+f"(d[36]), "+f"(d[37]), "+f"(d[38]), "+f"(d[39]), "+f"(d[40]), "+f"(d[41]), "+f"(d[42]), "+f"(d[43]), "+f"(d[44]), "+f"(d[45]), "+f"(d[46]), "+f"(d[47]), "+f"(d[48]), "+f"(d[49]), "+f"(d[50]), "+f"(d[51]), "+f"(d[52]), "+f"(d[53]), "+f"(d[54]), "+f"(d[55]), "+f"(d[56]), "+f"(d[57]), "+f"(d[58]), "+f"(d[59]), "+f"(d[60]), "+f"(d[61]), "+f"(d[62]), "+f"(d[63]), "+f"(d[64]), "+f"(d[65]), "+f"(d[66]), "+f"(d[67]), "+f"(d[68]), "+f"(d[69]), "+f"(d[70]), "+f"(d[71]), "+f"(d[72]), "+f"(d[73]), "+f"(d[74]), "+f"(d[75]), "+f"(d[76]), "+f"(d[77]), "+f"(d[78]), "+f"(d[79]), "+f"(d[80]), "+f"(d[81]), "+f"(d[82]), "+f"(d[83]), "+f"(d[84]), "+f"(d[85]), "+f"(d[86]), "+f"(d[87]), "+f"(d[88]), "+f"(d[89]), "+f"(d[90]), "+f"(d[91]), "+f"(d[92]), "+f"(d[93]), "+f"(d[94]), "+f"(d[95])
        : "l"(da), "l"(db), "r"(scale_d), "n"(TB));
}

__device__ __forceinline__ uint32_t pack_bf16(float lo, float hi) {
    uint32_t r;
    asm("cvt.rn.bf16x2.f32 %0, %1, %2;" : "=r"(r) : "f"(hi), "f"(lo));
    return r;
}
__device__ __forceinline__ float bf_lo(uint32_t v) { return __uint_as_float(v << 16); }
__device__ __forceinline__ float bf_hi(uint32_t v) { return __uint_as_float(v & 0xffff0000u); }

__device__ __forceinline__ void quad_transpose(uint32_t (&w)[4], int q) {
    const bool o1 = q & 1, o2 = q & 2;
    {
        uint32_t s0 = o1 ? w[0] : w[1], s1 = o1 ? w[2] : w[3];
        s0 = __shfl_xor_sync(0xffffffffu, s0, 1); s1 = __shfl_xor_sync(0xffffffffu, s1, 1);
        if (o1) { w[0] = s0; w[2] = s1; } else { w[1] = s0; w[3] = s1; }
    }
    {
        uint32_t s0 = o2 ? w[0] : w[2], s1 = o2 ? w[1] : w[3];
        s0 = __shfl_xor_sync(0xffffffffu, s0, 2); s1 = __shfl_xor_sync(0xffffffffu, s1, 2);
        if (o2) { w[0] = s0; w[1] = s1; } else { w[2] = s0; w[3] = s1; }
    }
}

__device__ __forceinline__ float ex2(float x) { float y; asm("ex2.approx.ftz.f32 %0, %1;" : "=f"(y) : "f"(x)); return y; }
__device__ __forceinline__ float rcp(float x) { float y; asm("rcp.approx.ftz.f32 %0, %1;" : "=f"(y) : "f"(x)); return y; }

__device__ __forceinline__ float ex2v(float x) { float y; asm volatile("ex2.approx.ftz.f32 %0, %1;" : "=f"(y) : "f"(x)); return y; }
__device__ __forceinline__ float rcpv(float x) { float y; asm volatile("rcp.approx.ftz.f32 %0, %1;" : "=f"(y) : "f"(x)); return y; }
__device__ __forceinline__ float mish_f(float h) {
    const float e = ex2v(1.4426950408889634f * fminf(h, 20.f));
    const float n = fmaf(e, e, e + e);
    return h * n * rcpv(n + 2.f);
}

__device__ __forceinline__ void pdl_wait()   { asm volatile("griddepcontrol.wait;" ::: "memory"); }
__device__ __forceinline__ void pdl_launch() { asm volatile("griddepcontrol.launch_dependents;" ::: "memory"); }

constexpr int K1_STAGES = 4;
constexpr int K1_XBYTES = 128 * 512 * 2;
constexpr int K1_BSTAGE = 3 * 8192;
constexpr int K1_SMEM   = K1_XBYTES + K1_STAGES * K1_BSTAGE + 2048   + 1024  ;

__global__ void __launch_bounds__(384, 1)
k1_kernel(const __grid_constant__ CUtensorMap tmX, const __grid_constant__ CUtensorMap tmWqkv,
          const __grid_constant__ CUtensorMap tmW1, const bf16* __restrict__ b1,
          const bf16* __restrict__ gate_w, const bf16* __restrict__ w1p, const bf16* __restrict__ wqkvp,
          const bf16* __restrict__ w2p, const bf16* __restrict__ wop)
{

    extern __shared__ uint8_t smem_raw[];
    const uint32_t sbase = (smem_u32(smem_raw) + 1023u) & ~1023u;
    uint8_t* sgen = smem_raw + (sbase - smem_u32(smem_raw));
    const uint32_t sX = sbase;
    const uint32_t sB = sbase + K1_XBYTES;
    const uint32_t sBar = sB + K1_STAGES * K1_BSTAGE;
    const uint32_t x_full = sBar;
    const uint32_t b_full = sBar + 64;
    const uint32_t b_empty = sBar + 96;
    float* sGate = (float*)(sgen + K1_XBYTES + K1_STAGES * K1_BSTAGE + 128);
    uint8_t* sGw = sgen + K1_XBYTES + K1_STAGES * K1_BSTAGE + 640;
    uint32_t* sBias = (uint32_t*)(sgen + K1_XBYTES + K1_STAGES * K1_BSTAGE + 1664);

    const int rb = blockIdx.x >> 3, j = blockIdx.x & 7;
    const int tid = threadIdx.x, lane = tid & 31;
    const int warp = __shfl_sync(0xffffffffu, tid >> 5, 0), wg = warp >> 2;
    TS(0, tid == 0);
    pdl_launch();

    if (tid == 0) {
        for (int i = 0; i < 8; i++) mbar_init(x_full + 8 * i, 1);
        for (int i = 0; i < K1_STAGES; i++) { mbar_init(b_full + 8 * i, 1); mbar_init(b_empty + 8 * i, 8); }
        fence_barrier_init();
    }
    __syncthreads();

    if (wg == 2) {
        reg_dealloc<40>();
        if (tid == 288) {
            const int b = blockIdx.x;
            mbar_wait(b_full + 8, 0);
            l2_prefetch((const uint8_t*)wqkvp + b * 12288, 12288);
            l2_prefetch((const uint8_t*)w2p + b * 11008, 11008);
            l2_prefetch((const uint8_t*)wop + b * 4096, 4096);
        }
        if (tid == 256) {
            for (int it = 0; it < 16; it++) {
                if (it < 8) {
                    mbar_expect_tx(x_full + 8 * it, 16384);
                    tma_load_2d(sX + it * 16384, &tmX, it * 64, rb * 128, x_full + 8 * it);
                }
                const int st = it & 3;
                if (it >= K1_STAGES) mbar_wait(b_empty + 8 * st, ((it >> 2) - 1) & 1);
                mbar_expect_tx(b_full + 8 * st, K1_BSTAGE);
                const uint32_t dst = sB + st * K1_BSTAGE;
                if (it < 8) {
                    for (int b = 0; b < 3; b++) tma_load_2d(dst + b * 8192, &tmW1, j * FCH + b * 64, it * 64, b_full + 8 * st);
                } else {
                    for (int b = 0; b < 3; b++) tma_load_2d(dst + b * 8192, &tmWqkv, b * 512 + j * 64, (it - 8) * 64, b_full + 8 * st);
                }
            }
        }
    } else {
        reg_alloc<232>();
        if (tid < 64) ((uint4*)sGw)[tid] = __ldg((const uint4*)gate_w + tid);
        else if (tid < 64 + 88) {
            const int c = j * FCH + (tid - 64) * 2;
            sBias[tid - 64] = c < F_ ? __ldg((const uint32_t*)(b1 + c)) : 0u;
        }
        bar_sync(3, 256);
        const int t128 = tid & 127, w4 = warp & 3, q = lane & 3;
        float accF[88], accQ[96];
        const uint64_t da0 = make_desc(sX + wg * 8192, 16, 1024);
        const uint64_t db0 = make_desc(sB, 8192, 1024);
        float gs = 0.f;
        const int grow = wg * 64 + (t128 >> 1), ghalf = t128 & 1;
#pragma unroll
        for (int kc = 0; kc < 8; kc++) {
            const int st = kc & 3;
            mbar_wait(x_full + 8 * kc, 0);
            mbar_wait(b_full + 8 * st, (kc >> 2) & 1);
            TS(1, tid == 0 && kc == 0); TS(2, tid == 0 && kc == 4);
            wgmma_fence();
#pragma unroll
            for (int k16 = 0; k16 < 4; k16++) {
                wgmma_n176<1>(accF, da0 + (kc * 1024 + k16 * 2), db0 + (st * (K1_BSTAGE >> 4) + k16 * 128), (kc | k16) != 0);
            }
            wgmma_commit();
#pragma unroll
            for (int c = 0; c < 4; c++) {
                const int cc = ghalf * 4 + c;
                const uint4 xv = *(const uint4*)(sgen + kc * 16384 + grow * 128 + ((cc ^ (grow & 7)) << 4));
                const uint4 gv = *(const uint4*)(sGw + kc * 128 + cc * 16);
                gs = fmaf(bf_lo(xv.x), bf_lo(gv.x), gs); gs = fmaf(bf_hi(xv.x), bf_hi(gv.x), gs);
                gs = fmaf(bf_lo(xv.y), bf_lo(gv.y), gs); gs = fmaf(bf_hi(xv.y), bf_hi(gv.y), gs);
                gs = fmaf(bf_lo(xv.z), bf_lo(gv.z), gs); gs = fmaf(bf_hi(xv.z), bf_hi(gv.z), gs);
                gs = fmaf(bf_lo(xv.w), bf_lo(gv.w), gs); gs = fmaf(bf_hi(xv.w), bf_hi(gv.w), gs);
            }
            if (kc > 0) { wgmma_wait<1>(); if (lane == 0) mbar_arrive(b_empty + 8 * ((kc - 1) & 3)); }
        }
        gs += __shfl_xor_sync(0xffffffffu, gs, 1);
        {
            const float g = 1.f / (1.f + __expf(-gs));
            if (ghalf == 0) {
                sGate[grow] = g;
                if (j == 0) g_gate[rb * 128 + grow] = g;
            }
        }
        wgmma_wait<0>();
        if (lane == 0) mbar_arrive(b_empty + 8 * 3);
        bar_sync(1 + wg, 128);
        TS(3, tid == 0);
        const int n0 = j * FCH;
        const int rl = wg * 64 + w4 * 16 + (lane >> 2);
        const float om0 = 1.f - sGate[rl], om1 = 1.f - sGate[rl + 8];
        bf16* frow0 = g_a2 + (size_t)(rb * 128 + rl) * KA2 + D_ + n0;
        bf16* frow1 = frow0 + 8 * KA2;
        auto ffn_chunk = [&](int u) {
            uint32_t w0[4], w1[4];
#pragma unroll
            for (int i = 0; i < 4; i++) {
                const int t = u * 4 + i;
                if (t < 22) {
                    const uint32_t bv = sBias[t * 4 + q];
                    const float bb0 = bf_lo(bv), bb1 = bf_hi(bv);
                    w0[i] = pack_bf16(mish_f(accF[t * 4 + 0] + bb0) * om0, mish_f(accF[t * 4 + 1] + bb1) * om0);
                    w1[i] = pack_bf16(mish_f(accF[t * 4 + 2] + bb0) * om1, mish_f(accF[t * 4 + 3] + bb1) * om1);
                } else { w0[i] = 0; w1[i] = 0; }
            }
            quad_transpose(w0, q);
            quad_transpose(w1, q);
            const int c = (u * 4 + q) * 8;
            if (c < FCH && n0 + c < F_) {
                *(uint4*)(frow0 + c) = make_uint4(w0[0], w0[1], w0[2], w0[3]);
                *(uint4*)(frow1 + c) = make_uint4(w1[0], w1[1], w1[2], w1[3]);
            }
        };
#pragma unroll
        for (int kc = 0; kc < 8; kc++) {
            const int st = kc & 3;
            mbar_wait(b_full + 8 * st, ((kc + 8) >> 2) & 1);
            wgmma_fence();
#pragma unroll
            for (int k16 = 0; k16 < 4; k16++) {
                wgmma_n192<1>(accQ, da0 + (kc * 1024 + k16 * 2), db0 + (st * (K1_BSTAGE >> 4) + k16 * 128), (kc | k16) != 0);
            }
            wgmma_commit();
            if (kc < 6) ffn_chunk(kc);
            if (kc > 0) { wgmma_wait<1>(); if (lane == 0) mbar_arrive(b_empty + 8 * ((kc - 1) & 3)); }
        }
        wgmma_wait<0>();
        TS(4, tid == 0);
        {
            bf16* orow0 = g_qkv + ((size_t)j * S_ + rb * 128 + rl) * 192;
            bf16* orow1 = orow0 + 8 * 192;
#pragma unroll
            for (int u = 0; u < 6; u++) {
                uint32_t w0[4], w1[4];
#pragma unroll
                for (int i = 0; i < 4; i++) {
                    const int t = u * 4 + i;
                    w0[i] = pack_bf16(accQ[t * 4 + 0], accQ[t * 4 + 1]);
                    w1[i] = pack_bf16(accQ[t * 4 + 2], accQ[t * 4 + 3]);
                }
                quad_transpose(w0, q);
                quad_transpose(w1, q);
                const int c = (u * 4 + q) * 8;
                *(uint4*)(orow0 + c) = make_uint4(w0[0], w0[1], w0[2], w0[3]);
                *(uint4*)(orow1 + c) = make_uint4(w1[0], w1[1], w1[2], w1[3]);
            }
        }
        TS(5, tid == 0);
    }
}

__device__ __forceinline__ void ldsm_x4(uint32_t (&r)[4], uint32_t addr) {
    asm("ldmatrix.sync.aligned.m8n8.x4.shared.b16 {%0,%1,%2,%3}, [%4];"
                 : "=r"(r[0]), "=r"(r[1]), "=r"(r[2]), "=r"(r[3]) : "r"(addr));
}
__device__ __forceinline__ void ldsm_x4_t(uint32_t (&r)[4], uint32_t addr) {
    asm("ldmatrix.sync.aligned.m8n8.x4.trans.shared.b16 {%0,%1,%2,%3}, [%4];"
                 : "=r"(r[0]), "=r"(r[1]), "=r"(r[2]), "=r"(r[3]) : "r"(addr));
}
__device__ __forceinline__ void mma16816(float (&d)[4], const uint32_t (&a)[4], uint32_t b0, uint32_t b1) {
    asm("mma.sync.aligned.m16n8k16.row.col.f32.bf16.bf16.f32 {%0,%1,%2,%3}, {%4,%5,%6,%7}, {%8,%9}, {%0,%1,%2,%3};"
                 : "+f"(d[0]), "+f"(d[1]), "+f"(d[2]), "+f"(d[3])
                 : "r"(a[0]), "r"(a[1]), "r"(a[2]), "r"(a[3]), "r"(b0), "r"(b1));
}
__device__ __forceinline__ void mma16816_z(float (&d)[4], const uint32_t (&a)[4], uint32_t b0, uint32_t b1) {
    asm("mma.sync.aligned.m16n8k16.row.col.f32.bf16.bf16.f32 {%0,%1,%2,%3}, {%4,%5,%6,%7}, {%8,%9}, {%10,%10,%10,%10};"
                 : "=f"(d[0]), "=f"(d[1]), "=f"(d[2]), "=f"(d[3])
                 : "r"(a[0]), "r"(a[1]), "r"(a[2]), "r"(a[3]), "r"(b0), "r"(b1), "f"(0.f));
}

constexpr int KV_PITCH = 128;

template <int EDGE, bool HEAD>
__device__ __forceinline__ void blk_scores(float (&s)[2][4], const uint32_t (&qa)[4], uint32_t kaddr, bool dead, int r0, int c0)
{
    uint32_t kf[4];
    ldsm_x4(kf, kaddr);
    mma16816_z(s[0], qa, kf[0], kf[1]);
    mma16816_z(s[1], qa, kf[2], kf[3]);
#pragma unroll
    for (int t = 0; t < 2; t++)
#pragma unroll
        for (int e = 0; e < 4; e++) {
            const int r = r0 + (e >> 1) * 8, c = t * 8 + c0 + (e & 1);
            if (EDGE == 1 && c <= r) s[t][e] = -1e30f;
            if (EDGE == 2 && c > r) s[t][e] = -1e30f;
            if (HEAD && dead) s[t][e] = -1e30f;
        }
}
__device__ __forceinline__ void blk_max(const float (&s)[2][4], float& n0, float& n1) {
    n0 = fmaxf(n0, fmaxf(fmaxf(s[0][0], s[0][1]), fmaxf(s[1][0], s[1][1])));
    n1 = fmaxf(n1, fmaxf(fmaxf(s[0][2], s[0][3]), fmaxf(s[1][2], s[1][3])));
}
__device__ __forceinline__ void blk_pv(const float (&s)[2][4], float mc0, float mc1, float (&l)[4],
                                       float (&o)[2][4], uint32_t vaddr) {
    const float C = 0.25f * 1.4426950408889634f;
    uint32_t pa[4];
#pragma unroll
    for (int t = 0; t < 2; t++) {
        const float p0 = ex2(fmaf(s[t][0], C, -mc0)), p1 = ex2(fmaf(s[t][1], C, -mc0));
        const float p2 = ex2(fmaf(s[t][2], C, -mc1)), p3 = ex2(fmaf(s[t][3], C, -mc1));
        pa[2 * t] = pack_bf16(p0, p1); pa[2 * t + 1] = pack_bf16(p2, p3);
    }
    uint32_t vf[4];
    ldsm_x4_t(vf, vaddr);
    mma16816(o[0], pa, vf[0], vf[1]);
    mma16816(o[1], pa, vf[2], vf[3]);
    mma16816(l, pa, 0x3F803F80u, 0x3F803F80u);
}
__device__ __forceinline__ void quad_max(float& n0, float& n1) {
    n0 = fmaxf(n0, __shfl_xor_sync(0xffffffffu, n0, 1)); n1 = fmaxf(n1, __shfl_xor_sync(0xffffffffu, n1, 1));
    n0 = fmaxf(n0, __shfl_xor_sync(0xffffffffu, n0, 2)); n1 = fmaxf(n1, __shfl_xor_sync(0xffffffffu, n1, 2));
}
template <int NC, int NN, bool FIRST, bool NEXT_IS_EDGE, bool HEAD>
__device__ __forceinline__ void pipe_step(const float (&sc)[5][2][4], float (&sn)[5][2][4], const uint32_t (&qa)[4],
                                          uint32_t ka, uint32_t va, int kc, int kn, int kb0, int r0, int c0,
                                          float& m0, float& m1, float& n0, float& n1, float (&l)[4], float (&o)[2][4])
{
    const float C = 0.25f * 1.4426950408889634f;
    const float mc0 = n0 * C, mc1 = n1 * C;
    if (!FIRST) {
        const float a0 = ex2(fmaf(m0, C, -mc0)), a1 = ex2(fmaf(m1, C, -mc1));
        l[0] *= a0; l[2] *= a1;
        o[0][0] *= a0; o[0][1] *= a0; o[1][0] *= a0; o[1][1] *= a0;
        o[0][2] *= a1; o[0][3] *= a1; o[1][2] *= a1; o[1][3] *= a1;
    }
    m0 = n0; m1 = n1;
#pragma unroll
    for (int b = 0; b < NC; b++) {
        if (b < NN) {
            if (NEXT_IS_EDGE && b == 0) blk_scores<1, HEAD>(sn[b], qa, ka + (kn + b) * 16 * KV_PITCH, kn + b < kb0, r0, c0);
            else                        blk_scores<0, HEAD>(sn[b], qa, ka + (kn + b) * 16 * KV_PITCH, kn + b < kb0, r0, c0);
        }
        blk_pv(sc[b], mc0, mc1, l, o, va + (kc + b) * 16 * KV_PITCH);
        if (b < NN) blk_max(sn[b], n0, n1);
    }
    if (NN > 0) quad_max(n0, n1);
}

__device__ __forceinline__ void kv_need(uint32_t kvbar, int blk, uint32_t& ka, uint32_t& va) {
    mbar_wait(kvbar + 8 * blk, 0);
    asm volatile("" : "+r"(ka), "+r"(va) :: "memory");
}
template <bool HEAD>
__device__ __forceinline__ void attn_task(const uint32_t (&qa)[4], uint32_t ka, uint32_t va, int kb0, int lane, int qt, uint32_t kvbar,
                                          bf16* __restrict__ out  , float g0, float g1)
{
    const int r0 = lane >> 2, c0 = (lane & 3) * 2;
    float m0 = -1e30f, m1 = -1e30f, n0 = -1e30f, n1 = -1e30f;
    float l[4] = {0.f, 0.f, 0.f, 0.f};
    float o[2][4] = {{0.f, 0.f, 0.f, 0.f}, {0.f, 0.f, 0.f, 0.f}};
    float sa[5][2][4], sb[5][2][4];
    kv_need(kvbar, 2, ka, va);
    if (qt < 4) kv_need(kvbar, 1, ka, va);
#pragma unroll
    for (int b = 0; b < 5; b++) {
        if (b == 4) blk_scores<2, HEAD>(sa[b], qa, ka + (12 + b) * 16 * KV_PITCH, false, r0, c0);
        else        blk_scores<0, HEAD>(sa[b], qa, ka + (12 + b) * 16 * KV_PITCH, 12 + b < kb0, r0, c0);
        blk_max(sa[b], n0, n1);
    }
    quad_max(n0, n1);
    kv_need(kvbar, 1, ka, va);
    if (HEAD) {
        pipe_step<5, 0, true, false, HEAD>(sa, sb, qa, ka, va, 12, 0, kb0, r0, c0, m0, m1, n0, n1, l, o);
        kv_need(kvbar, 0, ka, va);
#pragma unroll 1
        for (int kc = 8; kc >= 0 && kb0 < kc + 4; kc -= 4) {
#pragma unroll
            for (int b = 0; b < 4; b++) {
                blk_scores<0, HEAD>(sa[b], qa, ka + (kc + b) * 16 * KV_PITCH, kc + b < kb0, r0, c0);
                blk_max(sa[b], n0, n1);
            }
            quad_max(n0, n1);
            pipe_step<4, 0, false, false, HEAD>(sa, sb, qa, ka, va, kc, 0, kb0, r0, c0, m0, m1, n0, n1, l, o);
        }
    } else {
        pipe_step<5, 4, true,  false, HEAD>(sa, sb, qa, ka, va, 12, 8, kb0, r0, c0, m0, m1, n0, n1, l, o);
        if (qt < 4) kv_need(kvbar, 0, ka, va);
        pipe_step<4, 4, false, false, HEAD>(sb, sa, qa, ka, va, 8, 4, kb0, r0, c0, m0, m1, n0, n1, l, o);
        kv_need(kvbar, 0, ka, va);
        pipe_step<4, 4, false, true,  HEAD>(sa, sb, qa, ka, va, 4, 0, kb0, r0, c0, m0, m1, n0, n1, l, o);
        pipe_step<4, 0, false, false, HEAD>(sb, sa, qa, ka, va, 0, 0, kb0, r0, c0, m0, m1, n0, n1, l, o);
    }
    const float f0 = __fdividef(g0, l[0]), f1 = __fdividef(g1, l[2]);
#pragma unroll
    for (int t = 0; t < 2; t++) {
        *(uint32_t*)(out + (size_t)r0 * KA2 + t * 8 + c0) = pack_bf16(o[t][0] * f0, o[t][1] * f0);
        *(uint32_t*)(out + (size_t)(r0 + 8) * KA2 + t * 8 + c0) = pack_bf16(o[t][2] * f1, o[t][3] * f1);
    }
}

__device__ unsigned int g_epoch;
__device__ unsigned int g_done;
__device__ unsigned int g_flag_att[128];

constexpr int G_STAGES = 8;
constexpr int G_PRE = 5;
constexpr int G_STAGE = 16384 + 8192;
constexpr int G_KSTEPS = 30;
constexpr int K23_OFF_KV = G_PRE * G_STAGE;
constexpr int K23_OFF_BAR = K23_OFF_KV + 2 * 384 * KV_PITCH;
constexpr int K23_SMEM = K23_OFF_BAR + 256 + 1024;

__global__ void __launch_bounds__(512, 1)
k23_kernel(const __grid_constant__ CUtensorMap tmQKV, const __grid_constant__ CUtensorMap tmA2,
           const __grid_constant__ CUtensorMap tmWo, const __grid_constant__ CUtensorMap tmW2, bf16* __restrict__ out)
{
    extern __shared__ uint8_t smem_raw[];
    const uint32_t sbase = (smem_u32(smem_raw) + 1023u) & ~1023u;
    uint8_t* sgen = smem_raw + (sbase - smem_u32(smem_raw));
    const uint32_t sK = sbase + K23_OFF_KV, sV = sK + 384 * KV_PITCH;
    const uint32_t sBar = sbase + K23_OFF_BAR;
    const uint32_t full = sBar, empty = sBar + 80, kv_full = sBar + 160;
    const int rb = blockIdx.x >> 3, j = blockIdx.x & 7;
    const int tid = threadIdx.x, lane = tid & 31;
    const int warp = __shfl_sync(0xffffffffu, tid >> 5, 0), wg = warp >> 2;

    auto gload = [&](int ks) {
        const int st = ks % G_STAGES;
        mbar_expect_tx(full + 8 * st, G_STAGE);
        const uint32_t dst = sbase + st * G_STAGE;
        if (ks < 22) {
            tma_load_2d(dst, &tmA2, D_ + ks * 64, rb * 128, full + 8 * st);
            tma_load_2d(dst + 16384, &tmW2, j * 64, ks * 64, full + 8 * st);
        } else {
            tma_load_2d(dst, &tmA2, (ks - 22) * 64, rb * 128, full + 8 * st);
            tma_load_2d(dst + 16384, &tmWo, j * 64, (ks - 22) * 64, full + 8 * st);
        }
    };

    if (tid == 0) {
        for (int i = 0; i < 3; i++) mbar_init(kv_full + 8 * i, 1);
        for (int i = 0; i < G_STAGES; i++) { mbar_init(full + 8 * i, 1); mbar_init(empty + 8 * i, 8); }
        fence_barrier_init();
    }
    pdl_wait();
    TS(6, tid == 0);
    const unsigned int ep = *(volatile unsigned int*)&g_epoch + 1;
    if (tid == 0) {
        for (int i = 0; i < 3; i++) {
            const uint32_t bar = kv_full + 8 * (2 - i);
            if (rb - i >= 0) {
                const int row = j * S_ + (rb - i) * 128;
                mbar_expect_tx(bar, 2 * 16384);
                tma_load_2d(sK + (2 - i) * 16384, &tmQKV, 64, row, bar);
                tma_load_2d(sV + (2 - i) * 16384, &tmQKV, 128, row, bar);
            } else {
                mbar_arrive(bar);
            }
        }
        for (int ks = 0; ks < G_PRE; ks++) gload(ks);
    }
    if (rb < 2) {
        for (int i = tid; i < (2 - rb) * 1024; i += 512) {
            *(uint4*)(sgen + K23_OFF_KV + i * 16) = make_uint4(0, 0, 0, 0);
            *(uint4*)(sgen + K23_OFF_KV + 384 * KV_PITCH + i * 16) = make_uint4(0, 0, 0, 0);
        }
    }
    {
        const int qt = warp & 7, h0 = (warp >> 3) * 2;
        const int q0g = rb * 128 + qt * 16;
        const int r0 = lane >> 2, c0 = (lane & 3) * 2;
        const bf16* qsrc = g_qkv + ((size_t)j * S_ + q0g) * 192 + h0 * 16;
        uint32_t qa[4], qn[4];
        qa[0] = *(const uint32_t*)(qsrc + (size_t)r0 * 192 + c0);
        qa[1] = *(const uint32_t*)(qsrc + (size_t)(r0 + 8) * 192 + c0);
        qa[2] = *(const uint32_t*)(qsrc + (size_t)r0 * 192 + c0 + 8);
        qa[3] = *(const uint32_t*)(qsrc + (size_t)(r0 + 8) * 192 + c0 + 8);
        qn[0] = *(const uint32_t*)(qsrc + (size_t)r0 * 192 + 16 + c0);
        qn[1] = *(const uint32_t*)(qsrc + (size_t)(r0 + 8) * 192 + 16 + c0);
        qn[2] = *(const uint32_t*)(qsrc + (size_t)r0 * 192 + 16 + c0 + 8);
        qn[3] = *(const uint32_t*)(qsrc + (size_t)(r0 + 8) * 192 + 16 + c0 + 8);
        const float g0 = g_gate[q0g + r0], g1 = g_gate[q0g + r0 + 8];
        const int kb0 = q0g < 256 ? (256 - q0g) >> 4 : 0;
        __syncthreads();
        TS(7, tid == 0);
        const int krow = qt * 16 + (lane & 7) + ((lane >> 4) << 3);
        const int vrow = qt * 16 + (lane & 15);
#pragma unroll 1
        for (int hh = 0; hh < 2; hh++) {
            const int hl = h0 + hh;
            const uint32_t ka = sK + krow * KV_PITCH + (((2 * hl + ((lane >> 3) & 1)) ^ (lane & 7)) << 4);
            const uint32_t va = sV + vrow * KV_PITCH + (((2 * hl + (lane >> 4)) ^ (lane & 7)) << 4);
            if (rb < 2) attn_task<true>(qa, ka, va, kb0, lane, qt, kv_full, g_a2 + (size_t)q0g * KA2 + (j * 4 + hl) * 16, g0, g1);
            else        attn_task<false>(qa, ka, va, kb0, lane, qt, kv_full, g_a2 + (size_t)q0g * KA2 + (j * 4 + hl) * 16, g0, g1);
            TS(8 + hh, tid == 0);
            qa[0] = qn[0]; qa[1] = qn[1]; qa[2] = qn[2]; qa[3] = qn[3];
        }
    }
    __syncthreads();
    if (wg >= 2) {
        if (tid == 288) {
            __threadfence();
            asm volatile("st.release.gpu.global.u32 [%0], %1;" :: "l"(&g_flag_att[blockIdx.x]), "r"(ep) : "memory");
        }
        if (tid == 256) {
            asm volatile("fence.proxy.async;" ::: "memory");
            for (int ks = G_PRE; ks < G_KSTEPS; ks++) {
                if (ks >= G_STAGES) mbar_wait(empty + 8 * (ks % G_STAGES), ((ks / G_STAGES) - 1) & 1);
                if (ks == 22) {
                    for (int i = 0; i < 8; i++) {
                        for (uint32_t it = 0; it < (1u << 22); ++it) {
                            unsigned int x;
                            asm volatile("ld.acquire.gpu.global.u32 %0, [%1];" : "=r"(x) : "l"(&g_flag_att[rb * 8 + i]) : "memory");
                            if (x == ep) break;
                        }
                    }
                    asm volatile("fence.proxy.async;" ::: "memory");
                }
                gload(ks);
            }
        }
    } else {
        TS(10, tid == 0);
        float acc[32];
        const uint64_t da0 = make_desc(sbase + wg * 8192, 16, 1024);
        const uint64_t db0 = make_desc(sbase + 16384, 8192, 1024);
#pragma unroll 1
        for (int r = 0; r < 4; r++) {
#pragma unroll
            for (int st = 0; st < G_STAGES; st++) {
                if (r * G_STAGES + st < G_KSTEPS) {
                    mbar_wait(full + 8 * st, r & 1);
                    TS(11, tid == 0 && r == 0 && st == 0); TS(12, tid == 0 && r == 1 && st == 0); TS(13, tid == 0 && r == 2 && st == 6);
                    wgmma_fence();
#pragma unroll
                    for (int k16 = 0; k16 < 4; k16++)
                        wgmma_n64<1>(acc, da0 + (st * (G_STAGE >> 4) + k16 * 2), db0 + (st * (G_STAGE >> 4) + k16 * 128), (r | st | k16) != 0);
                    wgmma_commit();
                    if (r | st) { wgmma_wait<1>(); if (lane == 0) mbar_arrive(empty + 8 * ((st + G_STAGES - 1) % G_STAGES)); }
                }
            }
        }
        wgmma_wait<0>();
        TS(14, tid == 0);
        const int q = lane & 3;
        const int r = rb * 128 + wg * 64 + (warp & 3) * 16 + (lane >> 2);
        bf16* orow0 = out + (size_t)r * D_ + j * 64;
        bf16* orow1 = orow0 + 8 * D_;
#pragma unroll
        for (int u = 0; u < 2; u++) {
            uint32_t w0[4], w1[4];
#pragma unroll
            for (int i = 0; i < 4; i++) {
                const int t = u * 4 + i;
                w0[i] = pack_bf16(acc[t * 4 + 0], acc[t * 4 + 1]);
                w1[i] = pack_bf16(acc[t * 4 + 2], acc[t * 4 + 3]);
            }
            quad_transpose(w0, q);
            quad_transpose(w1, q);
            const int c = (u * 4 + q) * 8;
            *(uint4*)(orow0 + c) = make_uint4(w0[0], w0[1], w0[2], w0[3]);
            *(uint4*)(orow1 + c) = make_uint4(w1[0], w1[1], w1[2], w1[3]);
        }
        TS(15, tid == 0);
        if (tid == 0) {
            __threadfence();
            if (atomicAdd(&g_done, 1u) == gridDim.x - 1) {
                g_done = 0;
                __threadfence();
                atomicAdd(&g_epoch, 1u);
            }
        }
    }
}

typedef CUresult (*PFN_encodeTiled)(CUtensorMap*, CUtensorMapDataType, cuuint32_t, void*, const cuuint64_t*,
                                    const cuuint64_t*, const cuuint32_t*, const cuuint32_t*, CUtensorMapInterleave,
                                    CUtensorMapSwizzle, CUtensorMapL2promotion, CUtensorMapFloatOOBfill);

static void make_map(PFN_encodeTiled enc, CUtensorMap* m, const void* ptr, uint64_t cols, uint64_t rows,
                     uint32_t box_cols, uint32_t box_rows)
{
    cuuint64_t dims[2] = {cols, rows};
    cuuint64_t strides[1] = {cols * 2};
    cuuint32_t box[2] = {box_cols, box_rows};
    cuuint32_t es[2] = {1, 1};
    enc(m, CU_TENSOR_MAP_DATA_TYPE_BFLOAT16, 2, const_cast<void*>(ptr), dims, strides, box, es,
        CU_TENSOR_MAP_INTERLEAVE_NONE, CU_TENSOR_MAP_SWIZZLE_128B, CU_TENSOR_MAP_L2_PROMOTION_L2_128B,
        CU_TENSOR_MAP_FLOAT_OOB_FILL_NONE);
}

extern "C" void kernel_launch(void* const* d_in, const int* in_sizes, int n_in, void* d_out, int out_size)
{
    const bf16* x    = (const bf16*)d_in[0];
    const bf16* wqkv = (const bf16*)d_in[1];
    const bf16* wo   = (const bf16*)d_in[2];
    const bf16* w1   = (const bf16*)d_in[4];
    const bf16* b1   = (const bf16*)d_in[5];
    const bf16* w2   = (const bf16*)d_in[6];
    const bf16* gw   = (const bf16*)d_in[7];

    static PFN_encodeTiled enc = nullptr;
    if (!enc) {
        void* fn = nullptr;
        cudaDriverEntryPointQueryResult qr;
        cudaGetDriverEntryPoint("cuTensorMapEncodeTiled", &fn, cudaEnableDefault, &qr);
        enc = (PFN_encodeTiled)fn;
        cudaFuncSetAttribute(k1_kernel, cudaFuncAttributeMaxDynamicSharedMemorySize, K1_SMEM);
        cudaFuncSetAttribute(k23_kernel, cudaFuncAttributeMaxDynamicSharedMemorySize, K23_SMEM);
    }
    void* a2p = nullptr;
    cudaGetSymbolAddress(&a2p, g_a2);
    void* qkvp = nullptr;
    cudaGetSymbolAddress(&qkvp, g_qkv);
    CUtensorMap tmX, tmWqkv, tmW1, tmA2, tmWo, tmW2, tmQKV;
    make_map(enc, &tmQKV, qkvp, 192, 8 * S_, 64, 128);
    make_map(enc, &tmX, x, D_, S_, 64, 128);
    make_map(enc, &tmWqkv, wqkv, 3 * D_, D_, 64, 64);
    make_map(enc, &tmW1, w1, F_, D_, 64, 64);
    make_map(enc, &tmA2, a2p, KA2, S_, 64, 128);
    make_map(enc, &tmWo, wo, D_, D_, 64, 64);
    make_map(enc, &tmW2, w2, D_, F_, 64, 64);

    cudaStream_t st = cudaStreamPerThread;
    k1_kernel<<<128, 384, K1_SMEM, st>>>(tmX, tmWqkv, tmW1, b1, gw, w1, wqkv, w2, wo);
    cudaLaunchAttribute at[1];
    at[0].id = cudaLaunchAttributeProgrammaticStreamSerialization;
    at[0].val.programmaticStreamSerializationAllowed = 1;
    cudaLaunchConfig_t cfg = {};
    cfg.gridDim = dim3(128); cfg.stream = st; cfg.attrs = at; cfg.numAttrs = 1;
    cfg.blockDim = dim3(512); cfg.dynamicSmemBytes = K23_SMEM;
    k23_kernel<<<128, 512, K23_SMEM, st>>>(tmQKV, tmA2, tmWo, tmW2, (bf16*)d_out);
}
```

```cpp
#include <cuda_runtime.h>
#include <cuda_bf16.h>
#include <cuda.h>
#include <stdint.h>

typedef __nv_bfloat16 bf16;

constexpr int S_ = 2048, D_ = 512, F_ = 1376;
constexpr int KA2 = D_ + F_;
constexpr int FCH = 176;

__device__ bf16  g_qkv[8 * S_ * 192];
__device__ bf16  g_a2[S_ * KA2];
__device__ float g_gate[S_];

#define TS(k, cond) do { } while (0)

__device__ __forceinline__ uint32_t smem_u32(const void* p) { return (uint32_t)__cvta_generic_to_shared(p); }
__device__ __forceinline__ void mbar_init(uint32_t bar, uint32_t count) {
    asm volatile("mbarrier.init.shared::cta.b64 [%0], %1;" :: "r"(bar), "r"(count) : "memory");
}
__device__ __forceinline__ void mbar_expect_tx(uint32_t bar, uint32_t bytes) {
    asm volatile("mbarrier.arrive.expect_tx.shared::cta.b64 _, [%0], %1;" :: "r"(bar), "r"(bytes) : "memory");
}
__device__ __forceinline__ void mbar_arrive(uint32_t bar) {
    asm volatile("mbarrier.arrive.shared::cta.b64 _, [%0];" :: "r"(bar) : "memory");
}
__device__ __forceinline__ bool mbar_try_wait(uint32_t bar, uint32_t parity) {
    uint32_t ok;
    asm volatile("{\n.reg .pred p;\nmbarrier.try_wait.parity.shared::cta.b64 p, [%1], %2;\nselp.u32 %0, 1, 0, p;\n}"
                 : "=r"(ok) : "r"(bar), "r"(parity) : "memory");
    return ok != 0;
}
__device__ __forceinline__ void mbar_wait(uint32_t bar, uint32_t parity) {
    for (uint32_t it = 0; it < (1u << 22); ++it) { if (mbar_try_wait(bar, parity)) break; }
}
__device__ __forceinline__ void tma_load_2d(uint32_t dst, const CUtensorMap* map, int c0, int c1, uint32_t bar) {
    asm volatile("cp.async.bulk.tensor.2d.shared::cluster.global.mbarrier::complete_tx::bytes [%0], [%1, {%3, %4}], [%2];"
                 :: "r"(dst), "l"(map), "r"(bar), "r"(c0), "r"(c1) : "memory");
}
__device__ __forceinline__ void l2_prefetch(const void* p, uint32_t bytes) {
    asm volatile("cp.async.bulk.prefetch.L2.global [%0], %1;" :: "l"(p), "r"(bytes) : "memory");
}
__device__ __forceinline__ void fence_barrier_init() { asm volatile("fence.mbarrier_init.release.cluster;" ::: "memory"); }
__device__ __forceinline__ void wgmma_fence()  { asm volatile("wgmma.fence.sync.aligned;" ::: "memory"); }
__device__ __forceinline__ void wgmma_commit() { asm volatile("wgmma.commit_group.sync.aligned;" ::: "memory"); }
template <int N> __device__ __forceinline__ void wgmma_wait() { asm volatile("wgmma.wait_group.sync.aligned %0;" :: "n"(N) : "memory"); }
template <int R> __device__ __forceinline__ void reg_alloc()   { asm volatile("setmaxnreg.inc.sync.aligned.u32 %0;" :: "n"(R)); }
template <int R> __device__ __forceinline__ void reg_dealloc() { asm volatile("setmaxnreg.dec.sync.aligned.u32 %0;" :: "n"(R)); }
__device__ __forceinline__ void bar_sync(int id, int n)   { asm volatile("bar.sync %0, %1;" :: "r"(id), "r"(n) : "memory"); }
__device__ __forceinline__ void bar_arrive(int id, int n) { asm volatile("bar.arrive %0, %1;" :: "r"(id), "r"(n) : "memory"); }

__device__ __forceinline__ uint64_t make_desc(uint32_t addr, uint32_t lbo, uint32_t sbo) {
    uint64_t d = (uint64_t)((addr & 0x3FFFF) >> 4);
    d |= (uint64_t)((lbo & 0x3FFFF) >> 4) << 16;
    d |= (uint64_t)((sbo & 0x3FFFF) >> 4) << 32;
    d |= (uint64_t)1 << 62;
    return d;
}

template <int TB>
__device__ __forceinline__ void wgmma_n64(float (&d)[32], uint64_t da, uint64_t db, int scale_d) {
    asm volatile("{\n.reg .pred p;\nsetp.ne.b32 p, %34, 0;\n"
        "wgmma.mma_async.sync.aligned.m64n64k16.f32.bf16.bf16 {%0, %1, %2, %3, %4, %5, %6, %7, %8, %9, %10, %11, %12, %13, %14, %15, %16, %17, %18, %19, %20, %21, %22, %23, %24, %25, %26, %27, %28, %29, %30, %31}, %32, %33, p, 1, 1, 0, %35;\n}\n"
        : "+f"(d[0]), "+f"(d[1]), "+f"(d[2]), "+f"(d[3]), "+f"(d[4]), "+f"(d[5]), "+f"(d[6]), "+f"(d[7]), "+f"(d[8]), "+f"(d[9]), "+f"(d[10]), "+f"(d[11]), "+f"(d[12]), "+f"(d[13]), "+f"(d[14]), "+f"(d[15]), "+f"(d[16]), "+f"(d[17]), "+f"(d[18]), "+f"(d[19]), "+f"(d[20]), "+f"(d[21]), "+f"(d[22]), "+f"(d[23]), "+f"(d[24]), "+f"(d[25]), "+f"(d[26]), "+f"(d[27]), "+f"(d[28]), "+f"(d[29]), "+f"(d[30]), "+f"(d[31])
        : "l"(da), "l"(db), "r"(scale_d), "n"(TB));
}

template <int TB>
__device__ __forceinline__ void wgmma_n128(float (&d)[64], uint64_t da, uint64_t db, int scale_d) {
    asm volatile("{\n.reg .pred p;\nsetp.ne.b32 p, %66, 0;\n"
        "wgmma.mma_async.sync.aligned.m64n128k16.f32.bf16.bf16 {%0, %1, %2, %3, %4, %5, %6, %7, %8, %9, %10, %11, %12, %13, %14, %15, %16, %17, %18, %19, %20, %21, %22, %23, %24, %25, %26, %27, %28, %29, %30, %31, %32, %33, %34, %35, %36, %37, %38, %39, %40, %41, %42, %43, %44, %45, %46, %47, %48, %49, %50, %51, %52, %53, %54, %55, %56, %57, %58, %59, %60, %61, %62, %63}, %64, %65, p, 1, 1, 0, %67;\n}\n"
        : "+f"(d[0]), "+f"(d[1]), "+f"(d[2]), "+f"(d[3]), "+f"(d[4]), "+f"(d[5]), "+f"(d[6]), "+f"(d[7]), "+f"(d[8]), "+f"(d[9]), "+f"(d[10]), "+f"(d[11]), "+f"(d[12]), "+f"(d[13]), "+f"(d[14]), "+f"(d[15]), "+f"(d[16]), "+f"(d[17]), "+f"(d[18]), "+f"(d[19]), "+f"(d[20]), "+f"(d[21]), "+f"(d[22]), "+f"(d[23]), "+f"(d[24]), "+f"(d[25]), "+f"(d[26]), "+f"(d[27]), "+f"(d[28]), "+f"(d[29]), "+f"(d[30]), "+f"(d[31]), "+f"(d[32]), "+f"(d[33]), "+f"(d[34]), "+f"(d[35]), "+f"(d[36]), "+f"(d[37]), "+f"(d[38]), "+f"(d[39]), "+f"(d[40]), "+f"(d[41]), "+f"(d[42]), "+f"(d[43]), "+f"(d[44]), "+f"(d[45]), "+f"(d[46]), "+f"(d[47]), "+f"(d[48]), "+f"(d[49]), "+f"(d[50]), "+f"(d[51]), "+f"(d[52]), "+f"(d[53]), "+f"(d[54]), "+f"(d[55]), "+f"(d[56]), "+f"(d[57]), "+f"(d[58]), "+f"(d[59]), "+f"(d[60]), "+f"(d[61]), "+f"(d[62]), "+f"(d[63])
        : "l"(da), "l"(db), "r"(scale_d), "n"(TB));
}

template <int TB>
__device__ __forceinline__ void wgmma_n176(float (&d)[88], uint64_t da, uint64_t db, int scale_d) {
    asm volatile("{\n.reg .pred p;\nsetp.ne.b32 p, %90, 0;\n"
        "wgmma.mma_async.sync.aligned.m64n176k16.f32.bf16.bf16 {%0, %1, %2, %3, %4, %5, %6, %7, %8, %9, %10, %11, %12, %13, %14, %15, %16, %17, %18, %19, %20, %21, %22, %23, %24, %25, %26, %27, %28, %29, %30, %31, %32, %33, %34, %35, %36, %37, %38, %39, %40, %41, %42, %43, %44, %45, %46, %47, %48, %49, %50, %51, %52, %53, %54, %55, %56, %57, %58, %59, %60, %61, %62, %63, %64, %65, %66, %67, %68, %69, %70, %71, %72, %73, %74, %75, %76, %77, %78, %79, %80, %81, %82, %83, %84, %85, %86, %87}, %88, %89, p, 1, 1, 0, %91;\n}\n"
        : "+f"(d[0]), "+f"(d[1]), "+f"(d[2]), "+f"(d[3]), "+f"(d[4]), "+f"(d[5]), "+f"(d[6]), "+f"(d[7]), "+f"(d[8]), "+f"(d[9]), "+f"(d[10]), "+f"(d[11]), "+f"(d[12]), "+f"(d[13]), "+f"(d[14]), "+f"(d[15]), "+f"(d[16]), "+f"(d[17]), "+f"(d[18]), "+f"(d[19]), "+f"(d[20]), "+f"(d[21]), "+f"(d[22]), "+f"(d[23]), "+f"(d[24]), "+f"(d[25]), "+f"(d[26]), "+f"(d[27]), "+f"(d[28]), "+f"(d[29]), "+f"(d[30]), "+f"(d[31]), "+f"(d[32]), "+f"(d[33]), "+f"(d[34]), "+f"(d[35]), "+f"(d[36]), "+f"(d[37]), "+f"(d[38]), "+f"(d[39]), "+f"(d[40]), "+f"(d[41]), "+f"(d[42]), "+f"(d[43]), "+f"(d[44]), "+f"(d[45]), "+f"(d[46]), "+f"(d[47]), "+f"(d[48]), "+f"(d[49]), "+f"(d[50]), "+f"(d[51]), "+f"(d[52]), "+f"(d[53]), "+f"(d[54]), "+f"(d[55]), "+f"(d[56]), "+f"(d[57]), "+f"(d[58]), "+f"(d[59]), "+f"(d[60]), "+f"(d[61]), "+f"(d[62]), "+f"(d[63]), "+f"(d[64]), "+f"(d[65]), "+f"(d[66]), "+f"(d[67]), "+f"(d[68]), "+f"(d[69]), "+f"(d[70]), "+f"(d[71]), "+f"(d[72]), "+f"(d[73]), "+f"(d[74]), "+f"(d[75]), "+f"(d[76]), "+f"(d[77]), "+f"(d[78]), "+f"(d[79]), "+f"(d[80]), "+f"(d[81]), "+f"(d[82]), "+f"(d[83]), "+f"(d[84]), "+f"(d[85]), "+f"(d[86]), "+f"(d[87])
        : "l"(da), "l"(db), "r"(scale_d), "n"(TB));
}

template <int TB>
__device__ __forceinline__ void wgmma_n192(float (&d)[96], uint64_t da, uint64_t db, int scale_d) {
    asm volatile("{\n.reg .pred p;\nsetp.ne.b32 p, %98, 0;\n"
        "wgmma.mma_async.sync.aligned.m64n192k16.f32.bf16.bf16 {%0, %1, %2, %3, %4, %5, %6, %7, %8, %9, %10, %11, %12, %13, %14, %15, %16, %17, %18, %19, %20, %21, %22, %23, %24, %25, %26, %27, %28, %29, %30, %31, %32, %33, %34, %35, %36, %37, %38, %39, %40, %41, %42, %43, %44, %45, %46, %47, %48, %49, %50, %51, %52, %53, %54, %55, %56, %57, %58, %59, %60, %61, %62, %63, %64, %65, %66, %67, %68, %69, %70, %71, %72, %73, %74, %75, %76, %77, %78, %79, %80, %81, %82, %83, %84, %85, %86, %87, %88, %89, %90, %91, %92, %93, %94, %95}, %96, %97, p, 1, 1, 0, %99;\n}\n"
        : "+f"(d[0]), "+f"(d[1]), "+f"(d[2]), "+f"(d[3]), "+f"(d[4]), "+f"(d[5]), "+f"(d[6]), "+f"(d[7]), "+f"(d[8]), "+f"(d[9]), "+f"(d[10]), "+f"(d[11]), "+f"(d[12]), "+f"(d[13]), "+f"(d[14]), "+f"(d[15]), "+f"(d[16]), "+f"(d[17]), "+f"(d[18]), "+f"(d[19]), "+f"(d[20]), "+f"(d[21]), "+f"(d[22]), "+f"(d[23]), "+f"(d[24]), "+f"(d[25]), "+f"(d[26]), "+f"(d[27]), "+f"(d[28]), "+f"(d[29]), "+f"(d[30]), "+f"(d[31]), "+f"(d[32]), "+f"(d[33]), "+f"(d[34]), "+f"(d[35]), "+f"(d[36]), "+f"(d[37]), "+f"(d[38]), "+f"(d[39]), "+f"(d[40]), "+f"(d[41]), "+f"(d[42]), "+f"(d[43]), "+f"(d[44]), "+f"(d[45]), "+f"(d[46]), "+f"(d[47]), "+f"(d[48]), "+f"(d[49]), "+f"(d[50]), "+f"(d[51]), "+f"(d[52]), "+f"(d[53]), "+f"(d[54]), "+f"(d[55]), "+f"(d[56]), "+f"(d[57]), "+f"(d[58]), "+f"(d[59]), "+f"(d[60]), "+f"(d[61]), "+f"(d[62]), "+f"(d[63]), "+f"(d[64]), "+f"(d[65]), "+f"(d[66]), "+f"(d[67]), "+f"(d[68]), "+f"(d[69]), "+f"(d[70]), "+f"(d[71]), "+f"(d[72]), "+f"(d[73]), "+f"(d[74]), "+f"(d[75]), "+f"(d[76]), "+f"(d[77]), "+f"(d[78]), "+f"(d[79]), "+f"(d[80]), "+f"(d[81]), "+f"(d[82]), "+f"(d[83]), "+f"(d[84]), "+f"(d[85]), "+f"(d[86]), "+f"(d[87]), "+f"(d[88]), "+f"(d[89]), "+f"(d[90]), "+f"(d[91]), "+f"(d[92]), "+f"(d[93]), "+f"(d[94]), "+f"(d[95])
        : "l"(da), "l"(db), "r"(scale_d), "n"(TB));
}

__device__ __forceinline__ uint32_t pack_bf16(float lo, float hi) {
    uint32_t r;
    asm("cvt.rn.bf16x2.f32 %0, %1, %2;" : "=r"(r) : "f"(hi), "f"(lo));
    return r;
}
__device__ __forceinline__ float bf_lo(uint32_t v) { return __uint_as_float(v << 16); }
__device__ __forceinline__ float bf_hi(uint32_t v) { return __uint_as_float(v & 0xffff0000u); }

__device__ __forceinline__ void quad_transpose(uint32_t (&w)[4], int q) {
    const bool o1 = q & 1, o2 = q & 2;
    {
        uint32_t s0 = o1 ? w[0] : w[1], s1 = o1 ? w[2] : w[3];
        s0 = __shfl_xor_sync(0xffffffffu, s0, 1); s1 = __shfl_xor_sync(0xffffffffu, s1, 1);
        if (o1) { w[0] = s0; w[2] = s1; } else { w[1] = s0; w[3] = s1; }
    }
    {
        uint32_t s0 = o2 ? w[0] : w[2], s1 = o2 ? w[1] : w[3];
        s0 = __shfl_xor_sync(0xffffffffu, s0, 2); s1 = __shfl_xor_sync(0xffffffffu, s1, 2);
        if (o2) { w[0] = s0; w[1] = s1; } else { w[2] = s0; w[3] = s1; }
    }
}

__device__ __forceinline__ float ex2(float x) { float y; asm("ex2.approx.ftz.f32 %0, %1;" : "=f"(y) : "f"(x)); return y; }
__device__ __forceinline__ float rcp(float x) { float y; asm("rcp.approx.ftz.f32 %0, %1;" : "=f"(y) : "f"(x)); return y; }

__device__ __forceinline__ float ex2v(float x) { float y; asm volatile("ex2.approx.ftz.f32 %0, %1;" : "=f"(y) : "f"(x)); return y; }
__device__ __forceinline__ float rcpv(float x) { float y; asm volatile("rcp.approx.ftz.f32 %0, %1;" : "=f"(y) : "f"(x)); return y; }
__device__ __forceinline__ float mish_f(float h) {
    const float e = ex2v(1.4426950408889634f * fminf(h, 20.f));
    const float n = fmaf(e, e, e + e);
    return h * n * rcpv(n + 2.f);
}

__device__ __forceinline__ void pdl_wait()   { asm volatile("griddepcontrol.wait;" ::: "memory"); }
__device__ __forceinline__ void pdl_launch() { asm volatile("griddepcontrol.launch_dependents;" ::: "memory"); }

constexpr int K1_STAGES = 4;
constexpr int K1_XBYTES = 128 * 512 * 2;
constexpr int K1_BSTAGE = 3 * 8192;
constexpr int K1_SMEM   = K1_XBYTES + K1_STAGES * K1_BSTAGE + 2048   + 1024  ;

__global__ void __launch_bounds__(384, 1)
k1_kernel(const __grid_constant__ CUtensorMap tmX, const __grid_constant__ CUtensorMap tmWqkv,
          const __grid_constant__ CUtensorMap tmW1, const bf16* __restrict__ b1,
          const bf16* __restrict__ gate_w, const bf16* __restrict__ w1p, const bf16* __restrict__ wqkvp,
          const bf16* __restrict__ w2p, const bf16* __restrict__ wop)
{

    extern __shared__ uint8_t smem_raw[];
    const uint32_t sbase = (smem_u32(smem_raw) + 1023u) & ~1023u;
    uint8_t* sgen = smem_raw + (sbase - smem_u32(smem_raw));
    const uint32_t sX = sbase;
    const uint32_t sB = sbase + K1_XBYTES;
    const uint32_t sBar = sB + K1_STAGES * K1_BSTAGE;
    const uint32_t x_full = sBar;
    const uint32_t b_full = sBar + 64;
    const uint32_t b_empty = sBar + 96;
    float* sGate = (float*)(sgen + K1_XBYTES + K1_STAGES * K1_BSTAGE + 128);
    uint8_t* sGw = sgen + K1_XBYTES + K1_STAGES * K1_BSTAGE + 640;
    uint32_t* sBias = (uint32_t*)(sgen + K1_XBYTES + K1_STAGES * K1_BSTAGE + 1664);

    const int rb = blockIdx.x >> 3, j = blockIdx.x & 7;
    const int tid = threadIdx.x, lane = tid & 31;
    const int warp = __shfl_sync(0xffffffffu, tid >> 5, 0), wg = warp >> 2;
    TS(0, tid == 0);
    pdl_launch();

    if (tid == 0) {
        for (int i = 0; i < 8; i++) mbar_init(x_full + 8 * i, 1);
        for (int i = 0; i < K1_STAGES; i++) { mbar_init(b_full + 8 * i, 1); mbar_init(b_empty + 8 * i, 8); }
        fence_barrier_init();
    }
    __syncthreads();

    if (wg == 2) {
        reg_dealloc<40>();
        if (tid == 288) {
            const int b = blockIdx.x;
            mbar_wait(b_full + 8, 0);
            l2_prefetch((const uint8_t*)wqkvp + b * 12288, 12288);
            l2_prefetch((const uint8_t*)w2p + b * 11008, 11008);
            l2_prefetch((const uint8_t*)wop + b * 4096, 4096);
        }
        if (tid == 256) {
            for (int it = 0; it < 16; it++) {
                if (it < 8) {
                    mbar_expect_tx(x_full + 8 * it, 16384);
                    tma_load_2d(sX + it * 16384, &tmX, it * 64, rb * 128, x_full + 8 * it);
                }
                const int st = it & 3;
                if (it >= K1_STAGES) mbar_wait(b_empty + 8 * st, ((it >> 2) - 1) & 1);
                mbar_expect_tx(b_full + 8 * st, K1_BSTAGE);
                const uint32_t dst = sB + st * K1_BSTAGE;
                if (it < 8) {
                    for (int b = 0; b < 3; b++) tma_load_2d(dst + b * 8192, &tmW1, j * FCH + b * 64, it * 64, b_full + 8 * st);
                } else {
                    for (int b = 0; b < 3; b++) tma_load_2d(dst + b * 8192, &tmWqkv, b * 512 + j * 64, (it - 8) * 64, b_full + 8 * st);
                }
            }
        }
    } else {
        reg_alloc<232>();
        if (tid < 64) ((uint4*)sGw)[tid] = __ldg((const uint4*)gate_w + tid);
        else if (tid < 64 + 88) {
            const int c = j * FCH + (tid - 64) * 2;
            sBias[tid - 64] = c < F_ ? __ldg((const uint32_t*)(b1 + c)) : 0u;
        }
        bar_sync(3, 256);
        const int t128 = tid & 127, w4 = warp & 3, q = lane & 3;
        float accF[88], accQ[96];
        const uint64_t da0 = make_desc(sX + wg * 8192, 16, 1024);
        const uint64_t db0 = make_desc(sB, 8192, 1024);
        float gs = 0.f;
        const int grow = wg * 64 + (t128 >> 1), ghalf = t128 & 1;
#pragma unroll
        for (int kc = 0; kc < 8; kc++) {
            const int st = kc & 3;
            mbar_wait(x_full + 8 * kc, 0);
            mbar_wait(b_full + 8 * st, (kc >> 2) & 1);
            TS(1, tid == 0 && kc == 0); TS(2, tid == 0 && kc == 4);
            wgmma_fence();
#pragma unroll
            for (int k16 = 0; k16 < 4; k16++) {
                wgmma_n176<1>(accF, da0 + (kc * 1024 + k16 * 2), db0 + (st * (K1_BSTAGE >> 4) + k16 * 128), (kc | k16) != 0);
            }
            wgmma_commit();
#pragma unroll
            for (int c = 0; c < 4; c++) {
                const int cc = ghalf * 4 + c;
                const uint4 xv = *(const uint4*)(sgen + kc * 16384 + grow * 128 + ((cc ^ (grow & 7)) << 4));
                const uint4 gv = *(const uint4*)(sGw + kc * 128 + cc * 16);
                gs = fmaf(bf_lo(xv.x), bf_lo(gv.x), gs); gs = fmaf(bf_hi(xv.x), bf_hi(gv.x), gs);
                gs = fmaf(bf_lo(xv.y), bf_lo(gv.y), gs); gs = fmaf(bf_hi(xv.y), bf_hi(gv.y), gs);
                gs = fmaf(bf_lo(xv.z), bf_lo(gv.z), gs); gs = fmaf(bf_hi(xv.z), bf_hi(gv.z), gs);
                gs = fmaf(bf_lo(xv.w), bf_lo(gv.w), gs); gs = fmaf(bf_hi(xv.w), bf_hi(gv.w), gs);
            }
            if (kc > 0) { wgmma_wait<1>(); if (lane == 0) mbar_arrive(b_empty + 8 * ((kc - 1) & 3)); }
        }
        gs += __shfl_xor_sync(0xffffffffu, gs, 1);
        {
            const float g = 1.f / (1.f + __expf(-gs));
            if (ghalf == 0) {
                sGate[grow] = g;
                if (j == 0) g_gate[rb * 128 + grow] = g;
            }
        }
        wgmma_wait<0>();
        if (lane == 0) mbar_arrive(b_empty + 8 * 3);
        bar_sync(1 + wg, 128);
        TS(3, tid == 0);
        const int n0 = j * FCH;
        const int rl = wg * 64 + w4 * 16 + (lane >> 2);
        const float om0 = 1.f - sGate[rl], om1 = 1.f - sGate[rl + 8];
        bf16* frow0 = g_a2 + (size_t)(rb * 128 + rl) * KA2 + D_ + n0;
        bf16* frow1 = frow0 + 8 * KA2;
        auto ffn_chunk = [&](int u) {
            uint32_t w0[4], w1[4];
#pragma unroll
            for (int i = 0; i < 4; i++) {
                const int t = u * 4 + i;
                if (t < 22) {
                    const uint32_t bv = sBias[t * 4 + q];
                    const float bb0 = bf_lo(bv), bb1 = bf_hi(bv);
                    w0[i] = pack_bf16(mish_f(accF[t * 4 + 0] + bb0) * om0, mish_f(accF[t * 4 + 1] + bb1) * om0);
                    w1[i] = pack_bf16(mish_f(accF[t * 4 + 2] + bb0) * om1, mish_f(accF[t * 4 + 3] + bb1) * om1);
                } else { w0[i] = 0; w1[i] = 0; }
            }
            quad_transpose(w0, q);
            quad_transpose(w1, q);
            const int c = (u * 4 + q) * 8;
            if (c < FCH && n0 + c < F_) {
                *(uint4*)(frow0 + c) = make_uint4(w0[0], w0[1], w0[2], w0[3]);
                *(uint4*)(frow1 + c) = make_uint4(w1[0], w1[1], w1[2], w1[3]);
            }
        };
#pragma unroll
        for (int kc = 0; kc < 8; kc++) {
            const int st = kc & 3;
            mbar_wait(b_full + 8 * st, ((kc + 8) >> 2) & 1);
            wgmma_fence();
#pragma unroll
            for (int k16 = 0; k16 < 4; k16++) {
                wgmma_n192<1>(accQ, da0 + (kc * 1024 + k16 * 2), db0 + (st * (K1_BSTAGE >> 4) + k16 * 128), (kc | k16) != 0);
            }
            wgmma_commit();
            if (kc < 6) ffn_chunk(kc);
            if (kc > 0) { wgmma_wait<1>(); if (lane == 0) mbar_arrive(b_empty + 8 * ((kc - 1) & 3)); }
        }
        wgmma_wait<0>();
        TS(4, tid == 0);
        {
            bf16* orow0 = g_qkv + ((size_t)j * S_ + rb * 128 + rl) * 192;
            bf16* orow1 = orow0 + 8 * 192;
#pragma unroll
            for (int u = 0; u < 6; u++) {
                uint32_t w0[4], w1[4];
#pragma unroll
                for (int i = 0; i < 4; i++) {
                    const int t = u * 4 + i;
                    w0[i] = pack_bf16(accQ[t * 4 + 0], accQ[t * 4 + 1]);
                    w1[i] = pack_bf16(accQ[t * 4 + 2], accQ[t * 4 + 3]);
                }
                quad_transpose(w0, q);
                quad_transpose(w1, q);
                const int c = (u * 4 + q) * 8;
                *(uint4*)(orow0 + c) = make_uint4(w0[0], w0[1], w0[2], w0[3]);
                *(uint4*)(orow1 + c) = make_uint4(w1[0], w1[1], w1[2], w1[3]);
            }
        }
        TS(5, tid == 0);
    }
}

__device__ __forceinline__ void ldsm_x4(uint32_t (&r)[4], uint32_t addr) {
    asm("ldmatrix.sync.aligned.m8n8.x4.shared.b16 {%0,%1,%2,%3}, [%4];"
                 : "=r"(r[0]), "=r"(r[1]), "=r"(r[2]), "=r"(r[3]) : "r"(addr));
}
__device__ __forceinline__ void ldsm_x4_t(uint32_t (&r)[4], uint32_t addr) {
    asm("ldmatrix.sync.aligned.m8n8.x4.trans.shared.b16 {%0,%1,%2,%3}, [%4];"
                 : "=r"(r[0]), "=r"(r[1]), "=r"(r[2]), "=r"(r[3]) : "r"(addr));
}
__device__ __forceinline__ void mma16816(float (&d)[4], const uint32_t (&a)[4], uint32_t b0, uint32_t b1) {
    asm("mma.sync.aligned.m16n8k16.row.col.f32.bf16.bf16.f32 {%0,%1,%2,%3}, {%4,%5,%6,%7}, {%8,%9}, {%0,%1,%2,%3};"
                 : "+f"(d[0]), "+f"(d[1]), "+f"(d[2]), "+f"(d[3])
                 : "r"(a[0]), "r"(a[1]), "r"(a[2]), "r"(a[3]), "r"(b0), "r"(b1));
}
__device__ __forceinline__ void mma16816_z(float (&d)[4], const uint32_t (&a)[4], uint32_t b0, uint32_t b1) {
    asm("mma.sync.aligned.m16n8k16.row.col.f32.bf16.bf16.f32 {%0,%1,%2,%3}, {%4,%5,%6,%7}, {%8,%9}, {%10,%10,%10,%10};"
                 : "=f"(d[0]), "=f"(d[1]), "=f"(d[2]), "=f"(d[3])
                 : "r"(a[0]), "r"(a[1]), "r"(a[2]), "r"(a[3]), "r"(b0), "r"(b1), "f"(0.f));
}

constexpr int KV_PITCH = 128;

template <int EDGE, bool HEAD>
__device__ __forceinline__ void blk_scores(float (&s)[2][4], const uint32_t (&qa)[4], uint32_t kaddr, bool dead, int r0, int c0)
{
    uint32_t kf[4];
    ldsm_x4(kf, kaddr);
    mma16816_z(s[0], qa, kf[0], kf[1]);
    mma16816_z(s[1], qa, kf[2], kf[3]);
#pragma unroll
    for (int t = 0; t < 2; t++)
#pragma unroll
        for (int e = 0; e < 4; e++) {
            const int r = r0 + (e >> 1) * 8, c = t * 8 + c0 + (e & 1);
            if (EDGE == 1 && c <= r) s[t][e] = -1e30f;
            if (EDGE == 2 && c > r) s[t][e] = -1e30f;
            if (HEAD && dead) s[t][e] = -1e30f;
        }
}
__device__ __forceinline__ void blk_max(const float (&s)[2][4], float& n0, float& n1) {
    n0 = fmaxf(n0, fmaxf(fmaxf(s[0][0], s[0][1]), fmaxf(s[1][0], s[1][1])));
    n1 = fmaxf(n1, fmaxf(fmaxf(s[0][2], s[0][3]), fmaxf(s[1][2], s[1][3])));
}
__device__ __forceinline__ void blk_pv(const float (&s)[2][4], float mc0, float mc1, float (&l)[4],
                                       float (&o)[2][4], uint32_t vaddr) {
    const float C = 0.25f * 1.4426950408889634f;
    uint32_t pa[4];
#pragma unroll
    for (int t = 0; t < 2; t++) {
        const float p0 = ex2(fmaf(s[t][0], C, -mc0)), p1 = ex2(fmaf(s[t][1], C, -mc0));
        const float p2 = ex2(fmaf(s[t][2], C, -mc1)), p3 = ex2(fmaf(s[t][3], C, -mc1));
        pa[2 * t] = pack_bf16(p0, p1); pa[2 * t + 1] = pack_bf16(p2, p3);
    }
    uint32_t vf[4];
    ldsm_x4_t(vf, vaddr);
    mma16816(o[0], pa, vf[0], vf[1]);
    mma16816(o[1], pa, vf[2], vf[3]);
    mma16816(l, pa, 0x3F803F80u, 0x3F803F80u);
}
__device__ __forceinline__ void quad_max(float& n0, float& n1) {
    n0 = fmaxf(n0, __shfl_xor_sync(0xffffffffu, n0, 1)); n1 = fmaxf(n1, __shfl_xor_sync(0xffffffffu, n1, 1));
    n0 = fmaxf(n0, __shfl_xor_sync(0xffffffffu, n0, 2)); n1 = fmaxf(n1, __shfl_xor_sync(0xffffffffu, n1, 2));
}
template <int NC, int NN, bool FIRST, bool NEXT_IS_EDGE, bool HEAD>
__device__ __forceinline__ void pipe_step(const float (&sc)[5][2][4], float (&sn)[5][2][4], const uint32_t (&qa)[4],
                                          uint32_t ka, uint32_t va, int kc, int kn, int kb0, int r0, int c0,
                                          float& m0, float& m1, float& n0, float& n1, float (&l)[4], float (&o)[2][4])
{
    const float C = 0.25f * 1.4426950408889634f;
    const float mc0 = n0 * C, mc1 = n1 * C;
    if (!FIRST) {
        const float a0 = ex2(fmaf(m0, C, -mc0)), a1 = ex2(fmaf(m1, C, -mc1));
        l[0] *= a0; l[2] *= a1;
        o[0][0] *= a0; o[0][1] *= a0; o[1][0] *= a0; o[1][1] *= a0;
        o[0][2] *= a1; o[0][3] *= a1; o[1][2] *= a1; o[1][3] *= a1;
    }
    m0 = n0; m1 = n1;
#pragma unroll
    for (int b = 0; b < NC; b++) {
        if (b < NN) {
            if (NEXT_IS_EDGE && b == 0) blk_scores<1, HEAD>(sn[b], qa, ka + (kn + b) * 16 * KV_PITCH, kn + b < kb0, r0, c0);
            else                        blk_scores<0, HEAD>(sn[b], qa, ka + (kn + b) * 16 * KV_PITCH, kn + b < kb0, r0, c0);
        }
        blk_pv(sc[b], mc0, mc1, l, o, va + (kc + b) * 16 * KV_PITCH);
        if (b < NN) blk_max(sn[b], n0, n1);
    }
    if (NN > 0) quad_max(n0, n1);
}

__device__ __forceinline__ void kv_need(uint32_t kvbar, int blk, uint32_t& ka, uint32_t& va) {
    mbar_wait(kvbar + 8 * blk, 0);
    asm volatile("" : "+r"(ka), "+r"(va) :: "memory");
}
template <bool HEAD>
__device__ __forceinline__ void attn_task(const uint32_t (&qa)[4], uint32_t ka, uint32_t va, int kb0, int lane, int qt, uint32_t kvbar,
                                          bf16* __restrict__ out  , float g0, float g1)
{
    const int r0 = lane >> 2, c0 = (lane & 3) * 2;
    float m0 = -1e30f, m1 = -1e30f, n0 = -1e30f, n1 = -1e30f;
    float l[4] = {0.f, 0.f, 0.f, 0.f};
    float o[2][4] = {{0.f, 0.f, 0.f, 0.f}, {0.f, 0.f, 0.f, 0.f}};
    float sa[5][2][4], sb[5][2][4];
    kv_need(kvbar, 2, ka, va);
    if (qt < 4) kv_need(kvbar, 1, ka, va);
#pragma unroll
    for (int b = 0; b < 5; b++) {
        if (b == 4) blk_scores<2, HEAD>(sa[b], qa, ka + (12 + b) * 16 * KV_PITCH, false, r0, c0);
        else        blk_scores<0, HEAD>(sa[b], qa, ka + (12 + b) * 16 * KV_PITCH, 12 + b < kb0, r0, c0);
        blk_max(sa[b], n0, n1);
    }
    quad_max(n0, n1);
    kv_need(kvbar, 1, ka, va);
    if (HEAD) {
        pipe_step<5, 0, true, false, HEAD>(sa, sb, qa, ka, va, 12, 0, kb0, r0, c0, m0, m1, n0, n1, l, o);
        kv_need(kvbar, 0, ka, va);
#pragma unroll 1
        for (int kc = 8; kc >= 0 && kb0 < kc + 4; kc -= 4) {
#pragma unroll
            for (int b = 0; b < 4; b++) {
                blk_scores<0, HEAD>(sa[b], qa, ka + (kc + b) * 16 * KV_PITCH, kc + b < kb0, r0, c0);
                blk_max(sa[b], n0, n1);
            }
            quad_max(n0, n1);
            pipe_step<4, 0, false, false, HEAD>(sa, sb, qa, ka, va, kc, 0, kb0, r0, c0, m0, m1, n0, n1, l, o);
        }
    } else {
        pipe_step<5, 4, true,  false, HEAD>(sa, sb, qa, ka, va, 12, 8, kb0, r0, c0, m0, m1, n0, n1, l, o);
        if (qt < 4) kv_need(kvbar, 0, ka, va);
        pipe_step<4, 4, false, false, HEAD>(sb, sa, qa, ka, va, 8, 4, kb0, r0, c0, m0, m1, n0, n1, l, o);
        kv_need(kvbar, 0, ka, va);
        pipe_step<4, 4, false, true,  HEAD>(sa, sb, qa, ka, va, 4, 0, kb0, r0, c0, m0, m1, n0, n1, l, o);
        pipe_step<4, 0, false, false, HEAD>(sb, sa, qa, ka, va, 0, 0, kb0, r0, c0, m0, m1, n0, n1, l, o);
    }
    const float f0 = __fdividef(g0, l[0]), f1 = __fdividef(g1, l[2]);
#pragma unroll
    for (int t = 0; t < 2; t++) {
        *(uint32_t*)(out + (size_t)r0 * KA2 + t * 8 + c0) = pack_bf16(o[t][0] * f0, o[t][1] * f0);
        *(uint32_t*)(out + (size_t)(r0 + 8) * KA2 + t * 8 + c0) = pack_bf16(o[t][2] * f1, o[t][3] * f1);
    }
}

constexpr int K2_SMEM = 2 * 384 * KV_PITCH + 1024 + 64;

__global__ void __launch_bounds__(512, 1) k2_kernel(const __grid_constant__ CUtensorMap tmQKV)
{
    extern __shared__ uint8_t smem_raw[];
    const uint32_t sbase = (smem_u32(smem_raw) + 1023u) & ~1023u;
    uint8_t* sgen = smem_raw + (sbase - smem_u32(smem_raw));
    const uint32_t sK = sbase, sV = sK + 384 * KV_PITCH, kv_full = sbase + 2 * 384 * KV_PITCH;
    const int rb = blockIdx.x >> 3, j = blockIdx.x & 7;
    const int tid = threadIdx.x, warp = tid >> 5, lane = tid & 31;
    pdl_launch();
    if (tid == 0) {
        for (int i = 0; i < 3; i++) mbar_init(kv_full + 8 * i, 1);
        fence_barrier_init();
    }
    pdl_wait();
    TS(6, tid == 0);
    if (tid == 0) {
        for (int i = 0; i < 3; i++) {
            const uint32_t bar = kv_full + 8 * (2 - i);
            if (rb - i >= 0) {
                const int row = j * S_ + (rb - i) * 128;
                mbar_expect_tx(bar, 2 * 16384);
                tma_load_2d(sK + (2 - i) * 16384, &tmQKV, 64, row, bar);
                tma_load_2d(sV + (2 - i) * 16384, &tmQKV, 128, row, bar);
            } else {
                mbar_arrive(bar);
            }
        }
    }
    if (rb < 2) {
        for (int i = tid; i < (2 - rb) * 1024; i += 512) {
            *(uint4*)(sgen + i * 16) = make_uint4(0, 0, 0, 0);
            *(uint4*)(sgen + 384 * KV_PITCH + i * 16) = make_uint4(0, 0, 0, 0);
        }
    }
    const int qt = warp & 7, h0 = (warp >> 3) * 2;
    const int q0g = rb * 128 + qt * 16;
    const int r0 = lane >> 2, c0 = (lane & 3) * 2;
    const bf16* qsrc = g_qkv + ((size_t)j * S_ + q0g) * 192 + h0 * 16;
    uint32_t qa[4], qn[4];
    qa[0] = *(const uint32_t*)(qsrc + (size_t)r0 * 192 + c0);
    qa[1] = *(const uint32_t*)(qsrc + (size_t)(r0 + 8) * 192 + c0);
    qa[2] = *(const uint32_t*)(qsrc + (size_t)r0 * 192 + c0 + 8);
    qa[3] = *(const uint32_t*)(qsrc + (size_t)(r0 + 8) * 192 + c0 + 8);
    qn[0] = *(const uint32_t*)(qsrc + (size_t)r0 * 192 + 16 + c0);
    qn[1] = *(const uint32_t*)(qsrc + (size_t)(r0 + 8) * 192 + 16 + c0);
    qn[2] = *(const uint32_t*)(qsrc + (size_t)r0 * 192 + 16 + c0 + 8);
    qn[3] = *(const uint32_t*)(qsrc + (size_t)(r0 + 8) * 192 + 16 + c0 + 8);
    const float g0 = g_gate[q0g + r0], g1 = g_gate[q0g + r0 + 8];
    const int kb0 = q0g < 256 ? (256 - q0g) >> 4 : 0;
    __syncthreads();
    const uint32_t sKd = sK, sVd = sV;
    TS(7, tid == 0);
    const int krow = qt * 16 + (lane & 7) + ((lane >> 4) << 3);
    const int vrow = qt * 16 + (lane & 15);
#pragma unroll 1
    for (int hh = 0; hh < 2; hh++) {
        const int hl = h0 + hh;
        const uint32_t ka = sKd + krow * KV_PITCH + (((2 * hl + ((lane >> 3) & 1)) ^ (lane & 7)) << 4);
        const uint32_t va = sVd + vrow * KV_PITCH + (((2 * hl + (lane >> 4)) ^ (lane & 7)) << 4);
        if (rb < 2) attn_task<true>(qa, ka, va, kb0, lane, qt, kv_full, g_a2 + (size_t)q0g * KA2 + (j * 4 + hl) * 16, g0, g1);
        else        attn_task<false>(qa, ka, va, kb0, lane, qt, kv_full, g_a2 + (size_t)q0g * KA2 + (j * 4 + hl) * 16, g0, g1);
        TS(8 + hh, tid == 0);
        qa[0] = qn[0]; qa[1] = qn[1]; qa[2] = qn[2]; qa[3] = qn[3];
    }
}

constexpr int K3_STAGES = 8;
constexpr int K3_STAGE = 16384 + 8192;
constexpr int K3_SMEM = K3_STAGES * K3_STAGE + 1024 + 1024;
constexpr int K3_KSTEPS = 30;
#define K3_LAG 1

__global__ void __launch_bounds__(384, 1)
k3_kernel(const __grid_constant__ CUtensorMap tmA2, const __grid_constant__ CUtensorMap tmWo,
          const __grid_constant__ CUtensorMap tmW2, bf16* __restrict__ out)
{
    extern __shared__ uint8_t smem_raw[];
    const uint32_t sbase = (smem_u32(smem_raw) + 1023u) & ~1023u;
    const uint32_t sBar = sbase + K3_STAGES * K3_STAGE;
    const uint32_t full = sBar, empty = sBar + 64;
    const int rb = blockIdx.x >> 3, nb = blockIdx.x & 7;
    const int tid = threadIdx.x, lane = tid & 31;
    const int warp = __shfl_sync(0xffffffffu, tid >> 5, 0), wg = warp >> 2;
    if (tid == 0) {
        for (int i = 0; i < K3_STAGES; i++) { mbar_init(full + 8 * i, 1); mbar_init(empty + 8 * i, 8); }
        fence_barrier_init();
    }
    __syncthreads();
    pdl_wait();
    TS(10, tid == 0);
    if (wg == 2) {
        reg_dealloc<40>();
        if (tid == 256) {
            for (int ks = 0; ks < K3_KSTEPS; ks++) {
                const int st = ks % K3_STAGES;
                if (ks >= K3_STAGES) mbar_wait(empty + 8 * st, ((ks / K3_STAGES) - 1) & 1);
                mbar_expect_tx(full + 8 * st, K3_STAGE);
                const uint32_t dst = sbase + st * K3_STAGE;
                tma_load_2d(dst, &tmA2, ks * 64, rb * 128, full + 8 * st);
                if (ks < 8) tma_load_2d(dst + 16384, &tmWo, nb * 64, ks * 64, full + 8 * st);
                else        tma_load_2d(dst + 16384, &tmW2, nb * 64, (ks - 8) * 64, full + 8 * st);
            }
        }
    } else {
        reg_alloc<232>();
        float acc[32];
        const uint64_t da0 = make_desc(sbase + wg * 8192, 16, 1024);
        const uint64_t db0 = make_desc(sbase + 16384, 8192, 1024);
#pragma unroll 1
        for (int r = 0; r < 4; r++) {
#pragma unroll
            for (int st = 0; st < K3_STAGES; st++) {
                if (r * K3_STAGES + st < K3_KSTEPS) {
                    mbar_wait(full + 8 * st, r & 1);
                    TS(11, tid == 0 && r == 0 && st == 0); TS(12, tid == 0 && r == 1 && st == 0); TS(13, tid == 0 && r == 2 && st == 0);
                    wgmma_fence();
#pragma unroll
                    for (int k16 = 0; k16 < 4; k16++)
                        wgmma_n64<1>(acc, da0 + (st * (K3_STAGE >> 4) + k16 * 2), db0 + (st * (K3_STAGE >> 4) + k16 * 128), (r | st | k16) != 0);
                    wgmma_commit();
                    if (r > 0 || st >= K3_LAG) { wgmma_wait<K3_LAG>(); if (lane == 0) mbar_arrive(empty + 8 * ((st + K3_STAGES - K3_LAG) % K3_STAGES)); }
                }
            }
        }
        wgmma_wait<0>();
        TS(14, tid == 0);
        const int q = lane & 3;
        const int r = rb * 128 + wg * 64 + (warp & 3) * 16 + (lane >> 2);
        bf16* orow0 = out + (size_t)r * D_ + nb * 64;
        bf16* orow1 = orow0 + 8 * D_;
#pragma unroll
        for (int u = 0; u < 2; u++) {
            uint32_t w0[4], w1[4];
#pragma unroll
            for (int i = 0; i < 4; i++) {
                const int t = u * 4 + i;
                w0[i] = pack_bf16(acc[t * 4 + 0], acc[t * 4 + 1]);
                w1[i] = pack_bf16(acc[t * 4 + 2], acc[t * 4 + 3]);
            }
            quad_transpose(w0, q);
            quad_transpose(w1, q);
            const int c = (u * 4 + q) * 8;
            *(uint4*)(orow0 + c) = make_uint4(w0[0], w0[1], w0[2], w0[3]);
            *(uint4*)(orow1 + c) = make_uint4(w1[0], w1[1], w1[2], w1[3]);
        }
        TS(15, tid == 0);
    }
}

typedef CUresult (*PFN_encodeTiled)(CUtensorMap*, CUtensorMapDataType, cuuint32_t, void*, const cuuint64_t*,
                                    const cuuint64_t*, const cuuint32_t*, const cuuint32_t*, CUtensorMapInterleave,
                                    CUtensorMapSwizzle, CUtensorMapL2promotion, CUtensorMapFloatOOBfill);

static void make_map(PFN_encodeTiled enc, CUtensorMap* m, const void* ptr, uint64_t cols, uint64_t rows,
                     uint32_t box_cols, uint32_t box_rows)
{
    cuuint64_t dims[2] = {cols, rows};
    cuuint64_t strides[1] = {cols * 2};
    cuuint32_t box[2] = {box_cols, box_rows};
    cuuint32_t es[2] = {1, 1};
    enc(m, CU_TENSOR_MAP_DATA_TYPE_BFLOAT16, 2, const_cast<void*>(ptr), dims, strides, box, es,
        CU_TENSOR_MAP_INTERLEAVE_NONE, CU_TENSOR_MAP_SWIZZLE_128B, CU_TENSOR_MAP_L2_PROMOTION_L2_128B,
        CU_TENSOR_MAP_FLOAT_OOB_FILL_NONE);
}

extern "C" void kernel_launch(void* const* d_in, const int* in_sizes, int n_in, void* d_out, int out_size)
{
    const bf16* x    = (const bf16*)d_in[0];
    const bf16* wqkv = (const bf16*)d_in[1];
    const bf16* wo   = (const bf16*)d_in[2];
    const bf16* w1   = (const bf16*)d_in[4];
    const bf16* b1   = (const bf16*)d_in[5];
    const bf16* w2   = (const bf16*)d_in[6];
    const bf16* gw   = (const bf16*)d_in[7];

    static PFN_encodeTiled enc = nullptr;
    if (!enc) {
        void* fn = nullptr;
        cudaDriverEntryPointQueryResult qr;
        cudaGetDriverEntryPoint("cuTensorMapEncodeTiled", &fn, cudaEnableDefault, &qr);
        enc = (PFN_encodeTiled)fn;
        cudaFuncSetAttribute(k1_kernel, cudaFuncAttributeMaxDynamicSharedMemorySize, K1_SMEM);
        cudaFuncSetAttribute(k2_kernel, cudaFuncAttributeMaxDynamicSharedMemorySize, K2_SMEM);
        cudaFuncSetAttribute(k3_kernel, cudaFuncAttributeMaxDynamicSharedMemorySize, K3_SMEM);
    }
    void* a2p = nullptr;
    cudaGetSymbolAddress(&a2p, g_a2);
    void* qkvp = nullptr;
    cudaGetSymbolAddress(&qkvp, g_qkv);
    CUtensorMap tmX, tmWqkv, tmW1, tmA2, tmWo, tmW2, tmQKV;
    make_map(enc, &tmQKV, qkvp, 192, 8 * S_, 64, 128);
    make_map(enc, &tmX, x, D_, S_, 64, 128);
    make_map(enc, &tmWqkv, wqkv, 3 * D_, D_, 64, 64);
    make_map(enc, &tmW1, w1, F_, D_, 64, 64);
    make_map(enc, &tmA2, a2p, KA2, S_, 64, 128);
    make_map(enc, &tmWo, wo, D_, D_, 64, 64);
    make_map(enc, &tmW2, w2, D_, F_, 64, 64);

    cudaStream_t st = cudaStreamPerThread;
    k1_kernel<<<128, 384, K1_SMEM, st>>>(tmX, tmWqkv, tmW1, b1, gw, w1, wqkv, w2, wo);
    cudaLaunchAttribute at[1];
    at[0].id = cudaLaunchAttributeProgrammaticStreamSerialization;
    at[0].val.programmaticStreamSerializationAllowed = 1;
    cudaLaunchConfig_t cfg = {};
    cfg.gridDim = dim3(128); cfg.stream = st; cfg.attrs = at; cfg.numAttrs = 1;
    cfg.blockDim = dim3(512); cfg.dynamicSmemBytes = K2_SMEM;
    cudaLaunchKernelEx(&cfg, k2_kernel, tmQKV);
    k3_kernel<<<128, 384, K3_SMEM, st>>>(tmA2, tmWo, tmW2, (bf16*)d_out);
}
```
